```python
import torch

def _softmax(x, axis=-1):
    return torch.softmax(x, dim=axis)
def _gelu(x):
    return torch.nn.functional.gelu(x, approximate="tanh")
def _silu(x):
    return torch.nn.functional.silu(x)
def _sigmoid(x):
    return torch.sigmoid(x)
def _layernorm(x, axis=-1, eps=1e-5):
    m = x.mean(dim=axis, keepdim=True)
    v = x.var(dim=axis, keepdim=True, unbiased=False)
    return (x - m) / torch.sqrt(v + eps)
def _scatter_add(tgt, idx, src, axis=0):
    return tgt.clone().index_add_(axis, idx, src)
def _segment_sum(src, seg, n):
    out = torch.zeros((n,) + src.shape[1:], dtype=src.dtype)
    return out.index_add_(0, seg, src)
def _pad(x, pw):
    flat = tuple(v for pair in reversed(pw) for v in pair)
    return torch.nn.functional.pad(x, flat)

kernel_name = 'standalone__hybrid_graph_tf_graphgps__graph'

def setup_inputs():

    _w = (lambda a: (lambda t: t.to(torch.bfloat16) if t.is_floating_point() else t)(torch.as_tensor(a)))
    N, deg, D = 10000, 16, 256
    E = N * deg
    src = (lambda lo, hi, *s: torch.randint(lo, hi, s))(0, N, E).to(torch.int64)
    dst = (lambda lo, hi, *s: torch.randint(lo, hi, s))(0, N, E).to(torch.int64)
    deg_cnt = torch.bincount(dst, minlength=N).to(float) + 1.0
    sc = 1.0 / float(D) ** 0.5
    return {
        "x": _w((lambda *s: torch.randn(*s, dtype=torch.bfloat16) * 0.05)(N, D)),
        "src": _w(src),
        "dst": _w(dst),
        "deg_inv": _w((1.0 / deg_cnt).to(float)),
        "w_msg": _w((lambda *s: torch.randn(*s, dtype=torch.bfloat16) * 0.2)(D, D) * sc),
        "wq": _w((lambda *s: torch.randn(*s, dtype=torch.bfloat16) * 1.6)(D, D) * sc),
        "wk": _w((lambda *s: torch.randn(*s, dtype=torch.bfloat16) * 1.6)(D, D) * sc),
        "wv": _w((lambda *s: torch.randn(*s, dtype=torch.bfloat16) * 0.2)(D, D) * sc),
        "w_out": _w((lambda *s: torch.randn(*s, dtype=torch.bfloat16) * 0.2)(D, D) * sc),
    }

def reference(x, src, dst, deg_inv, w_msg, wq, wk, wv, w_out):
    N, D = x.shape[0], x.shape[1]
    h = _layernorm(x, axis=-1)
    m_e = torch.einsum('nd,de->ne', h, w_msg)
    h_local = _segment_sum(m_e[src], dst, N) * deg_inv[:, None]
    q = torch.einsum('nd,de->ne', h, wq)
    k = torch.einsum('nd,de->ne', h, wk)
    v = torch.einsum('nd,de->ne', h, wv)
    logits = torch.einsum('id,jd->ij', q, k) / (float(D) ** 0.5)
    attn = _softmax(logits, axis=-1)
    h_global = torch.einsum('ij,jd->id', attn, v)
    y = torch.einsum('nd,de->ne', h_local + h_global, w_out)
    return x + y
```

```cpp
#include <cuda_runtime.h>
#include <cuda.h>
#include <cuda_bf16.h>
#include <stdint.h>
#include <stddef.h>

namespace {

constexpr int NN = 10000;
constexpr int BN = 80;
constexpr int NKV = NN / BN;
constexpr int NQB = 158;
constexpr int NCTA = 132;
constexpr int NAUX = 3 * (NCTA - 2);
constexpr int STAGES = 4;
constexpr int KV_BYTES = BN * 512;
constexpr int QB_BYTES = 64 * 512;
constexpr int PART_BYTES = QB_BYTES + 512;
constexpr int CAP = 32;
constexpr int MAXE = 160000;

#define QRND(v) (((v) + 0x00040004u) & 0xFFF8FFF8u)
#define HPIECE 8192
#define GO0 48
#define GO1 50
#define GSPLIT 11
#define GF0 2
#define REG_C 224
#define REG_P 56

enum { SY_A = 0, SY_H1 = 5, SY_CSR = 6, SY_AUX = 7, SY_DONE = 8, SY_AUX0 = 9, SY_B = 10, SY_AUX1 = 11, SY_H0 = 12 };
struct Scratch {
    uint8_t hz[4096 + NN * 512];
    uint8_t w[12 * QB_BYTES];
    int sync[24 * 32];
    int pflag[NQB / 2 + 1];
    int qflag[NQB / 2 + 1];
    int ovf_n[32];
    float r255[512];
    int cnt[NN + 16];
    int bucket[NN * CAP];
    int2 ovf[MAXE];
    uint8_t q[NQB * QB_BYTES];
    uint8_t agg[NQB * QB_BYTES];
    uint8_t part[NQB * PART_BYTES];
};
static_assert(offsetof(Scratch, ovf) <= (8 << 20), "window");
static_assert(offsetof(Scratch, w) % 1024 == 0 && offsetof(Scratch, sync) % 128 == 0 &&
              offsetof(Scratch, bucket) % 128 == 0 && offsetof(Scratch, q) % 128 == 0, "alignment");
__device__ uint8_t g_raw[(8 << 20) + sizeof(Scratch)];
#define g_hz (H.s->hz)
#define g_w (H.s->w)
#define g_sync (H.s->sync)
#define g_pflag (H.s->pflag)
#define g_qflag (H.s->qflag)
#define g_ovf_n (H.s->ovf_n)
#define g_cnt (H.s->cnt)
#define g_bucket (H.s->bucket)
#define g_ovf (H.s->ovf)
#define g_q (H.s->q)
#define g_agg (H.s->agg)
#define g_part (H.s->part)

__device__ __forceinline__ void wgmma_ss_n80(float (&d)[40], uint64_t da, uint64_t db) {
    asm volatile("wgmma.mma_async.sync.aligned.m64n80k16.f32.f16.f16 {"
        "%0, %1, %2, %3, %4, %5, %6, %7, %8, %9, %10, %11, %12, %13, %14, %15, %16, %17, %18, %19, %20, %21, %22, %23, %24, %25, %26, %27, %28, %29, %30, %31, "
        "%32, %33, %34, %35, %36, %37, %38, %39}, %40, %41, 1, 1, 1, 0, 0;\n"
        : "+f"(d[0]), "+f"(d[1]), "+f"(d[2]), "+f"(d[3]), "+f"(d[4]), "+f"(d[5]), "+f"(d[6]), "+f"(d[7]),
          "+f"(d[8]), "+f"(d[9]), "+f"(d[10]), "+f"(d[11]), "+f"(d[12]), "+f"(d[13]), "+f"(d[14]), "+f"(d[15]),
          "+f"(d[16]), "+f"(d[17]), "+f"(d[18]), "+f"(d[19]), "+f"(d[20]), "+f"(d[21]), "+f"(d[22]), "+f"(d[23]),
          "+f"(d[24]), "+f"(d[25]), "+f"(d[26]), "+f"(d[27]), "+f"(d[28]), "+f"(d[29]), "+f"(d[30]), "+f"(d[31]),
          "+f"(d[32]), "+f"(d[33]), "+f"(d[34]), "+f"(d[35]), "+f"(d[36]), "+f"(d[37]), "+f"(d[38]), "+f"(d[39])
        : "l"(da), "l"(db));
}
__device__ __forceinline__ void wgmma_ss_n80_init(float (&d)[40], uint64_t da, uint64_t db) {
    asm volatile("wgmma.mma_async.sync.aligned.m64n80k16.f32.f16.f16 {"
        "%0, %1, %2, %3, %4, %5, %6, %7, %8, %9, %10, %11, %12, %13, %14, %15, %16, %17, %18, %19, %20, %21, %22, %23, %24, %25, %26, %27, %28, %29, %30, %31, "
        "%32, %33, %34, %35, %36, %37, %38, %39}, %40, %41, 0, 1, 1, 0, 0;\n"
        : "=f"(d[0]), "=f"(d[1]), "=f"(d[2]), "=f"(d[3]), "=f"(d[4]), "=f"(d[5]), "=f"(d[6]), "=f"(d[7]),
          "=f"(d[8]), "=f"(d[9]), "=f"(d[10]), "=f"(d[11]), "=f"(d[12]), "=f"(d[13]), "=f"(d[14]), "=f"(d[15]),
          "=f"(d[16]), "=f"(d[17]), "=f"(d[18]), "=f"(d[19]), "=f"(d[20]), "=f"(d[21]), "=f"(d[22]), "=f"(d[23]),
          "=f"(d[24]), "=f"(d[25]), "=f"(d[26]), "=f"(d[27]), "=f"(d[28]), "=f"(d[29]), "=f"(d[30]), "=f"(d[31]),
          "=f"(d[32]), "=f"(d[33]), "=f"(d[34]), "=f"(d[35]), "=f"(d[36]), "=f"(d[37]), "=f"(d[38]), "=f"(d[39])
        : "l"(da), "l"(db));
}
__device__ __forceinline__ void wgmma_rs_n256_tb(float (&d)[128], uint32_t a0, uint32_t a1, uint32_t a2, uint32_t a3, uint64_t db) {
    asm volatile("wgmma.mma_async.sync.aligned.m64n256k16.f32.f16.f16 {"
        "%0, %1, %2, %3, %4, %5, %6, %7, %8, %9, %10, %11, %12, %13, %14, %15, %16, %17, %18, %19, %20, %21, %22, %23, %24, %25, %26, %27, %28, %29, %30, %31, "
        "%32, %33, %34, %35, %36, %37, %38, %39, %40, %41, %42, %43, %44, %45, %46, %47, %48, %49, %50, %51, %52, %53, %54, %55, %56, %57, %58, %59, %60, %61, %62, %63, "
        "%64, %65, %66, %67, %68, %69, %70, %71, %72, %73, %74, %75, %76, %77, %78, %79, %80, %81, %82, %83, %84, %85, %86, %87, %88, %89, %90, %91, %92, %93, %94, %95, "
        "%96, %97, %98, %99, %100, %101, %102, %103, %104, %105, %106, %107, %108, %109, %110, %111, %112, %113, %114, %115, %116, %117, %118, %119, %120, %121, %122, %123, %124, %125, %126, %127}, {%128, %129, %130, %131}, %132, 1, 1, 1, 1;\n"
        : "+f"(d[0]), "+f"(d[1]), "+f"(d[2]), "+f"(d[3]), "+f"(d[4]), "+f"(d[5]), "+f"(d[6]), "+f"(d[7]),
          "+f"(d[8]), "+f"(d[9]), "+f"(d[10]), "+f"(d[11]), "+f"(d[12]), "+f"(d[13]), "+f"(d[14]), "+f"(d[15]),
          "+f"(d[16]), "+f"(d[17]), "+f"(d[18]), "+f"(d[19]), "+f"(d[20]), "+f"(d[21]), "+f"(d[22]), "+f"(d[23]),
          "+f"(d[24]), "+f"(d[25]), "+f"(d[26]), "+f"(d[27]), "+f"(d[28]), "+f"(d[29]), "+f"(d[30]), "+f"(d[31]),
          "+f"(d[32]), "+f"(d[33]), "+f"(d[34]), "+f"(d[35]), "+f"(d[36]), "+f"(d[37]), "+f"(d[38]), "+f"(d[39]),
          "+f"(d[40]), "+f"(d[41]), "+f"(d[42]), "+f"(d[43]), "+f"(d[44]), "+f"(d[45]), "+f"(d[46]), "+f"(d[47]),
          "+f"(d[48]), "+f"(d[49]), "+f"(d[50]), "+f"(d[51]), "+f"(d[52]), "+f"(d[53]), "+f"(d[54]), "+f"(d[55]),
          "+f"(d[56]), "+f"(d[57]), "+f"(d[58]), "+f"(d[59]), "+f"(d[60]), "+f"(d[61]), "+f"(d[62]), "+f"(d[63]),
          "+f"(d[64]), "+f"(d[65]), "+f"(d[66]), "+f"(d[67]), "+f"(d[68]), "+f"(d[69]), "+f"(d[70]), "+f"(d[71]),
          "+f"(d[72]), "+f"(d[73]), "+f"(d[74]), "+f"(d[75]), "+f"(d[76]), "+f"(d[77]), "+f"(d[78]), "+f"(d[79]),
          "+f"(d[80]), "+f"(d[81]), "+f"(d[82]), "+f"(d[83]), "+f"(d[84]), "+f"(d[85]), "+f"(d[86]), "+f"(d[87]),
          "+f"(d[88]), "+f"(d[89]), "+f"(d[90]), "+f"(d[91]), "+f"(d[92]), "+f"(d[93]), "+f"(d[94]), "+f"(d[95]),
          "+f"(d[96]), "+f"(d[97]), "+f"(d[98]), "+f"(d[99]), "+f"(d[100]), "+f"(d[101]), "+f"(d[102]), "+f"(d[103]),
          "+f"(d[104]), "+f"(d[105]), "+f"(d[106]), "+f"(d[107]), "+f"(d[108]), "+f"(d[109]), "+f"(d[110]), "+f"(d[111]),
          "+f"(d[112]), "+f"(d[113]), "+f"(d[114]), "+f"(d[115]), "+f"(d[116]), "+f"(d[117]), "+f"(d[118]), "+f"(d[119]),
          "+f"(d[120]), "+f"(d[121]), "+f"(d[122]), "+f"(d[123]), "+f"(d[124]), "+f"(d[125]), "+f"(d[126]), "+f"(d[127])
        : "r"(a0), "r"(a1), "r"(a2), "r"(a3), "l"(db));
}
__device__ __forceinline__ void wgmma_rs_n256_tb_init(float (&d)[128], uint32_t a0, uint32_t a1, uint32_t a2, uint32_t a3, uint64_t db) {
    asm volatile("wgmma.mma_async.sync.aligned.m64n256k16.f32.f16.f16 {"
        "%0, %1, %2, %3, %4, %5, %6, %7, %8, %9, %10, %11, %12, %13, %14, %15, %16, %17, %18, %19, %20, %21, %22, %23, %24, %25, %26, %27, %28, %29, %30, %31, "
        "%32, %33, %34, %35, %36, %37, %38, %39, %40, %41, %42, %43, %44, %45, %46, %47, %48, %49, %50, %51, %52, %53, %54, %55, %56, %57, %58, %59, %60, %61, %62, %63, "
        "%64, %65, %66, %67, %68, %69, %70, %71, %72, %73, %74, %75, %76, %77, %78, %79, %80, %81, %82, %83, %84, %85, %86, %87, %88, %89, %90, %91, %92, %93, %94, %95, "
        "%96, %97, %98, %99, %100, %101, %102, %103, %104, %105, %106, %107, %108, %109, %110, %111, %112, %113, %114, %115, %116, %117, %118, %119, %120, %121, %122, %123, %124, %125, %126, %127}, {%128, %129, %130, %131}, %132, 0, 1, 1, 1;\n"
        : "=f"(d[0]), "=f"(d[1]), "=f"(d[2]), "=f"(d[3]), "=f"(d[4]), "=f"(d[5]), "=f"(d[6]), "=f"(d[7]),
          "=f"(d[8]), "=f"(d[9]), "=f"(d[10]), "=f"(d[11]), "=f"(d[12]), "=f"(d[13]), "=f"(d[14]), "=f"(d[15]),
          "=f"(d[16]), "=f"(d[17]), "=f"(d[18]), "=f"(d[19]), "=f"(d[20]), "=f"(d[21]), "=f"(d[22]), "=f"(d[23]),
          "=f"(d[24]), "=f"(d[25]), "=f"(d[26]), "=f"(d[27]), "=f"(d[28]), "=f"(d[29]), "=f"(d[30]), "=f"(d[31]),
          "=f"(d[32]), "=f"(d[33]), "=f"(d[34]), "=f"(d[35]), "=f"(d[36]), "=f"(d[37]), "=f"(d[38]), "=f"(d[39]),
          "=f"(d[40]), "=f"(d[41]), "=f"(d[42]), "=f"(d[43]), "=f"(d[44]), "=f"(d[45]), "=f"(d[46]), "=f"(d[47]),
          "=f"(d[48]), "=f"(d[49]), "=f"(d[50]), "=f"(d[51]), "=f"(d[52]), "=f"(d[53]), "=f"(d[54]), "=f"(d[55]),
          "=f"(d[56]), "=f"(d[57]), "=f"(d[58]), "=f"(d[59]), "=f"(d[60]), "=f"(d[61]), "=f"(d[62]), "=f"(d[63]),
          "=f"(d[64]), "=f"(d[65]), "=f"(d[66]), "=f"(d[67]), "=f"(d[68]), "=f"(d[69]), "=f"(d[70]), "=f"(d[71]),
          "=f"(d[72]), "=f"(d[73]), "=f"(d[74]), "=f"(d[75]), "=f"(d[76]), "=f"(d[77]), "=f"(d[78]), "=f"(d[79]),
          "=f"(d[80]), "=f"(d[81]), "=f"(d[82]), "=f"(d[83]), "=f"(d[84]), "=f"(d[85]), "=f"(d[86]), "=f"(d[87]),
          "=f"(d[88]), "=f"(d[89]), "=f"(d[90]), "=f"(d[91]), "=f"(d[92]), "=f"(d[93]), "=f"(d[94]), "=f"(d[95]),
          "=f"(d[96]), "=f"(d[97]), "=f"(d[98]), "=f"(d[99]), "=f"(d[100]), "=f"(d[101]), "=f"(d[102]), "=f"(d[103]),
          "=f"(d[104]), "=f"(d[105]), "=f"(d[106]), "=f"(d[107]), "=f"(d[108]), "=f"(d[109]), "=f"(d[110]), "=f"(d[111]),
          "=f"(d[112]), "=f"(d[113]), "=f"(d[114]), "=f"(d[115]), "=f"(d[116]), "=f"(d[117]), "=f"(d[118]), "=f"(d[119]),
          "=f"(d[120]), "=f"(d[121]), "=f"(d[122]), "=f"(d[123]), "=f"(d[124]), "=f"(d[125]), "=f"(d[126]), "=f"(d[127])
        : "r"(a0), "r"(a1), "r"(a2), "r"(a3), "l"(db));
}
__device__ __forceinline__ void wgmma_rs_n256_tb_pred(float (&d)[128], uint32_t a0, uint32_t a1, uint32_t a2, uint32_t a3, uint64_t db, int acc) {
    asm volatile("{\n.reg .pred p;\nsetp.ne.s32 p, %133, 0;\nwgmma.mma_async.sync.aligned.m64n256k16.f32.f16.f16 {"
        "%0, %1, %2, %3, %4, %5, %6, %7, %8, %9, %10, %11, %12, %13, %14, %15, %16, %17, %18, %19, %20, %21, %22, %23, %24, %25, %26, %27, %28, %29, %30, %31, "
        "%32, %33, %34, %35, %36, %37, %38, %39, %40, %41, %42, %43, %44, %45, %46, %47, %48, %49, %50, %51, %52, %53, %54, %55, %56, %57, %58, %59, %60, %61, %62, %63, "
        "%64, %65, %66, %67, %68, %69, %70, %71, %72, %73, %74, %75, %76, %77, %78, %79, %80, %81, %82, %83, %84, %85, %86, %87, %88, %89, %90, %91, %92, %93, %94, %95, "
        "%96, %97, %98, %99, %100, %101, %102, %103, %104, %105, %106, %107, %108, %109, %110, %111, %112, %113, %114, %115, %116, %117, %118, %119, %120, %121, %122, %123, %124, %125, %126, %127}, {%128, %129, %130, %131}, %132, p, 1, 1, 1;\n}\n"
        : "+f"(d[0]), "+f"(d[1]), "+f"(d[2]), "+f"(d[3]), "+f"(d[4]), "+f"(d[5]), "+f"(d[6]), "+f"(d[7]),
          "+f"(d[8]), "+f"(d[9]), "+f"(d[10]), "+f"(d[11]), "+f"(d[12]), "+f"(d[13]), "+f"(d[14]), "+f"(d[15]),
          "+f"(d[16]), "+f"(d[17]), "+f"(d[18]), "+f"(d[19]), "+f"(d[20]), "+f"(d[21]), "+f"(d[22]), "+f"(d[23]),
          "+f"(d[24]), "+f"(d[25]), "+f"(d[26]), "+f"(d[27]), "+f"(d[28]), "+f"(d[29]), "+f"(d[30]), "+f"(d[31]),
          "+f"(d[32]), "+f"(d[33]), "+f"(d[34]), "+f"(d[35]), "+f"(d[36]), "+f"(d[37]), "+f"(d[38]), "+f"(d[39]),
          "+f"(d[40]), "+f"(d[41]), "+f"(d[42]), "+f"(d[43]), "+f"(d[44]), "+f"(d[45]), "+f"(d[46]), "+f"(d[47]),
          "+f"(d[48]), "+f"(d[49]), "+f"(d[50]), "+f"(d[51]), "+f"(d[52]), "+f"(d[53]), "+f"(d[54]), "+f"(d[55]),
          "+f"(d[56]), "+f"(d[57]), "+f"(d[58]), "+f"(d[59]), "+f"(d[60]), "+f"(d[61]), "+f"(d[62]), "+f"(d[63]),
          "+f"(d[64]), "+f"(d[65]), "+f"(d[66]), "+f"(d[67]), "+f"(d[68]), "+f"(d[69]), "+f"(d[70]), "+f"(d[71]),
          "+f"(d[72]), "+f"(d[73]), "+f"(d[74]), "+f"(d[75]), "+f"(d[76]), "+f"(d[77]), "+f"(d[78]), "+f"(d[79]),
          "+f"(d[80]), "+f"(d[81]), "+f"(d[82]), "+f"(d[83]), "+f"(d[84]), "+f"(d[85]), "+f"(d[86]), "+f"(d[87]),
          "+f"(d[88]), "+f"(d[89]), "+f"(d[90]), "+f"(d[91]), "+f"(d[92]), "+f"(d[93]), "+f"(d[94]), "+f"(d[95]),
          "+f"(d[96]), "+f"(d[97]), "+f"(d[98]), "+f"(d[99]), "+f"(d[100]), "+f"(d[101]), "+f"(d[102]), "+f"(d[103]),
          "+f"(d[104]), "+f"(d[105]), "+f"(d[106]), "+f"(d[107]), "+f"(d[108]), "+f"(d[109]), "+f"(d[110]), "+f"(d[111]),
          "+f"(d[112]), "+f"(d[113]), "+f"(d[114]), "+f"(d[115]), "+f"(d[116]), "+f"(d[117]), "+f"(d[118]), "+f"(d[119]),
          "+f"(d[120]), "+f"(d[121]), "+f"(d[122]), "+f"(d[123]), "+f"(d[124]), "+f"(d[125]), "+f"(d[126]), "+f"(d[127])
        : "r"(a0), "r"(a1), "r"(a2), "r"(a3), "l"(db), "r"(acc));
}
__device__ __forceinline__ void wgmma_ss_n256_tb(float (&d)[128], uint64_t da, uint64_t db) {
    asm volatile("wgmma.mma_async.sync.aligned.m64n256k16.f32.bf16.bf16 {"
        "%0, %1, %2, %3, %4, %5, %6, %7, %8, %9, %10, %11, %12, %13, %14, %15, %16, %17, %18, %19, %20, %21, %22, %23, %24, %25, %26, %27, %28, %29, %30, %31, "
        "%32, %33, %34, %35, %36, %37, %38, %39, %40, %41, %42, %43, %44, %45, %46, %47, %48, %49, %50, %51, %52, %53, %54, %55, %56, %57, %58, %59, %60, %61, %62, %63, "
        "%64, %65, %66, %67, %68, %69, %70, %71, %72, %73, %74, %75, %76, %77, %78, %79, %80, %81, %82, %83, %84, %85, %86, %87, %88, %89, %90, %91, %92, %93, %94, %95, "
        "%96, %97, %98, %99, %100, %101, %102, %103, %104, %105, %106, %107, %108, %109, %110, %111, %112, %113, %114, %115, %116, %117, %118, %119, %120, %121, %122, %123, %124, %125, %126, %127}, %128, %129, 1, 1, 1, 0, 1;\n"
        : "+f"(d[0]), "+f"(d[1]), "+f"(d[2]), "+f"(d[3]), "+f"(d[4]), "+f"(d[5]), "+f"(d[6]), "+f"(d[7]),
          "+f"(d[8]), "+f"(d[9]), "+f"(d[10]), "+f"(d[11]), "+f"(d[12]), "+f"(d[13]), "+f"(d[14]), "+f"(d[15]),
          "+f"(d[16]), "+f"(d[17]), "+f"(d[18]), "+f"(d[19]), "+f"(d[20]), "+f"(d[21]), "+f"(d[22]), "+f"(d[23]),
          "+f"(d[24]), "+f"(d[25]), "+f"(d[26]), "+f"(d[27]), "+f"(d[28]), "+f"(d[29]), "+f"(d[30]), "+f"(d[31]),
          "+f"(d[32]), "+f"(d[33]), "+f"(d[34]), "+f"(d[35]), "+f"(d[36]), "+f"(d[37]), "+f"(d[38]), "+f"(d[39]),
          "+f"(d[40]), "+f"(d[41]), "+f"(d[42]), "+f"(d[43]), "+f"(d[44]), "+f"(d[45]), "+f"(d[46]), "+f"(d[47]),
          "+f"(d[48]), "+f"(d[49]), "+f"(d[50]), "+f"(d[51]), "+f"(d[52]), "+f"(d[53]), "+f"(d[54]), "+f"(d[55]),
          "+f"(d[56]), "+f"(d[57]), "+f"(d[58]), "+f"(d[59]), "+f"(d[60]), "+f"(d[61]), "+f"(d[62]), "+f"(d[63]),
          "+f"(d[64]), "+f"(d[65]), "+f"(d[66]), "+f"(d[67]), "+f"(d[68]), "+f"(d[69]), "+f"(d[70]), "+f"(d[71]),
          "+f"(d[72]), "+f"(d[73]), "+f"(d[74]), "+f"(d[75]), "+f"(d[76]), "+f"(d[77]), "+f"(d[78]), "+f"(d[79]),
          "+f"(d[80]), "+f"(d[81]), "+f"(d[82]), "+f"(d[83]), "+f"(d[84]), "+f"(d[85]), "+f"(d[86]), "+f"(d[87]),
          "+f"(d[88]), "+f"(d[89]), "+f"(d[90]), "+f"(d[91]), "+f"(d[92]), "+f"(d[93]), "+f"(d[94]), "+f"(d[95]),
          "+f"(d[96]), "+f"(d[97]), "+f"(d[98]), "+f"(d[99]), "+f"(d[100]), "+f"(d[101]), "+f"(d[102]), "+f"(d[103]),
          "+f"(d[104]), "+f"(d[105]), "+f"(d[106]), "+f"(d[107]), "+f"(d[108]), "+f"(d[109]), "+f"(d[110]), "+f"(d[111]),
          "+f"(d[112]), "+f"(d[113]), "+f"(d[114]), "+f"(d[115]), "+f"(d[116]), "+f"(d[117]), "+f"(d[118]), "+f"(d[119]),
          "+f"(d[120]), "+f"(d[121]), "+f"(d[122]), "+f"(d[123]), "+f"(d[124]), "+f"(d[125]), "+f"(d[126]), "+f"(d[127])
        : "l"(da), "l"(db));
}
__device__ __forceinline__ void wgmma_ss_n256_tb_init(float (&d)[128], uint64_t da, uint64_t db) {
    asm volatile("wgmma.mma_async.sync.aligned.m64n256k16.f32.bf16.bf16 {"
        "%0, %1, %2, %3, %4, %5, %6, %7, %8, %9, %10, %11, %12, %13, %14, %15, %16, %17, %18, %19, %20, %21, %22, %23, %24, %25, %26, %27, %28, %29, %30, %31, "
        "%32, %33, %34, %35, %36, %37, %38, %39, %40, %41, %42, %43, %44, %45, %46, %47, %48, %49, %50, %51, %52, %53, %54, %55, %56, %57, %58, %59, %60, %61, %62, %63, "
        "%64, %65, %66, %67, %68, %69, %70, %71, %72, %73, %74, %75, %76, %77, %78, %79, %80, %81, %82, %83, %84, %85, %86, %87, %88, %89, %90, %91, %92, %93, %94, %95, "
        "%96, %97, %98, %99, %100, %101, %102, %103, %104, %105, %106, %107, %108, %109, %110, %111, %112, %113, %114, %115, %116, %117, %118, %119, %120, %121, %122, %123, %124, %125, %126, %127}, %128, %129, 0, 1, 1, 0, 1;\n"
        : "=f"(d[0]), "=f"(d[1]), "=f"(d[2]), "=f"(d[3]), "=f"(d[4]), "=f"(d[5]), "=f"(d[6]), "=f"(d[7]),
          "=f"(d[8]), "=f"(d[9]), "=f"(d[10]), "=f"(d[11]), "=f"(d[12]), "=f"(d[13]), "=f"(d[14]), "=f"(d[15]),
          "=f"(d[16]), "=f"(d[17]), "=f"(d[18]), "=f"(d[19]), "=f"(d[20]), "=f"(d[21]), "=f"(d[22]), "=f"(d[23]),
          "=f"(d[24]), "=f"(d[25]), "=f"(d[26]), "=f"(d[27]), "=f"(d[28]), "=f"(d[29]), "=f"(d[30]), "=f"(d[31]),
          "=f"(d[32]), "=f"(d[33]), "=f"(d[34]), "=f"(d[35]), "=f"(d[36]), "=f"(d[37]), "=f"(d[38]), "=f"(d[39]),
          "=f"(d[40]), "=f"(d[41]), "=f"(d[42]), "=f"(d[43]), "=f"(d[44]), "=f"(d[45]), "=f"(d[46]), "=f"(d[47]),
          "=f"(d[48]), "=f"(d[49]), "=f"(d[50]), "=f"(d[51]), "=f"(d[52]), "=f"(d[53]), "=f"(d[54]), "=f"(d[55]),
          "=f"(d[56]), "=f"(d[57]), "=f"(d[58]), "=f"(d[59]), "=f"(d[60]), "=f"(d[61]), "=f"(d[62]), "=f"(d[63]),
          "=f"(d[64]), "=f"(d[65]), "=f"(d[66]), "=f"(d[67]), "=f"(d[68]), "=f"(d[69]), "=f"(d[70]), "=f"(d[71]),
          "=f"(d[72]), "=f"(d[73]), "=f"(d[74]), "=f"(d[75]), "=f"(d[76]), "=f"(d[77]), "=f"(d[78]), "=f"(d[79]),
          "=f"(d[80]), "=f"(d[81]), "=f"(d[82]), "=f"(d[83]), "=f"(d[84]), "=f"(d[85]), "=f"(d[86]), "=f"(d[87]),
          "=f"(d[88]), "=f"(d[89]), "=f"(d[90]), "=f"(d[91]), "=f"(d[92]), "=f"(d[93]), "=f"(d[94]), "=f"(d[95]),
          "=f"(d[96]), "=f"(d[97]), "=f"(d[98]), "=f"(d[99]), "=f"(d[100]), "=f"(d[101]), "=f"(d[102]), "=f"(d[103]),
          "=f"(d[104]), "=f"(d[105]), "=f"(d[106]), "=f"(d[107]), "=f"(d[108]), "=f"(d[109]), "=f"(d[110]), "=f"(d[111]),
          "=f"(d[112]), "=f"(d[113]), "=f"(d[114]), "=f"(d[115]), "=f"(d[116]), "=f"(d[117]), "=f"(d[118]), "=f"(d[119]),
          "=f"(d[120]), "=f"(d[121]), "=f"(d[122]), "=f"(d[123]), "=f"(d[124]), "=f"(d[125]), "=f"(d[126]), "=f"(d[127])
        : "l"(da), "l"(db));
}
__device__ __forceinline__ void wgmma_ss_n128_tb(float (&d)[64], uint64_t da, uint64_t db) {
    asm volatile("wgmma.mma_async.sync.aligned.m64n128k16.f32.bf16.bf16 {"
        "%0, %1, %2, %3, %4, %5, %6, %7, %8, %9, %10, %11, %12, %13, %14, %15, %16, %17, %18, %19, %20, %21, %22, %23, %24, %25, %26, %27, %28, %29, %30, %31, "
        "%32, %33, %34, %35, %36, %37, %38, %39, %40, %41, %42, %43, %44, %45, %46, %47, %48, %49, %50, %51, %52, %53, %54, %55, %56, %57, %58, %59, %60, %61, %62, %63}, %64, %65, 1, 1, 1, 0, 1;\n"
        : "+f"(d[0]), "+f"(d[1]), "+f"(d[2]), "+f"(d[3]), "+f"(d[4]), "+f"(d[5]), "+f"(d[6]), "+f"(d[7]),
          "+f"(d[8]), "+f"(d[9]), "+f"(d[10]), "+f"(d[11]), "+f"(d[12]), "+f"(d[13]), "+f"(d[14]), "+f"(d[15]),
          "+f"(d[16]), "+f"(d[17]), "+f"(d[18]), "+f"(d[19]), "+f"(d[20]), "+f"(d[21]), "+f"(d[22]), "+f"(d[23]),
          "+f"(d[24]), "+f"(d[25]), "+f"(d[26]), "+f"(d[27]), "+f"(d[28]), "+f"(d[29]), "+f"(d[30]), "+f"(d[31]),
          "+f"(d[32]), "+f"(d[33]), "+f"(d[34]), "+f"(d[35]), "+f"(d[36]), "+f"(d[37]), "+f"(d[38]), "+f"(d[39]),
          "+f"(d[40]), "+f"(d[41]), "+f"(d[42]), "+f"(d[43]), "+f"(d[44]), "+f"(d[45]), "+f"(d[46]), "+f"(d[47]),
          "+f"(d[48]), "+f"(d[49]), "+f"(d[50]), "+f"(d[51]), "+f"(d[52]), "+f"(d[53]), "+f"(d[54]), "+f"(d[55]),
          "+f"(d[56]), "+f"(d[57]), "+f"(d[58]), "+f"(d[59]), "+f"(d[60]), "+f"(d[61]), "+f"(d[62]), "+f"(d[63])
        : "l"(da), "l"(db));
}
__device__ __forceinline__ void wgmma_ss_n128_tb_init(float (&d)[64], uint64_t da, uint64_t db) {
    asm volatile("wgmma.mma_async.sync.aligned.m64n128k16.f32.bf16.bf16 {"
        "%0, %1, %2, %3, %4, %5, %6, %7, %8, %9, %10, %11, %12, %13, %14, %15, %16, %17, %18, %19, %20, %21, %22, %23, %24, %25, %26, %27, %28, %29, %30, %31, "
        "%32, %33, %34, %35, %36, %37, %38, %39, %40, %41, %42, %43, %44, %45, %46, %47, %48, %49, %50, %51, %52, %53, %54, %55, %56, %57, %58, %59, %60, %61, %62, %63}, %64, %65, 0, 1, 1, 0, 1;\n"
        : "=f"(d[0]), "=f"(d[1]), "=f"(d[2]), "=f"(d[3]), "=f"(d[4]), "=f"(d[5]), "=f"(d[6]), "=f"(d[7]),
          "=f"(d[8]), "=f"(d[9]), "=f"(d[10]), "=f"(d[11]), "=f"(d[12]), "=f"(d[13]), "=f"(d[14]), "=f"(d[15]),
          "=f"(d[16]), "=f"(d[17]), "=f"(d[18]), "=f"(d[19]), "=f"(d[20]), "=f"(d[21]), "=f"(d[22]), "=f"(d[23]),
          "=f"(d[24]), "=f"(d[25]), "=f"(d[26]), "=f"(d[27]), "=f"(d[28]), "=f"(d[29]), "=f"(d[30]), "=f"(d[31]),
          "=f"(d[32]), "=f"(d[33]), "=f"(d[34]), "=f"(d[35]), "=f"(d[36]), "=f"(d[37]), "=f"(d[38]), "=f"(d[39]),
          "=f"(d[40]), "=f"(d[41]), "=f"(d[42]), "=f"(d[43]), "=f"(d[44]), "=f"(d[45]), "=f"(d[46]), "=f"(d[47]),
          "=f"(d[48]), "=f"(d[49]), "=f"(d[50]), "=f"(d[51]), "=f"(d[52]), "=f"(d[53]), "=f"(d[54]), "=f"(d[55]),
          "=f"(d[56]), "=f"(d[57]), "=f"(d[58]), "=f"(d[59]), "=f"(d[60]), "=f"(d[61]), "=f"(d[62]), "=f"(d[63])
        : "l"(da), "l"(db));
}
__device__ __forceinline__ void wgmma_rs_n128_tb(float (&d)[64], uint32_t a0, uint32_t a1, uint32_t a2, uint32_t a3, uint64_t db) {
    asm volatile("wgmma.mma_async.sync.aligned.m64n128k16.f32.bf16.bf16 {"
        "%0, %1, %2, %3, %4, %5, %6, %7, %8, %9, %10, %11, %12, %13, %14, %15, %16, %17, %18, %19, %20, %21, %22, %23, %24, %25, %26, %27, %28, %29, %30, %31, "
        "%32, %33, %34, %35, %36, %37, %38, %39, %40, %41, %42, %43, %44, %45, %46, %47, %48, %49, %50, %51, %52, %53, %54, %55, %56, %57, %58, %59, %60, %61, %62, %63}, {%64, %65, %66, %67}, %68, 1, 1, 1, 1;\n"
        : "+f"(d[0]), "+f"(d[1]), "+f"(d[2]), "+f"(d[3]), "+f"(d[4]), "+f"(d[5]), "+f"(d[6]), "+f"(d[7]),
          "+f"(d[8]), "+f"(d[9]), "+f"(d[10]), "+f"(d[11]), "+f"(d[12]), "+f"(d[13]), "+f"(d[14]), "+f"(d[15]),
          "+f"(d[16]), "+f"(d[17]), "+f"(d[18]), "+f"(d[19]), "+f"(d[20]), "+f"(d[21]), "+f"(d[22]), "+f"(d[23]),
          "+f"(d[24]), "+f"(d[25]), "+f"(d[26]), "+f"(d[27]), "+f"(d[28]), "+f"(d[29]), "+f"(d[30]), "+f"(d[31]),
          "+f"(d[32]), "+f"(d[33]), "+f"(d[34]), "+f"(d[35]), "+f"(d[36]), "+f"(d[37]), "+f"(d[38]), "+f"(d[39]),
          "+f"(d[40]), "+f"(d[41]), "+f"(d[42]), "+f"(d[43]), "+f"(d[44]), "+f"(d[45]), "+f"(d[46]), "+f"(d[47]),
          "+f"(d[48]), "+f"(d[49]), "+f"(d[50]), "+f"(d[51]), "+f"(d[52]), "+f"(d[53]), "+f"(d[54]), "+f"(d[55]),
          "+f"(d[56]), "+f"(d[57]), "+f"(d[58]), "+f"(d[59]), "+f"(d[60]), "+f"(d[61]), "+f"(d[62]), "+f"(d[63])
        : "r"(a0), "r"(a1), "r"(a2), "r"(a3), "l"(db));
}
__device__ __forceinline__ void wgmma_rs_n128_tb_init(float (&d)[64], uint32_t a0, uint32_t a1, uint32_t a2, uint32_t a3, uint64_t db) {
    asm volatile("wgmma.mma_async.sync.aligned.m64n128k16.f32.bf16.bf16 {"
        "%0, %1, %2, %3, %4, %5, %6, %7, %8, %9, %10, %11, %12, %13, %14, %15, %16, %17, %18, %19, %20, %21, %22, %23, %24, %25, %26, %27, %28, %29, %30, %31, "
        "%32, %33, %34, %35, %36, %37, %38, %39, %40, %41, %42, %43, %44, %45, %46, %47, %48, %49, %50, %51, %52, %53, %54, %55, %56, %57, %58, %59, %60, %61, %62, %63}, {%64, %65, %66, %67}, %68, 0, 1, 1, 1;\n"
        : "=f"(d[0]), "=f"(d[1]), "=f"(d[2]), "=f"(d[3]), "=f"(d[4]), "=f"(d[5]), "=f"(d[6]), "=f"(d[7]),
          "=f"(d[8]), "=f"(d[9]), "=f"(d[10]), "=f"(d[11]), "=f"(d[12]), "=f"(d[13]), "=f"(d[14]), "=f"(d[15]),
          "=f"(d[16]), "=f"(d[17]), "=f"(d[18]), "=f"(d[19]), "=f"(d[20]), "=f"(d[21]), "=f"(d[22]), "=f"(d[23]),
          "=f"(d[24]), "=f"(d[25]), "=f"(d[26]), "=f"(d[27]), "=f"(d[28]), "=f"(d[29]), "=f"(d[30]), "=f"(d[31]),
          "=f"(d[32]), "=f"(d[33]), "=f"(d[34]), "=f"(d[35]), "=f"(d[36]), "=f"(d[37]), "=f"(d[38]), "=f"(d[39]),
          "=f"(d[40]), "=f"(d[41]), "=f"(d[42]), "=f"(d[43]), "=f"(d[44]), "=f"(d[45]), "=f"(d[46]), "=f"(d[47]),
          "=f"(d[48]), "=f"(d[49]), "=f"(d[50]), "=f"(d[51]), "=f"(d[52]), "=f"(d[53]), "=f"(d[54]), "=f"(d[55]),
          "=f"(d[56]), "=f"(d[57]), "=f"(d[58]), "=f"(d[59]), "=f"(d[60]), "=f"(d[61]), "=f"(d[62]), "=f"(d[63])
        : "r"(a0), "r"(a1), "r"(a2), "r"(a3), "l"(db));
}

__device__ __forceinline__ void wg_fence() { asm volatile("wgmma.fence.sync.aligned;\n" ::: "memory"); }
__device__ __forceinline__ void wg_commit() { asm volatile("wgmma.commit_group.sync.aligned;\n" ::: "memory"); }
template <int N> __device__ __forceinline__ void wg_wait() { asm volatile("wgmma.wait_group.sync.aligned %0;\n" ::"n"(N) : "memory"); }
template <int N> __device__ __forceinline__ void fence_regs(float (&a)[N]) {
#pragma unroll
    for (int i = 0; i < N; i++) asm volatile("" : "+f"(a[i])::"memory");
}
template <int N> __device__ __forceinline__ void fence_regs(uint32_t (&a)[N]) {
#pragma unroll
    for (int i = 0; i < N; i++) asm volatile("" : "+r"(a[i])::"memory");
}
__device__ __forceinline__ uint64_t desc64(uint32_t lo) { return (uint64_t)lo | (0x40000100ull << 32); }
__device__ __forceinline__ uint64_t desc64k(uint32_t lo) { return (uint64_t)lo | (0x40000080ull << 32); }
__device__ __forceinline__ void mbar_init(uint32_t bar, uint32_t cnt) {
    asm volatile("mbarrier.init.shared::cta.b64 [%0], %1;\n" ::"r"(bar), "r"(cnt) : "memory");
}
__device__ __forceinline__ void mbar_expect_tx(uint32_t bar, uint32_t bytes) {
    asm volatile("mbarrier.arrive.expect_tx.shared::cta.b64 _, [%0], %1;\n" ::"r"(bar), "r"(bytes) : "memory");
}
__device__ __forceinline__ void mbar_wait(uint32_t bar, uint32_t parity) {
    asm volatile("{\n.reg .pred p;\n.reg .u32 c;\nmbarrier.try_wait.parity.shared::cta.b64 p, [%0], %1;\n@p bra LD;\nmov.u32 c, 0;\n"
                 "LW:\nmbarrier.try_wait.parity.shared::cta.b64 p, [%0], %1;\n@p bra LD;\n"
                 "add.u32 c, c, 1;\nsetp.ge.u32 p, c, 67108864;\n@p trap;\nbra LW;\nLD:\n}\n" ::"r"(bar), "r"(parity) : "memory");
}
__device__ __forceinline__ void mbar_wait_sleep(uint32_t bar, uint32_t parity) {
    asm volatile("{\n.reg .pred p;\n.reg .u32 c;\nmov.u32 c, 0;\nLW:\nmbarrier.try_wait.parity.shared::cta.b64 p, [%0], %1, 20000;\n@p bra LD;\n"
                 "add.u32 c, c, 1;\nsetp.ge.u32 p, c, 1048576;\n@p trap;\nbra LW;\nLD:\n}\n" ::"r"(bar), "r"(parity) : "memory");
}
__device__ __forceinline__ void flag_wait(const int* p, int v) {
    asm volatile("{\n.reg .pred p;\n.reg .u32 c;\n.reg .s32 f;\nmov.u32 c, 0;\nLW:\nld.acquire.gpu.global.s32 f, [%0];\nsub.s32 f, f, %1;\nsetp.ge.s32 p, f, 0;\n@p bra LD;\n"
                 "add.u32 c, c, 1;\nsetp.ge.u32 p, c, 16777216;\n@p trap;\nbra LW;\nLD:\n}\n" ::"l"(p), "r"(v) : "memory");
}
__device__ __forceinline__ void flag_wait_sleep(const int* p, int v) {
    asm volatile("{\n.reg .pred p;\n.reg .u32 c;\n.reg .s32 f;\nmov.u32 c, 0;\nLW:\nld.acquire.gpu.global.s32 f, [%0];\nsub.s32 f, f, %1;\nsetp.ge.s32 p, f, 0;\n@p bra LD;\n"
                 "nanosleep.u32 500;\nadd.u32 c, c, 1;\nsetp.ge.u32 p, c, 4194304;\n@p trap;\nbra LW;\nLD:\n}\n" ::"l"(p), "r"(v) : "memory");
}
__device__ __forceinline__ void bulk_g2s(uint32_t dst, const void* src, uint32_t bytes, uint32_t bar) {
    asm volatile("cp.async.bulk.shared::cluster.global.mbarrier::complete_tx::bytes [%0], [%1], %2, [%3];\n"
                 ::"r"(dst), "l"(src), "r"(bytes), "r"(bar) : "memory");
}
__device__ __forceinline__ void bulk_g2s_mc(uint32_t dst, const void* src, uint32_t bytes, uint32_t bar, uint16_t mask) {
    asm volatile("cp.async.bulk.shared::cluster.global.mbarrier::complete_tx::bytes.multicast::cluster [%0], [%1], %2, [%3], %4;\n"
                 ::"r"(dst), "l"(src), "r"(bytes), "r"(bar), "h"(mask) : "memory");
}
__device__ __forceinline__ void tma_g2s(uint32_t dst, const CUtensorMap* tm, int rowgroup, uint32_t bar) {
    asm volatile("cp.async.bulk.tensor.4d.shared::cluster.global.tile.mbarrier::complete_tx::bytes [%0], [%1, {0, 0, 0, %2}], [%3];\n"
                 ::"r"(dst), "l"(tm), "r"(rowgroup), "r"(bar) : "memory");
}
__device__ __forceinline__ void bar_sync(int id, int n) { asm volatile("bar.sync %0, %1;\n" ::"r"(id), "r"(n) : "memory"); }
__device__ __forceinline__ void bar_arrive(int id, int n) { asm volatile("bar.arrive %0, %1;\n" ::"r"(id), "r"(n) : "memory"); }
__device__ __forceinline__ void cluster_sync() {
    asm volatile("barrier.cluster.arrive.relaxed.aligned;\nbarrier.cluster.wait.acquire.aligned;\n" ::: "memory");
}
__device__ __forceinline__ float shfl_f32(float v, int src) {
    float r; asm volatile("shfl.sync.idx.b32 %0, %1, %2, 31, -1;\n" : "=f"(r) : "f"(v), "r"(src)); return r;
}
__device__ __forceinline__ float ex2(float x) { float y; asm("ex2.approx.ftz.f32 %0, %1;\n" : "=f"(y) : "f"(x)); return y; }
__device__ __forceinline__ uint32_t pack_bf16(float lo, float hi) {
    uint32_t r; asm("cvt.rn.bf16x2.f32 %0, %1, %2;\n" : "=r"(r) : "f"(hi), "f"(lo)); return r;
}
__device__ __forceinline__ uint32_t pack_f16(float lo, float hi) {
    uint32_t r; asm("cvt.rn.f16x2.f32 %0, %1, %2;\n" : "=r"(r) : "f"(hi), "f"(lo)); return r;
}
__device__ __forceinline__ uint32_t pack_f16_sat(float lo, float hi) {
    uint32_t r; asm("cvt.rn.satfinite.f16x2.f32 %0, %1, %2;\n" : "=r"(r) : "f"(hi), "f"(lo)); return r;
}
__device__ __forceinline__ float f16_lo(uint32_t v) { float r; asm("cvt.f32.f16 %0, %1;\n" : "=f"(r) : "h"((unsigned short)v)); return r; }
__device__ __forceinline__ float f16_hi(uint32_t v) { return f16_lo(v >> 16); }
__device__ __forceinline__ float bf_lo(uint32_t v) { return __uint_as_float(v << 16); }
__device__ __forceinline__ float bf_hi(uint32_t v) { return __uint_as_float(v & 0xFFFF0000u); }
__device__ __forceinline__ float bf_round(float x) { return __uint_as_float(pack_bf16(0.f, x)); }
__device__ __forceinline__ void st_release(int* p, int v) {
    asm volatile("st.release.gpu.global.s32 [%0], %1;\n" ::"l"(p), "r"(v) : "memory");
}
__device__ __forceinline__ uint4 ldg_pinned(const uint4* p) {
    uint4 v; asm volatile("ld.global.nc.v4.u32 {%0, %1, %2, %3}, [%4];\n" : "=r"(v.x), "=r"(v.y), "=r"(v.z), "=r"(v.w) : "l"(p) : "memory"); return v;
}
__device__ __forceinline__ void stmatrix_x4(uint32_t addr, uint32_t r0, uint32_t r1, uint32_t r2, uint32_t r3) {
    asm volatile("stmatrix.sync.aligned.m8n8.x4.shared.b16 [%0], {%1, %2, %3, %4};\n" ::"r"(addr), "r"(r0), "r"(r1), "r"(r2), "r"(r3) : "memory");
}

__device__ __forceinline__ uint32_t tile_off(int r, int ch) {
    return (uint32_t)((r >> 3) * 4096 + (ch >> 3) * 1024 + (r & 7) * 128 + (((ch ^ r) & 7) << 4));
}
__device__ __forceinline__ int h_unit(int qt, int u) { return qt < 78 ? u * 78 + qt : 624; }
__device__ __forceinline__ int row_off(int r) { return 4096 + h_unit(r >> 7, (r >> 4) & 7) * 8192 + (r & 8) * 512 + (r & 7) * 144; }

__device__ __forceinline__ float2 lds64f(uint32_t a) { float2 v; asm volatile("ld.shared.v2.f32 {%0, %1}, [%2];\n" : "=f"(v.x), "=f"(v.y) : "r"(a) : "memory"); return v; }
__device__ __forceinline__ uint64_t lds64(uint32_t a) { uint64_t v; asm volatile("ld.shared.u64 %0, [%1];\n" : "=l"(v) : "r"(a) : "memory"); return v; }
__device__ __forceinline__ uint4 lds128(uint32_t a) {
    uint4 v; asm volatile("ld.shared.v4.u32 {%0, %1, %2, %3}, [%4];\n" : "=r"(v.x), "=r"(v.y), "=r"(v.z), "=r"(v.w) : "r"(a) : "memory"); return v;
}
__device__ __forceinline__ void sts128(uint32_t a, uint32_t x, uint32_t y, uint32_t z, uint32_t w) {
    asm volatile("st.shared.v4.u32 [%0], {%1, %2, %3, %4};\n" ::"r"(a), "r"(x), "r"(y), "r"(z), "r"(w) : "memory");
}
__device__ __forceinline__ void mbar_arrive(uint32_t bar) {
    asm volatile("mbarrier.arrive.shared::cta.b64 _, [%0];\n" ::"r"(bar) : "memory");
}
__device__ __forceinline__ uint64_t mkaddr(uint32_t lo, uint32_t hi) { uint64_t a; asm("mov.b64 %0, {%1, %2};\n" : "=l"(a) : "r"(lo), "r"(hi)); return a; }
__device__ __forceinline__ void red_release(int* p) {
    asm volatile("fence.proxy.async.global;\nfence.acq_rel.gpu;\nred.relaxed.gpu.global.add.s32 [%0], 1;\n" ::"l"(p) : "memory");
}
__device__ __forceinline__ void fence_async_global() { asm volatile("fence.proxy.async.global;\n" ::: "memory"); }
__device__ __forceinline__ void fence_async_smem() { asm volatile("fence.proxy.async.shared::cta;\n" ::: "memory"); }
__device__ __forceinline__ void bulk_s2g(void* dst, uint32_t src, uint32_t bytes) {
    asm volatile("cp.async.bulk.global.shared::cta.bulk_group [%0], [%1], %2;\ncp.async.bulk.commit_group;\n" ::"l"(dst), "r"(src), "r"(bytes) : "memory");
}
__device__ __forceinline__ void mma16816(float (&c)[4], uint32_t a0, uint32_t a1, uint32_t a2, uint32_t a3, uint32_t b0, uint32_t b1) {
    asm("mma.sync.aligned.m16n8k16.row.col.f32.bf16.bf16.f32 {%0, %1, %2, %3}, {%4, %5, %6, %7}, {%8, %9}, {%0, %1, %2, %3};\n"
        : "+f"(c[0]), "+f"(c[1]), "+f"(c[2]), "+f"(c[3]) : "r"(a0), "r"(a1), "r"(a2), "r"(a3), "r"(b0), "r"(b1));
}
__device__ __forceinline__ void mma1688(float (&c)[4], uint32_t a0, uint32_t a1, uint32_t b0) {
    asm("mma.sync.aligned.m16n8k8.row.col.f32.bf16.bf16.f32 {%0, %1, %2, %3}, {%4, %5}, {%6}, {%0, %1, %2, %3};\n"
        : "+f"(c[0]), "+f"(c[1]), "+f"(c[2]), "+f"(c[3]) : "r"(a0), "r"(a1), "r"(b0));
}
__device__ __forceinline__ uint32_t hadd2_f16(uint32_t a, uint32_t b) { uint32_t r; asm("add.rn.f16x2 %0, %1, %2;\n" : "=r"(r) : "r"(a), "r"(b)); return r; }
__device__ __forceinline__ uint32_t hfma2(uint32_t a, uint32_t b, uint32_t c) { uint32_t r; asm("fma.rn.bf16x2 %0, %1, %2, %3;\n" : "=r"(r) : "r"(a), "r"(b), "r"(c)); return r; }

constexpr int SM_Q = 0;
constexpr int SM_KV = 65536;
constexpr int SM_ML = SM_KV + STAGES * KV_BYTES;
constexpr int SM_BAR = SM_ML + 1024;
constexpr int SM_TOTAL = SM_BAR + 256;
constexpr float SCALE_LOG2 = 1.4426950408889634f / 16.0f;
constexpr float KV_SCALE = 0.75f;
constexpr float KV_OFF = 6.f;
constexpr uint32_t KV_OFF2 = 0x46004600u;
constexpr uint32_t KV_NEG4 = 0xCE00CE00u;
constexpr uint32_t P_LIMIT = 0x78007800u;
__device__ __forceinline__ uint32_t kvf(uint32_t a) {
    uint32_t r; asm("fma.rn.f16x2 %0, %1, %2, %3;\n" : "=r"(r) : "r"(a), "r"(pack_f16(KV_SCALE, KV_SCALE)), "r"(KV_OFF2)); return r;
}
enum { BAR_PP0 = 1, BAR_PP1 = 2, BAR_WG0 = 3, BAR_WG1 = 4, BAR_H0 = 5, BAR_WG2 = 6, BAR_AUX = 7, BAR_BF = 8, BAR_H1 = 9, BAR_X = 10, BAR_GO = 11, BAR_H2 = 12, BAR_ST = 13 };

struct Sched { int qt0, kv0, n0, qt1, kv1, n1, owner, pin, mc, pair, zb, nz; };
static Sched get_sched(int c, int r) {
    Sched s;
    s.mc = 0; s.qt1 = s.kv1 = s.n1 = 0; s.pin = 0; s.zb = s.nz = 0; s.pair = c < 52; s.kv0 = 0; s.n0 = 75;
    if (c < 52) {
        const int p = c >> 1, odd = c & 1, tc = p, ta = 26 + 2 * p, tb = ta + 1;
        s.owner = r == 0; s.pin = odd; s.kv0 = odd ? 75 : 25;
        s.zb = 2 * (odd ? tb : ta) + 1 - r;
        if (r == 0) {
            s.qt0 = odd ? tb : ta;
        } else if (!odd) {
            s.qt0 = tb; s.n0 = 25; s.qt1 = ta; s.kv1 = 100; s.n1 = 50;
        } else {
            s.qt0 = tc; s.n0 = 50; s.qt1 = tb; s.kv1 = 50; s.n1 = 25;
        }
    } else if (c < 65) {
        s.owner = 1; s.mc = 1; s.qt0 = 2 * (c - 52) + r; s.pin = 1;
    } else {
        s.qt0 = 78; s.owner = (r == 0); s.kv0 = r ? 75 : 0; s.n0 = r ? 50 : 75; s.pin = r ? 0 : 1;
        s.zb = r ? 156 : 0; s.nz = r ? 27 : 26;
    }
    return s;
}

struct Hot {
    const __nv_bfloat16 *wk, *wq, *x;
    Scratch* s;
};
struct Params {
    const __nv_bfloat16* deg_inv;
    const int *src, *dst;
    __nv_bfloat16* out;
    uint32_t dhi;
    int E;
    uint32_t sched[NCTA][3];
    CUtensorMap tm_out;
    CUtensorMap tm_outc;
    CUtensorMap tm_w[3];
};
static_assert(offsetof(Params, tm_outc) == offsetof(Params, tm_out) + 128, "layout");
#define SC_QT(seg) ((int)(P.sched[blockIdx.x][seg] & 255))
#define SC_KV(seg) ((int)((P.sched[blockIdx.x][seg] >> 8) & 255))
#define SC_N(seg) ((int)((P.sched[blockIdx.x][seg] >> 16) & 255))
#define SC_OWNER ((P.sched[blockIdx.x][0] >> 24) & 1)
#define SC_PIN ((P.sched[blockIdx.x][0] >> 25) & 1)
#define SC_MC ((P.sched[blockIdx.x][0] >> 27) & 1)
#define SC_PAIR ((P.sched[blockIdx.x][0] >> 28) & 1)
#define SC_NZ ((int)(P.sched[blockIdx.x][2] >> 8))
#define SC_ZB(k) ((int)(P.sched[blockIdx.x][2] & 255) + 2 * (k) - ((P.sched[blockIdx.x][2] & 255) + 2 * (k) >= 157 ? 157 : 0))
#define SC_TAIL (blockIdx.x >= NCTA - 2)

__global__ void __cluster_dims__(2, 1, 1) __launch_bounds__(384, 1) k_main(const __grid_constant__ Hot H, const __grid_constant__ Params P) {
    extern __shared__ __align__(1024) uint8_t smem[];
    const uint32_t sb = (uint32_t)__cvta_generic_to_shared(smem);
    const int tid = threadIdx.x, wg = __shfl_sync(~0u, tid >> 7, 0);
    const int lane = tid & 31, g = lane >> 2, q = lane & 3;
    const uint32_t rank = blockIdx.x & 1;
    const uint32_t bar_full = sb + SM_BAR, bar_empty = bar_full + 32, bar_q = bar_full + 64;
    const uint32_t bar_qfree = bar_full + 80, bar_pdone = bar_full + 96, bar_zst = bar_full + 112, bar_x = bar_full + 128, bar_rfree = bar_full + 192, s_tm = bar_full + 208, bar_go = bar_full + 200;
    const uint32_t bar_pin = bar_full + 224;

    if (wg == 2) {
        const int warp = __shfl_sync(~0u, (tid >> 5) & 3, 0);
        const int t = tid & 127;
        unsigned done;
        {
            uint4 ra[8], rb[8], rk[8], rz[8];
            if (blockIdx.x < 128) {
                const int rg = blockIdx.x >> 2;
                const int e = (rg >> 2) * 32 + (g >> 1) * 8 + (rg & 2) * 2 + (rg & 1) * 2 + (g & 1);
                const int f = (blockIdx.x & 3) * 64 + (warp >> 1) * 32 + (g >> 1) * 8 + (warp & 1) * 4 + (g & 1);
                const uint4* pk = (const uint4*)(H.wk + f * 256 + q * 8);
                const uint4* pq = (const uint4*)(H.wq + e * 256 + q * 8);
                const uint4* pz = (const uint4*)(H.wk + 255 * 256) + q;
                asm volatile("" : "+l"(pz));
#pragma unroll
                for (int s = 0; s < 8; s++) {
                    ra[s] = ldg_pinned(pk + 4 * s);
                    rb[s] = ldg_pinned(pk + 4 * s + 64);
                    rk[s] = ldg_pinned(pq + 4 * s);
                    rz[s] = ldg_pinned(pz + 4 * s);
                }
            }
            asm volatile("{\n.reg .pred p;\nsetp.eq.s32 p, %2, 0;\nmov.u32 %0, 0;\n@p ld.global.cg.u32 %0, [%1];\n}\n" : "=r"(done) : "l"(&g_sync[SY_DONE * 32]), "r"(lane) : "memory");
            bar_arrive(BAR_X, 384);
            if (t == 0) {
                if (sb & 1023) asm volatile("trap;\n");
                for (int i = 0; i < STAGES; i++) { mbar_init(bar_full + 8 * i, 1); mbar_init(bar_empty + 8 * i, SC_TAIL ? 4 : SC_MC ? 16 : 8); }
                for (int i = 0; i < 2; i++) { mbar_init(bar_q + 8 * i, 1); mbar_init(bar_qfree + 8 * i, 4); mbar_init(bar_pdone + 8 * i, 4); }
                mbar_init(bar_zst, 4); mbar_init(bar_zst + 8, 4); mbar_init(bar_rfree, 4); mbar_init(bar_go, 1);
                for (int i = 0; i < 4; i++) { mbar_init(bar_pin + 8 * i, 1); mbar_expect_tx(bar_pin + 8 * i, QB_BYTES / 2 + ((i & 1) ? 0 : 512)); }
                asm volatile("fence.mbarrier_init.release.cluster;\n" ::: "memory");
            }
            __syncwarp();
            asm volatile("barrier.cluster.arrive.relaxed.aligned;\n" ::: "memory");
            if (blockIdx.x < 128) {
                float c0[4] = {0.f, 0.f, 0.f, 0.f}, c1[4] = {0.f, 0.f, 0.f, 0.f}, z0[4] = {0.f, 0.f, 0.f, 0.f}, z1[4] = {0.f, 0.f, 0.f, 0.f};
#pragma unroll
                for (int s = 0; s < 8; s++) {
                    mma16816(c0, ra[s].x, rb[s].x, ra[s].y, rb[s].y, rk[s].x, rk[s].y);
                    mma16816(c1, ra[s].z, rb[s].z, ra[s].w, rb[s].w, rk[s].z, rk[s].w);
                    mma16816(z0, rz[s].x, rz[s].x, rz[s].y, rz[s].y, rk[s].x, rk[s].y);
                    mma16816(z1, rz[s].z, rz[s].z, rz[s].w, rz[s].w, rk[s].z, rk[s].w);
                }
#pragma unroll
                for (int i = 0; i < 4; i++) c0[i] = ((c0[i] + c1[i]) - (z0[i] + z1[i])) * (SCALE_LOG2 / KV_SCALE);
                asm volatile("stmatrix.sync.aligned.m8n8.x2.trans.shared.b16 [%0], {%1, %2};\n"
                             ::"r"(sb + SM_ML + (lane & 7) * 128 + (((2 * warp + ((lane >> 3) & 1)) ^ lane) & 7) * 16),
                             "r"(pack_f16_sat(c0[0], c0[1])), "r"(pack_f16_sat(c0[2], c0[3])) : "memory");
                fence_async_smem();
            }
        }
        asm volatile("setmaxnreg.dec.sync.aligned.u32 %0;\n" ::"n"(REG_P));
        if (blockIdx.x < 128) {
            bar_sync(BAR_WG2, 128);
            if (t == 32) {
                bulk_s2g(g_w + blockIdx.x * 1024, sb + SM_ML, 1024);
                asm volatile("cp.async.bulk.wait_group 0;\n" ::: "memory");
                red_release(&g_sync[(SY_A + (blockIdx.x >> 5)) * 32]);
            }
            __syncwarp();
        }
        if (warp == 1) bar_arrive(BAR_GO, 160);
        done = __shfl_sync(~0u, done, 0);
        const int ep = (int)(done / NCTA) + 1;
        if (SC_TAIL) {
            bar_sync(BAR_WG2, 128);
            if (t == 32) atomicAdd(&g_sync[SY_DONE * 32], 1);
        }
        asm volatile("barrier.cluster.wait.acquire.aligned;\n" ::: "memory");
        if (warp == 0) {
            if (lane == 0) asm volatile("st.shared.u64 [%0], %1;\n" ::"r"(s_tm), "l"(&P.tm_out) : "memory");
            if (lane < 4) mbar_expect_tx(bar_full + 8 * lane, QB_BYTES);
            if (rank == 1) {
                flag_wait(&g_sync[(SY_A + (lane & 3)) * 32], 32 * ep);
                fence_async_global();
                __syncwarp();
                if (lane == 0) {
#pragma unroll
                    for (int j = 0; j < 4; j++) bulk_g2s_mc(sb + SM_KV + j * KV_BYTES, g_w + j * QB_BYTES, QB_BYTES, bar_full + 8 * j, 3);
                }
            }
            if (lane == 0) {
                int it = 4;
                auto load = [&](const uint8_t* src, uint32_t bytes) {
                    const int st = it & (STAGES - 1);
                    mbar_wait_sleep(bar_empty + 8 * st, ((it / STAGES) & 1) ^ 1);
                    mbar_expect_tx(bar_full + 8 * st, bytes);
                    const uint32_t dst = sb + SM_KV + st * KV_BYTES;
                    if (SC_MC) bulk_g2s_mc(dst + rank * (bytes / 2), src + rank * (bytes / 2), bytes / 2, bar_full + 8 * st, 3);
                    else bulk_g2s(dst, src, bytes, bar_full + 8 * st);
                    if (it == GO0 || it == GO1) mbar_arrive(bar_go);
                    it++;
                };
                auto place = [&](int j) {
                    if (j >= NKV) j -= NKV;
                    return (unsigned)(j - 4) < 4 ? j + 21 : (unsigned)(j - 8) < 4 ? j + 67 : (unsigned)(j - 25) < 4 ? j - 21 : (unsigned)(j - 75) < 4 ? j - 67 : j;
                };
#pragma unroll 1
                for (int j = 0; j < SC_N(0); j++) {
                    const int pl = place(SC_KV(0) + j);
                    if (j <= 4) {
                        if (j < 4) flag_wait(&g_sync[(SY_H0 + pl) * 32], 5 * ep);
                        else flag_wait(&g_sync[SY_H1 * 32], 79 * ep);
                        fence_async_global();
                    }
                    load(g_hz + 4096 + pl * KV_BYTES, KV_BYTES);
                }
#pragma unroll 1
                for (int j = 0; j < SC_N(1); j++) {
                    if (j == 2) {
                        flag_wait(&g_qflag[SC_QT(1)], ep);
                        fence_async_global();
#pragma unroll 1
                        for (int w = 0; w < 2; w++) {
                            mbar_wait_sleep(bar_qfree + 8 * w, 0);
                            mbar_expect_tx(bar_q + 8 * w, QB_BYTES);
                            bulk_g2s(sb + SM_Q + w * QB_BYTES, g_q + (2 * SC_QT(1) + 1 - w) * QB_BYTES, QB_BYTES, bar_q + 8 * w);
                        }
                    }
                    if ((j | 1) == 3) {
                        mbar_wait_sleep(bar_pdone + 8 * (j - 2), 0);
                        bulk_s2g(g_part + (2 * SC_QT(0) + j - 2) * PART_BYTES, sb + SM_KV + (it & 3) * KV_BYTES, PART_BYTES);
                        asm volatile("cp.async.bulk.wait_group.read 0;\n" ::: "memory");
                    } else if (j == 5) {
                        asm volatile("cp.async.bulk.wait_group 0;\nfence.proxy.async.global;\n" ::: "memory");
                        st_release(&g_pflag[SC_QT(0)], ep);
                    }
                    load(g_hz + 4096 + place(SC_KV(1) + j) * KV_BYTES, KV_BYTES);
                }
                asm volatile("prefetch.tensormap [%0];\n" ::"l"(blockIdx.x != NCTA - 1 ? &P.tm_outc : &P.tm_out) : "memory");
                const bool early_w = blockIdx.x != NCTA - 1;
                auto load_agg = [&](int k) {
                    mbar_expect_tx(bar_q + 8 * (k & 1), QB_BYTES);
                    bulk_g2s(sb + SM_Q + (k & 1) * QB_BYTES, g_agg + SC_ZB(k) * QB_BYTES, QB_BYTES, bar_q + 8 * (k & 1));
                };
                if (early_w) {
                    flag_wait(&g_sync[SY_B * 32], ep);
                    if (SC_TAIL) flag_wait_sleep(&g_sync[SY_AUX0 * 32], NAUX * ep);
                    else flag_wait(&g_sync[SY_AUX * 32], NAUX / 3 * ep);
                    if (SC_PIN) flag_wait(&g_pflag[SC_PAIR ? SC_ZB(0) >> 1 : SC_QT(0)], ep);
                    fence_async_global();
                    if (SC_PAIR) {
#pragma unroll 1
                        for (int j = 0; j < 4; j++) {
                            if (j == 2) { mbar_wait_sleep(bar_qfree, rank); load_agg(0); }
                            if (SC_PIN) {
                                mbar_wait_sleep(bar_empty + 8 * (it & 3), ((it / STAGES) & 1) ^ 1);
                                if (j == 0) bulk_g2s(sb + SM_ML, g_part + SC_ZB(0) * PART_BYTES + QB_BYTES, 512, bar_pin);
                                bulk_g2s(sb + SM_KV + (it & 3) * KV_BYTES + QB_BYTES, g_part + SC_ZB(0) * PART_BYTES + j * 8192, 8192, bar_pin + (j >> 1) * 8);
                            }
                            load(g_w + (8 + j) * QB_BYTES, QB_BYTES);
                        }
                    }
#pragma unroll 1
                    for (int j = 0; j < 4; j++) {
                        if (j == 2 && !SC_PAIR) {
#pragma unroll 1
                            for (int w = 0; w < (SC_TAIL ? 1 : 2); w++) {
                                const uint8_t* src = g_part + (2 * SC_QT(0) + w) * PART_BYTES;
                                mbar_wait_sleep(bar_qfree + 8 * w, 0);
                                bulk_g2s(sb + SM_ML + w * 512, src + QB_BYTES, 512, bar_pin + 16 * w);
                                bulk_g2s(sb + SM_Q + w * QB_BYTES, src, QB_BYTES / 2, bar_pin + 16 * w);
                                bulk_g2s(sb + SM_Q + w * QB_BYTES + QB_BYTES / 2, src + QB_BYTES / 2, QB_BYTES / 2, bar_pin + 16 * w + 8);
                            }
                        }
                        load(g_w + (4 + j) * QB_BYTES, QB_BYTES);
                    }
                } else {
                    mbar_wait_sleep(bar_pdone, 0);
                    bulk_s2g(g_part + 2 * SC_QT(0) * PART_BYTES, sb + SM_Q, PART_BYTES);
                    asm volatile("cp.async.bulk.wait_group 0;\nfence.proxy.async.global;\n" ::: "memory");
                    st_release(&g_pflag[SC_QT(0)], ep);
                }
                if (SC_TAIL) {
                    int k0 = 0;
                    if (!early_w) {
#pragma unroll 1
                        for (int j = 0; j < 4; j++) {
                            const int st = it & (STAGES - 1);
                            mbar_wait_sleep(bar_empty + 8 * st, ((it / STAGES) & 1) ^ 1);
                            mbar_expect_tx(bar_full + 8 * st, QB_BYTES);
                            tma_g2s(sb + SM_KV + st * KV_BYTES, &P.tm_w[2], 8 * j, bar_full + 8 * st);
                            it++;
                        }
#pragma unroll 1
                        for (; k0 < 8; k0++) {
                            mbar_wait_sleep(bar_qfree + 8 * (k0 & 1), ((k0 >> 1) ^ (k0 & 1) ^ 1) & 1);
                            mbar_expect_tx(bar_q + 8 * (k0 & 1), QB_BYTES);
#pragma unroll 1
                            for (int hf = 0; hf < 2; hf++)
                                asm volatile("cp.async.bulk.tensor.5d.shared::cluster.global.tile.mbarrier::complete_tx::bytes [%0], [%1, {0, 0, %2, 0, 0}], [%3];\n"
                                             ::"r"(sb + SM_Q + (k0 & 1) * QB_BYTES + hf * 16384), "l"(&P.tm_w[k0 & 1]),
                                             "r"(8 * (((k0 >> 1) + 3) & 3) + 4 * hf), "r"(bar_q + 8 * (k0 & 1)) : "memory");
                        }
                        flag_wait_sleep(&g_sync[SY_B * 32], ep);
                        flag_wait_sleep(&g_sync[SY_AUX0 * 32], NAUX * ep);
                        fence_async_global();
                    }
#pragma unroll 1
                    for (int j = 0; j < 4; j++) load(g_w + (8 + j) * QB_BYTES, QB_BYTES);
#pragma unroll 1
                    for (int k = 0; k < SC_NZ; k++) {
                        if (k == ((GF0 + 1) * NAUX - 16) / 128) { flag_wait_sleep(&g_sync[SY_AUX1 * 32], NAUX * ep); fence_async_global(); }
                        mbar_wait_sleep(bar_qfree + 8 * (k & 1), ((k >> 1) ^ (k & 1) ^ 1) & 1);
                        load_agg(k);
                    }
                }
            }
        } else {
            if (warp == 2 && SC_OWNER) {
                auto send = [&](int u0, int u1) {
#pragma unroll 1
                    for (int o = u0 * 8192; o < u1 * 8192; o += HPIECE) {
                        bulk_s2g(g_hz + 4096 + h_unit(SC_QT(0), o >> 13) * 8192 + (o & 8191), sb + SM_Q + o, HPIECE);
                        asm volatile("cp.async.bulk.wait_group 0;\n" ::: "memory");
                    }
                };
                bar_sync(BAR_H0, 64);
                if (lane == 0) {
                    send(0, 1);
                    if (SC_QT(0) < 60) red_release(&g_sync[(SY_H0 + SC_QT(0) / 5) * 32]);
                }
                bar_sync(BAR_H1, 160);
                if (lane == 0) {
                    if (!SC_TAIL) send(1, 4);
                    mbar_arrive(bar_q);
                }
                bar_sync(BAR_H2, 160);
                if (lane == 0) {
                    if (!SC_TAIL) { send(4, 8); mbar_arrive(bar_q + 8); }
                    red_release(&g_sync[SY_H1 * 32]);
                }
                __syncwarp();
            }
            if (t == 96 && SC_OWNER && SC_PAIR) {
                flag_wait_sleep(&g_sync[SY_H1 * 32], 79 * ep);
                mbar_wait_sleep(bar_pdone, 0);
                mbar_wait_sleep(bar_pdone + 8, 0);
#pragma unroll 1
                for (int u = 0; u < 16; u++) {
                    bulk_s2g(g_q + SC_QT(0) * (2 * QB_BYTES) + u * 4096, sb + SM_Q + u * 4096, 4096);
                    asm volatile("cp.async.bulk.wait_group 0;\n" ::: "memory");
                }
                fence_async_global();
                st_release(&g_qflag[SC_QT(0)], ep);
            }
            __syncwarp();
            if (!SC_TAIL) {
            mbar_wait_sleep(bar_go, 0);
            const int par = ep & 1;
            if (blockIdx.x == 0 && t == 32) g_ovf_n[par ^ 1] = 0;
            if (blockIdx.x == 0 && warp == 1) *(uint4*)(g_hz + (lane >> 3) * 1024 + (lane & 7) * 16) = make_uint4(KV_OFF2, KV_OFF2, KV_OFF2, KV_OFF2);
            const uint32_t wlo = (uint32_t)(uintptr_t)H.s, whi = (uint32_t)((uintptr_t)H.s >> 32);
            const uint32_t blo = wlo + (uint32_t)offsetof(Scratch, bucket);
            {
                constexpr int NE = (MAXE + NAUX * 32 - 1) / (NAUX * 32);
                const int e0 = blockIdx.x * 96 + (t - 32);
                const int* pd = P.dst + e0;
                const int* ps = P.src + e0;
                int d[NE], sl[NE];
#pragma unroll
                for (int i = 0; i < NE; i++) {
                    const bool ok = e0 + i * NAUX * 32 < P.E;
                    d[i] = ok ? __ldg(pd + i * NAUX * 32) : -1;
                    sl[i] = ok ? __ldg(ps + i * NAUX * 32) : 0;
                }
#pragma unroll
                for (int i = 0; i < NE; i++) {
                    const uint64_t ca = mkaddr(wlo + (uint32_t)offsetof(Scratch, cnt) + d[i] * 4, whi);
                    d[i] = d[i] << 16 | sl[i];
                    asm volatile("{\n.reg .pred p;\nsetp.ge.s32 p, %2, 0;\n@p atom.relaxed.gpu.global.add.s32 %0, [%1], 1;\n}\n" : "+r"(sl[i]) : "l"(ca), "r"(d[i]) : "memory");
                }
                uint32_t ov = 0;
#pragma unroll
                for (int i = 0; i < NE; i++) {
                    asm volatile("{\n.reg .pred p;\nsetp.ne.s32 p, %2, 0;\n@p st.global.s32 [%0], %1;\n}\n"
                                 ::"l"(mkaddr(blo + ((d[i] >> 16) * CAP + sl[i]) * 4, whi)), "r"(row_off(d[i] & 0xFFFF)), "r"((int)(d[i] >= 0 && sl[i] < CAP)) : "memory");
                    if (sl[i] >= CAP) ov |= 1u << i;
                }
#pragma unroll 1
                for (; ov; ov &= ov - 1) {
                    const int i = __ffs(ov) - 1;
                    g_ovf[atomicAdd(&g_ovf_n[par], 1)] = make_int2(__ldg(pd + i * NAUX * 32), row_off(__ldg(ps + i * NAUX * 32)));
                }
            }
            bar_sync(BAR_AUX, 96);
            if (t == 32) { red_release(&g_sync[SY_CSR * 32]); }
            __syncwarp();
            {
                const int r0 = blockIdx.x * 3 + warp - 1;
                const uint4* xp = (const uint4*)(H.x + r0 * 256) + lane;
                uint4* op = (uint4*)(P.out + r0 * 256) + lane;
#pragma unroll 1
                for (int r = r0; r < NN; r += 9 * NAUX, xp += 9 * NAUX * 32, op += 9 * NAUX * 32) {
                    uint4 v[9];
#pragma unroll
                    for (int i = 0; i < 9; i++) if (r + i * NAUX < NN) v[i] = ldg_pinned(xp + i * NAUX * 32);
#pragma unroll
                    for (int i = 0; i < 9; i++) if (r + i * NAUX < NN) op[i * NAUX * 32] = v[i];
                }
            }
            flag_wait_sleep(&g_sync[SY_CSR * 32], NAUX / 3 * ep);
            {
                const uint32_t lc = (lane >> 3) * 1024 + (lane & 7) * 16;
                const uint32_t alo = wlo ^ lc;
                const int node0 = blockIdx.x * 3 + warp - 17;
                auto node = [&](int i) { const int nd = node0 + i * NAUX; return (int)min((unsigned)nd, (unsigned)(nd + NN)); };
                const int num = (NN - 17 - node0) / NAUX + 1;
                uint32_t mine = 0;
                if (lane < num) {
                    mine = min(__ldcg(&g_cnt[node(lane)]), CAP + 1) | (uint32_t)__ldg((const unsigned short*)P.deg_inv + node(lane)) << 16;
                    g_cnt[node(lane)] = 0;
                }
                auto row = [&](int off) {
                    uint4 v;
                    asm volatile("ld.global.v4.u32 {%0, %1, %2, %3}, [%4];\n"
                                 : "=r"(v.x), "=r"(v.y), "=r"(v.z), "=r"(v.w) : "l"(mkaddr(alo ^ off, whi)));
                    return v;
                };
                auto ents = [&](int i) {
                    int e;
                    asm volatile("ld.global.cg.s32 %0, [%1];\n" : "=r"(e) : "l"(mkaddr(blo + (min(node(i), NN - 1) * CAP + lane) * 4, whi)));
                    return e;
                };
                auto store = [&](int i, const float (&a)[8]) {
                    const float di = bf_hi(__shfl_sync(~0u, mine, i)) * (1.f / KV_SCALE);
                    const int nd = node(i);
                    *(uint4*)(g_agg + (uint32_t)(((nd >> 3) * 4096 + (nd & 7) * 144) ^ lc)) =
                        make_uint4(pack_bf16(a[0] * di, a[1] * di), pack_bf16(a[2] * di, a[3] * di), pack_bf16(a[4] * di, a[5] * di), pack_bf16(a[6] * di, a[7] * di));
                };
#pragma unroll 1
                for (uint32_t big = __ballot_sync(~0u, (mine & 0xFFFF) > CAP); big; big &= big - 1) {
                    const int i = __ffs(big) - 1, no = __ldcg(&g_ovf_n[par]);
                    float a[8] = {};
#pragma unroll 1
                    for (int k = -32; k < no; k += 32) {
                        const int2 pr = k < 0 ? make_int2(node(i), ents(i)) : k + lane < no ? __ldcg(&g_ovf[k + lane]) : make_int2(-1, 0);
#pragma unroll 1
                        for (uint32_t mk = __ballot_sync(~0u, pr.x == node(i)); mk; mk &= mk - 1) {
                            const uint4 v = row(__shfl_sync(~0u, pr.y, __ffs(mk) - 1));
                            a[0] += f16_lo(v.x) - KV_OFF; a[1] += f16_hi(v.x) - KV_OFF; a[2] += f16_lo(v.y) - KV_OFF; a[3] += f16_hi(v.y) - KV_OFF;
                            a[4] += f16_lo(v.z) - KV_OFF; a[5] += f16_hi(v.z) - KV_OFF; a[6] += f16_lo(v.w) - KV_OFF; a[7] += f16_hi(v.w) - KV_OFF;
                        }
                    }
                    store(i, a);
                }
                auto add4 = [&](const uint4& a, const uint4& b) { return make_uint4(hadd2_f16(a.x, b.x), hadd2_f16(a.y, b.y), hadd2_f16(a.z, b.z), hadd2_f16(a.w, b.w)); };
                int ni = -1, left = 0, pos = 0, ec = 0, en = ents(0);
                uint4 acc = make_uint4(0, 0, 0, 0);
                auto issue = [&](uint4 (&v)[4]) {
                    if (left <= 0) {
                        ni++;
                        if (ni == GSPLIT) mbar_wait_sleep(bar_go, 1);
                        left = __shfl_sync(~0u, mine, ni) & 0xFFFF;
                        if (left > CAP) left = 0;
                        ec = lane < left ? en : 0;
                        en = ents(ni + 1);
                        pos = 0;
                    }
#pragma unroll
                    for (int j = 0; j < 4; j++) v[j] = row(__shfl_sync(~0u, ec, pos + j));
                    pos += 4; left -= 4;
                    return left <= 0 ? ni : -1;
                };
                auto step = [&](uint4 (&v)[4], int& tag) {
                    acc = add4(acc, add4(add4(add4(v[0], v[1]), make_uint4(KV_NEG4, KV_NEG4, KV_NEG4, KV_NEG4)), add4(v[2], v[3])));
                    const int i = tag;
                    tag = issue(v);
                    if (i >= 0) {
                        const float a[8] = {f16_lo(acc.x), f16_hi(acc.x), f16_lo(acc.y), f16_hi(acc.y), f16_lo(acc.z), f16_hi(acc.z), f16_lo(acc.w), f16_hi(acc.w)};
                        if ((__shfl_sync(~0u, mine, i) & 0xFFFF) <= CAP) store(i, a);
                        acc = make_uint4(0, 0, 0, 0);
                        if (i == GF0 || i == 8) {
                            __syncwarp();
                            if (lane == 0) red_release(&g_sync[(i == 8 ? SY_AUX1 : SY_AUX0) * 32]);
                            __syncwarp();
                        }
                    }
                    return i == num - 1;
                };
                uint4 va[4], vb[4];
                int ta = issue(va), tb = issue(vb);
#pragma unroll 1
                while (!step(va, ta) && !step(vb, tb)) {}
            }
            bar_sync(BAR_AUX, 96);
            if (t == 32) {
                red_release(&g_sync[SY_AUX * 32]);
                atomicAdd(&g_sync[SY_DONE * 32], 1);
            }
            }
        }
        __syncwarp();
        cluster_sync();
    } else {
        const int t = tid & 127, warp = t >> 5;
        const uint32_t sq = sb + SM_Q + wg * QB_BYTES;
        const uint32_t qbar = bar_q + 8 * wg;
        const uint32_t dq0 = __shfl_sync(~0u, ((sq & 0x3FFFF) >> 4) | (64u << 16), 0);
        const uint32_t dk0 = __shfl_sync(~0u, (((sb + SM_KV) & 0x3FFFF) >> 4) | (64u << 16), 0);
        float o[128];
        int it = 0;
        uint32_t rel_addr;
        asm("mapa.shared::cluster.u32 %0, %1, %2;\n" : "=r"(rel_addr) : "r"(bar_empty), "r"(rank ^ (lane & 1)));
        if (lane >= (SC_MC ? 2 : 1)) rel_addr = 0;
        asm volatile("" : "+r"(rel_addr));
        auto release = [&](int st) {
            asm volatile("{\n.reg .pred p;\nsetp.ne.u32 p, %1, 0;\n@p mbarrier.arrive.shared::cluster.b64 _, [%0];\n}\n"
                         ::"r"(rel_addr + 8 * st), "r"(rel_addr) : "memory");
        };
        const bool active = !(SC_TAIL && wg == 1);
        const int nn = __shfl_sync(~0u, SC_N(0) | SC_N(1) << 8 | (active ? (SC_N(1) ? 2 : 1) : 0) << 16, 0);
        auto pp_sync = [&]() { if (!SC_TAIL) bar_sync(BAR_PP0 + wg, 256); };
        auto pp_arrive = [&]() { if (!SC_TAIL) bar_arrive(BAR_PP1 - wg, 256); };
        auto warp_arrive = [&](uint32_t bar) {
            __syncwarp();
            asm volatile("{\n.reg .pred p;\nsetp.eq.s32 p, %1, 0;\n@p mbarrier.arrive.shared::cta.b64 _, [%0];\n}\n" ::"r"(bar + 8 * wg), "r"(lane) : "memory");
        };
        auto stage_q = [&]() {
            auto pk = [&](int i) { return QRND(pack_f16_sat(o[i], o[i + 1])); };
#pragma unroll
            for (int i = 0; i < 16; i++)
                stmatrix_x4(sq + warp * 8192 + tile_off(lane & 15, 2 * i + (lane >> 4)), pk(8 * i), pk(8 * i + 2), pk(8 * i + 4), pk(8 * i + 6));
        };

        {
            const int rb = (2 * SC_QT(0) + wg) * 64 + warp * 16;
            const uint32_t xbar = bar_x + 8 * (tid >> 5);
            if (lane == 0) {
                mbar_init(xbar, 1);
                asm volatile("fence.mbarrier_init.release.cluster;\nfence.proxy.async.shared::cta;\n" ::: "memory");
                mbar_expect_tx(xbar, rb < NN ? 8192 : 0);
            }
            asm volatile("barrier.cluster.arrive.relaxed.aligned;\n" ::: "memory");
            if (wg == 1) pp_arrive();
            bar_sync(BAR_X, 384);
            if (wg == 1) bar_sync(BAR_GO, 160);
            if (lane == 0 && rb < NN) bulk_g2s(sq + warp * 8192, H.x + (size_t)rb * 256, 8192, xbar);
            if (rb >= NN) {
#pragma unroll 1
                for (int i = 0; i < 16; i++) sts128(sq + warp * 8192 + i * 512 + lane * 16, 0, 0, 0, 0);
            }
            __syncwarp();
            mbar_wait(xbar, 0);
            uint4 xa[8], xb[8];
#pragma unroll
            for (int s = 0; s < 8; s++) {
                xa[s] = lds128(sq + (warp * 16 + g) * 512 + (4 * s + q) * 16);
                xb[s] = lds128(sq + (warp * 16 + g + 8) * 512 + (4 * s + q) * 16);
            }
            float sm[2][4], sq2[2][4][4];
#pragma unroll
            for (int i = 0; i < 4; i++) {
                sm[0][i] = sm[1][i] = 0.f;
#pragma unroll
                for (int k = 0; k < 4; k++) sq2[0][k][i] = sq2[1][k][i] = 0.f;
            }
#pragma unroll
            for (int s = 0; s < 8; s++) {
#pragma unroll
                for (int hh = 0; hh < 2; hh++) {
                    const uint4 v = hh ? xb[s] : xa[s];
                    mma16816(sm[hh], v.x, v.y, v.z, v.w, 0x3F803F80u, 0x3F803F80u);
                    mma1688(sq2[hh][0], v.x, v.y, v.x); mma1688(sq2[hh][1], v.x, v.y, v.y);
                    mma1688(sq2[hh][2], v.z, v.w, v.z); mma1688(sq2[hh][3], v.z, v.w, v.w);
                }
            }
            float inv[2], off[2];
#pragma unroll
            for (int hh = 0; hh < 2; hh++) {
                const float mean = (sm[hh][0] + sm[hh][2]) * (1.f / 256.f);
                const float d0 = (sq2[hh][0][0] + sq2[hh][2][0]) + (sq2[hh][1][2] + sq2[hh][3][2]);
                const float d1 = (sq2[hh][0][1] + sq2[hh][2][1]) + (sq2[hh][1][3] + sq2[hh][3][3]);
                const float ss = __shfl_sync(~0u, (g & 1) ? d1 : d0, g * 4 + (g >> 1));
                const float var = fmaxf(ss * (1.f / 256.f) - mean * mean, 0.f);
                float sd;
                asm("sqrt.approx.ftz.f32 %0, %1;\n" : "=f"(sd) : "f"(bf_round(bf_round(var) + 1e-5f)));
                asm("rcp.approx.ftz.f32 %0, %1;\n" : "=f"(inv[hh]) : "f"(bf_round(sd)));
                off[hh] = -mean * inv[hh];
            }
            uint32_t a[64];
#pragma unroll
            for (int s = 0; s < 8; s++) {
                a[8 * s] = xa[s].x; a[8 * s + 1] = xb[s].x; a[8 * s + 2] = xa[s].y; a[8 * s + 3] = xb[s].y;
                a[8 * s + 4] = xa[s].z; a[8 * s + 5] = xb[s].z; a[8 * s + 6] = xa[s].w; a[8 * s + 7] = xb[s].w;
            }
            fence_regs(a);
            if (wg == 1 && __any_sync(~0u, inv[0] + inv[1] != -1.f)) bar_arrive(BAR_ST, 256);
            asm volatile("setmaxnreg.inc.sync.aligned.u32 %0;\n" ::"n"(REG_C));
            fence_regs(a);
#pragma unroll
            for (int i = 0; i < 64; i++)
                a[i] = pack_f16(fmaf(bf_lo(a[i]), inv[i & 1], off[i & 1]), fmaf(bf_hi(a[i]), inv[i & 1], off[i & 1]));
            if (SC_OWNER) {
#pragma unroll
                for (int i = 0; i < 16; i++) {
                    const uint32_t mk = (i == 15 && q == 3) ? 0xFFFFu : ~0u;
                    stmatrix_x4(sq + warp * 8192 + tile_off(lane & 15, 2 * i + (lane >> 4)), kvf(a[4 * i]), kvf(a[4 * i + 1]),
                                kvf(a[4 * i + 2] & mk), kvf(a[4 * i + 3] & mk));
                }
                fence_async_smem();
                if (tid < 32) bar_arrive(BAR_H0, 64);
                bar_arrive(wg ? BAR_H2 : BAR_H1, 160);
            }
            asm volatile("barrier.cluster.wait.acquire.aligned;\n" ::: "memory");
            if (wg == 0) bar_sync(BAR_ST, 256);
            if (active) {
                fence_regs(a);
#pragma unroll
                for (int c = 0; c < 4; c++) {
                    if (c == 1) {
                        if (wg == 1) {
                            wg_wait<0>();
                            release(0);
                        }
                        pp_sync();
                    }
                    mbar_wait(bar_full + 8 * c, 0);
                    const uint32_t wb = dk0 + c * (KV_BYTES >> 4);
                    wg_fence();
#pragma unroll
                    for (int kk = 0; kk < 4; kk++) {
                        if (c | kk) wgmma_rs_n256_tb(o, a[16 * c + 4 * kk], a[16 * c + 4 * kk + 1], a[16 * c + 4 * kk + 2], a[16 * c + 4 * kk + 3], desc64(wb + kk * 512));
                        else wgmma_rs_n256_tb_init(o, a[0], a[1], a[2], a[3], desc64(wb));
                    }
                    wg_commit();
                    if (c > 0) { wg_wait<1>(); if (c > 1 || wg == 0) release(c - 1); }
                }
                if (wg == 0) pp_arrive();
                wg_wait<0>();
                fence_regs(o);
                release((it + 3) & 3);
                if (SC_OWNER) mbar_wait(qbar, 0);
                stage_q();
                fence_async_smem();
                bar_sync(BAR_WG0 + wg, 128);
            }
            it += 4;
        }

        float s[40];
        uint32_t p[20] = {};
        const uint32_t dhi = P.dhi;
        float m0, m1, e0, e1, l0, l1;
        uint32_t plim;
        uint32_t qphase = (SC_OWNER && active) ? 1 : 0;
        auto issue_qk = [&](int st) {
            const uint64_t kb = mkaddr(dk0 + st * (KV_BYTES >> 4), dhi);
            const uint64_t qd = mkaddr(dq0 + ((uint32_t)it >> 24), dhi);
            wgmma_ss_n80_init(s, qd + 198, kb + 198);
#pragma unroll
            for (int kk = 0; kk < 15; kk++) wgmma_ss_n80(s, qd + ((kk >> 2) * 64 + (kk & 3) * 2), kb + ((kk >> 2) * 64 + (kk & 3) * 2));
            wg_commit();
        };
        auto issue_pv = [&](int st, int acc) {
            const uint64_t vb = mkaddr(dk0 + st * (KV_BYTES >> 4), dhi);
            wgmma_rs_n256_tb_pred(o, p[0], p[1], p[2], p[3], vb, acc);
#pragma unroll
            for (int kk = 1; kk < 5; kk++)
                wgmma_rs_n256_tb(o, p[4 * kk], p[4 * kk + 1], p[4 * kk + 2], p[4 * kk + 3], vb + kk * 512);
            wg_commit();
        };
        const uint32_t mq_addr = sq + tile_off(warp * 16 + g, 31) + 14;
        auto exceeds = [&](const uint32_t (&p)[20]) {
            uint32_t a = __vimax3_s16x2(P_LIMIT, p[0], p[1]), b = __vimax3_s16x2(p[2], p[3], p[4]);
#pragma unroll
            for (int i = 5; i < 17; i += 4) { a = __vimax3_s16x2(a, p[i], p[i + 1]); b = __vimax3_s16x2(b, p[i + 2], p[i + 3]); }
            a = __vimax3_s16x2(a, p[17], p[18]);
            return __any_sync(~0u, __vimax3_s16x2(a, b, p[19]) != plim);
        };
        auto remax = [&](float& a, float& b, bool store) {
            float a1 = fmaxf(s[0], s[1]), b1 = fmaxf(s[2], s[3]), a2 = fmaxf(s[4], s[5]), b2 = fmaxf(s[6], s[7]);
#pragma unroll
            for (int i = 2; i < 10; i++) {
                a1 = fmaxf(a1, s[4 * i]); a2 = fmaxf(a2, s[4 * i + 1]);
                b1 = fmaxf(b1, s[4 * i + 2]); b2 = fmaxf(b2, s[4 * i + 3]);
            }
            a1 = fmaxf(a1, a2); b1 = fmaxf(b1, b2);
            a1 = fmaxf(a1, __shfl_xor_sync(~0u, a1, 1)); b1 = fmaxf(b1, __shfl_xor_sync(~0u, b1, 1));
            a1 = fmaxf(a1, __shfl_xor_sync(~0u, a1, 2)); b1 = fmaxf(b1, __shfl_xor_sync(~0u, b1, 2));
            a = fmaxf(a, floorf(a1 - e0)); b = fmaxf(b, floorf(b1 - e1));
            unsigned short u0, u1;
            asm("cvt.rp.f16.f32 %0, %2;\ncvt.rp.f16.f32 %1, %3;\n" : "=h"(u0), "=h"(u1)
                : "f"(fminf(ceilf((m0 + a) * (-1.f / 3.f) - 1e-3f) * 0.5f, 65504.f)), "f"(fminf(ceilf((m1 + b) * (-1.f / 3.f) - 1e-3f) * 0.5f, 65504.f)));
            const float g0 = (m0 + a) + KV_OFF * f16_lo(u0), g1 = (m1 + b) + KV_OFF * f16_lo(u1);
            const bool x0 = g0 >= 0.f && g0 < 8.f, x1 = g1 >= 0.f && g1 < 8.f;
            if (x0) a -= g0;
            if (x1) b -= g1;
            const float da = a + e0, db = b + e1;
            m0 += a; m1 += b;
            e0 = x0 ? 0.f : g0; e1 = x1 ? 0.f : g1;
            plim = (x0 && x1) ? P_LIMIT : 0u;
            asm volatile("{\n.reg .pred p;\nsetp.ne.s32 p, %3, 0;\n@p st.shared.u16 [%0], %1;\n@p st.shared.u16 [%0 + 4096], %2;\n}\n"
                         ::"r"(mq_addr), "h"(u0), "h"(u1), "r"((int)(store && q == 0)) : "memory");
#pragma unroll
            for (int i = 0; i < 10; i++) {
                p[2 * i] = pack_f16(ex2(s[4 * i] - da), ex2(s[4 * i + 1] - da));
                p[2 * i + 1] = pack_f16(ex2(s[4 * i + 2] - db), ex2(s[4 * i + 3] - db));
            }
            fence_regs(p);
            fence_async_smem();
            __syncwarp();
        };

        auto row_sums = [&](float& z0, float& z1) {
            z0 = shfl_f32(o[125], lane | 3); z1 = shfl_f32(o[127], lane | 3);
            l0 = z0 * (KV_SCALE / KV_OFF); l1 = z1 * (KV_SCALE / KV_OFF);
        };
        auto stage_partial = [&](uint32_t dst) {
            float z0, z1;
            row_sums(z0, z1);
#pragma unroll
            for (int i = 0; i < 16; i++)
                sts128(dst + t * 16 + i * 2048, pack_bf16(o[8 * i] - z0, o[8 * i + 1] - z0), pack_bf16(o[8 * i + 2] - z1, o[8 * i + 3] - z1),
                       pack_bf16(o[8 * i + 4] - z0, o[8 * i + 5] - z0), pack_bf16(o[8 * i + 6] - z1, o[8 * i + 7] - z1));
            asm volatile("{\n.reg .pred p;\nsetp.eq.s32 p, %5, 0;\n@p st.shared.v2.f32 [%0], {%1, %2};\n@p st.shared.v2.f32 [%0 + 64], {%3, %4};\n}\n"
                         ::"r"(dst + QB_BYTES + (warp * 16 + g) * 8), "f"(m0), "f"(l0), "f"(m1), "f"(l1), "r"(q) : "memory");
            fence_async_smem();
            warp_arrive(bar_pdone);
        };
        const int nseg = nn >> 16;
        if (active) {
            mbar_wait(bar_full + 8 * (it & 3), (it >> 2) & 1);
            wg_fence();
            issue_qk(it & 3);
            if (wg == 1) pp_arrive();
            wg_wait<0>();
        }
#pragma unroll 1
        for (int seg = 0; seg < nseg; seg++) {
            const int n = (nn >> (8 * seg)) & 255;
            fence_regs(s);
            {
                m0 = m1 = e0 = e1 = 0.f;
                bool redo = true;
                if (seg) {
                    unsigned short u0, u1;
                    asm volatile("ld.shared.u16 %0, [%2];\nld.shared.u16 %1, [%2 + 4096];\n" : "=h"(u0), "=h"(u1) : "r"(mq_addr) : "memory");
                    m0 = -KV_OFF * f16_lo(u0); m1 = -KV_OFF * f16_lo(u1);
                    plim = (u0 != 0x7BFF && u1 != 0x7BFF) ? P_LIMIT : 0u;
#pragma unroll
                    for (int i = 0; i < 20; i++) p[i] = pack_f16(ex2(s[2 * i]), ex2(s[2 * i + 1]));
                    redo = exceeds(p);
                }
                if (redo) {
                    __syncwarp();
                    float d0 = -INFINITY, d1 = -INFINITY;
                    remax(d0, d1, true);
                }
                if (SC_OWNER) warp_arrive(bar_pdone);
            }
            const int it0 = it, itl = it + n - 1;
            const int itx = (wg == 1 && seg + 1 == nseg) ? itl : -1;
#pragma unroll 1
            while (it != itl) {
                const int stp = it & 3;
                it++;
                mbar_wait(bar_full + 8 * (it & 3), (it >> 2) & 1);
                pp_sync();
                fence_regs(o); fence_regs(p);
                wg_fence();
                issue_qk(it & 3);
                asm volatile("{\n.reg .pred p;\nsetp.eq.s32 p, %0, %1;\n@p bar.sync %2, 256;\n}\n" ::"r"(it), "r"(itx), "n"((int)BAR_ST) : "memory");
                issue_pv(stp, it - 1 - it0);
                pp_arrive();
                if (it == itl) {
                    wg_wait<1>();
                    if (SC_PAIR && wg == 1 && seg + 1 == nseg) {
                        asm volatile("{\n.reg .pred p;\n.reg .b32 a;\nsetp.eq.s32 p, %1, 0;\nmapa.shared::cluster.u32 a, %0, %2;\n"
                                     "@p mbarrier.arrive.shared::cluster.b64 _, [a];\n}\n" ::"r"(bar_rfree), "r"(lane), "r"(rank ^ 1) : "memory");
                    } else {
                        warp_arrive(bar_qfree);
                    }
                }
                auto fixup = [&]() {
                    float d0 = 0.f, d1 = 0.f;
                    remax(d0, d1, it != itl);
                    const float a0 = ex2(-d0), a1 = ex2(-d1);
#pragma unroll
                    for (int i = 0; i < 32; i++) { o[4 * i] *= a0; o[4 * i + 1] *= a0; o[4 * i + 2] *= a1; o[4 * i + 3] *= a1; }
                };
                bool redo;
                if (SC_TAIL || it == itx) {
                    uint32_t p2[20];
                    wg_wait<1>();
                    fence_regs(s);
#pragma unroll
                    for (int i = 0; i < 20; i++) p2[i] = pack_f16(ex2(s[2 * i]), ex2(s[2 * i + 1]));
                    redo = exceeds(p2);
                    if (redo) asm volatile("wgmma.wait_group.sync.aligned 0;\nnanosleep.u32 0;\n" ::: "memory");
                    else wg_wait<0>();
                    fence_regs(o); fence_regs(p);
#pragma unroll
                    for (int i = 0; i < 20; i++) p[i] = p2[i];
                } else {
                    wg_wait<0>();
                    fence_regs(s); fence_regs(o); fence_regs(p);
#pragma unroll
                    for (int i = 0; i < 20; i++) p[i] = pack_f16(ex2(s[2 * i]), ex2(s[2 * i + 1]));
                    redo = exceeds(p);
                }
                release(stp);
                if (redo) fixup();
            }
            fence_regs(o); fence_regs(p);
            wg_fence();
            issue_pv(it & 3, 1);
            asm volatile("{\n.reg .pred p;\nsetp.ne.s32 p, %0, 0;\n@p bar.arrive %1, 256;\n}\n" ::"r"((int)(wg == 0 && seg + 1 == nseg && !SC_TAIL)), "n"((int)BAR_ST) : "memory");
            it++;
            if (seg + 1 < nseg) {
                mbar_wait(qbar, qphase); qphase ^= 1;
                mbar_wait(bar_full + 8 * (it & 3), (it >> 2) & 1);
                wg_fence();
                issue_qk(it & 3);
                wg_wait<1>();
                fence_regs(o);
                release((it - 1) & 3);
                const int is = it - 2 + wg;
                mbar_wait(bar_empty + 8 * (is & 3), (is >> 2) & 1);
                stage_partial(sb + SM_KV + (is & 3) * KV_BYTES);
                wg_wait<0>();
            } else {
                wg_wait<0>();
                fence_regs(o);
                release((it - 1) & 3);
            }
        }
        auto wait_full = [&](int i) { mbar_wait(bar_full + 8 * (i & 3), (i >> 2) & 1); return dk0 + (i & 3) * (KV_BYTES >> 4); };
        auto output = [&](const float (&y)[64], int c, int cb, int rg, uint64_t tm) {
            const uint32_t base = sq + warp * 8192 + c * 4096 + cb * 2048;
#pragma unroll
            for (int i = 4 * cb; i < 4 * cb + 4; i++)
                stmatrix_x4(base + (lane & 15) * 128 + (((2 * i + (lane >> 4)) ^ lane) & 7) * 16, pack_bf16(y[8 * i], y[8 * i + 1]),
                            pack_bf16(y[8 * i + 2], y[8 * i + 3]), pack_bf16(y[8 * i + 4], y[8 * i + 5]), pack_bf16(y[8 * i + 6], y[8 * i + 7]));
            fence_async_smem();
            __syncwarp();
            asm volatile("{\n.reg .pred p;\nsetp.eq.s32 p, %4, 0;\n"
                         "@p cp.reduce.async.bulk.tensor.4d.global.shared::cta.add.tile.bulk_group [%0, {0, 0, %1, %2}], [%3];\n}\n"
                         ::"l"(tm + 128), "r"(2 * c + cb), "r"(rg), "r"(base), "r"(lane) : "memory");
        };
        float r0, r1, c0, c1;
        uint32_t u0, u1, w0 = 0, w1 = 0;
        auto weights = [&](uint32_t ml, uint32_t ml2) {
            const float2 pa = lds64f(ml + (warp * 16 + g) * 8), pb = lds64f(ml + (warp * 16 + g + 8) * 8);
            float2 qa = make_float2(-INFINITY, 0.f), qb = qa;
            if (ml2) { qa = lds64f(ml2 + (warp * 16 + g) * 8); qb = lds64f(ml2 + (warp * 16 + g + 8) * 8); }
            row_sums(c0, c1);
            const float n0 = fmaxf(fmaxf(m0, pa.x), qa.x), n1 = fmaxf(fmaxf(m1, pb.x), qb.x);
            const float a0 = ex2(m0 - n0), a1 = ex2(m1 - n1), b0 = ex2(pa.x - n0), b1 = ex2(pb.x - n1), d0 = ex2(qa.x - n0), d1 = ex2(qb.x - n1);
            const float i0 = __fdividef(1.f, l0 * a0 + pa.y * b0 + qa.y * d0), i1 = __fdividef(1.f, l1 * a1 + pb.y * b1 + qb.y * d1);
            r0 = a0 * i0; r1 = a1 * i1; c0 *= -r0; c1 *= -r1;
            u0 = pack_bf16(b0 * i0, b0 * i0); u1 = pack_bf16(b1 * i1, b1 * i1);
            w0 = pack_bf16(d0 * i0, d0 * i0); w1 = pack_bf16(d1 * i1, d1 * i1);
        };
        auto merged = [&](int i, const uint4& v) {
            return make_uint4(hfma2(v.x, u0, pack_bf16(fmaf(o[8 * i], r0, c0), fmaf(o[8 * i + 1], r0, c0))),
                              hfma2(v.y, u1, pack_bf16(fmaf(o[8 * i + 2], r1, c1), fmaf(o[8 * i + 3], r1, c1))),
                              hfma2(v.z, u0, pack_bf16(fmaf(o[8 * i + 4], r0, c0), fmaf(o[8 * i + 5], r0, c0))),
                              hfma2(v.w, u1, pack_bf16(fmaf(o[8 * i + 6], r1, c1), fmaf(o[8 * i + 7], r1, c1))));
        };
        if (SC_PAIR && wg == 0) {
            uint32_t rq, rbar, rml;
            asm("mapa.shared::cluster.u32 %0, %3, %6;\nmapa.shared::cluster.u32 %1, %4, %6;\nmapa.shared::cluster.u32 %2, %5, %6;\n"
                : "=r"(rq), "=r"(rbar), "=r"(rml) : "r"(sq + QB_BYTES + warp * 8192 + lane * 16), "r"(bar_pin + 16),
                "r"(sb + SM_ML + 512 + (warp * 16 + g) * 8), "r"(rank ^ 1));
            float z0, z1, y0[64], y1[64];
            row_sums(z0, z1);
            auto send = [&](int hf) {
#pragma unroll
                for (int i = 8 * hf; i < 8 * hf + 8; i++)
                    asm volatile("st.async.weak.shared::cluster.mbarrier::complete_tx::bytes.v4.b32 [%0], {%1, %2, %3, %4}, [%5];\n"
                                 ::"r"(rq + (i & 4) * 1024 + hf * 2048 + (i & 3) * 512), "r"(pack_bf16(o[8 * i] - z0, o[8 * i + 1] - z0)),
                                 "r"(pack_bf16(o[8 * i + 2] - z1, o[8 * i + 3] - z1)), "r"(pack_bf16(o[8 * i + 4] - z0, o[8 * i + 5] - z0)),
                                 "r"(pack_bf16(o[8 * i + 6] - z1, o[8 * i + 7] - z1)), "r"(rbar + hf * 8) : "memory");
            };
            auto release2 = [&](int i) {
                asm volatile("{\n.reg .pred p;\nsetp.ne.u32 p, %1, 0;\n@p mbarrier.arrive.shared::cluster.b64 _, [%0], 2;\n}\n"
                             ::"r"(rel_addr + 8 * (i & 3)), "r"(rel_addr) : "memory");
            };
            auto gemm1 = [&](float (&y)[64], int c, int hf, uint32_t wb) {
#pragma unroll
                for (int kk = 0; kk < 4; kk++) {
                    if (c | kk) wgmma_ss_n128_tb(y, desc64(dq0 + c * 64 + kk * 2), desc64(wb + hf * 128 + kk * 512));
                    else wgmma_ss_n128_tb_init(y, desc64(dq0), desc64(wb + hf * 128));
                }
            };
            auto gemm2 = [&](float (&y)[64], int c, int kh) {
                const uint32_t wb = wait_full(it + 4 + 2 * c + kh);
                wg_fence();
#pragma unroll
                for (int kk = 0; kk < 8; kk++)
                    wgmma_ss_n128_tb(y, desc64(dq0 + (QB_BYTES >> 4) + kh * 128 + (kk >> 2) * 64 + (kk & 3) * 2), desc64k(wb + kk * 256));
                wg_commit();
            };
            mbar_wait(bar_rfree, 0);
            asm volatile("{\n.reg .pred p;\nsetp.eq.s32 p, %6, 0;\n"
                         "@p st.async.weak.shared::cluster.mbarrier::complete_tx::bytes.v2.f32 [%0], {%1, %2}, [%5];\n"
                         "@p st.async.weak.shared::cluster.mbarrier::complete_tx::bytes.v2.f32 [%0 + 64], {%3, %4}, [%5];\n}\n"
                         ::"r"(rml), "f"(m0), "f"(l0), "f"(m1), "f"(l1), "r"(rbar), "r"(q) : "memory");
            send(0);
            mbar_wait(qbar, qphase);
            const uint32_t wb0 = wait_full(it), wb1 = wait_full(it + 1);
            wg_fence();
            gemm1(y0, 0, 0, wb0); gemm1(y0, 1, 0, wb1);
            wg_commit();
            send(1);
            wg_fence();
            gemm1(y1, 0, 1, wb0);
            wg_commit();
            gemm1(y1, 1, 1, wb1);
            wg_commit();
            const int rg = SC_ZB(0) * 8 + warp * 2;
            const uint64_t tm = lds64(s_tm);
#pragma unroll
            for (int c = 2; c < 4; c++) {
                wg_wait<1>();
                release2(it + c - 2);
                const uint32_t wb = wait_full(it + c);
                wg_fence();
                gemm1(y0, c, 0, wb); gemm1(y1, c, 1, wb);
                wg_commit();
            }
            wg_wait<1>();
            release2(it + 2);
            bar_sync(BAR_BF, 256);
            gemm2(y0, 0, 0);
            wg_wait<1>();
            release2(it + 3);
            bar_sync(BAR_H0, 256);
            gemm2(y0, 0, 1);
            gemm2(y1, 1, 0);
            wg_wait<1>();
            fence_regs(y0);
            output(y0, 0, 0, rg, tm);
            gemm2(y1, 1, 1);
            output(y0, 0, 1, rg, tm);
            wg_wait<0>();
            fence_regs(y1);
            output(y1, 1, 0, rg, tm);
            output(y1, 1, 1, rg, tm);
            asm volatile("cp.async.bulk.commit_group;\ncp.async.bulk.wait_group.read 0;\n" ::: "memory");
        } else if (SC_PAIR) {
            const uint32_t pc = sb + SM_KV + QB_BYTES + t * 16;
            if (SC_PIN) mbar_wait(bar_pin, 0);
            mbar_wait(bar_pin + 16, 0);
            weights(sb + SM_ML + 512, SC_PIN ? sb + SM_ML : 0);
#pragma unroll
            for (int hf = 0; hf < 2; hf++) {
                uint4 v[8];
                if (hf) mbar_wait(bar_pin + 24, 0);
#pragma unroll
                for (int i = 0; i < 8; i++) v[i] = lds128(sq + warp * 8192 + lane * 16 + (i & 4) * 1024 + hf * 2048 + (i & 3) * 512);
#pragma unroll
                for (int i = 0; i < 8; i++) v[i] = merged(8 * hf + i, v[i]);
                if (SC_PIN) {
                    if (hf) mbar_wait(bar_pin + 8, 0);
#pragma unroll
                    for (int i = 0; i < 8; i++) {
                        const uint4 e = lds128(pc + ((it + 2 * hf + (i >> 2)) & 3) * KV_BYTES + (i & 3) * 2048);
                        v[i] = make_uint4(hfma2(e.x, w0, v[i].x), hfma2(e.y, w1, v[i].y), hfma2(e.z, w0, v[i].z), hfma2(e.w, w1, v[i].w));
                    }
                }
                __syncwarp();
#pragma unroll
                for (int i = 0; i < 8; i++)
                    stmatrix_x4(sq + warp * 8192 + tile_off(lane & 15, 16 * hf + 2 * i + (lane >> 4)), v[i].x, v[i].y, v[i].z, v[i].w);
                fence_async_smem();
                bar_arrive(hf ? BAR_H0 : BAR_BF, 256);
            }
        } else if (blockIdx.x == NCTA - 1) {
            if (active) {
                bar_sync(BAR_WG0 + wg, 128);
                stage_partial(sq);
            }
        } else if (active) {
            uint32_t a[64];
            float y0[64], y1[64];
            auto merge = [&](int hf) {
                uint4 v[8];
#pragma unroll
                for (int i = 0; i < 8; i++) v[i] = lds128(sq + t * 16 + (8 * hf + i) * 2048);
#pragma unroll
                for (int i = 8 * hf; i < 8 * hf + 8; i++) {
                    const uint4 x = merged(i, v[i & 7]);
                    a[4 * i] = x.x; a[4 * i + 1] = x.y; a[4 * i + 2] = x.z; a[4 * i + 3] = x.w;
                }
            };
            auto gemm = [&](float (&y)[64], int c, int kh) {
                const uint32_t wb = wait_full(it + 2 * c + kh);
                wg_fence();
#pragma unroll
                for (int kk = 0; kk < 8; kk++) {
                    const int r = 32 * kh + 4 * kk;
                    if (kh | kk) wgmma_rs_n128_tb(y, a[r], a[r + 1], a[r + 2], a[r + 3], desc64k(wb + kk * 256));
                    else wgmma_rs_n128_tb_init(y, a[0], a[1], a[2], a[3], desc64k(wb));
                }
                wg_commit();
            };
            mbar_wait(bar_pin + 16 * wg, 0);
            weights(sb + SM_ML + wg * 512, 0);
            merge(0);
            mbar_wait(bar_pin + 16 * wg + 8, 0);
            merge(1);
            const int rg = (2 * SC_QT(0) + wg) * 8 + warp * 2;
            const uint64_t tm = lds64(s_tm);
            pp_sync();
            gemm(y0, 0, 0);
            gemm(y0, 0, 1);
            gemm(y1, 1, 0);
            bar_sync(BAR_WG0 + wg, 128);
            wg_wait<1>();
            fence_regs(y0);
            output(y0, 0, 0, rg, tm);
            gemm(y1, 1, 1);
            pp_arrive();
            output(y0, 0, 1, rg, tm);
            wg_wait<0>();
            fence_regs(y1);
            if (SC_TAIL) for (int i = 0; i < 4; i++) release(i);
            output(y1, 1, 0, rg, tm);
            output(y1, 1, 1, rg, tm);
            asm volatile("cp.async.bulk.commit_group;\ncp.async.bulk.wait_group.read 0;\n" ::: "memory");
        }
        auto emit = [&](uint32_t base, int lane, int row0, uint8_t* wdst, int turn) {
            const uint64_t tm = lds64(s_tm);
#pragma unroll
            for (int hh = 0; hh < 2; hh++) {
                if (turn > 0 && SC_TAIL) mbar_wait(bar_zst + 8 * hh, (turn - 1) & 1);
#pragma unroll
                for (int i = 0; i < 8; i++)
                    stmatrix_x4(base + tile_off(8 * hh + (lane & 7), 4 * i + (lane >> 3)),
                                pack_bf16(o[16 * i + 2 * hh], o[16 * i + 2 * hh + 1]), pack_bf16(o[16 * i + 4 + 2 * hh], o[16 * i + 5 + 2 * hh]),
                                pack_bf16(o[16 * i + 8 + 2 * hh], o[16 * i + 9 + 2 * hh]), pack_bf16(o[16 * i + 12 + 2 * hh], o[16 * i + 13 + 2 * hh]));
                fence_async_smem();
                __syncwarp();
                if (wdst) {
                    if (lane < 4)
                        asm volatile("cp.async.bulk.global.shared::cta.bulk_group [%0], [%1], 1024;\n"
                                     ::"l"(wdst + ((turn & 1) ? hh * 4096 + lane * 1024 : hh * 2048 + (lane >> 1) * (2 * QB_BYTES) + (lane & 1) * 1024)), "r"(base + hh * 4096 + lane * 1024) : "memory");
                    asm volatile("cp.async.bulk.commit_group;\n" ::: "memory");
                } else {
                    asm volatile("{\n.reg .pred p;\nsetp.eq.s32 p, %3, 0;\n"
                                 "@p cp.reduce.async.bulk.tensor.4d.global.shared::cta.add.tile.bulk_group [%0, {0, 0, 0, %1}], [%2];\n"
                                 "cp.async.bulk.commit_group;\n}\n"
                                 ::"l"(tm), "r"((row0 >> 3) + hh), "r"(base + hh * 4096), "r"(lane) : "memory");
                }
            }
            asm volatile("cp.async.bulk.wait_group.read 1;\n" ::: "memory");
            warp_arrive(bar_zst - 8 * wg);
        };
        auto emit_done = [&](bool pending) {
            asm volatile("cp.async.bulk.wait_group.read 0;\n" ::: "memory");
            __syncwarp();
            asm volatile("{\n.reg .pred p;\nsetp.eq.s32 p, %1, 0;\n@p mbarrier.arrive.shared::cta.b64 _, [%0];\n}\n"
                         ::"r"(bar_zst + 8), "r"(pending ? lane : 1) : "memory");
        };
        if (SC_TAIL) {
            bar_sync(BAR_BF, 256);
            warp_arrive(bar_qfree);
        }
        const int nf = blockIdx.x == NCTA - 1 ? 8 : 0;
        const int nz = __shfl_sync(~0u, nf + SC_NZ, 0);
        const int itz = __shfl_sync(~0u, 4 + SC_N(0) + SC_N(1) + (SC_OWNER ? 4 : 0), 0);
        bool pend = false;
#pragma unroll 1
        for (int k = wg; k < nz; k += 2) {
            const int iz = itz + (k < nf ? 0 : nf >> 1) + (k >> 16);
            mbar_wait(qbar, qphase); qphase ^= 1;
            pp_sync();
#pragma unroll
            for (int c = 0; c < 4; c++) {
                mbar_wait(bar_full + 8 * ((iz + c) & 3), ((iz + c) >> 2) & 1);
                wg_fence();
                const uint32_t wb = dk0 + ((iz + c) & 3) * (KV_BYTES >> 4);
#pragma unroll
                for (int kk = 0; kk < 4; kk++) {
                    if (c | kk) wgmma_ss_n256_tb(o, desc64(dq0 + (k >> 16) + c * 64 + kk * 2), desc64(wb + kk * 512));
                    else wgmma_ss_n256_tb_init(o, desc64(dq0 + (k >> 16)), desc64(wb));
                }
                if (c == 0) emit_done(pend);
            }
            wg_commit();
            pp_arrive();
            wg_wait<0>();
            fence_regs(o);
            warp_arrive(bar_qfree);
            bar_sync(BAR_WG0 + wg, 128);
            const int fb = ((k >> 1) + 3) & 3;
            if (k < nf) {
                float2* r255 = (float2*)H.s->r255 + wg * 128 + q;
                if (k < 2) {
                    if (t >= 124) {
#pragma unroll
                        for (int i = 0; i < 32; i++) r255[4 * i] = make_float2(o[4 * i + 2], o[4 * i + 3]);
                    }
                    bar_sync(BAR_WG0 + wg, 128);
                }
#pragma unroll
                for (int i = 0; i < 32; i++) {
                    const float2 v = __ldcg(r255 + 4 * i);
                    o[4 * i] -= v.x; o[4 * i + 1] -= v.y; o[4 * i + 2] -= v.x; o[4 * i + 3] -= v.y;
                }
            }
            int ln = lane;
            asm volatile("" : "+r"(ln));
            emit(SC_TAIL ? sb + SM_KV + QB_BYTES + warp * KV_BYTES : sq + warp * 8192, ln, SC_ZB(k - nf) * 64 + warp * 16,
                 k >= nf ? nullptr : (k & 1) ? g_w + (8 + fb) * QB_BYTES + warp * 8192 : g_w + 4 * QB_BYTES + fb * 16384 + warp * 4096, k);
            pend = k + 2 < nz && (k | 1) != nf - 1;
            if (!pend) emit_done(true);
            if ((k | 1) == nf - 1) {
                asm volatile("cp.async.bulk.wait_group 0;\nfence.proxy.async.global;\nfence.acq_rel.gpu;\n" ::: "memory");
                bar_sync(BAR_BF, 256);
                if (tid == 0) red_release(&g_sync[SY_B * 32]);
                if (wg == 0) { release(0); release(1); release(2); release(3); }
            }
        }
        if (wg == 0) pp_sync();
        asm volatile("barrier.cluster.arrive.relaxed.aligned;\n" ::: "memory");
    }
}

}

extern "C" void kernel_launch(void* const* d_in, const int* in_sizes, int n_in, void* d_out, int out_size) {
    Hot H;
    Params P;
    H.x = (const __nv_bfloat16*)d_in[0];
    P.src = (const int*)d_in[1];
    P.dst = (const int*)d_in[2];
    P.deg_inv = (const __nv_bfloat16*)d_in[3];
    H.wq = (const __nv_bfloat16*)d_in[5];
    H.wk = (const __nv_bfloat16*)d_in[6];
    P.out = (__nv_bfloat16*)d_out;
    typedef CUresult (*EncodeFn)(CUtensorMap*, CUtensorMapDataType, cuuint32_t, void*, const cuuint64_t*, const cuuint64_t*, const cuuint32_t*,
                                 const cuuint32_t*, CUtensorMapInterleave, CUtensorMapSwizzle, CUtensorMapL2promotion, CUtensorMapFloatOOBfill);
    void* fn = nullptr;
    cudaDriverEntryPointQueryResult qr;
    cudaGetDriverEntryPoint("cuTensorMapEncodeTiled", &fn, cudaEnableDefault, &qr);
    auto encode = [&](CUtensorMap* tm, const void* ptr, int rows, int box_rows, int box_cb = 4) {
        const cuuint64_t dims[4] = {64, 8, 4, (cuuint64_t)rows / 8};
        const cuuint64_t strides[3] = {512, 128, 4096};
        const cuuint32_t box[4] = {64, 8, (cuuint32_t)box_cb, (cuuint32_t)box_rows / 8}, es[4] = {1, 1, 1, 1};
        ((EncodeFn)fn)(tm, CU_TENSOR_MAP_DATA_TYPE_BFLOAT16, 4, (void*)ptr, dims, strides, box, es, CU_TENSOR_MAP_INTERLEAVE_NONE,
                       CU_TENSOR_MAP_SWIZZLE_128B, CU_TENSOR_MAP_L2_PROMOTION_NONE, CU_TENSOR_MAP_FLOAT_OOB_FILL_NONE);
    };
    encode(&P.tm_out, d_out, NN, 8);
    encode(&P.tm_outc, d_out, NN, 16, 1);
    for (int i = 0; i < 2; i++) {
        const cuuint64_t dims[5] = {64, 2, 32, 4, 4};
        const cuuint64_t strides[4] = {512, 4096, 128, 1024};
        const cuuint32_t box[5] = {64, 2, 4, 4, 4}, es[5] = {1, 1, 1, 1, 1};
        ((EncodeFn)fn)(&P.tm_w[i], CU_TENSOR_MAP_DATA_TYPE_BFLOAT16, 5, d_in[i ? 4 : 7], dims, strides, box, es, CU_TENSOR_MAP_INTERLEAVE_NONE,
                       CU_TENSOR_MAP_SWIZZLE_128B, CU_TENSOR_MAP_L2_PROMOTION_NONE, CU_TENSOR_MAP_FLOAT_OOB_FILL_NONE);
    }
    encode(&P.tm_w[2], d_in[8], 256, 64);
    void* raw = nullptr;
    cudaGetSymbolAddress(&raw, g_raw);
    H.s = (Scratch*)(((uintptr_t)raw + ((8 << 20) - 1)) & ~(uintptr_t)((8 << 20) - 1));
    P.dhi = 0x40000100u;
    P.E = in_sizes[1] < MAXE ? in_sizes[1] : MAXE;
    for (int b = 0; b < NCTA; b++) {
        const Sched s = get_sched(b >> 1, b & 1);
        P.sched[b][0] = s.qt0 | s.kv0 << 8 | s.n0 << 16 | s.owner << 24 | s.pin << 25 | s.mc << 27 | s.pair << 28;
        P.sched[b][1] = s.qt1 | s.kv1 << 8 | s.n1 << 16;
        P.sched[b][2] = s.zb | s.nz << 8;
    }
    cudaFuncSetAttribute(k_main, cudaFuncAttributeMaxDynamicSharedMemorySize, SM_TOTAL);
    k_main<<<NCTA, 384, SM_TOTAL>>>(H, P);
}
```

```cpp
#include <cuda_runtime.h>
#include <cuda.h>
#include <cuda_bf16.h>
#include <stdint.h>
#include <stddef.h>

namespace {

constexpr int NN = 10000;
constexpr int BN = 80;
constexpr int NKV = NN / BN;
constexpr int NQB = 158;
constexpr int NCTA = 132;
constexpr int NAUX = 3 * (NCTA - 2);
constexpr int STAGES = 4;
constexpr int KV_BYTES = BN * 512;
constexpr int QB_BYTES = 64 * 512;
constexpr int PART_BYTES = QB_BYTES + 512;
constexpr int CAP = 32;
constexpr int MAXE = 160000;

#define QRND(v) (((v) + 0x00040004u) & 0xFFF8FFF8u)
#define GO0 30
#define GF0 2
#define PAIR_MC 1
#define A_MC 0
#define CSRU 5
#define CPYU 5
#define SGRP 4
#define REG_C 224
#define REG_P 56

enum { SY_A = 0, SY_H1 = 5, SY_CSR = 6, SY_AUX = 7, SY_DONE = 8, SY_AUX0 = 9, SY_B = 10, SY_AUX1 = 11, SY_H0 = 12 };
struct Scratch {
    uint8_t hz[4096 + NN * 512];
    uint8_t w[12 * QB_BYTES];
    int sync[24 * 32];
    int pflag[NQB / 2 + 1];
    int qflag[NQB / 2 + 1];
    int ovf_n[32];
    float r255[512];
    int cnt[NN + 16];
    int bucket[(NN + 1) * CAP];
    int2 ovf[MAXE];
    uint8_t q[NQB * QB_BYTES];
    uint8_t agg[NQB * QB_BYTES];
    uint8_t part[78 * 2 * PART_BYTES];
};
static_assert(offsetof(Scratch, ovf) <= (8 << 20), "window");
static_assert(offsetof(Scratch, pflag) == offsetof(Scratch, sync) + 24 * 128 && offsetof(Scratch, qflag) == offsetof(Scratch, pflag) + 320, "flags");
static_assert(offsetof(Scratch, w) % 1024 == 0 && offsetof(Scratch, sync) % 128 == 0 &&
              offsetof(Scratch, bucket) % 128 == 0 && offsetof(Scratch, q) % 128 == 0, "alignment");
__device__ uint8_t g_raw[(8 << 20) + sizeof(Scratch)];
#define g_hz (H.s->hz)
#define g_w (H.s->w)
#define g_sync (H.s->sync)
#define g_pflag (H.s->pflag)
#define g_qflag (H.s->qflag)
#define g_ovf_n (H.s->ovf_n)
#define g_cnt (H.s->cnt)
#define g_bucket (H.s->bucket)
#define g_ovf (H.s->ovf)
#define g_q (H.s->q)
#define g_agg (H.s->agg)
#define g_part (H.s->part)

__device__ __forceinline__ void wgmma_ss_n80(float (&d)[40], uint64_t da, uint64_t db) {
    asm volatile("wgmma.mma_async.sync.aligned.m64n80k16.f32.f16.f16 {"
        "%0, %1, %2, %3, %4, %5, %6, %7, %8, %9, %10, %11, %12, %13, %14, %15, %16, %17, %18, %19, %20, %21, %22, %23, %24, %25, %26, %27, %28, %29, %30, %31, "
        "%32, %33, %34, %35, %36, %37, %38, %39}, %40, %41, 1, 1, 1, 0, 0;\n"
        : "+f"(d[0]), "+f"(d[1]), "+f"(d[2]), "+f"(d[3]), "+f"(d[4]), "+f"(d[5]), "+f"(d[6]), "+f"(d[7]),
          "+f"(d[8]), "+f"(d[9]), "+f"(d[10]), "+f"(d[11]), "+f"(d[12]), "+f"(d[13]), "+f"(d[14]), "+f"(d[15]),
          "+f"(d[16]), "+f"(d[17]), "+f"(d[18]), "+f"(d[19]), "+f"(d[20]), "+f"(d[21]), "+f"(d[22]), "+f"(d[23]),
          "+f"(d[24]), "+f"(d[25]), "+f"(d[26]), "+f"(d[27]), "+f"(d[28]), "+f"(d[29]), "+f"(d[30]), "+f"(d[31]),
          "+f"(d[32]), "+f"(d[33]), "+f"(d[34]), "+f"(d[35]), "+f"(d[36]), "+f"(d[37]), "+f"(d[38]), "+f"(d[39])
        : "l"(da), "l"(db));
}
__device__ __forceinline__ void wgmma_ss_n80_init(float (&d)[40], uint64_t da, uint64_t db) {
    asm volatile("wgmma.mma_async.sync.aligned.m64n80k16.f32.f16.f16 {"
        "%0, %1, %2, %3, %4, %5, %6, %7, %8, %9, %10, %11, %12, %13, %14, %15, %16, %17, %18, %19, %20, %21, %22, %23, %24, %25, %26, %27, %28, %29, %30, %31, "
        "%32, %33, %34, %35, %36, %37, %38, %39}, %40, %41, 0, 1, 1, 0, 0;\n"
        : "=f"(d[0]), "=f"(d[1]), "=f"(d[2]), "=f"(d[3]), "=f"(d[4]), "=f"(d[5]), "=f"(d[6]), "=f"(d[7]),
          "=f"(d[8]), "=f"(d[9]), "=f"(d[10]), "=f"(d[11]), "=f"(d[12]), "=f"(d[13]), "=f"(d[14]), "=f"(d[15]),
          "=f"(d[16]), "=f"(d[17]), "=f"(d[18]), "=f"(d[19]), "=f"(d[20]), "=f"(d[21]), "=f"(d[22]), "=f"(d[23]),
          "=f"(d[24]), "=f"(d[25]), "=f"(d[26]), "=f"(d[27]), "=f"(d[28]), "=f"(d[29]), "=f"(d[30]), "=f"(d[31]),
          "=f"(d[32]), "=f"(d[33]), "=f"(d[34]), "=f"(d[35]), "=f"(d[36]), "=f"(d[37]), "=f"(d[38]), "=f"(d[39])
        : "l"(da), "l"(db));
}
__device__ __forceinline__ void wgmma_rs_n256_tb(float (&d)[128], uint32_t a0, uint32_t a1, uint32_t a2, uint32_t a3, uint64_t db) {
    asm volatile("wgmma.mma_async.sync.aligned.m64n256k16.f32.f16.f16 {"
        "%0, %1, %2, %3, %4, %5, %6, %7, %8, %9, %10, %11, %12, %13, %14, %15, %16, %17, %18, %19, %20, %21, %22, %23, %24, %25, %26, %27, %28, %29, %30, %31, "
        "%32, %33, %34, %35, %36, %37, %38, %39, %40, %41, %42, %43, %44, %45, %46, %47, %48, %49, %50, %51, %52, %53, %54, %55, %56, %57, %58, %59, %60, %61, %62, %63, "
        "%64, %65, %66, %67, %68, %69, %70, %71, %72, %73, %74, %75, %76, %77, %78, %79, %80, %81, %82, %83, %84, %85, %86, %87, %88, %89, %90, %91, %92, %93, %94, %95, "
        "%96, %97, %98, %99, %100, %101, %102, %103, %104, %105, %106, %107, %108, %109, %110, %111, %112, %113, %114, %115, %116, %117, %118, %119, %120, %121, %122, %123, %124, %125, %126, %127}, {%128, %129, %130, %131}, %132, 1, 1, 1, 1;\n"
        : "+f"(d[0]), "+f"(d[1]), "+f"(d[2]), "+f"(d[3]), "+f"(d[4]), "+f"(d[5]), "+f"(d[6]), "+f"(d[7]),
          "+f"(d[8]), "+f"(d[9]), "+f"(d[10]), "+f"(d[11]), "+f"(d[12]), "+f"(d[13]), "+f"(d[14]), "+f"(d[15]),
          "+f"(d[16]), "+f"(d[17]), "+f"(d[18]), "+f"(d[19]), "+f"(d[20]), "+f"(d[21]), "+f"(d[22]), "+f"(d[23]),
          "+f"(d[24]), "+f"(d[25]), "+f"(d[26]), "+f"(d[27]), "+f"(d[28]), "+f"(d[29]), "+f"(d[30]), "+f"(d[31]),
          "+f"(d[32]), "+f"(d[33]), "+f"(d[34]), "+f"(d[35]), "+f"(d[36]), "+f"(d[37]), "+f"(d[38]), "+f"(d[39]),
          "+f"(d[40]), "+f"(d[41]), "+f"(d[42]), "+f"(d[43]), "+f"(d[44]), "+f"(d[45]), "+f"(d[46]), "+f"(d[47]),
          "+f"(d[48]), "+f"(d[49]), "+f"(d[50]), "+f"(d[51]), "+f"(d[52]), "+f"(d[53]), "+f"(d[54]), "+f"(d[55]),
          "+f"(d[56]), "+f"(d[57]), "+f"(d[58]), "+f"(d[59]), "+f"(d[60]), "+f"(d[61]), "+f"(d[62]), "+f"(d[63]),
          "+f"(d[64]), "+f"(d[65]), "+f"(d[66]), "+f"(d[67]), "+f"(d[68]), "+f"(d[69]), "+f"(d[70]), "+f"(d[71]),
          "+f"(d[72]), "+f"(d[73]), "+f"(d[74]), "+f"(d[75]), "+f"(d[76]), "+f"(d[77]), "+f"(d[78]), "+f"(d[79]),
          "+f"(d[80]), "+f"(d[81]), "+f"(d[82]), "+f"(d[83]), "+f"(d[84]), "+f"(d[85]), "+f"(d[86]), "+f"(d[87]),
          "+f"(d[88]), "+f"(d[89]), "+f"(d[90]), "+f"(d[91]), "+f"(d[92]), "+f"(d[93]), "+f"(d[94]), "+f"(d[95]),
          "+f"(d[96]), "+f"(d[97]), "+f"(d[98]), "+f"(d[99]), "+f"(d[100]), "+f"(d[101]), "+f"(d[102]), "+f"(d[103]),
          "+f"(d[104]), "+f"(d[105]), "+f"(d[106]), "+f"(d[107]), "+f"(d[108]), "+f"(d[109]), "+f"(d[110]), "+f"(d[111]),
          "+f"(d[112]), "+f"(d[113]), "+f"(d[114]), "+f"(d[115]), "+f"(d[116]), "+f"(d[117]), "+f"(d[118]), "+f"(d[119]),
          "+f"(d[120]), "+f"(d[121]), "+f"(d[122]), "+f"(d[123]), "+f"(d[124]), "+f"(d[125]), "+f"(d[126]), "+f"(d[127])
        : "r"(a0), "r"(a1), "r"(a2), "r"(a3), "l"(db));
}
__device__ __forceinline__ void wgmma_rs_n256_tb_init(float (&d)[128], uint32_t a0, uint32_t a1, uint32_t a2, uint32_t a3, uint64_t db) {
    asm volatile("wgmma.mma_async.sync.aligned.m64n256k16.f32.f16.f16 {"
        "%0, %1, %2, %3, %4, %5, %6, %7, %8, %9, %10, %11, %12, %13, %14, %15, %16, %17, %18, %19, %20, %21, %22, %23, %24, %25, %26, %27, %28, %29, %30, %31, "
        "%32, %33, %34, %35, %36, %37, %38, %39, %40, %41, %42, %43, %44, %45, %46, %47, %48, %49, %50, %51, %52, %53, %54, %55, %56, %57, %58, %59, %60, %61, %62, %63, "
        "%64, %65, %66, %67, %68, %69, %70, %71, %72, %73, %74, %75, %76, %77, %78, %79, %80, %81, %82, %83, %84, %85, %86, %87, %88, %89, %90, %91, %92, %93, %94, %95, "
        "%96, %97, %98, %99, %100, %101, %102, %103, %104, %105, %106, %107, %108, %109, %110, %111, %112, %113, %114, %115, %116, %117, %118, %119, %120, %121, %122, %123, %124, %125, %126, %127}, {%128, %129, %130, %131}, %132, 0, 1, 1, 1;\n"
        : "=f"(d[0]), "=f"(d[1]), "=f"(d[2]), "=f"(d[3]), "=f"(d[4]), "=f"(d[5]), "=f"(d[6]), "=f"(d[7]),
          "=f"(d[8]), "=f"(d[9]), "=f"(d[10]), "=f"(d[11]), "=f"(d[12]), "=f"(d[13]), "=f"(d[14]), "=f"(d[15]),
          "=f"(d[16]), "=f"(d[17]), "=f"(d[18]), "=f"(d[19]), "=f"(d[20]), "=f"(d[21]), "=f"(d[22]), "=f"(d[23]),
          "=f"(d[24]), "=f"(d[25]), "=f"(d[26]), "=f"(d[27]), "=f"(d[28]), "=f"(d[29]), "=f"(d[30]), "=f"(d[31]),
          "=f"(d[32]), "=f"(d[33]), "=f"(d[34]), "=f"(d[35]), "=f"(d[36]), "=f"(d[37]), "=f"(d[38]), "=f"(d[39]),
          "=f"(d[40]), "=f"(d[41]), "=f"(d[42]), "=f"(d[43]), "=f"(d[44]), "=f"(d[45]), "=f"(d[46]), "=f"(d[47]),
          "=f"(d[48]), "=f"(d[49]), "=f"(d[50]), "=f"(d[51]), "=f"(d[52]), "=f"(d[53]), "=f"(d[54]), "=f"(d[55]),
          "=f"(d[56]), "=f"(d[57]), "=f"(d[58]), "=f"(d[59]), "=f"(d[60]), "=f"(d[61]), "=f"(d[62]), "=f"(d[63]),
          "=f"(d[64]), "=f"(d[65]), "=f"(d[66]), "=f"(d[67]), "=f"(d[68]), "=f"(d[69]), "=f"(d[70]), "=f"(d[71]),
          "=f"(d[72]), "=f"(d[73]), "=f"(d[74]), "=f"(d[75]), "=f"(d[76]), "=f"(d[77]), "=f"(d[78]), "=f"(d[79]),
          "=f"(d[80]), "=f"(d[81]), "=f"(d[82]), "=f"(d[83]), "=f"(d[84]), "=f"(d[85]), "=f"(d[86]), "=f"(d[87]),
          "=f"(d[88]), "=f"(d[89]), "=f"(d[90]), "=f"(d[91]), "=f"(d[92]), "=f"(d[93]), "=f"(d[94]), "=f"(d[95]),
          "=f"(d[96]), "=f"(d[97]), "=f"(d[98]), "=f"(d[99]), "=f"(d[100]), "=f"(d[101]), "=f"(d[102]), "=f"(d[103]),
          "=f"(d[104]), "=f"(d[105]), "=f"(d[106]), "=f"(d[107]), "=f"(d[108]), "=f"(d[109]), "=f"(d[110]), "=f"(d[111]),
          "=f"(d[112]), "=f"(d[113]), "=f"(d[114]), "=f"(d[115]), "=f"(d[116]), "=f"(d[117]), "=f"(d[118]), "=f"(d[119]),
          "=f"(d[120]), "=f"(d[121]), "=f"(d[122]), "=f"(d[123]), "=f"(d[124]), "=f"(d[125]), "=f"(d[126]), "=f"(d[127])
        : "r"(a0), "r"(a1), "r"(a2), "r"(a3), "l"(db));
}
__device__ __forceinline__ void wgmma_rs_n256_tb_pred(float (&d)[128], uint32_t a0, uint32_t a1, uint32_t a2, uint32_t a3, uint64_t db, int acc) {
    asm volatile("{\n.reg .pred p;\nsetp.ne.s32 p, %133, 0;\nwgmma.mma_async.sync.aligned.m64n256k16.f32.f16.f16 {"
        "%0, %1, %2, %3, %4, %5, %6, %7, %8, %9, %10, %11, %12, %13, %14, %15, %16, %17, %18, %19, %20, %21, %22, %23, %24, %25, %26, %27, %28, %29, %30, %31, "
        "%32, %33, %34, %35, %36, %37, %38, %39, %40, %41, %42, %43, %44, %45, %46, %47, %48, %49, %50, %51, %52, %53, %54, %55, %56, %57, %58, %59, %60, %61, %62, %63, "
        "%64, %65, %66, %67, %68, %69, %70, %71, %72, %73, %74, %75, %76, %77, %78, %79, %80, %81, %82, %83, %84, %85, %86, %87, %88, %89, %90, %91, %92, %93, %94, %95, "
        "%96, %97, %98, %99, %100, %101, %102, %103, %104, %105, %106, %107, %108, %109, %110, %111, %112, %113, %114, %115, %116, %117, %118, %119, %120, %121, %122, %123, %124, %125, %126, %127}, {%128, %129, %130, %131}, %132, p, 1, 1, 1;\n}\n"
        : "+f"(d[0]), "+f"(d[1]), "+f"(d[2]), "+f"(d[3]), "+f"(d[4]), "+f"(d[5]), "+f"(d[6]), "+f"(d[7]),
          "+f"(d[8]), "+f"(d[9]), "+f"(d[10]), "+f"(d[11]), "+f"(d[12]), "+f"(d[13]), "+f"(d[14]), "+f"(d[15]),
          "+f"(d[16]), "+f"(d[17]), "+f"(d[18]), "+f"(d[19]), "+f"(d[20]), "+f"(d[21]), "+f"(d[22]), "+f"(d[23]),
          "+f"(d[24]), "+f"(d[25]), "+f"(d[26]), "+f"(d[27]), "+f"(d[28]), "+f"(d[29]), "+f"(d[30]), "+f"(d[31]),
          "+f"(d[32]), "+f"(d[33]), "+f"(d[34]), "+f"(d[35]), "+f"(d[36]), "+f"(d[37]), "+f"(d[38]), "+f"(d[39]),
          "+f"(d[40]), "+f"(d[41]), "+f"(d[42]), "+f"(d[43]), "+f"(d[44]), "+f"(d[45]), "+f"(d[46]), "+f"(d[47]),
          "+f"(d[48]), "+f"(d[49]), "+f"(d[50]), "+f"(d[51]), "+f"(d[52]), "+f"(d[53]), "+f"(d[54]), "+f"(d[55]),
          "+f"(d[56]), "+f"(d[57]), "+f"(d[58]), "+f"(d[59]), "+f"(d[60]), "+f"(d[61]), "+f"(d[62]), "+f"(d[63]),
          "+f"(d[64]), "+f"(d[65]), "+f"(d[66]), "+f"(d[67]), "+f"(d[68]), "+f"(d[69]), "+f"(d[70]), "+f"(d[71]),
          "+f"(d[72]), "+f"(d[73]), "+f"(d[74]), "+f"(d[75]), "+f"(d[76]), "+f"(d[77]), "+f"(d[78]), "+f"(d[79]),
          "+f"(d[80]), "+f"(d[81]), "+f"(d[82]), "+f"(d[83]), "+f"(d[84]), "+f"(d[85]), "+f"(d[86]), "+f"(d[87]),
          "+f"(d[88]), "+f"(d[89]), "+f"(d[90]), "+f"(d[91]), "+f"(d[92]), "+f"(d[93]), "+f"(d[94]), "+f"(d[95]),
          "+f"(d[96]), "+f"(d[97]), "+f"(d[98]), "+f"(d[99]), "+f"(d[100]), "+f"(d[101]), "+f"(d[102]), "+f"(d[103]),
          "+f"(d[104]), "+f"(d[105]), "+f"(d[106]), "+f"(d[107]), "+f"(d[108]), "+f"(d[109]), "+f"(d[110]), "+f"(d[111]),
          "+f"(d[112]), "+f"(d[113]), "+f"(d[114]), "+f"(d[115]), "+f"(d[116]), "+f"(d[117]), "+f"(d[118]), "+f"(d[119]),
          "+f"(d[120]), "+f"(d[121]), "+f"(d[122]), "+f"(d[123]), "+f"(d[124]), "+f"(d[125]), "+f"(d[126]), "+f"(d[127])
        : "r"(a0), "r"(a1), "r"(a2), "r"(a3), "l"(db), "r"(acc));
}
__device__ __forceinline__ void wgmma_ss_n256_tb(float (&d)[128], uint64_t da, uint64_t db) {
    asm volatile("wgmma.mma_async.sync.aligned.m64n256k16.f32.bf16.bf16 {"
        "%0, %1, %2, %3, %4, %5, %6, %7, %8, %9, %10, %11, %12, %13, %14, %15, %16, %17, %18, %19, %20, %21, %22, %23, %24, %25, %26, %27, %28, %29, %30, %31, "
        "%32, %33, %34, %35, %36, %37, %38, %39, %40, %41, %42, %43, %44, %45, %46, %47, %48, %49, %50, %51, %52, %53, %54, %55, %56, %57, %58, %59, %60, %61, %62, %63, "
        "%64, %65, %66, %67, %68, %69, %70, %71, %72, %73, %74, %75, %76, %77, %78, %79, %80, %81, %82, %83, %84, %85, %86, %87, %88, %89, %90, %91, %92, %93, %94, %95, "
        "%96, %97, %98, %99, %100, %101, %102, %103, %104, %105, %106, %107, %108, %109, %110, %111, %112, %113, %114, %115, %116, %117, %118, %119, %120, %121, %122, %123, %124, %125, %126, %127}, %128, %129, 1, 1, 1, 0, 1;\n"
        : "+f"(d[0]), "+f"(d[1]), "+f"(d[2]), "+f"(d[3]), "+f"(d[4]), "+f"(d[5]), "+f"(d[6]), "+f"(d[7]),
          "+f"(d[8]), "+f"(d[9]), "+f"(d[10]), "+f"(d[11]), "+f"(d[12]), "+f"(d[13]), "+f"(d[14]), "+f"(d[15]),
          "+f"(d[16]), "+f"(d[17]), "+f"(d[18]), "+f"(d[19]), "+f"(d[20]), "+f"(d[21]), "+f"(d[22]), "+f"(d[23]),
          "+f"(d[24]), "+f"(d[25]), "+f"(d[26]), "+f"(d[27]), "+f"(d[28]), "+f"(d[29]), "+f"(d[30]), "+f"(d[31]),
          "+f"(d[32]), "+f"(d[33]), "+f"(d[34]), "+f"(d[35]), "+f"(d[36]), "+f"(d[37]), "+f"(d[38]), "+f"(d[39]),
          "+f"(d[40]), "+f"(d[41]), "+f"(d[42]), "+f"(d[43]), "+f"(d[44]), "+f"(d[45]), "+f"(d[46]), "+f"(d[47]),
          "+f"(d[48]), "+f"(d[49]), "+f"(d[50]), "+f"(d[51]), "+f"(d[52]), "+f"(d[53]), "+f"(d[54]), "+f"(d[55]),
          "+f"(d[56]), "+f"(d[57]), "+f"(d[58]), "+f"(d[59]), "+f"(d[60]), "+f"(d[61]), "+f"(d[62]), "+f"(d[63]),
          "+f"(d[64]), "+f"(d[65]), "+f"(d[66]), "+f"(d[67]), "+f"(d[68]), "+f"(d[69]), "+f"(d[70]), "+f"(d[71]),
          "+f"(d[72]), "+f"(d[73]), "+f"(d[74]), "+f"(d[75]), "+f"(d[76]), "+f"(d[77]), "+f"(d[78]), "+f"(d[79]),
          "+f"(d[80]), "+f"(d[81]), "+f"(d[82]), "+f"(d[83]), "+f"(d[84]), "+f"(d[85]), "+f"(d[86]), "+f"(d[87]),
          "+f"(d[88]), "+f"(d[89]), "+f"(d[90]), "+f"(d[91]), "+f"(d[92]), "+f"(d[93]), "+f"(d[94]), "+f"(d[95]),
          "+f"(d[96]), "+f"(d[97]), "+f"(d[98]), "+f"(d[99]), "+f"(d[100]), "+f"(d[101]), "+f"(d[102]), "+f"(d[103]),
          "+f"(d[104]), "+f"(d[105]), "+f"(d[106]), "+f"(d[107]), "+f"(d[108]), "+f"(d[109]), "+f"(d[110]), "+f"(d[111]),
          "+f"(d[112]), "+f"(d[113]), "+f"(d[114]), "+f"(d[115]), "+f"(d[116]), "+f"(d[117]), "+f"(d[118]), "+f"(d[119]),
          "+f"(d[120]), "+f"(d[121]), "+f"(d[122]), "+f"(d[123]), "+f"(d[124]), "+f"(d[125]), "+f"(d[126]), "+f"(d[127])
        : "l"(da), "l"(db));
}
__device__ __forceinline__ void wgmma_ss_n256_tb_pred(float (&d)[128], uint64_t da, uint64_t db, int acc) {
    asm volatile("{\n.reg .pred p;\nsetp.ne.s32 p, %130, 0;\nwgmma.mma_async.sync.aligned.m64n256k16.f32.bf16.bf16 {"
        "%0, %1, %2, %3, %4, %5, %6, %7, %8, %9, %10, %11, %12, %13, %14, %15, %16, %17, %18, %19, %20, %21, %22, %23, %24, %25, %26, %27, %28, %29, %30, %31, "
        "%32, %33, %34, %35, %36, %37, %38, %39, %40, %41, %42, %43, %44, %45, %46, %47, %48, %49, %50, %51, %52, %53, %54, %55, %56, %57, %58, %59, %60, %61, %62, %63, "
        "%64, %65, %66, %67, %68, %69, %70, %71, %72, %73, %74, %75, %76, %77, %78, %79, %80, %81, %82, %83, %84, %85, %86, %87, %88, %89, %90, %91, %92, %93, %94, %95, "
        "%96, %97, %98, %99, %100, %101, %102, %103, %104, %105, %106, %107, %108, %109, %110, %111, %112, %113, %114, %115, %116, %117, %118, %119, %120, %121, %122, %123, %124, %125, %126, %127}, %128, %129, p, 1, 1, 0, 1;\n}\n"
        : "+f"(d[0]), "+f"(d[1]), "+f"(d[2]), "+f"(d[3]), "+f"(d[4]), "+f"(d[5]), "+f"(d[6]), "+f"(d[7]),
          "+f"(d[8]), "+f"(d[9]), "+f"(d[10]), "+f"(d[11]), "+f"(d[12]), "+f"(d[13]), "+f"(d[14]), "+f"(d[15]),
          "+f"(d[16]), "+f"(d[17]), "+f"(d[18]), "+f"(d[19]), "+f"(d[20]), "+f"(d[21]), "+f"(d[22]), "+f"(d[23]),
          "+f"(d[24]), "+f"(d[25]), "+f"(d[26]), "+f"(d[27]), "+f"(d[28]), "+f"(d[29]), "+f"(d[30]), "+f"(d[31]),
          "+f"(d[32]), "+f"(d[33]), "+f"(d[34]), "+f"(d[35]), "+f"(d[36]), "+f"(d[37]), "+f"(d[38]), "+f"(d[39]),
          "+f"(d[40]), "+f"(d[41]), "+f"(d[42]), "+f"(d[43]), "+f"(d[44]), "+f"(d[45]), "+f"(d[46]), "+f"(d[47]),
          "+f"(d[48]), "+f"(d[49]), "+f"(d[50]), "+f"(d[51]), "+f"(d[52]), "+f"(d[53]), "+f"(d[54]), "+f"(d[55]),
          "+f"(d[56]), "+f"(d[57]), "+f"(d[58]), "+f"(d[59]), "+f"(d[60]), "+f"(d[61]), "+f"(d[62]), "+f"(d[63]),
          "+f"(d[64]), "+f"(d[65]), "+f"(d[66]), "+f"(d[67]), "+f"(d[68]), "+f"(d[69]), "+f"(d[70]), "+f"(d[71]),
          "+f"(d[72]), "+f"(d[73]), "+f"(d[74]), "+f"(d[75]), "+f"(d[76]), "+f"(d[77]), "+f"(d[78]), "+f"(d[79]),
          "+f"(d[80]), "+f"(d[81]), "+f"(d[82]), "+f"(d[83]), "+f"(d[84]), "+f"(d[85]), "+f"(d[86]), "+f"(d[87]),
          "+f"(d[88]), "+f"(d[89]), "+f"(d[90]), "+f"(d[91]), "+f"(d[92]), "+f"(d[93]), "+f"(d[94]), "+f"(d[95]),
          "+f"(d[96]), "+f"(d[97]), "+f"(d[98]), "+f"(d[99]), "+f"(d[100]), "+f"(d[101]), "+f"(d[102]), "+f"(d[103]),
          "+f"(d[104]), "+f"(d[105]), "+f"(d[106]), "+f"(d[107]), "+f"(d[108]), "+f"(d[109]), "+f"(d[110]), "+f"(d[111]),
          "+f"(d[112]), "+f"(d[113]), "+f"(d[114]), "+f"(d[115]), "+f"(d[116]), "+f"(d[117]), "+f"(d[118]), "+f"(d[119]),
          "+f"(d[120]), "+f"(d[121]), "+f"(d[122]), "+f"(d[123]), "+f"(d[124]), "+f"(d[125]), "+f"(d[126]), "+f"(d[127])
        : "l"(da), "l"(db), "r"(acc));
}
__device__ __forceinline__ void wgmma_ss_n128_tb(float (&d)[64], uint64_t da, uint64_t db) {
    asm volatile("wgmma.mma_async.sync.aligned.m64n128k16.f32.bf16.bf16 {"
        "%0, %1, %2, %3, %4, %5, %6, %7, %8, %9, %10, %11, %12, %13, %14, %15, %16, %17, %18, %19, %20, %21, %22, %23, %24, %25, %26, %27, %28, %29, %30, %31, "
        "%32, %33, %34, %35, %36, %37, %38, %39, %40, %41, %42, %43, %44, %45, %46, %47, %48, %49, %50, %51, %52, %53, %54, %55, %56, %57, %58, %59, %60, %61, %62, %63}, %64, %65, 1, 1, 1, 0, 1;\n"
        : "+f"(d[0]), "+f"(d[1]), "+f"(d[2]), "+f"(d[3]), "+f"(d[4]), "+f"(d[5]), "+f"(d[6]), "+f"(d[7]),
          "+f"(d[8]), "+f"(d[9]), "+f"(d[10]), "+f"(d[11]), "+f"(d[12]), "+f"(d[13]), "+f"(d[14]), "+f"(d[15]),
          "+f"(d[16]), "+f"(d[17]), "+f"(d[18]), "+f"(d[19]), "+f"(d[20]), "+f"(d[21]), "+f"(d[22]), "+f"(d[23]),
          "+f"(d[24]), "+f"(d[25]), "+f"(d[26]), "+f"(d[27]), "+f"(d[28]), "+f"(d[29]), "+f"(d[30]), "+f"(d[31]),
          "+f"(d[32]), "+f"(d[33]), "+f"(d[34]), "+f"(d[35]), "+f"(d[36]), "+f"(d[37]), "+f"(d[38]), "+f"(d[39]),
          "+f"(d[40]), "+f"(d[41]), "+f"(d[42]), "+f"(d[43]), "+f"(d[44]), "+f"(d[45]), "+f"(d[46]), "+f"(d[47]),
          "+f"(d[48]), "+f"(d[49]), "+f"(d[50]), "+f"(d[51]), "+f"(d[52]), "+f"(d[53]), "+f"(d[54]), "+f"(d[55]),
          "+f"(d[56]), "+f"(d[57]), "+f"(d[58]), "+f"(d[59]), "+f"(d[60]), "+f"(d[61]), "+f"(d[62]), "+f"(d[63])
        : "l"(da), "l"(db));
}
__device__ __forceinline__ void wgmma_ss_n128_tb_pred(float (&d)[64], uint64_t da, uint64_t db, int acc) {
    asm volatile("{\n.reg .pred p;\nsetp.ne.s32 p, %66, 0;\nwgmma.mma_async.sync.aligned.m64n128k16.f32.bf16.bf16 {"
        "%0, %1, %2, %3, %4, %5, %6, %7, %8, %9, %10, %11, %12, %13, %14, %15, %16, %17, %18, %19, %20, %21, %22, %23, %24, %25, %26, %27, %28, %29, %30, %31, "
        "%32, %33, %34, %35, %36, %37, %38, %39, %40, %41, %42, %43, %44, %45, %46, %47, %48, %49, %50, %51, %52, %53, %54, %55, %56, %57, %58, %59, %60, %61, %62, %63}, %64, %65, p, 1, 1, 0, 1;\n}\n"
        : "+f"(d[0]), "+f"(d[1]), "+f"(d[2]), "+f"(d[3]), "+f"(d[4]), "+f"(d[5]), "+f"(d[6]), "+f"(d[7]),
          "+f"(d[8]), "+f"(d[9]), "+f"(d[10]), "+f"(d[11]), "+f"(d[12]), "+f"(d[13]), "+f"(d[14]), "+f"(d[15]),
          "+f"(d[16]), "+f"(d[17]), "+f"(d[18]), "+f"(d[19]), "+f"(d[20]), "+f"(d[21]), "+f"(d[22]), "+f"(d[23]),
          "+f"(d[24]), "+f"(d[25]), "+f"(d[26]), "+f"(d[27]), "+f"(d[28]), "+f"(d[29]), "+f"(d[30]), "+f"(d[31]),
          "+f"(d[32]), "+f"(d[33]), "+f"(d[34]), "+f"(d[35]), "+f"(d[36]), "+f"(d[37]), "+f"(d[38]), "+f"(d[39]),
          "+f"(d[40]), "+f"(d[41]), "+f"(d[42]), "+f"(d[43]), "+f"(d[44]), "+f"(d[45]), "+f"(d[46]), "+f"(d[47]),
          "+f"(d[48]), "+f"(d[49]), "+f"(d[50]), "+f"(d[51]), "+f"(d[52]), "+f"(d[53]), "+f"(d[54]), "+f"(d[55]),
          "+f"(d[56]), "+f"(d[57]), "+f"(d[58]), "+f"(d[59]), "+f"(d[60]), "+f"(d[61]), "+f"(d[62]), "+f"(d[63])
        : "l"(da), "l"(db), "r"(acc));
}

__device__ __forceinline__ void wg_fence() { asm volatile("wgmma.fence.sync.aligned;\n" ::: "memory"); }
__device__ __forceinline__ void wg_commit() { asm volatile("wgmma.commit_group.sync.aligned;\n" ::: "memory"); }
template <int N> __device__ __forceinline__ void wg_wait() { asm volatile("wgmma.wait_group.sync.aligned %0;\n" ::"n"(N) : "memory"); }
template <int N> __device__ __forceinline__ void fence_regs(float (&a)[N]) {
#pragma unroll
    for (int i = 0; i < N; i++) asm volatile("" : "+f"(a[i])::"memory");
}
template <int N> __device__ __forceinline__ void fence_regs(uint32_t (&a)[N]) {
#pragma unroll
    for (int i = 0; i < N; i++) asm volatile("" : "+r"(a[i])::"memory");
}
__device__ __forceinline__ void mbar_init(uint32_t bar, uint32_t cnt) {
    asm volatile("mbarrier.init.shared::cta.b64 [%0], %1;\n" ::"r"(bar), "r"(cnt) : "memory");
}
__device__ __forceinline__ void mbar_expect_tx(uint32_t bar, uint32_t bytes) {
    asm volatile("mbarrier.arrive.expect_tx.shared::cta.b64 _, [%0], %1;\n" ::"r"(bar), "r"(bytes) : "memory");
}
__device__ __forceinline__ void mbar_wait(uint32_t bar, uint32_t parity) {
    asm volatile("{\n.reg .pred p;\nLW:\nmbarrier.try_wait.parity.shared::cta.b64 p, [%0], %1;\n@!p pmevent 0;\n@!p bra LW;\n}\n" ::"r"(bar), "r"(parity) : "memory");
}
__device__ __forceinline__ void mbar_wait_sleep(uint32_t bar, uint32_t parity) {
    asm volatile("{\n.reg .pred p;\nLW:\nmbarrier.try_wait.parity.shared::cta.b64 p, [%0], %1, 20000;\n@!p pmevent 0;\n@!p bra LW;\n}\n" ::"r"(bar), "r"(parity) : "memory");
}
__device__ __forceinline__ void mbar_wait_bounded(uint32_t bar, uint32_t parity) {
    asm volatile("{\n.reg .pred p;\n.reg .u32 c;\nmov.u32 c, 0;\nLW:\nmbarrier.try_wait.parity.shared::cta.b64 p, [%0], %1, 20000;\n@p bra LD;\n"
                 "add.u32 c, c, 1;\nsetp.ge.u32 p, c, 262144;\n@p trap;\nbra LW;\nLD:\n}\n" ::"r"(bar), "r"(parity) : "memory");
}
__device__ __forceinline__ void flag_wait(const int* p, int v) {
    asm volatile("{\n.reg .pred p;\n.reg .s32 f;\nLW:\nld.acquire.gpu.global.s32 f, [%0];\nsub.s32 f, f, %1;\nsetp.lt.s32 p, f, 0;\n@p bra LW;\n}\n" ::"l"(p), "r"(v) : "memory");
}
__device__ __forceinline__ void flag_wait_bounded(const int* p, int v) {
    asm volatile("{\n.reg .pred p;\n.reg .u32 c;\n.reg .s32 f;\nmov.u32 c, 0;\nLW:\nld.acquire.gpu.global.s32 f, [%0];\nsub.s32 f, f, %1;\nsetp.ge.s32 p, f, 0;\n@p bra LD;\n"
                 "nanosleep.u32 500;\nadd.u32 c, c, 1;\nsetp.ge.u32 p, c, 4194304;\n@p trap;\nbra LW;\nLD:\n}\n" ::"l"(p), "r"(v) : "memory");
}
__device__ __forceinline__ bool elect() {
    uint32_t p; asm volatile("{\n.reg .pred p;\nelect.sync _|p, -1;\nselp.u32 %0, 1, 0, p;\n}\n" : "=r"(p)); return p;
}
__device__ __forceinline__ void bulk_g2s(uint32_t dst, const void* src, uint32_t bytes, uint32_t bar) {
    asm volatile("cp.async.bulk.shared::cluster.global.mbarrier::complete_tx::bytes [%0], [%1], %2, [%3];\n"
                 ::"r"(dst), "l"(src), "r"(bytes), "r"(bar) : "memory");
}
__device__ __forceinline__ void bulk_g2s_mc(uint32_t dst, const void* src, uint32_t bytes, uint32_t bar, uint16_t mask) {
    asm volatile("cp.async.bulk.shared::cluster.global.mbarrier::complete_tx::bytes.multicast::cluster [%0], [%1], %2, [%3], %4;\n"
                 ::"r"(dst), "l"(src), "r"(bytes), "r"(bar), "h"(mask) : "memory");
}
__device__ __forceinline__ void tma_g2s(uint32_t dst, const CUtensorMap* tm, int rowgroup, uint32_t bar) {
    asm volatile("cp.async.bulk.tensor.4d.shared::cluster.global.tile.mbarrier::complete_tx::bytes [%0], [%1, {0, 0, 0, %2}], [%3];\n"
                 ::"r"(dst), "l"(tm), "r"(rowgroup), "r"(bar) : "memory");
}
__device__ __forceinline__ void bar_sync(int id, int n) { asm volatile("bar.sync %0, %1;\n" ::"r"(id), "r"(n) : "memory"); }
__device__ __forceinline__ void bar_arrive(int id, int n) { asm volatile("bar.arrive %0, %1;\n" ::"r"(id), "r"(n) : "memory"); }
__device__ __forceinline__ float shfl_f32(float v, int src) {
    float r; asm volatile("shfl.sync.idx.b32 %0, %1, %2, 31, -1;\n" : "=f"(r) : "f"(v), "r"(src)); return r;
}
__device__ __forceinline__ float ex2(float x) { float y; asm("ex2.approx.ftz.f32 %0, %1;\n" : "=f"(y) : "f"(x)); return y; }
__device__ __forceinline__ float rcp(float x) { float y; asm("rcp.approx.ftz.f32 %0, %1;\n" : "=f"(y) : "f"(x)); return y; }
__device__ __forceinline__ uint32_t pack_bf16(float lo, float hi) {
    uint32_t r; asm("cvt.rn.bf16x2.f32 %0, %1, %2;\n" : "=r"(r) : "f"(hi), "f"(lo)); return r;
}
__device__ __forceinline__ uint32_t pack_f16(float lo, float hi) {
    uint32_t r; asm("cvt.rn.f16x2.f32 %0, %1, %2;\n" : "=r"(r) : "f"(hi), "f"(lo)); return r;
}
__device__ __forceinline__ uint32_t pack_f16_sat(float lo, float hi) {
    uint32_t r; asm("cvt.rn.satfinite.f16x2.f32 %0, %1, %2;\n" : "=r"(r) : "f"(hi), "f"(lo)); return r;
}
__device__ __forceinline__ float f16_lo(uint32_t v) { float r; asm("cvt.f32.f16 %0, %1;\n" : "=f"(r) : "h"((unsigned short)v)); return r; }
__device__ __forceinline__ float f16_hi(uint32_t v) { return f16_lo(v >> 16); }
__device__ __forceinline__ float bf_lo(uint32_t v) { return __uint_as_float(v << 16); }
__device__ __forceinline__ float bf_hi(uint32_t v) { return __uint_as_float(v & 0xFFFF0000u); }
__device__ __forceinline__ float bf_round(float x) { return __uint_as_float(pack_bf16(0.f, x)); }
__device__ __forceinline__ void st_release(int* p, int v) {
    asm volatile("st.release.gpu.global.s32 [%0], %1;\n" ::"l"(p), "r"(v) : "memory");
}
__device__ __forceinline__ uint4 ldg_pinned(const uint4* p) {
    uint4 v; asm volatile("ld.global.nc.v4.u32 {%0, %1, %2, %3}, [%4];\n" : "=r"(v.x), "=r"(v.y), "=r"(v.z), "=r"(v.w) : "l"(p) : "memory"); return v;
}
__device__ __forceinline__ void stmatrix_x4(uint32_t addr, uint32_t r0, uint32_t r1, uint32_t r2, uint32_t r3) {
    asm volatile("stmatrix.sync.aligned.m8n8.x4.shared.b16 [%0], {%1, %2, %3, %4};\n" ::"r"(addr), "r"(r0), "r"(r1), "r"(r2), "r"(r3) : "memory");
}

__device__ __forceinline__ uint32_t tile_off(int r, int ch) {
    return (uint32_t)((r >> 3) * 4096 + (ch >> 3) * 1024 + (r & 7) * 128 + (((ch ^ r) & 7) << 4));
}
__device__ __forceinline__ constexpr int frag_off(int i) { return (i & 4) * 1024 + (i & 8) * 256 + (i & 3) * 512; }
__device__ __forceinline__ int h_unit(int qt, int u) { return qt < 78 ? u * 78 + qt : 624; }
__device__ __forceinline__ int row_off(int r) { return 4096 + h_unit(r >> 7, (r >> 4) & 7) * 8192 + (r & 8) * 512 + (r & 7) * 144; }

__device__ __forceinline__ float2 lds64f(uint32_t a) { float2 v; asm volatile("ld.shared.v2.f32 {%0, %1}, [%2];\n" : "=f"(v.x), "=f"(v.y) : "r"(a) : "memory"); return v; }
__device__ __forceinline__ uint64_t lds64(uint32_t a) { uint64_t v; asm volatile("ld.shared.u64 %0, [%1];\n" : "=l"(v) : "r"(a) : "memory"); return v; }
__device__ __forceinline__ uint4 lds128(uint32_t a) {
    uint4 v; asm volatile("ld.shared.v4.u32 {%0, %1, %2, %3}, [%4];\n" : "=r"(v.x), "=r"(v.y), "=r"(v.z), "=r"(v.w) : "r"(a) : "memory"); return v;
}
__device__ __forceinline__ void sts128(uint32_t a, uint32_t x, uint32_t y, uint32_t z, uint32_t w) {
    asm volatile("st.shared.v4.u32 [%0], {%1, %2, %3, %4};\n" ::"r"(a), "r"(x), "r"(y), "r"(z), "r"(w) : "memory");
}
__device__ __forceinline__ void mbar_arrive(uint32_t bar) {
    asm volatile("mbarrier.arrive.shared::cta.b64 _, [%0];\n" ::"r"(bar) : "memory");
}
__device__ __forceinline__ uint64_t mkaddr(uint32_t lo, uint32_t hi) { uint64_t a; asm("mov.b64 %0, {%1, %2};\n" : "=l"(a) : "r"(lo), "r"(hi)); return a; }
__device__ __forceinline__ void red_add(int* p) { asm volatile("red.relaxed.gpu.global.add.s32 [%0], 1;\n" ::"l"(p) : "memory"); }
__device__ __forceinline__ void red_release(int* p) {
    asm volatile("fence.proxy.async.global;\nfence.acq_rel.gpu;\nred.relaxed.gpu.global.add.s32 [%0], 1;\n" ::"l"(p) : "memory");
}
__device__ __forceinline__ void fence_async_global() { asm volatile("fence.proxy.async.global;\n" ::: "memory"); }
__device__ __forceinline__ void fence_async_smem() { asm volatile("fence.proxy.async.shared::cta;\n" ::: "memory"); }
__device__ __forceinline__ void bulk_s2g(void* dst, uint32_t src, uint32_t bytes) {
    asm volatile("cp.async.bulk.global.shared::cta.bulk_group [%0], [%1], %2;\ncp.async.bulk.commit_group;\n" ::"l"(dst), "r"(src), "r"(bytes) : "memory");
}
__device__ __forceinline__ void mma16816(float (&c)[4], uint32_t a0, uint32_t a1, uint32_t a2, uint32_t a3, uint32_t b0, uint32_t b1) {
    asm("mma.sync.aligned.m16n8k16.row.col.f32.bf16.bf16.f32 {%0, %1, %2, %3}, {%4, %5, %6, %7}, {%8, %9}, {%0, %1, %2, %3};\n"
        : "+f"(c[0]), "+f"(c[1]), "+f"(c[2]), "+f"(c[3]) : "r"(a0), "r"(a1), "r"(a2), "r"(a3), "r"(b0), "r"(b1));
}
__device__ __forceinline__ void mma1688(float (&c)[4], uint32_t a0, uint32_t a1, uint32_t b0) {
    asm("mma.sync.aligned.m16n8k8.row.col.f32.bf16.bf16.f32 {%0, %1, %2, %3}, {%4, %5}, {%6}, {%0, %1, %2, %3};\n"
        : "+f"(c[0]), "+f"(c[1]), "+f"(c[2]), "+f"(c[3]) : "r"(a0), "r"(a1), "r"(b0));
}
__device__ __forceinline__ uint32_t hadd2_f16(uint32_t a, uint32_t b) { uint32_t r; asm("add.rn.f16x2 %0, %1, %2;\n" : "=r"(r) : "r"(a), "r"(b)); return r; }
__device__ __forceinline__ uint32_t hfma2(uint32_t a, uint32_t b, uint32_t c) { uint32_t r; asm("fma.rn.bf16x2 %0, %1, %2, %3;\n" : "=r"(r) : "r"(a), "r"(b), "r"(c)); return r; }

constexpr int SM_Q = 0;
constexpr int SM_KV = 65536;
constexpr int SM_ML = SM_KV + STAGES * KV_BYTES;
constexpr int SM_BAR = SM_ML + 1024;
constexpr int SM_TOTAL = SM_BAR + 256;
constexpr float SCALE_LOG2 = 1.4426950408889634f / 16.0f;
constexpr float KV_SCALE = 0.75f;
constexpr float KV_OFF = 6.f;
constexpr uint32_t KV_OFF2 = 0x46004600u;
constexpr uint32_t KV_NEG4 = 0xCE00CE00u;
constexpr uint32_t P_LIMIT = 0x78007800u;
__device__ __forceinline__ uint32_t kvf(uint32_t a) {
    uint32_t r; asm("fma.rn.f16x2 %0, %1, %2, %3;\n" : "=r"(r) : "r"(a), "r"(pack_f16(KV_SCALE, KV_SCALE)), "r"(KV_OFF2)); return r;
}
enum { BAR_PP0 = 1, BAR_PP1 = 2, BAR_WG0 = 3, BAR_WG1 = 4, BAR_H0 = 5, BAR_H1 = 6, BAR_AUX = 7, BAR_BF = 8, BAR_H2 = 9, BAR_X = 10, BAR_GO = 11, BAR_WG2 = 12, BAR_ST = 13 };

struct Sched { int qt0, n0, nkv, qt1, cls, owner, pin, nmc, pair, zb, nz, nw; };
static Sched get_sched(int c, int r) {
    Sched s;
    s.qt1 = s.pin = s.zb = s.nz = 0; s.pair = c < 52; s.n0 = s.nkv = 75; s.cls = 0x420; s.owner = r == 0; s.nw = 4;
    if (c < 52) {
        const int p = c >> 1, odd = c & 1, tc = p, ta = 26 + 2 * p, tb = ta + 1;
        s.pin = odd; s.nmc = PAIR_MC * (odd ? 50 : 25); s.nw = 8;
        s.zb = 2 * (odd ? tb : ta) + 1 - r;
        if (r == 0) {
            s.qt0 = odd ? tb : ta; s.cls = odd ? 0x431 : 0x420;
        } else {
            s.qt0 = odd ? tc : tb; s.qt1 = odd ? tb : ta; s.n0 = odd ? 50 : 25; s.cls = odd ? 0x231 : 0x130;
        }
    } else if (c < 65) {
        s.owner = 1; s.nmc = 75; s.qt0 = 2 * (c - 52) + r; s.pin = 1;
    } else {
        s.qt0 = 78; s.nmc = 0;
        if (r) { s.n0 = s.nkv = 50; s.cls = 0x31; s.nw = 0; }
        s.zb = r ? 156 : 0; s.nz = r ? 27 : 26;
    }
    return s;
}

struct Hot {
    const __nv_bfloat16 *wk, *wq, *x;
    Scratch* s;
};
struct Params {
    const __nv_bfloat16* deg_inv;
    const int *src, *dst;
    __nv_bfloat16* out;
    uint32_t dhi;
    int E;
    uint32_t sched[NCTA][3];
    CUtensorMap tm_out;
    CUtensorMap tm_outc;
    CUtensorMap tm_w[3];
};
static_assert(offsetof(Params, tm_outc) == offsetof(Params, tm_out) + 128, "layout");
#define SC_QT(seg) ((int)(P.sched[blockIdx.x][seg] & 255))
#define SC_N0 ((int)((P.sched[blockIdx.x][0] >> 8) & 255))
#define SC_NKV ((int)((P.sched[blockIdx.x][0] >> 16) & 255))
#define SC_OWNER ((P.sched[blockIdx.x][0] >> 24) & 1)
#define SC_PIN ((P.sched[blockIdx.x][0] >> 25) & 1)
#define SC_NMC ((int)((P.sched[blockIdx.x][1] >> 8) & 255))
#define SC_CLS (P.sched[blockIdx.x][1] >> 16)
#define SC_ZB(k) ((int)(P.sched[blockIdx.x][2] & 255) + 2 * (k) - ((P.sched[blockIdx.x][2] & 255) + 2 * (k) >= 157 ? 157 : 0))
#define SC_NZ ((int)((P.sched[blockIdx.x][2] >> 8) & 255))
#define SC_NW ((int)(P.sched[blockIdx.x][2] >> 16))
#define SC_PAIR (blockIdx.x < 104)
#define SC_TAIL (blockIdx.x >= NCTA - 2)

__global__ void __cluster_dims__(2, 1, 1) __launch_bounds__(384, 1) k_main(const __grid_constant__ Hot H, const __grid_constant__ Params P) {
    extern __shared__ __align__(1024) uint8_t smem[];
    const uint32_t sb = (uint32_t)__cvta_generic_to_shared(smem);
    const int tid = threadIdx.x, wg = __shfl_sync(~0u, tid >> 7, 0);
    const int lane = tid & 31, g = lane >> 2, q = lane & 3;
    const uint32_t rank = blockIdx.x & 1;
    const uint32_t bar_full = sb + SM_BAR, bar_q = bar_full + 32, bar_go = bar_full + 48;
    const uint32_t bar_pin = bar_full + 56;
    const uint32_t bar_qfree = bar_full + 88, bar_pdone = bar_full + 104, bar_zst = bar_full + 120, bar_rfree = bar_full + 136;
    const uint32_t bar_empty = bar_full + 144, bar_end = bar_full + 176, bar_x = bar_full + 192;

    if (wg == 2) {
        const int warp = __shfl_sync(~0u, (tid >> 5) & 3, 0);
        const int t = tid & 127;
        unsigned done;
        {
            uint4 ra[8], rb[8], rk[8], rz[8];
            if (blockIdx.x < 128) {
                const int rg = blockIdx.x >> 2;
                const int e = (rg >> 2) * 32 + (g >> 1) * 8 + (rg & 2) * 2 + (rg & 1) * 2 + (g & 1);
                const int f = (blockIdx.x & 3) * 64 + (warp >> 1) * 32 + (g >> 1) * 8 + (warp & 1) * 4 + (g & 1);
                const uint4* pk = (const uint4*)(H.wk + f * 256 + q * 8);
                const uint4* pq = (const uint4*)(H.wq + e * 256 + q * 8);
                const uint4* pz = (const uint4*)(H.wk + 255 * 256) + q;
                asm volatile("" : "+l"(pz));
#pragma unroll
                for (int s = 0; s < 8; s++) {
                    ra[s] = ldg_pinned(pk + 4 * s);
                    rb[s] = ldg_pinned(pk + 4 * s + 64);
                    rk[s] = ldg_pinned(pq + 4 * s);
                    rz[s] = ldg_pinned(pz + 4 * s);
                }
            }
            asm volatile("{\n.reg .pred p;\nsetp.eq.s32 p, %2, 0;\nmov.u32 %0, 0;\n@p ld.global.cg.u32 %0, [%1];\n}\n" : "=r"(done) : "l"(&g_sync[SY_DONE * 32]), "r"(lane) : "memory");
            bar_arrive(BAR_X, 384);
            if (warp == 0 && elect()) {
#pragma unroll
                for (int i = 0; i < 23; i++) mbar_init(bar_full + 8 * i, i < 11 ? 1 : i < 18 ? 4 : i == 22 ? 11 : SC_TAIL ? 8 : 16);
                mbar_expect_tx(bar_pin, QB_BYTES / 2 + 512); mbar_expect_tx(bar_pin + 8, QB_BYTES / 2);
                mbar_expect_tx(bar_pin + 16, SC_PAIR ? 512 : 1024); mbar_expect_tx(bar_pin + 24, QB_BYTES);
                asm volatile("fence.mbarrier_init.release.cluster;\n" ::: "memory");
            }
            __syncwarp();
            asm volatile("barrier.cluster.arrive.relaxed.aligned;\n" ::: "memory");
            if (blockIdx.x < 128) {
                float c0[4] = {0.f, 0.f, 0.f, 0.f}, c1[4] = {0.f, 0.f, 0.f, 0.f}, z0[4] = {0.f, 0.f, 0.f, 0.f}, z1[4] = {0.f, 0.f, 0.f, 0.f};
#pragma unroll
                for (int s = 0; s < 8; s++) {
                    mma16816(c0, ra[s].x, rb[s].x, ra[s].y, rb[s].y, rk[s].x, rk[s].y);
                    mma16816(c1, ra[s].z, rb[s].z, ra[s].w, rb[s].w, rk[s].z, rk[s].w);
                    mma16816(z0, rz[s].x, rz[s].x, rz[s].y, rz[s].y, rk[s].x, rk[s].y);
                    mma16816(z1, rz[s].z, rz[s].z, rz[s].w, rz[s].w, rk[s].z, rk[s].w);
                }
#pragma unroll
                for (int i = 0; i < 4; i++) c0[i] = ((c0[i] + c1[i]) - (z0[i] + z1[i])) * (SCALE_LOG2 / KV_SCALE);
                asm volatile("stmatrix.sync.aligned.m8n8.x2.trans.shared.b16 [%0], {%1, %2};\n"
                             ::"r"(sb + SM_ML + (lane & 7) * 128 + (((2 * warp + ((lane >> 3) & 1)) ^ lane) & 7) * 16),
                             "r"(pack_f16_sat(c0[0], c0[1])), "r"(pack_f16_sat(c0[2], c0[3])) : "memory");
                fence_async_smem();
            }
        }
        asm volatile("setmaxnreg.dec.sync.aligned.u32 %0;\n" ::"n"(REG_P));
        if (blockIdx.x < 128) {
            bar_sync(BAR_WG2, 128);
            if (warp == 1 && elect()) {
                bulk_s2g(g_w + blockIdx.x * 1024, sb + SM_ML, 1024);
                asm volatile("cp.async.bulk.wait_group 0;\n" ::: "memory");
                red_release(&g_sync[(SY_A + (blockIdx.x >> 5)) * 32]);
            }
            __syncwarp();
        }
        if (warp == 1) bar_arrive(BAR_GO, 160);
        done = __shfl_sync(~0u, done, 0);
        const int ep = (int)(done / NCTA) + 1;
        if (SC_TAIL) {
            bar_sync(BAR_WG2, 128);
            if (warp == 1 && elect()) red_add(&g_sync[SY_DONE * 32]);
            __syncwarp();
        }
        asm volatile("barrier.cluster.wait.acquire.aligned;\n" ::: "memory");
        if (warp == 0) {
            if (lane < 4) mbar_expect_tx(bar_full + 8 * lane, QB_BYTES);
            if (rank == 1 || !A_MC) {
                flag_wait(&g_sync[(SY_A + (lane & 3)) * 32], 32 * ep);
                fence_async_global();
                __syncwarp();
                if (elect()) {
#pragma unroll 1
                    for (int j = 0; j < 4; j++) {
                        if (A_MC) bulk_g2s_mc(sb + SM_KV + j * KV_BYTES, g_w + j * QB_BYTES, QB_BYTES, bar_full + 8 * j, 3);
                        else bulk_g2s(sb + SM_KV + j * KV_BYTES, g_w + j * QB_BYTES, QB_BYTES, bar_full + 8 * j);
                    }
                }
            }
            __syncwarp();
            if (elect()) {
                const uint8_t* base = (const uint8_t*)H.s;
                const uint32_t pt = offsetof(Scratch, part) + (SC_PAIR ? SC_ZB(0) >> 1 : SC_QT(0)) * (2 * PART_BYTES);
                uint32_t cls = SC_CLS, tile = cls & 15;
#pragma unroll 1
                for (int j = 0; j < SC_NKV + SC_NW; j++) {
                    const int k = j - SC_NKV;
                    const int sw = k < 0 ? j - SC_N0 : -1;
                    const uint32_t st = j & 3, slot = sb + SM_KV + st * KV_BYTES;
                    int fo = -1, fv = 1;
                    if (j < 3) { fo = (SY_H0 + tile) * 32; fv = 5; }
                    if (j == 3) { fo = SY_H1 * 32; fv = 79; }
                    if (sw == 1) fo = 24 * 32 + 80 + SC_QT(1);
                    if (k == -1 && SC_PIN) fo = 24 * 32 + (SC_PAIR ? SC_ZB(0) >> 1 : SC_QT(0));
                    if (k == 0) fo = SY_B * 32;
                    if (k == 1) { fo = (SC_TAIL ? SY_AUX0 : SY_AUX) * 32; fv = SC_TAIL ? NAUX : NAUX / 3; }
                    if (fo >= 0) {
                        flag_wait(g_sync + fo, fv * ep);
                        fence_async_global();
                    }
                    if (sw == 2 || (k == 2 && !SC_TAIL)) {
                        uint32_t src = sw == 2 ? offsetof(Scratch, q) + (2 * SC_QT(1) + 1) * QB_BYTES : SC_PAIR ? offsetof(Scratch, agg) + SC_ZB(0) * QB_BYTES : pt;
#pragma unroll 1
                        for (int w = 0; w < (k == 2 && SC_PAIR ? 1 : 2); w++) {
                            mbar_wait_sleep(bar_qfree + 8 * w, k == 2 && !SC_OWNER);
                            mbar_expect_tx(bar_q + 8 * w, QB_BYTES);
                            bulk_g2s(sb + SM_Q + w * QB_BYTES, base + src, QB_BYTES, bar_q + 8 * w);
                            src += sw == 2 ? -QB_BYTES : PART_BYTES + 512;
                        }
                    }
                    if ((sw | 1) == 3) {
                        mbar_wait_sleep(bar_pdone + 8 * (sw - 2), 0);
                        bulk_s2g(g_part + (2 * SC_QT(0) + sw - 2) * PART_BYTES, slot, PART_BYTES);
                        asm volatile("cp.async.bulk.wait_group.read 0;\n" ::: "memory");
                    }
                    if (sw == 5) {
                        asm volatile("cp.async.bulk.wait_group 0;\nfence.proxy.async.global;\n" ::: "memory");
                        st_release(&g_pflag[SC_QT(0)], ep);
                    }
                    mbar_wait_sleep(bar_empty + 8 * st, (j >> 2) & 1);
                    if (k == 0) {
                        asm volatile("prefetch.tensormap [%0];\n" ::"l"(&P.tm_outc) : "memory");
                        if (SC_PIN) bulk_g2s(sb + SM_ML, base + (pt + QB_BYTES + (SC_PAIR ? 512 - rank * 512 : 0)), SC_PAIR ? 512 : 1024, bar_pin + 16);
                    }
                    if ((unsigned)k < 4 && SC_PIN && SC_PAIR)
                        bulk_g2s(slot + QB_BYTES, base + (pt + (1 - rank) * (PART_BYTES + 512) + k * 8192), 8192, bar_pin + 24);
                    const uint32_t bytes = k < 0 ? KV_BYTES : QB_BYTES;
                    const uint32_t src = k < 0 ? 4096 + tile * KV_BYTES : offsetof(Scratch, w) + (12 - SC_NW + k) * QB_BYTES;
                    mbar_expect_tx(bar_full + 8 * st, bytes);
                    if (j < SC_NMC) bulk_g2s_mc(slot + rank * (KV_BYTES / 2), base + (src + rank * (KV_BYTES / 2)), KV_BYTES / 2, bar_full + 8 * st, 3);
                    else bulk_g2s(slot, base + src, bytes, bar_full + 8 * st);
                    if (SC_TAIL ? k + 1 == SC_NW : j == GO0) mbar_arrive(bar_go);
                    tile += 5;
                    if (tile >= NKV) { cls >>= 4; tile = cls & 15; }
                }
            }
        } else {
            if (warp == 2 && SC_OWNER) {
                uint8_t* dst = g_hz + 4096 + h_unit(SC_QT(0), 0) * 8192;
                auto send = [&](int u0, int u1) {
#pragma unroll
                    for (int u = u0; u < u1; u++) {
                        bulk_s2g(dst + u * (78 * 8192), sb + SM_Q + u * 8192, 8192);
                        asm volatile("cp.async.bulk.wait_group 0;\n" ::: "memory");
                    }
                };
                int* f0 = &g_sync[(SY_H0 + SC_QT(0) / 5) * 32];
                bar_sync(BAR_H0, 64);
                if (elect()) {
                    send(0, 1);
                    if (SC_QT(0) < 60) red_release(f0);
                }
                bar_sync(BAR_H1, 160);
                if (elect()) {
                    if (!SC_TAIL) send(1, 4);
                    mbar_arrive(bar_q);
                }
                bar_sync(BAR_H2, 160);
                if (elect()) {
                    if (!SC_TAIL) { send(4, 8); mbar_arrive(bar_q + 8); }
                    red_release(&g_sync[SY_H1 * 32]);
                }
                __syncwarp();
            }
            if (warp == 3 && SC_OWNER && SC_PAIR && elect()) {
                flag_wait_bounded(&g_sync[SY_H1 * 32], 79 * ep);
                mbar_wait_sleep(bar_pdone, 0);
                mbar_wait_sleep(bar_pdone + 8, 0);
#pragma unroll 1
                for (int u = 0; u < 16; u++) {
                    bulk_s2g(g_q + SC_QT(0) * (2 * QB_BYTES) + u * 4096, sb + SM_Q + u * 4096, 4096);
                    asm volatile("cp.async.bulk.wait_group 0;\n" ::: "memory");
                }
                fence_async_global();
                st_release(&g_qflag[SC_QT(0)], ep);
            }
            __syncwarp();
            mbar_wait_bounded(bar_go, 0);
            if (SC_TAIL) {
                if (warp == 3 && elect()) {
                    int it = 4 + SC_NKV + SC_NW;
                    asm volatile("prefetch.tensormap [%0];\n" ::"l"(&P.tm_out) : "memory");
                    if (rank) {
#pragma unroll 1
                        for (int j = 0; j < 4; j++, it++) {
                            mbar_wait_sleep(bar_empty + 8 * (it & 3), ((it >> 2) & 1) ^ 1);
                            mbar_expect_tx(bar_full + 8 * (it & 3), QB_BYTES);
                            tma_g2s(sb + SM_KV + (it & 3) * KV_BYTES, &P.tm_w[2], 8 * j, bar_full + 8 * (it & 3));
                        }
#pragma unroll 1
                        for (int k = 0; k < 8; k++) {
                            mbar_wait_sleep(bar_qfree + 8 * (k & 1), ((k >> 1) ^ (k & 1) ^ 1) & 1);
                            mbar_expect_tx(bar_q + 8 * (k & 1), QB_BYTES);
#pragma unroll 1
                            for (int hf = 0; hf < 2; hf++)
                                asm volatile("cp.async.bulk.tensor.5d.shared::cluster.global.tile.mbarrier::complete_tx::bytes [%0], [%1, {0, 0, %2, 0, 0}], [%3];\n"
                                             ::"r"(sb + SM_Q + (k & 1) * QB_BYTES + hf * 16384), "l"(&P.tm_w[k & 1]),
                                             "r"(8 * (((k >> 1) + 3) & 3) + 4 * hf), "r"(bar_q + 8 * (k & 1)) : "memory");
                        }
                        flag_wait_bounded(&g_sync[SY_B * 32], ep);
                        fence_async_global();
                    }
#pragma unroll 1
                    for (int j = 0; j < 4; j++, it++) {
                        mbar_wait_sleep(bar_empty + 8 * (it & 3), ((it >> 2) & 1) ^ 1);
                        mbar_expect_tx(bar_full + 8 * (it & 3), QB_BYTES);
                        bulk_g2s(sb + SM_KV + (it & 3) * KV_BYTES, g_w + (4 + j) * QB_BYTES, QB_BYTES, bar_full + 8 * (it & 3));
                    }
#pragma unroll 1
                    for (int k = 0; k < SC_NZ; k++) {
                        if (k == 0 || k == ((GF0 + 1) * NAUX - 16) / 128) { flag_wait_bounded(&g_sync[(k ? SY_AUX1 : SY_AUX0) * 32], NAUX * ep); fence_async_global(); }
                        mbar_wait_sleep(bar_qfree + 8 * (k & 1), ((k >> 1) ^ (k & 1) ^ 1) & 1);
                        mbar_expect_tx(bar_q + 8 * (k & 1), QB_BYTES);
                        bulk_g2s(sb + SM_Q + (k & 1) * QB_BYTES, g_agg + SC_ZB(k) * QB_BYTES, QB_BYTES, bar_q + 8 * (k & 1));
                    }
                }
            } else {
            const int par = ep & 1;
            if (blockIdx.x == 0 && t == 32) g_ovf_n[par ^ 1] = 0;
            if (blockIdx.x == 0 && warp == 1) *(uint4*)(g_hz + (lane >> 3) * 1024 + (lane & 7) * 16) = make_uint4(KV_OFF2, KV_OFF2, KV_OFF2, KV_OFF2);
            const uint32_t wlo = (uint32_t)(uintptr_t)H.s, whi = (uint32_t)((uintptr_t)H.s >> 32);
            const uint32_t blo = wlo + (uint32_t)offsetof(Scratch, bucket);
            {
                const int* pd = P.dst + blockIdx.x * 96 + (t - 32);
                const int* ps = P.src + blockIdx.x * 96 + (t - 32);
#pragma unroll 1
                for (int e = P.E - (blockIdx.x * 96 + (t - 32)); e > 0; e -= CSRU * NAUX * 32, pd += CSRU * NAUX * 32, ps += CSRU * NAUX * 32) {
                    int d[CSRU], sr[CSRU], sl[CSRU];
#pragma unroll
                    for (int i = 0; i < CSRU; i++) {
                        d[i] = e > i * NAUX * 32 ? __ldg(pd + i * NAUX * 32) : NN;
                        sr[i] = e > i * NAUX * 32 ? __ldg(ps + i * NAUX * 32) : 0;
                    }
#pragma unroll
                    for (int i = 0; i < CSRU; i++) {
                        sl[i] = 0;
                        asm volatile("{\n.reg .pred p;\nsetp.lt.s32 p, %2, %3;\n@p atom.relaxed.gpu.global.add.s32 %0, [%1], 1;\n}\n"
                                     : "+r"(sl[i]) : "l"(mkaddr(wlo + (uint32_t)offsetof(Scratch, cnt) + d[i] * 4, whi)), "r"(d[i]), "n"(NN) : "memory");
                    }
                    uint32_t ov = 0;
#pragma unroll
                    for (int i = 0; i < CSRU; i++) {
                        asm volatile("{\n.reg .pred p;\nsetp.lt.s32 p, %3, %4;\n@p st.global.s32 [%1], %2;\n@!p or.b32 %0, %0, %5;\n}\n"
                                     : "+r"(ov) : "l"(mkaddr(blo + (d[i] * CAP + sl[i]) * 4, whi)), "r"(sr[i]), "r"(sl[i]), "n"(CAP), "r"(1 << i) : "memory");
                    }
#pragma unroll 1
                    for (; ov; ov &= ov - 1) {
                        const int i = (__ffs(ov) - 1) * (NAUX * 32);
                        int at;
                        asm volatile("atom.relaxed.gpu.global.add.s32 %0, [%1], 1;\n" : "=r"(at) : "l"(&g_ovf_n[par]) : "memory");
                        g_ovf[at] = make_int2(__ldg(pd + i), __ldg(ps + i));
                    }
                }
            }
            bar_sync(BAR_AUX, 96);
            if (warp == 1 && elect()) { red_release(&g_sync[SY_CSR * 32]); }
            __syncwarp();
            {
                const int r0 = blockIdx.x * 3 + warp - 1;
                const uint4* xp = (const uint4*)(H.x + r0 * 256) + lane;
                uint4* op = (uint4*)(P.out + r0 * 256) + lane;
#pragma unroll 1
                for (int r = r0; r < NN; r += CPYU * NAUX, xp += CPYU * NAUX * 32, op += CPYU * NAUX * 32) {
                    uint4 v[CPYU];
#pragma unroll
                    for (int i = 0; i < CPYU; i++) if (r + i * NAUX < NN) v[i] = ldg_pinned(xp + i * NAUX * 32);
#pragma unroll
                    for (int i = 0; i < CPYU; i++) if (r + i * NAUX < NN) op[i * NAUX * 32] = v[i];
                }
            }
            flag_wait_bounded(&g_sync[SY_CSR * 32], NAUX / 3 * ep);
            {
                const uint32_t lc = (lane >> 3) * 1024 + (lane & 7) * 16;
                const uint32_t alo = wlo ^ lc;
                const int node0 = blockIdx.x * 3 + warp - 17;
                auto node = [&](int i) { const int nd = node0 + i * NAUX; return (int)min((unsigned)nd, (unsigned)(nd + NN)); };
                const int num = (NN - 17 - node0) / NAUX + 1;
                uint32_t mine = 0;
                if (lane < num) {
                    mine = min(__ldcg(&g_cnt[node(lane)]), CAP + 1) | (uint32_t)__ldg((const unsigned short*)P.deg_inv + node(lane)) << 16;
                    g_cnt[node(lane)] = 0;
                }
                auto row = [&](int off) {
                    uint4 v;
                    asm volatile("ld.global.v4.u32 {%0, %1, %2, %3}, [%4];\n"
                                 : "=r"(v.x), "=r"(v.y), "=r"(v.z), "=r"(v.w) : "l"(mkaddr(alo ^ off, whi)));
                    return v;
                };
                auto ents = [&](int i) {
                    int e;
                    asm volatile("ld.global.cg.s32 %0, [%1];\n" : "=r"(e) : "l"(mkaddr(blo + (min(node(i), NN - 1) * CAP + lane) * 4, whi)));
                    return e;
                };
                auto store = [&](int i, const float (&a)[8]) {
                    const float di = bf_hi(__shfl_sync(~0u, mine, i)) * (1.f / KV_SCALE);
                    const int nd = node(i);
                    *(uint4*)(g_agg + (uint32_t)(((nd >> 3) * 4096 + (nd & 7) * 144) ^ lc)) =
                        make_uint4(pack_bf16(a[0] * di, a[1] * di), pack_bf16(a[2] * di, a[3] * di), pack_bf16(a[4] * di, a[5] * di), pack_bf16(a[6] * di, a[7] * di));
                };
#pragma unroll 1
                for (uint32_t big = __ballot_sync(~0u, (mine & 0xFFFF) > CAP); big; big &= big - 1) {
                    const int i = __ffs(big) - 1, no = __ldcg(&g_ovf_n[par]);
                    float a[8] = {};
#pragma unroll 1
                    for (int k = -32; k < no; k += 32) {
                        const int2 pr = k < 0 ? make_int2(node(i), ents(i)) : k + lane < no ? __ldcg(&g_ovf[k + lane]) : make_int2(-1, 0);
#pragma unroll 1
                        for (uint32_t mk = __ballot_sync(~0u, pr.x == node(i)); mk; mk &= mk - 1) {
                            const uint4 v = row(row_off(__shfl_sync(~0u, pr.y, __ffs(mk) - 1)));
                            a[0] += f16_lo(v.x) - KV_OFF; a[1] += f16_hi(v.x) - KV_OFF; a[2] += f16_lo(v.y) - KV_OFF; a[3] += f16_hi(v.y) - KV_OFF;
                            a[4] += f16_lo(v.z) - KV_OFF; a[5] += f16_hi(v.z) - KV_OFF; a[6] += f16_lo(v.w) - KV_OFF; a[7] += f16_hi(v.w) - KV_OFF;
                        }
                    }
                    store(i, a);
                }
                auto add4 = [&](const uint4& a, const uint4& b) { return make_uint4(hadd2_f16(a.x, b.x), hadd2_f16(a.y, b.y), hadd2_f16(a.z, b.z), hadd2_f16(a.w, b.w)); };
                int ni = -1, left = 0, pos = 0, ec = 0, en = ents(0);
                uint4 acc = make_uint4(0, 0, 0, 0);
                auto issue = [&](uint4 (&v)[4]) {
                    if (left <= 0) {
                        ni++;
                        left = __shfl_sync(~0u, mine, ni) & 0xFFFF;
                        if (left > CAP) left = 0;
                        ec = lane < left ? row_off(en) : 0;
                        en = ents(ni + 1);
                        pos = 0;
                    }
#pragma unroll
                    for (int j = 0; j < 4; j++) v[j] = row(__shfl_sync(~0u, ec, pos + j));
                    pos += 4; left -= 4;
                    return left <= 0 ? ni : -1;
                };
                auto step = [&](uint4 (&v)[4], int& tag) {
                    acc = add4(acc, add4(add4(add4(v[0], v[1]), make_uint4(KV_NEG4, KV_NEG4, KV_NEG4, KV_NEG4)), add4(v[2], v[3])));
                    const int i = tag;
                    tag = issue(v);
                    if (i >= 0) {
                        const float a[8] = {f16_lo(acc.x), f16_hi(acc.x), f16_lo(acc.y), f16_hi(acc.y), f16_lo(acc.z), f16_hi(acc.z), f16_lo(acc.w), f16_hi(acc.w)};
                        if ((__shfl_sync(~0u, mine, i) & 0xFFFF) <= CAP) store(i, a);
                        acc = make_uint4(0, 0, 0, 0);
                        if (i == GF0 || i == 8) {
                            __syncwarp();
                            if (elect()) red_release(&g_sync[(i == 8 ? SY_AUX1 : SY_AUX0) * 32]);
                            __syncwarp();
                        }
                    }
                    return i == num - 1;
                };
                uint4 va[4], vb[4];
#pragma unroll
                for (int j = 0; j < 4; j++) va[j] = vb[j] = make_uint4(KV_OFF2, KV_OFF2, KV_OFF2, KV_OFF2);
                int ta = -1, tb = -1;
#pragma unroll 1
                while (!step(va, ta) && !step(vb, tb)) {}
            }
            bar_sync(BAR_AUX, 96);
            if (warp == 1 && elect()) {
                red_release(&g_sync[SY_AUX * 32]);
                red_add(&g_sync[SY_DONE * 32]);
            }
            }
        }
        __syncwarp();
        asm volatile("barrier.cluster.arrive.relaxed.aligned;\n" ::: "memory");
        if (warp == 1) mbar_wait_bounded(bar_end, 0);
        else if (elect()) mbar_arrive(bar_end);
        __syncwarp();
        asm volatile("barrier.cluster.wait.acquire.aligned;\n" ::: "memory");
    } else {
        const int t = tid & 127, warp = __shfl_sync(~0u, t >> 5, 0);
        const uint32_t sq = sb + SM_Q + wg * QB_BYTES;
        const uint32_t qbar = bar_q + 8 * wg;
        const uint32_t dq0 = __shfl_sync(~0u, ((sq & 0x3FFFF) >> 4) | (64u << 16), 0);
        const uint32_t dk0 = __shfl_sync(~0u, (((sb + SM_KV) & 0x3FFFF) >> 4) | (64u << 16), 0);
        float o[128];
        int it = 4;
        const uint32_t dhi = P.dhi;
        uint32_t rel_addr;
        auto rel_target = [&](uint32_t r) {
            asm("mapa.shared::cluster.u32 %0, %1, %2;\n" : "=r"(rel_addr) : "r"(bar_empty), "r"(r));
            if (lane >= 2) rel_addr = 0;
            asm volatile("" : "+r"(rel_addr));
        };
        rel_target(SC_NMC ? rank ^ (lane & 1) : rank);
        auto release = [&](int st) {
            asm volatile("{\n.reg .pred p;\nsetp.ne.u32 p, %1, 0;\n@p mbarrier.arrive.shared::cluster.b64 _, [%0];\n}\n"
                         ::"r"(rel_addr + 8 * st), "r"(rel_addr) : "memory");
        };
        const bool active = !(SC_TAIL && wg == 1);
        const int nn = __shfl_sync(~0u, (SC_N0 + 3) | (SC_NKV + 3) << 8 | (active ? (SC_NKV != SC_N0 ? 2 : 1) : 0) << 16 | SC_NMC << 24, 0);
        auto pp_sync = [&]() { if (!SC_TAIL) bar_sync(BAR_PP0 + wg, 256); };
        auto pp_arrive = [&]() { if (!SC_TAIL) bar_arrive(BAR_PP1 - wg, 256); };
        auto warp_arrive = [&](uint32_t bar) {
            __syncwarp();
            asm volatile("{\n.reg .pred p;\nelect.sync _|p, -1;\n@p mbarrier.arrive.shared::cta.b64 _, [%0];\n}\n" ::"r"(bar + 8 * wg) : "memory");
        };
        auto peer_arrive = [&]() {
            asm volatile("{\n.reg .pred p;\n.reg .b32 a;\nelect.sync _|p, -1;\nmapa.shared::cluster.u32 a, %0, %1;\n"
                         "@p mbarrier.arrive.shared::cluster.b64 _, [a];\n}\n" ::"r"(bar_rfree), "r"(rank ^ 1) : "memory");
        };
        auto stage_q = [&]() {
            auto pk = [&](int i) { return QRND(pack_f16_sat(o[i], o[i + 1])); };
#pragma unroll
            for (int i = 0; i < 16; i++)
                stmatrix_x4(sq + warp * 8192 + tile_off(lane & 15, 2 * i + (lane >> 4)), pk(8 * i), pk(8 * i + 2), pk(8 * i + 4), pk(8 * i + 6));
        };
        float s[40];
        auto issue_qk = [&](int st) {
            const uint64_t kb = mkaddr(dk0 + st * (KV_BYTES >> 4), dhi);
            const uint64_t qd = mkaddr(dq0 + ((uint32_t)it >> 24), dhi);
            wgmma_ss_n80_init(s, qd + 198, kb + 198);
#pragma unroll
            for (int kk = 0; kk < 15; kk++) wgmma_ss_n80(s, qd + ((kk >> 2) * 64 + (kk & 3) * 2), kb + ((kk >> 2) * 64 + (kk & 3) * 2));
            wg_commit();
        };

        {
            const int rb = (2 * SC_QT(0) + wg) * 64 + warp * 16;
            const uint32_t xbar = bar_x + 32 * wg + 8 * warp;
            if (elect()) {
                mbar_init(xbar, 1);
                asm volatile("fence.mbarrier_init.release.cluster;\nfence.proxy.async.shared::cta;\n" ::: "memory");
                mbar_expect_tx(xbar, rb < NN ? 8192 : 0);
            }
            asm volatile("barrier.cluster.arrive.relaxed.aligned;\n" ::: "memory");
            if (wg == 1) pp_arrive();
            bar_sync(BAR_X, 384);
            if (wg == 1) bar_sync(BAR_GO, 160);
            if (rb < NN && elect()) bulk_g2s(sq + warp * 8192, H.x + (size_t)rb * 256, 8192, xbar);
            if (rb >= NN) {
#pragma unroll 1
                for (int i = 0; i < 16; i++) sts128(sq + warp * 8192 + i * 512 + lane * 16, 0, 0, 0, 0);
            }
            __syncwarp();
            mbar_wait(xbar, 0);
            uint4 xa[8], xb[8];
#pragma unroll
            for (int s = 0; s < 8; s++) {
                xa[s] = lds128(sq + (warp * 16 + g) * 512 + (4 * s + q) * 16);
                xb[s] = lds128(sq + (warp * 16 + g + 8) * 512 + (4 * s + q) * 16);
            }
            float sm[2][4], sq2[2][4][4];
#pragma unroll
            for (int i = 0; i < 4; i++) {
                sm[0][i] = sm[1][i] = 0.f;
#pragma unroll
                for (int k = 0; k < 4; k++) sq2[0][k][i] = sq2[1][k][i] = 0.f;
            }
#pragma unroll
            for (int s = 0; s < 8; s++) {
#pragma unroll
                for (int hh = 0; hh < 2; hh++) {
                    const uint4 v = hh ? xb[s] : xa[s];
                    mma16816(sm[hh], v.x, v.y, v.z, v.w, 0x3F803F80u, 0x3F803F80u);
                    mma1688(sq2[hh][0], v.x, v.y, v.x); mma1688(sq2[hh][1], v.x, v.y, v.y);
                    mma1688(sq2[hh][2], v.z, v.w, v.z); mma1688(sq2[hh][3], v.z, v.w, v.w);
                }
            }
            float inv[2], off[2];
#pragma unroll
            for (int hh = 0; hh < 2; hh++) {
                const float mean = (sm[hh][0] + sm[hh][2]) * (1.f / 256.f);
                const float d0 = (sq2[hh][0][0] + sq2[hh][2][0]) + (sq2[hh][1][2] + sq2[hh][3][2]);
                const float d1 = (sq2[hh][0][1] + sq2[hh][2][1]) + (sq2[hh][1][3] + sq2[hh][3][3]);
                const float ss = __shfl_sync(~0u, (g & 1) ? d1 : d0, g * 4 + (g >> 1));
                const float var = fmaxf(ss * (1.f / 256.f) - mean * mean, 0.f);
                float sd;
                asm("sqrt.approx.ftz.f32 %0, %1;\n" : "=f"(sd) : "f"(bf_round(bf_round(var) + 1e-5f)));
                asm("rcp.approx.ftz.f32 %0, %1;\n" : "=f"(inv[hh]) : "f"(bf_round(sd)));
                off[hh] = -mean * inv[hh];
            }
            uint32_t a[64];
#pragma unroll
            for (int s = 0; s < 8; s++) {
                a[8 * s] = xa[s].x; a[8 * s + 1] = xb[s].x; a[8 * s + 2] = xa[s].y; a[8 * s + 3] = xb[s].y;
                a[8 * s + 4] = xa[s].z; a[8 * s + 5] = xb[s].z; a[8 * s + 6] = xa[s].w; a[8 * s + 7] = xb[s].w;
            }
            fence_regs(a);
            if (wg == 1 && __any_sync(~0u, inv[0] + inv[1] != -1.f)) bar_arrive(BAR_ST, 256);
            asm volatile("setmaxnreg.inc.sync.aligned.u32 %0;\n" ::"n"(REG_C));
            fence_regs(a);
#pragma unroll
            for (int i = 0; i < 64; i++)
                a[i] = pack_f16(fmaf(bf_lo(a[i]), inv[i & 1], off[i & 1]), fmaf(bf_hi(a[i]), inv[i & 1], off[i & 1]));
            if (SC_OWNER) {
#pragma unroll
                for (int i = 0; i < 16; i++) {
                    const uint32_t mk = (i == 15 && q == 3) ? 0xFFFFu : ~0u;
                    stmatrix_x4(sq + warp * 8192 + tile_off(lane & 15, 2 * i + (lane >> 4)), kvf(a[4 * i]), kvf(a[4 * i + 1]),
                                kvf(a[4 * i + 2] & mk), kvf(a[4 * i + 3] & mk));
                }
                fence_async_smem();
                if (tid < 32) bar_arrive(BAR_H0, 64);
                bar_arrive(wg ? BAR_H2 : BAR_H1, 160);
            }
            asm volatile("barrier.cluster.wait.acquire.aligned;\n" ::: "memory");
            if (wg == 0) bar_sync(BAR_ST, 256);
            if (active) {
                fence_regs(a);
#pragma unroll
                for (int c = 0; c < 4; c++) {
                    if (c == 1) {
                        if (wg == 1) {
                            wg_wait<0>();
                            release(0);
                        }
                        pp_sync();
                    }
                    mbar_wait(bar_full + 8 * c, 0);
                    const uint64_t wb = mkaddr(dk0 + c * (KV_BYTES >> 4), dhi);
                    wg_fence();
#pragma unroll
                    for (int kk = 0; kk < 4; kk++) {
                        if (c | kk) wgmma_rs_n256_tb(o, a[16 * c + 4 * kk], a[16 * c + 4 * kk + 1], a[16 * c + 4 * kk + 2], a[16 * c + 4 * kk + 3], wb + kk * 512);
                        else wgmma_rs_n256_tb_init(o, a[0], a[1], a[2], a[3], wb);
                    }
                    wg_commit();
                    if (c > 0) { wg_wait<1>(); if (c > 1 || wg == 0) release(c - 1); }
                }
                if (wg == 0) pp_arrive();
                wg_wait<0>();
                fence_regs(o);
                release(3);
                if (SC_OWNER) mbar_wait(qbar, 0);
                stage_q();
                fence_async_smem();
                bar_sync(BAR_WG0 + wg, 128);
                mbar_wait(bar_full, 1);
                wg_fence();
                issue_qk(0);
                if (wg == 1) pp_arrive();
            } else {
                peer_arrive();
            }
        }

        uint32_t p[20];
        float m0, m1, e0, e1, l0, l1;
        uint32_t plim;
        uint32_t qphase = (SC_OWNER && active) ? 1 : 0;
        auto issue_pv = [&](int st, int acc) {
            const uint64_t vb = mkaddr(dk0 + st * (KV_BYTES >> 4), dhi);
            wgmma_rs_n256_tb_pred(o, p[0], p[1], p[2], p[3], vb, acc);
#pragma unroll
            for (int kk = 1; kk < 5; kk++)
                wgmma_rs_n256_tb(o, p[4 * kk], p[4 * kk + 1], p[4 * kk + 2], p[4 * kk + 3], vb + kk * 512);
            wg_commit();
        };
        const uint32_t mq_addr = sq + tile_off(warp * 16 + g, 31) + 14;
        auto exceeds = [&](const uint32_t (&p)[20]) {
            uint32_t a = __vimax3_s16x2(P_LIMIT, p[0], p[1]), b = __vimax3_s16x2(p[2], p[3], p[4]);
#pragma unroll
            for (int i = 5; i < 17; i += 4) { a = __vimax3_s16x2(a, p[i], p[i + 1]); b = __vimax3_s16x2(b, p[i + 2], p[i + 3]); }
            a = __vimax3_s16x2(a, p[17], p[18]);
            return __any_sync(~0u, __vimax3_s16x2(a, b, p[19]) != plim);
        };
        auto remax = [&](float& a, float& b, bool store) {
            float a1 = fmaxf(s[0], s[1]), b1 = fmaxf(s[2], s[3]), a2 = fmaxf(s[4], s[5]), b2 = fmaxf(s[6], s[7]);
#pragma unroll
            for (int i = 2; i < 10; i++) {
                a1 = fmaxf(a1, s[4 * i]); a2 = fmaxf(a2, s[4 * i + 1]);
                b1 = fmaxf(b1, s[4 * i + 2]); b2 = fmaxf(b2, s[4 * i + 3]);
            }
            a1 = fmaxf(a1, a2); b1 = fmaxf(b1, b2);
            a1 = fmaxf(a1, __shfl_xor_sync(~0u, a1, 1)); b1 = fmaxf(b1, __shfl_xor_sync(~0u, b1, 1));
            a1 = fmaxf(a1, __shfl_xor_sync(~0u, a1, 2)); b1 = fmaxf(b1, __shfl_xor_sync(~0u, b1, 2));
            a = fmaxf(a, floorf(a1 - e0)); b = fmaxf(b, floorf(b1 - e1));
            unsigned short u0, u1;
            asm("cvt.rp.f16.f32 %0, %2;\ncvt.rp.f16.f32 %1, %3;\n" : "=h"(u0), "=h"(u1)
                : "f"(fminf(ceilf((m0 + a) * (-1.f / 3.f) - 1e-3f) * 0.5f, 65504.f)), "f"(fminf(ceilf((m1 + b) * (-1.f / 3.f) - 1e-3f) * 0.5f, 65504.f)));
            const float g0 = (m0 + a) + KV_OFF * f16_lo(u0), g1 = (m1 + b) + KV_OFF * f16_lo(u1);
            const bool x0 = g0 >= 0.f && g0 < 8.f, x1 = g1 >= 0.f && g1 < 8.f;
            if (x0) a -= g0;
            if (x1) b -= g1;
            const float da = a + e0, db = b + e1;
            m0 += a; m1 += b;
            e0 = x0 ? 0.f : g0; e1 = x1 ? 0.f : g1;
            plim = (x0 && x1) ? P_LIMIT : 0u;
            asm volatile("{\n.reg .pred p;\nsetp.ne.s32 p, %3, 0;\n@p st.shared.u16 [%0], %1;\n@p st.shared.u16 [%0 + 4096], %2;\n}\n"
                         ::"r"(mq_addr), "h"(u0), "h"(u1), "r"((int)(store && q == 0)) : "memory");
#pragma unroll
            for (int i = 0; i < 10; i++) {
                p[2 * i] = pack_f16(ex2(s[4 * i] - da), ex2(s[4 * i + 1] - da));
                p[2 * i + 1] = pack_f16(ex2(s[4 * i + 2] - db), ex2(s[4 * i + 3] - db));
            }
            fence_regs(p);
            fence_async_smem();
            __syncwarp();
        };

        auto row_sums = [&](float& z0, float& z1) {
            z0 = shfl_f32(o[125], lane | 3); z1 = shfl_f32(o[127], lane | 3);
            l0 = z0 * (KV_SCALE / KV_OFF); l1 = z1 * (KV_SCALE / KV_OFF);
        };
        const int nseg = (nn >> 16) & 255;
#pragma unroll 1
        for (int seg = 0; seg < nseg; seg++) {
            wg_wait<0>();
            fence_regs(s);
            m0 = m1 = e0 = e1 = 0.f;
            if (seg) {
                unsigned short u0, u1;
                asm volatile("ld.shared.u16 %0, [%2];\nld.shared.u16 %1, [%2 + 4096];\n" : "=h"(u0), "=h"(u1) : "r"(mq_addr) : "memory");
                m0 = -KV_OFF * f16_lo(u0); m1 = -KV_OFF * f16_lo(u1);
                plim = (u0 != 0x7BFF && u1 != 0x7BFF) ? P_LIMIT : 0u;
                __syncwarp();
            }
            const int it0 = it, itl = __shfl_sync(~0u, (nn >> (8 * seg)) & 255, 0);
            const int itx = (wg == 1 && seg + 1 == nseg) ? itl : -1;
            bool redo = true, have = !seg;
#pragma unroll 1
            for (;;) {
                if (!have) {
#pragma unroll
                    for (int i = 0; i < 20; i++) p[i] = pack_f16(ex2(s[2 * i]), ex2(s[2 * i + 1]));
                    redo = exceeds(p);
                }
                if (redo) {
                    float d0 = it != it0 ? 0.f : -INFINITY, d1 = d0;
                    remax(d0, d1, it != itl);
                    if (it != it0) {
                        const float a0 = ex2(-d0), a1 = ex2(-d1);
#pragma unroll
                        for (int i = 0; i < 32; i++) { o[4 * i] *= a0; o[4 * i + 1] *= a0; o[4 * i + 2] *= a1; o[4 * i + 3] *= a1; }
                    } else if (SC_OWNER) {
                        warp_arrive(bar_pdone);
                    }
                }
                if (it == itl) break;
                const int stp = it & 3;
                it++;
                mbar_wait(bar_full + 8 * (it & 3), (it >> 2) & 1);
                pp_sync();
                fence_regs(o); fence_regs(p);
                wg_fence();
                issue_qk(it & 3);
                asm volatile("{\n.reg .pred p;\nsetp.eq.s32 p, %0, %1;\n@p bar.sync %2, 256;\n}\n" ::"r"(it), "r"(itx), "n"((int)BAR_ST) : "memory");
                issue_pv(stp, it - 1 - it0);
                pp_arrive();
                if (it == itl) {
                    wg_wait<1>();
                    if (SC_PAIR && it == itx) peer_arrive(); else warp_arrive(bar_qfree);
                }
                have = SC_TAIL || it == itx;
                if (have) {
                    uint32_t p2[20];
                    wg_wait<1>();
                    fence_regs(s);
#pragma unroll
                    for (int i = 0; i < 20; i++) p2[i] = pack_f16(ex2(s[2 * i]), ex2(s[2 * i + 1]));
                    redo = exceeds(p2);
                    if (redo) asm volatile("wgmma.wait_group.sync.aligned 0;\nnanosleep.u32 0;\n" ::: "memory");
                    else wg_wait<0>();
                    fence_regs(o); fence_regs(p);
#pragma unroll
                    for (int i = 0; i < 20; i++) p[i] = p2[i];
                } else {
                    wg_wait<0>();
                    fence_regs(s); fence_regs(o); fence_regs(p);
                }
                release(stp);
                if (it == (nn >> 24)) rel_target(rank);
            }
            if (seg + 1 < nseg) pp_sync();
            fence_regs(o); fence_regs(p);
            wg_fence();
            issue_pv(it & 3, 1);
            asm volatile("{\n.reg .pred p;\nsetp.ne.s32 p, %0, 0;\n@p bar.arrive %1, 256;\n}\n" ::"r"((int)(wg == 0 && seg + 1 == nseg && !SC_TAIL)), "n"((int)BAR_ST) : "memory");
            it++;
            const int loc = seg + 1 < nseg;
            if (loc) {
                mbar_wait(qbar, qphase); qphase ^= 1;
                mbar_wait(bar_full + 8 * (it & 3), (it >> 2) & 1);
                wg_fence();
                issue_qk(it & 3);
                pp_arrive();
                wg_wait<1>();
            } else {
                wg_wait<0>();
            }
            fence_regs(o);
            release((it - 1) & 3);
            if (loc || (wg == 0 && (SC_PAIR || !SC_OWNER))) {
                const int is = it - 2 + wg;
                uint32_t dst = sb + SM_KV + (is & 3) * KV_BYTES, dml = dst + (wg ? 0 : QB_BYTES), rbar = 0;
                dst += wg * 512;
                if (!loc)
                    asm("mapa.shared::cluster.u32 %0, %3, %6;\nmapa.shared::cluster.u32 %1, %4, %6;\nmapa.shared::cluster.u32 %2, %5, %6;\n"
                        : "=r"(dst), "=r"(dml), "=r"(rbar) : "r"(sb + SM_Q + QB_BYTES), "r"(sb + SM_ML + 512), "r"(bar_pin), "r"(rank ^ 1));
                int ln = lane;
                asm volatile("" : "+r"(ln));
                dst += warp * 8192 + ln * 16; dml += warp * 128 + (ln >> 2) * 8;
                float z0, z1;
                row_sums(z0, z1);
                mbar_wait(loc ? bar_empty + 8 * (is & 3) : bar_rfree, loc & (is >> 2));
                asm volatile("{\n.reg .pred p, r;\nsetp.eq.s32 p, %6, 4;\nsetp.eq.s32 r, %6, 0;\n@p st.shared.v2.f32 [%0], {%1, %2};\n@p st.shared.v2.f32 [%0 + 64], {%3, %4};\n"
                             "@r st.async.weak.shared::cluster.mbarrier::complete_tx::bytes.v2.f32 [%0], {%1, %2}, [%5];\n"
                             "@r st.async.weak.shared::cluster.mbarrier::complete_tx::bytes.v2.f32 [%0 + 64], {%3, %4}, [%5];\n}\n"
                             ::"r"(dml), "f"(m0), "f"(l0), "f"(m1), "f"(l1), "r"(rbar), "r"((ln & 3) + 4 * loc) : "memory");
#pragma unroll
                for (int i4 = 0; i4 < 16; i4 += SGRP) {
                    uint32_t v[4 * SGRP];
#pragma unroll
                    for (int j = 0; j < 2 * SGRP; j++) {
                        v[2 * j] = pack_bf16(o[8 * i4 + 4 * j] - z0, o[8 * i4 + 4 * j + 1] - z0);
                        v[2 * j + 1] = pack_bf16(o[8 * i4 + 4 * j + 2] - z1, o[8 * i4 + 4 * j + 3] - z1);
                    }
                    if (loc) {
#pragma unroll
                        for (int j = 0; j < SGRP; j++) sts128(dst + frag_off(i4 + j), v[4 * j], v[4 * j + 1], v[4 * j + 2], v[4 * j + 3]);
                    } else {
#pragma unroll
                        for (int j = 0; j < SGRP; j++)
                            asm volatile("st.async.weak.shared::cluster.mbarrier::complete_tx::bytes.v4.b32 [%0], {%1, %2, %3, %4}, [%5];\n"
                                         ::"r"(dst + frag_off(i4 + j)), "r"(v[4 * j]), "r"(v[4 * j + 1]), "r"(v[4 * j + 2]), "r"(v[4 * j + 3]), "r"(rbar + (i4 & 8)) : "memory");
                    }
                }
                if (loc) { fence_async_smem(); warp_arrive(bar_pdone); }
            }
        }
        wg_wait<0>();
        auto wait_full = [&](int i, uint32_t hi) { mbar_wait(bar_full + 8 * (i & 3), (i >> 2) & 1); return mkaddr(dk0 + (i & 3) * (KV_BYTES >> 4), hi); };
        auto release2 = [&](int i, int on) {
            asm volatile("{\n.reg .pred p;\nsetp.ne.u32 p, %1, 0;\n@p mbarrier.arrive.shared::cluster.b64 _, [%0], 2;\n}\n"
                         ::"r"(rel_addr + 8 * (i & 3)), "r"(on ? rel_addr : 0) : "memory");
        };
        const bool fin = active && blockIdx.x != NCTA - 1;
        const int mw = (SC_PAIR || SC_TAIL) ? 1 : wg;
        if (fin) do {
        float y0[64], y1[64];
        if (SC_PAIR && wg == 0) {
            mbar_wait(qbar, qphase);
#pragma unroll 1
            for (int c = 0; c < 4; c++, it++) {
                const uint64_t wb = wait_full(it, dhi), ab = mkaddr(dq0 + c * 64, dhi);
                wg_fence();
                wgmma_ss_n128_tb_pred(y0, ab, wb, c);
#pragma unroll
                for (int kk = 1; kk < 4; kk++) wgmma_ss_n128_tb(y0, ab + kk * 2, wb + kk * 512);
                wgmma_ss_n128_tb_pred(y1, ab, wb + 128, c);
#pragma unroll
                for (int kk = 1; kk < 4; kk++) wgmma_ss_n128_tb(y1, ab + kk * 2, wb + (128 + kk * 512));
                wg_commit();
                wg_wait<1>();
                release2(it - 1, c);
            }
        } else {
            const bool two = SC_PAIR && SC_PIN, glob = !(SC_PAIR || SC_TAIL);
            const uint32_t ml = sb + SM_ML + (warp * 16 + g) * 8, reg = sb + SM_Q + mw * QB_BYTES + warp * 8192;
            if (SC_PIN) mbar_wait(bar_pin + 16, 0);
            mbar_wait(glob ? qbar : bar_pin, glob ? qphase : 0);
            const float2 pa = lds64f(ml + mw * 512), pb = lds64f(ml + mw * 512 + 64);
            float2 qa = lds64f(ml), qb = lds64f(ml + 64);
            if (!two) qa = qb = make_float2(-INFINITY, 0.f);
            float c0, c1;
            row_sums(c0, c1);
            const float n0 = fmaxf(fmaxf(m0, pa.x), qa.x), n1 = fmaxf(fmaxf(m1, pb.x), qb.x);
            const float a0 = ex2(m0 - n0), a1 = ex2(m1 - n1), b0 = ex2(pa.x - n0), b1 = ex2(pb.x - n1), d0 = ex2(qa.x - n0), d1 = ex2(qb.x - n1);
            const float i0 = rcp(l0 * a0 + pa.y * b0 + qa.y * d0), i1 = rcp(l1 * a1 + pb.y * b1 + qb.y * d1);
            const float r0 = a0 * i0, r1 = a1 * i1;
            c0 *= -r0; c1 *= -r1;
            const uint32_t u0 = pack_bf16(b0 * i0, b0 * i0), u1 = pack_bf16(b1 * i1, b1 * i1);
            const uint32_t w0 = pack_bf16(d0 * i0, d0 * i0), w1 = pack_bf16(d1 * i1, d1 * i1);
#pragma unroll
            for (int hf = 0; hf < 2; hf++) {
                uint4 v[8];
                if (hf && !glob) mbar_wait(bar_pin + 8, 0);
#pragma unroll
                for (int i = 0; i < 8; i++) v[i] = lds128(reg + lane * 16 + frag_off(8 * hf + i));
#pragma unroll
                for (int i = 0; i < 8; i++) {
                    const float* x = o + 64 * hf + 8 * i;
                    v[i] = make_uint4(hfma2(v[i].x, u0, pack_bf16(fmaf(x[0], r0, c0), fmaf(x[1], r0, c0))), hfma2(v[i].y, u1, pack_bf16(fmaf(x[2], r1, c1), fmaf(x[3], r1, c1))),
                                      hfma2(v[i].z, u0, pack_bf16(fmaf(x[4], r0, c0), fmaf(x[5], r0, c0))), hfma2(v[i].w, u1, pack_bf16(fmaf(x[6], r1, c1), fmaf(x[7], r1, c1))));
                }
                if (two) {
                    if (!hf) mbar_wait(bar_pin + 24, 0);
#pragma unroll
                    for (int i = 0; i < 8; i++) {
                        const uint4 e = lds128(sb + SM_KV + QB_BYTES + ((it + warp) & 3) * KV_BYTES + lane * 16 + frag_off(8 * hf + i));
                        v[i] = make_uint4(hfma2(e.x, w0, v[i].x), hfma2(e.y, w1, v[i].y), hfma2(e.z, w0, v[i].z), hfma2(e.w, w1, v[i].w));
                    }
                }
                __syncwarp();
#pragma unroll
                for (int i = 0; i < 8; i++) stmatrix_x4(reg + tile_off(lane & 15, 16 * hf + 2 * i + (lane >> 4)), v[i].x, v[i].y, v[i].z, v[i].w);
                fence_async_smem();
                if (SC_PAIR) bar_arrive(hf ? BAR_H0 : BAR_BF, 256);
            }
            if (SC_PAIR) break;
            pp_sync();
        }
        {
            const int pair = SC_PAIR;
            auto gemm = [&](float (&y)[64], int c, int kh) {
                const uint64_t ab = mkaddr(dq0 + (mw - wg) * (QB_BYTES >> 4) + ((uint32_t)it >> (23 + c)), dhi);
                const uint64_t wb = wait_full(it + 2 * c + kh, dhi - 128);
                wg_fence();
#pragma unroll
                for (int kk = 0; kk < 8; kk++) {
                    if (kh | kk) wgmma_ss_n128_tb(y, ab + (kh * 128 + (kk >> 2) * 64 + (kk & 3) * 2), wb + kk * 256);
                    else wgmma_ss_n128_tb_pred(y, ab, wb, pair);
                }
                wg_commit();
            };
            const int rg = (SC_PAIR ? SC_ZB(0) : 2 * SC_QT(0) + wg) * 8 + warp * 2;
            auto output = [&](const float (&y)[64], int c, int cb) {
                const uint32_t base = (c ? sq + warp * 8192 : sb + SM_KV + QB_BYTES + warp * KV_BYTES + wg * 4096) + cb * 2048;
#pragma unroll
                for (int i = 4 * cb; i < 4 * cb + 4; i++)
                    stmatrix_x4(base + (lane & 15) * 128 + (((2 * i + (lane >> 4)) ^ lane) & 7) * 16, pack_bf16(y[8 * i], y[8 * i + 1]),
                                pack_bf16(y[8 * i + 2], y[8 * i + 3]), pack_bf16(y[8 * i + 4], y[8 * i + 5]), pack_bf16(y[8 * i + 6], y[8 * i + 7]));
                fence_async_smem();
                __syncwarp();
                asm volatile("{\n.reg .pred p;\nelect.sync _|p, -1;\n"
                             "@p cp.reduce.async.bulk.tensor.4d.global.shared::cta.add.tile.bulk_group [%0, {0, 0, %1, %2}], [%3];\n}\n"
                             ::"l"(&P.tm_outc), "r"(2 * c + cb), "r"(rg), "r"(base) : "memory");
            };
            auto pair_sync = [&](int id) { asm volatile("{\n.reg .pred p;\nsetp.ne.s32 p, %0, 0;\n@p bar.sync %1, 256;\n}\n" ::"r"(pair), "r"(id) : "memory"); };
            pair_sync(BAR_BF);
            gemm(y0, 0, 0);
            wg_wait<1>();
            release2(it - 1, pair);
            pair_sync(BAR_H0);
            gemm(y0, 0, 1);
            gemm(y1, 1, 0);
            mbar_wait(bar_empty + 8 * ((it - 1) & 3), ((it - 1) >> 2) & 1);
            wg_wait<1>();
            fence_regs(y0);
            output(y0, 0, 0);
            gemm(y1, 1, 1);
            if (!pair) pp_arrive();
            output(y0, 0, 1);
            wg_wait<0>();
            fence_regs(y1);
            output(y1, 1, 0);
            output(y1, 1, 1);
            asm volatile("cp.async.bulk.commit_group;\ncp.async.bulk.wait_group.read 0;\n" ::: "memory");
        }
        } while (0);
        if (SC_TAIL) {
        float o[128];
        auto emit = [&](uint32_t base, int lane, int row0, uint8_t* wdst, int turn) {
#pragma unroll
            for (int hh = 0; hh < 2; hh++) {
                if (turn > 0) mbar_wait(bar_zst + 8 * hh, (turn - 1) & 1);
#pragma unroll
                for (int i = 0; i < 8; i++)
                    stmatrix_x4(base + tile_off(8 * hh + (lane & 7), 4 * i + (lane >> 3)),
                                pack_bf16(o[16 * i + 2 * hh], o[16 * i + 2 * hh + 1]), pack_bf16(o[16 * i + 4 + 2 * hh], o[16 * i + 5 + 2 * hh]),
                                pack_bf16(o[16 * i + 8 + 2 * hh], o[16 * i + 9 + 2 * hh]), pack_bf16(o[16 * i + 12 + 2 * hh], o[16 * i + 13 + 2 * hh]));
                fence_async_smem();
                __syncwarp();
                if (wdst) {
                    if (lane < 4)
                        asm volatile("cp.async.bulk.global.shared::cta.bulk_group [%0], [%1], 1024;\n"
                                     ::"l"(wdst + ((turn & 1) ? hh * 4096 + lane * 1024 : hh * 2048 + (lane >> 1) * (2 * QB_BYTES) + (lane & 1) * 1024)), "r"(base + hh * 4096 + lane * 1024) : "memory");
                    asm volatile("cp.async.bulk.commit_group;\n" ::: "memory");
                } else {
                    asm volatile("{\n.reg .pred p;\nsetp.eq.s32 p, %3, 0;\n"
                                 "@p cp.reduce.async.bulk.tensor.4d.global.shared::cta.add.tile.bulk_group [%0, {0, 0, 0, %1}], [%2];\n"
                                 "cp.async.bulk.commit_group;\n}\n"
                                 ::"l"(&P.tm_out), "r"((row0 >> 3) + hh), "r"(base + hh * 4096), "r"(lane) : "memory");
                }
            }
            asm volatile("cp.async.bulk.wait_group.read 1;\n" ::: "memory");
            warp_arrive(bar_zst - 8 * wg);
        };
        auto emit_done = [&](bool pending) {
            asm volatile("cp.async.bulk.wait_group.read 0;\n" ::: "memory");
            __syncwarp();
            asm volatile("{\n.reg .pred p;\nsetp.eq.s32 p, %1, 0;\n@p mbarrier.arrive.shared::cta.b64 _, [%0];\n}\n"
                         ::"r"(bar_zst + 8), "r"(pending ? lane : 1) : "memory");
        };
        if (fin) { release(0); release(1); release(2); release(3); }
        bar_sync(BAR_BF, 256);
        warp_arrive(bar_qfree);
        const int nf = blockIdx.x == NCTA - 1 ? 8 : 0;
        const int nz = __shfl_sync(~0u, nf + SC_NZ, 0);
        const int itz = __shfl_sync(~0u, 4 + SC_NKV + SC_NW, 0);
        bool pend = false;
#pragma unroll 1
        for (int k = wg; k < nz; k += 2) {
            const int iz = itz + (k < nf ? 0 : nf >> 1);
            mbar_wait(qbar, qphase); qphase ^= 1;
#pragma unroll 1
            for (int c = 0; c < 4; c++) {
                const uint64_t wb = wait_full(iz + c, dhi), ab = mkaddr(dq0 + c * 64, dhi);
                wg_fence();
                wgmma_ss_n256_tb_pred(o, ab, wb, c);
#pragma unroll
                for (int kk = 1; kk < 4; kk++) wgmma_ss_n256_tb(o, ab + kk * 2, wb + kk * 512);
                wg_commit();
                emit_done(pend);
                pend = false;
            }
            wg_wait<0>();
            fence_regs(o);
            warp_arrive(bar_qfree);
            const int fb = ((k >> 1) + 3) & 3;
            if (k < nf) {
                float2* r255 = (float2*)H.s->r255 + wg * 128 + q;
                if (k < 2) {
                    if (t >= 124) {
#pragma unroll
                        for (int i = 0; i < 32; i++) r255[4 * i] = make_float2(o[4 * i + 2], o[4 * i + 3]);
                    }
                    bar_sync(BAR_WG0 + wg, 128);
                }
#pragma unroll
                for (int i = 0; i < 32; i++) {
                    const float2 v = __ldcg(r255 + 4 * i);
                    o[4 * i] -= v.x; o[4 * i + 1] -= v.y; o[4 * i + 2] -= v.x; o[4 * i + 3] -= v.y;
                }
            }
            int ln = lane;
            asm volatile("" : "+r"(ln));
            emit(sb + SM_KV + QB_BYTES + warp * KV_BYTES, ln, SC_ZB(k - nf) * 64 + warp * 16,
                 k >= nf ? nullptr : (k & 1) ? g_w + (4 + fb) * QB_BYTES + warp * 8192 : g_w + 8 * QB_BYTES + fb * 16384 + warp * 4096, k);
            pend = k + 2 < nz && (k | 1) != nf - 1;
            if (!pend) emit_done(true);
            if ((k | 1) == nf - 1) {
                asm volatile("cp.async.bulk.wait_group 0;\nfence.proxy.async.global;\nfence.acq_rel.gpu;\n" ::: "memory");
                bar_sync(BAR_BF, 256);
                if (tid == 0) red_release(&g_sync[SY_B * 32]);
                if (wg == 0) { release(0); release(1); release(2); release(3); }
            }
        }
        }
        if (wg == 0) pp_sync();
        warp_arrive(bar_end - 8 * wg);
        asm volatile("barrier.cluster.arrive.relaxed.aligned;\n" ::: "memory");
    }
}

}

extern "C" void kernel_launch(void* const* d_in, const int* in_sizes, int n_in, void* d_out, int out_size) {
    Hot H;
    Params P;
    H.x = (const __nv_bfloat16*)d_in[0];
    P.src = (const int*)d_in[1];
    P.dst = (const int*)d_in[2];
    P.deg_inv = (const __nv_bfloat16*)d_in[3];
    H.wq = (const __nv_bfloat16*)d_in[5];
    H.wk = (const __nv_bfloat16*)d_in[6];
    P.out = (__nv_bfloat16*)d_out;
    typedef CUresult (*EncodeFn)(CUtensorMap*, CUtensorMapDataType, cuuint32_t, void*, const cuuint64_t*, const cuuint64_t*, const cuuint32_t*,
                                 const cuuint32_t*, CUtensorMapInterleave, CUtensorMapSwizzle, CUtensorMapL2promotion, CUtensorMapFloatOOBfill);
    void* fn = nullptr;
    cudaDriverEntryPointQueryResult qr;
    cudaGetDriverEntryPoint("cuTensorMapEncodeTiled", &fn, cudaEnableDefault, &qr);
    auto encode = [&](CUtensorMap* tm, const void* ptr, int rows, int box_rows, int box_cb = 4) {
        const cuuint64_t dims[4] = {64, 8, 4, (cuuint64_t)rows / 8};
        const cuuint64_t strides[3] = {512, 128, 4096};
        const cuuint32_t box[4] = {64, 8, (cuuint32_t)box_cb, (cuuint32_t)box_rows / 8}, es[4] = {1, 1, 1, 1};
        ((EncodeFn)fn)(tm, CU_TENSOR_MAP_DATA_TYPE_BFLOAT16, 4, (void*)ptr, dims, strides, box, es, CU_TENSOR_MAP_INTERLEAVE_NONE,
                       CU_TENSOR_MAP_SWIZZLE_128B, CU_TENSOR_MAP_L2_PROMOTION_NONE, CU_TENSOR_MAP_FLOAT_OOB_FILL_NONE);
    };
    encode(&P.tm_out, d_out, NN, 8);
    encode(&P.tm_outc, d_out, NN, 16, 1);
    for (int i = 0; i < 2; i++) {
        const cuuint64_t dims[5] = {64, 2, 32, 4, 4};
        const cuuint64_t strides[4] = {512, 4096, 128, 1024};
        const cuuint32_t box[5] = {64, 2, 4, 4, 4}, es[5] = {1, 1, 1, 1, 1};
        ((EncodeFn)fn)(&P.tm_w[i], CU_TENSOR_MAP_DATA_TYPE_BFLOAT16, 5, d_in[i ? 4 : 7], dims, strides, box, es, CU_TENSOR_MAP_INTERLEAVE_NONE,
                       CU_TENSOR_MAP_SWIZZLE_128B, CU_TENSOR_MAP_L2_PROMOTION_NONE, CU_TENSOR_MAP_FLOAT_OOB_FILL_NONE);
    }
    encode(&P.tm_w[2], d_in[8], 256, 64);
    void* raw = nullptr;
    cudaGetSymbolAddress(&raw, g_raw);
    H.s = (Scratch*)(((uintptr_t)raw + ((8 << 20) - 1)) & ~(uintptr_t)((8 << 20) - 1));
    P.dhi = 0x40000100u;
    P.E = in_sizes[1] < MAXE ? in_sizes[1] : MAXE;
    for (int b = 0; b < NCTA; b++) {
        const Sched s = get_sched(b >> 1, b & 1);
        P.sched[b][0] = s.qt0 | s.n0 << 8 | s.nkv << 16 | s.owner << 24 | s.pin << 25;
        P.sched[b][1] = s.qt1 | s.nmc << 8 | s.cls << 16;
        P.sched[b][2] = s.zb | s.nz << 8 | s.nw << 16;
    }
    cudaFuncSetAttribute(k_main, cudaFuncAttributeMaxDynamicSharedMemorySize, SM_TOTAL);
    k_main<<<NCTA, 384, SM_TOTAL>>>(H, P);
}
```

```cpp
#include <cuda_runtime.h>
#include <cuda.h>
#include <cuda_bf16.h>
#include <stdint.h>
#include <stddef.h>

namespace {

constexpr int NN = 10000;
constexpr int BN = 80;
constexpr int NKV = NN / BN;
constexpr int NQB = 158;
constexpr int NCTA = 132;
constexpr int NAUX = 3 * (NCTA - 2);
constexpr int STAGES = 4;
constexpr int KV_BYTES = BN * 512;
constexpr int QB_BYTES = 64 * 512;
constexpr int PART_BYTES = QB_BYTES + 512;
constexpr int CAP = 32;
constexpr int MAXE = 160000;

#define QRND(v) (((v) + 0x00040004u) & 0xFFF8FFF8u)
#define GO0 30
#define GF0 2
#define PAIR_MC 1
#define A_MC 0
#define CSRU 5
#define CPYU 5
#define REFUP 2.f
#define SND0 10
#define CUT2 2
#define ZHOLD 1
#define REG_C 224
#define REG_P 56

enum { SY_A = 0, SY_H1 = 5, SY_CSR = 6, SY_AUX = 7, SY_DONE = 8, SY_AUX0 = 9, SY_B = 10, SY_AUX1 = 11, SY_H0 = 12 };
struct Scratch {
    uint8_t hz[4096 + NN * 512];
    uint8_t w[12 * QB_BYTES];
    int sync[24 * 32];
    int pflag[NQB / 2 + 1];
    int qflag[NQB / 2 + 1];
    int ovf_n[32];
    float r255[512];
    int cnt[NN + 16];
    int bucket[(NN + 1) * CAP];
    int2 ovf[MAXE];
    uint8_t q[NQB * QB_BYTES];
    uint8_t agg[NQB * QB_BYTES];
    uint8_t part[78 * 2 * PART_BYTES];
};
static_assert(offsetof(Scratch, ovf) <= (8 << 20), "window");
static_assert(offsetof(Scratch, pflag) == offsetof(Scratch, sync) + 24 * 128 && offsetof(Scratch, qflag) == offsetof(Scratch, pflag) + 320, "flags");
static_assert(offsetof(Scratch, w) % 1024 == 0 && offsetof(Scratch, sync) % 128 == 0 &&
              offsetof(Scratch, bucket) % 128 == 0 && offsetof(Scratch, q) % 128 == 0, "alignment");
__device__ uint8_t g_raw[(8 << 20) + sizeof(Scratch)];
#define g_hz (H.s->hz)
#define g_w (H.s->w)
#define g_sync (H.s->sync)
#define g_pflag (H.s->pflag)
#define g_qflag (H.s->qflag)
#define g_ovf_n (H.s->ovf_n)
#define g_cnt (H.s->cnt)
#define g_bucket (H.s->bucket)
#define g_ovf (H.s->ovf)
#define g_q (H.s->q)
#define g_agg (H.s->agg)
#define g_part (H.s->part)

__device__ __forceinline__ void wgmma_ss_n80(float (&d)[40], uint64_t da, uint64_t db) {
    asm volatile("wgmma.mma_async.sync.aligned.m64n80k16.f32.f16.f16 {"
        "%0, %1, %2, %3, %4, %5, %6, %7, %8, %9, %10, %11, %12, %13, %14, %15, %16, %17, %18, %19, %20, %21, %22, %23, %24, %25, %26, %27, %28, %29, %30, %31, "
        "%32, %33, %34, %35, %36, %37, %38, %39}, %40, %41, 1, 1, 1, 0, 0;\n"
        : "+f"(d[0]), "+f"(d[1]), "+f"(d[2]), "+f"(d[3]), "+f"(d[4]), "+f"(d[5]), "+f"(d[6]), "+f"(d[7]),
          "+f"(d[8]), "+f"(d[9]), "+f"(d[10]), "+f"(d[11]), "+f"(d[12]), "+f"(d[13]), "+f"(d[14]), "+f"(d[15]),
          "+f"(d[16]), "+f"(d[17]), "+f"(d[18]), "+f"(d[19]), "+f"(d[20]), "+f"(d[21]), "+f"(d[22]), "+f"(d[23]),
          "+f"(d[24]), "+f"(d[25]), "+f"(d[26]), "+f"(d[27]), "+f"(d[28]), "+f"(d[29]), "+f"(d[30]), "+f"(d[31]),
          "+f"(d[32]), "+f"(d[33]), "+f"(d[34]), "+f"(d[35]), "+f"(d[36]), "+f"(d[37]), "+f"(d[38]), "+f"(d[39])
        : "l"(da), "l"(db));
}
__device__ __forceinline__ void wgmma_ss_n80_init(float (&d)[40], uint64_t da, uint64_t db) {
    asm volatile("wgmma.mma_async.sync.aligned.m64n80k16.f32.f16.f16 {"
        "%0, %1, %2, %3, %4, %5, %6, %7, %8, %9, %10, %11, %12, %13, %14, %15, %16, %17, %18, %19, %20, %21, %22, %23, %24, %25, %26, %27, %28, %29, %30, %31, "
        "%32, %33, %34, %35, %36, %37, %38, %39}, %40, %41, 0, 1, 1, 0, 0;\n"
        : "=f"(d[0]), "=f"(d[1]), "=f"(d[2]), "=f"(d[3]), "=f"(d[4]), "=f"(d[5]), "=f"(d[6]), "=f"(d[7]),
          "=f"(d[8]), "=f"(d[9]), "=f"(d[10]), "=f"(d[11]), "=f"(d[12]), "=f"(d[13]), "=f"(d[14]), "=f"(d[15]),
          "=f"(d[16]), "=f"(d[17]), "=f"(d[18]), "=f"(d[19]), "=f"(d[20]), "=f"(d[21]), "=f"(d[22]), "=f"(d[23]),
          "=f"(d[24]), "=f"(d[25]), "=f"(d[26]), "=f"(d[27]), "=f"(d[28]), "=f"(d[29]), "=f"(d[30]), "=f"(d[31]),
          "=f"(d[32]), "=f"(d[33]), "=f"(d[34]), "=f"(d[35]), "=f"(d[36]), "=f"(d[37]), "=f"(d[38]), "=f"(d[39])
        : "l"(da), "l"(db));
}
__device__ __forceinline__ void wgmma_rs_n256_tb(float (&d)[128], uint32_t a0, uint32_t a1, uint32_t a2, uint32_t a3, uint64_t db) {
    asm volatile("wgmma.mma_async.sync.aligned.m64n256k16.f32.f16.f16 {"
        "%0, %1, %2, %3, %4, %5, %6, %7, %8, %9, %10, %11, %12, %13, %14, %15, %16, %17, %18, %19, %20, %21, %22, %23, %24, %25, %26, %27, %28, %29, %30, %31, "
        "%32, %33, %34, %35, %36, %37, %38, %39, %40, %41, %42, %43, %44, %45, %46, %47, %48, %49, %50, %51, %52, %53, %54, %55, %56, %57, %58, %59, %60, %61, %62, %63, "
        "%64, %65, %66, %67, %68, %69, %70, %71, %72, %73, %74, %75, %76, %77, %78, %79, %80, %81, %82, %83, %84, %85, %86, %87, %88, %89, %90, %91, %92, %93, %94, %95, "
        "%96, %97, %98, %99, %100, %101, %102, %103, %104, %105, %106, %107, %108, %109, %110, %111, %112, %113, %114, %115, %116, %117, %118, %119, %120, %121, %122, %123, %124, %125, %126, %127}, {%128, %129, %130, %131}, %132, 1, 1, 1, 1;\n"
        : "+f"(d[0]), "+f"(d[1]), "+f"(d[2]), "+f"(d[3]), "+f"(d[4]), "+f"(d[5]), "+f"(d[6]), "+f"(d[7]),
          "+f"(d[8]), "+f"(d[9]), "+f"(d[10]), "+f"(d[11]), "+f"(d[12]), "+f"(d[13]), "+f"(d[14]), "+f"(d[15]),
          "+f"(d[16]), "+f"(d[17]), "+f"(d[18]), "+f"(d[19]), "+f"(d[20]), "+f"(d[21]), "+f"(d[22]), "+f"(d[23]),
          "+f"(d[24]), "+f"(d[25]), "+f"(d[26]), "+f"(d[27]), "+f"(d[28]), "+f"(d[29]), "+f"(d[30]), "+f"(d[31]),
          "+f"(d[32]), "+f"(d[33]), "+f"(d[34]), "+f"(d[35]), "+f"(d[36]), "+f"(d[37]), "+f"(d[38]), "+f"(d[39]),
          "+f"(d[40]), "+f"(d[41]), "+f"(d[42]), "+f"(d[43]), "+f"(d[44]), "+f"(d[45]), "+f"(d[46]), "+f"(d[47]),
          "+f"(d[48]), "+f"(d[49]), "+f"(d[50]), "+f"(d[51]), "+f"(d[52]), "+f"(d[53]), "+f"(d[54]), "+f"(d[55]),
          "+f"(d[56]), "+f"(d[57]), "+f"(d[58]), "+f"(d[59]), "+f"(d[60]), "+f"(d[61]), "+f"(d[62]), "+f"(d[63]),
          "+f"(d[64]), "+f"(d[65]), "+f"(d[66]), "+f"(d[67]), "+f"(d[68]), "+f"(d[69]), "+f"(d[70]), "+f"(d[71]),
          "+f"(d[72]), "+f"(d[73]), "+f"(d[74]), "+f"(d[75]), "+f"(d[76]), "+f"(d[77]), "+f"(d[78]), "+f"(d[79]),
          "+f"(d[80]), "+f"(d[81]), "+f"(d[82]), "+f"(d[83]), "+f"(d[84]), "+f"(d[85]), "+f"(d[86]), "+f"(d[87]),
          "+f"(d[88]), "+f"(d[89]), "+f"(d[90]), "+f"(d[91]), "+f"(d[92]), "+f"(d[93]), "+f"(d[94]), "+f"(d[95]),
          "+f"(d[96]), "+f"(d[97]), "+f"(d[98]), "+f"(d[99]), "+f"(d[100]), "+f"(d[101]), "+f"(d[102]), "+f"(d[103]),
          "+f"(d[104]), "+f"(d[105]), "+f"(d[106]), "+f"(d[107]), "+f"(d[108]), "+f"(d[109]), "+f"(d[110]), "+f"(d[111]),
          "+f"(d[112]), "+f"(d[113]), "+f"(d[114]), "+f"(d[115]), "+f"(d[116]), "+f"(d[117]), "+f"(d[118]), "+f"(d[119]),
          "+f"(d[120]), "+f"(d[121]), "+f"(d[122]), "+f"(d[123]), "+f"(d[124]), "+f"(d[125]), "+f"(d[126]), "+f"(d[127])
        : "r"(a0), "r"(a1), "r"(a2), "r"(a3), "l"(db));
}
__device__ __forceinline__ void wgmma_rs_n256_tb_init(float (&d)[128], uint32_t a0, uint32_t a1, uint32_t a2, uint32_t a3, uint64_t db) {
    asm volatile("wgmma.mma_async.sync.aligned.m64n256k16.f32.f16.f16 {"
        "%0, %1, %2, %3, %4, %5, %6, %7, %8, %9, %10, %11, %12, %13, %14, %15, %16, %17, %18, %19, %20, %21, %22, %23, %24, %25, %26, %27, %28, %29, %30, %31, "
        "%32, %33, %34, %35, %36, %37, %38, %39, %40, %41, %42, %43, %44, %45, %46, %47, %48, %49, %50, %51, %52, %53, %54, %55, %56, %57, %58, %59, %60, %61, %62, %63, "
        "%64, %65, %66, %67, %68, %69, %70, %71, %72, %73, %74, %75, %76, %77, %78, %79, %80, %81, %82, %83, %84, %85, %86, %87, %88, %89, %90, %91, %92, %93, %94, %95, "
        "%96, %97, %98, %99, %100, %101, %102, %103, %104, %105, %106, %107, %108, %109, %110, %111, %112, %113, %114, %115, %116, %117, %118, %119, %120, %121, %122, %123, %124, %125, %126, %127}, {%128, %129, %130, %131}, %132, 0, 1, 1, 1;\n"
        : "=f"(d[0]), "=f"(d[1]), "=f"(d[2]), "=f"(d[3]), "=f"(d[4]), "=f"(d[5]), "=f"(d[6]), "=f"(d[7]),
          "=f"(d[8]), "=f"(d[9]), "=f"(d[10]), "=f"(d[11]), "=f"(d[12]), "=f"(d[13]), "=f"(d[14]), "=f"(d[15]),
          "=f"(d[16]), "=f"(d[17]), "=f"(d[18]), "=f"(d[19]), "=f"(d[20]), "=f"(d[21]), "=f"(d[22]), "=f"(d[23]),
          "=f"(d[24]), "=f"(d[25]), "=f"(d[26]), "=f"(d[27]), "=f"(d[28]), "=f"(d[29]), "=f"(d[30]), "=f"(d[31]),
          "=f"(d[32]), "=f"(d[33]), "=f"(d[34]), "=f"(d[35]), "=f"(d[36]), "=f"(d[37]), "=f"(d[38]), "=f"(d[39]),
          "=f"(d[40]), "=f"(d[41]), "=f"(d[42]), "=f"(d[43]), "=f"(d[44]), "=f"(d[45]), "=f"(d[46]), "=f"(d[47]),
          "=f"(d[48]), "=f"(d[49]), "=f"(d[50]), "=f"(d[51]), "=f"(d[52]), "=f"(d[53]), "=f"(d[54]), "=f"(d[55]),
          "=f"(d[56]), "=f"(d[57]), "=f"(d[58]), "=f"(d[59]), "=f"(d[60]), "=f"(d[61]), "=f"(d[62]), "=f"(d[63]),
          "=f"(d[64]), "=f"(d[65]), "=f"(d[66]), "=f"(d[67]), "=f"(d[68]), "=f"(d[69]), "=f"(d[70]), "=f"(d[71]),
          "=f"(d[72]), "=f"(d[73]), "=f"(d[74]), "=f"(d[75]), "=f"(d[76]), "=f"(d[77]), "=f"(d[78]), "=f"(d[79]),
          "=f"(d[80]), "=f"(d[81]), "=f"(d[82]), "=f"(d[83]), "=f"(d[84]), "=f"(d[85]), "=f"(d[86]), "=f"(d[87]),
          "=f"(d[88]), "=f"(d[89]), "=f"(d[90]), "=f"(d[91]), "=f"(d[92]), "=f"(d[93]), "=f"(d[94]), "=f"(d[95]),
          "=f"(d[96]), "=f"(d[97]), "=f"(d[98]), "=f"(d[99]), "=f"(d[100]), "=f"(d[101]), "=f"(d[102]), "=f"(d[103]),
          "=f"(d[104]), "=f"(d[105]), "=f"(d[106]), "=f"(d[107]), "=f"(d[108]), "=f"(d[109]), "=f"(d[110]), "=f"(d[111]),
          "=f"(d[112]), "=f"(d[113]), "=f"(d[114]), "=f"(d[115]), "=f"(d[116]), "=f"(d[117]), "=f"(d[118]), "=f"(d[119]),
          "=f"(d[120]), "=f"(d[121]), "=f"(d[122]), "=f"(d[123]), "=f"(d[124]), "=f"(d[125]), "=f"(d[126]), "=f"(d[127])
        : "r"(a0), "r"(a1), "r"(a2), "r"(a3), "l"(db));
}
__device__ __forceinline__ void wgmma_rs_n256_tb_pred(float (&d)[128], uint32_t a0, uint32_t a1, uint32_t a2, uint32_t a3, uint64_t db, int acc) {
    asm volatile("{\n.reg .pred p;\nsetp.ne.s32 p, %133, 0;\nwgmma.mma_async.sync.aligned.m64n256k16.f32.f16.f16 {"
        "%0, %1, %2, %3, %4, %5, %6, %7, %8, %9, %10, %11, %12, %13, %14, %15, %16, %17, %18, %19, %20, %21, %22, %23, %24, %25, %26, %27, %28, %29, %30, %31, "
        "%32, %33, %34, %35, %36, %37, %38, %39, %40, %41, %42, %43, %44, %45, %46, %47, %48, %49, %50, %51, %52, %53, %54, %55, %56, %57, %58, %59, %60, %61, %62, %63, "
        "%64, %65, %66, %67, %68, %69, %70, %71, %72, %73, %74, %75, %76, %77, %78, %79, %80, %81, %82, %83, %84, %85, %86, %87, %88, %89, %90, %91, %92, %93, %94, %95, "
        "%96, %97, %98, %99, %100, %101, %102, %103, %104, %105, %106, %107, %108, %109, %110, %111, %112, %113, %114, %115, %116, %117, %118, %119, %120, %121, %122, %123, %124, %125, %126, %127}, {%128, %129, %130, %131}, %132, p, 1, 1, 1;\n}\n"
        : "+f"(d[0]), "+f"(d[1]), "+f"(d[2]), "+f"(d[3]), "+f"(d[4]), "+f"(d[5]), "+f"(d[6]), "+f"(d[7]),
          "+f"(d[8]), "+f"(d[9]), "+f"(d[10]), "+f"(d[11]), "+f"(d[12]), "+f"(d[13]), "+f"(d[14]), "+f"(d[15]),
          "+f"(d[16]), "+f"(d[17]), "+f"(d[18]), "+f"(d[19]), "+f"(d[20]), "+f"(d[21]), "+f"(d[22]), "+f"(d[23]),
          "+f"(d[24]), "+f"(d[25]), "+f"(d[26]), "+f"(d[27]), "+f"(d[28]), "+f"(d[29]), "+f"(d[30]), "+f"(d[31]),
          "+f"(d[32]), "+f"(d[33]), "+f"(d[34]), "+f"(d[35]), "+f"(d[36]), "+f"(d[37]), "+f"(d[38]), "+f"(d[39]),
          "+f"(d[40]), "+f"(d[41]), "+f"(d[42]), "+f"(d[43]), "+f"(d[44]), "+f"(d[45]), "+f"(d[46]), "+f"(d[47]),
          "+f"(d[48]), "+f"(d[49]), "+f"(d[50]), "+f"(d[51]), "+f"(d[52]), "+f"(d[53]), "+f"(d[54]), "+f"(d[55]),
          "+f"(d[56]), "+f"(d[57]), "+f"(d[58]), "+f"(d[59]), "+f"(d[60]), "+f"(d[61]), "+f"(d[62]), "+f"(d[63]),
          "+f"(d[64]), "+f"(d[65]), "+f"(d[66]), "+f"(d[67]), "+f"(d[68]), "+f"(d[69]), "+f"(d[70]), "+f"(d[71]),
          "+f"(d[72]), "+f"(d[73]), "+f"(d[74]), "+f"(d[75]), "+f"(d[76]), "+f"(d[77]), "+f"(d[78]), "+f"(d[79]),
          "+f"(d[80]), "+f"(d[81]), "+f"(d[82]), "+f"(d[83]), "+f"(d[84]), "+f"(d[85]), "+f"(d[86]), "+f"(d[87]),
          "+f"(d[88]), "+f"(d[89]), "+f"(d[90]), "+f"(d[91]), "+f"(d[92]), "+f"(d[93]), "+f"(d[94]), "+f"(d[95]),
          "+f"(d[96]), "+f"(d[97]), "+f"(d[98]), "+f"(d[99]), "+f"(d[100]), "+f"(d[101]), "+f"(d[102]), "+f"(d[103]),
          "+f"(d[104]), "+f"(d[105]), "+f"(d[106]), "+f"(d[107]), "+f"(d[108]), "+f"(d[109]), "+f"(d[110]), "+f"(d[111]),
          "+f"(d[112]), "+f"(d[113]), "+f"(d[114]), "+f"(d[115]), "+f"(d[116]), "+f"(d[117]), "+f"(d[118]), "+f"(d[119]),
          "+f"(d[120]), "+f"(d[121]), "+f"(d[122]), "+f"(d[123]), "+f"(d[124]), "+f"(d[125]), "+f"(d[126]), "+f"(d[127])
        : "r"(a0), "r"(a1), "r"(a2), "r"(a3), "l"(db), "r"(acc));
}
__device__ __forceinline__ void wgmma_ss_n256_tb(float (&d)[128], uint64_t da, uint64_t db) {
    asm volatile("wgmma.mma_async.sync.aligned.m64n256k16.f32.bf16.bf16 {"
        "%0, %1, %2, %3, %4, %5, %6, %7, %8, %9, %10, %11, %12, %13, %14, %15, %16, %17, %18, %19, %20, %21, %22, %23, %24, %25, %26, %27, %28, %29, %30, %31, "
        "%32, %33, %34, %35, %36, %37, %38, %39, %40, %41, %42, %43, %44, %45, %46, %47, %48, %49, %50, %51, %52, %53, %54, %55, %56, %57, %58, %59, %60, %61, %62, %63, "
        "%64, %65, %66, %67, %68, %69, %70, %71, %72, %73, %74, %75, %76, %77, %78, %79, %80, %81, %82, %83, %84, %85, %86, %87, %88, %89, %90, %91, %92, %93, %94, %95, "
        "%96, %97, %98, %99, %100, %101, %102, %103, %104, %105, %106, %107, %108, %109, %110, %111, %112, %113, %114, %115, %116, %117, %118, %119, %120, %121, %122, %123, %124, %125, %126, %127}, %128, %129, 1, 1, 1, 0, 1;\n"
        : "+f"(d[0]), "+f"(d[1]), "+f"(d[2]), "+f"(d[3]), "+f"(d[4]), "+f"(d[5]), "+f"(d[6]), "+f"(d[7]),
          "+f"(d[8]), "+f"(d[9]), "+f"(d[10]), "+f"(d[11]), "+f"(d[12]), "+f"(d[13]), "+f"(d[14]), "+f"(d[15]),
          "+f"(d[16]), "+f"(d[17]), "+f"(d[18]), "+f"(d[19]), "+f"(d[20]), "+f"(d[21]), "+f"(d[22]), "+f"(d[23]),
          "+f"(d[24]), "+f"(d[25]), "+f"(d[26]), "+f"(d[27]), "+f"(d[28]), "+f"(d[29]), "+f"(d[30]), "+f"(d[31]),
          "+f"(d[32]), "+f"(d[33]), "+f"(d[34]), "+f"(d[35]), "+f"(d[36]), "+f"(d[37]), "+f"(d[38]), "+f"(d[39]),
          "+f"(d[40]), "+f"(d[41]), "+f"(d[42]), "+f"(d[43]), "+f"(d[44]), "+f"(d[45]), "+f"(d[46]), "+f"(d[47]),
          "+f"(d[48]), "+f"(d[49]), "+f"(d[50]), "+f"(d[51]), "+f"(d[52]), "+f"(d[53]), "+f"(d[54]), "+f"(d[55]),
          "+f"(d[56]), "+f"(d[57]), "+f"(d[58]), "+f"(d[59]), "+f"(d[60]), "+f"(d[61]), "+f"(d[62]), "+f"(d[63]),
          "+f"(d[64]), "+f"(d[65]), "+f"(d[66]), "+f"(d[67]), "+f"(d[68]), "+f"(d[69]), "+f"(d[70]), "+f"(d[71]),
          "+f"(d[72]), "+f"(d[73]), "+f"(d[74]), "+f"(d[75]), "+f"(d[76]), "+f"(d[77]), "+f"(d[78]), "+f"(d[79]),
          "+f"(d[80]), "+f"(d[81]), "+f"(d[82]), "+f"(d[83]), "+f"(d[84]), "+f"(d[85]), "+f"(d[86]), "+f"(d[87]),
          "+f"(d[88]), "+f"(d[89]), "+f"(d[90]), "+f"(d[91]), "+f"(d[92]), "+f"(d[93]), "+f"(d[94]), "+f"(d[95]),
          "+f"(d[96]), "+f"(d[97]), "+f"(d[98]), "+f"(d[99]), "+f"(d[100]), "+f"(d[101]), "+f"(d[102]), "+f"(d[103]),
          "+f"(d[104]), "+f"(d[105]), "+f"(d[106]), "+f"(d[107]), "+f"(d[108]), "+f"(d[109]), "+f"(d[110]), "+f"(d[111]),
          "+f"(d[112]), "+f"(d[113]), "+f"(d[114]), "+f"(d[115]), "+f"(d[116]), "+f"(d[117]), "+f"(d[118]), "+f"(d[119]),
          "+f"(d[120]), "+f"(d[121]), "+f"(d[122]), "+f"(d[123]), "+f"(d[124]), "+f"(d[125]), "+f"(d[126]), "+f"(d[127])
        : "l"(da), "l"(db));
}
__device__ __forceinline__ void wgmma_ss_n256_tb_init(float (&d)[128], uint64_t da, uint64_t db) {
    asm volatile("wgmma.mma_async.sync.aligned.m64n256k16.f32.bf16.bf16 {"
        "%0, %1, %2, %3, %4, %5, %6, %7, %8, %9, %10, %11, %12, %13, %14, %15, %16, %17, %18, %19, %20, %21, %22, %23, %24, %25, %26, %27, %28, %29, %30, %31, "
        "%32, %33, %34, %35, %36, %37, %38, %39, %40, %41, %42, %43, %44, %45, %46, %47, %48, %49, %50, %51, %52, %53, %54, %55, %56, %57, %58, %59, %60, %61, %62, %63, "
        "%64, %65, %66, %67, %68, %69, %70, %71, %72, %73, %74, %75, %76, %77, %78, %79, %80, %81, %82, %83, %84, %85, %86, %87, %88, %89, %90, %91, %92, %93, %94, %95, "
        "%96, %97, %98, %99, %100, %101, %102, %103, %104, %105, %106, %107, %108, %109, %110, %111, %112, %113, %114, %115, %116, %117, %118, %119, %120, %121, %122, %123, %124, %125, %126, %127}, %128, %129, 0, 1, 1, 0, 1;\n"
        : "=f"(d[0]), "=f"(d[1]), "=f"(d[2]), "=f"(d[3]), "=f"(d[4]), "=f"(d[5]), "=f"(d[6]), "=f"(d[7]),
          "=f"(d[8]), "=f"(d[9]), "=f"(d[10]), "=f"(d[11]), "=f"(d[12]), "=f"(d[13]), "=f"(d[14]), "=f"(d[15]),
          "=f"(d[16]), "=f"(d[17]), "=f"(d[18]), "=f"(d[19]), "=f"(d[20]), "=f"(d[21]), "=f"(d[22]), "=f"(d[23]),
          "=f"(d[24]), "=f"(d[25]), "=f"(d[26]), "=f"(d[27]), "=f"(d[28]), "=f"(d[29]), "=f"(d[30]), "=f"(d[31]),
          "=f"(d[32]), "=f"(d[33]), "=f"(d[34]), "=f"(d[35]), "=f"(d[36]), "=f"(d[37]), "=f"(d[38]), "=f"(d[39]),
          "=f"(d[40]), "=f"(d[41]), "=f"(d[42]), "=f"(d[43]), "=f"(d[44]), "=f"(d[45]), "=f"(d[46]), "=f"(d[47]),
          "=f"(d[48]), "=f"(d[49]), "=f"(d[50]), "=f"(d[51]), "=f"(d[52]), "=f"(d[53]), "=f"(d[54]), "=f"(d[55]),
          "=f"(d[56]), "=f"(d[57]), "=f"(d[58]), "=f"(d[59]), "=f"(d[60]), "=f"(d[61]), "=f"(d[62]), "=f"(d[63]),
          "=f"(d[64]), "=f"(d[65]), "=f"(d[66]), "=f"(d[67]), "=f"(d[68]), "=f"(d[69]), "=f"(d[70]), "=f"(d[71]),
          "=f"(d[72]), "=f"(d[73]), "=f"(d[74]), "=f"(d[75]), "=f"(d[76]), "=f"(d[77]), "=f"(d[78]), "=f"(d[79]),
          "=f"(d[80]), "=f"(d[81]), "=f"(d[82]), "=f"(d[83]), "=f"(d[84]), "=f"(d[85]), "=f"(d[86]), "=f"(d[87]),
          "=f"(d[88]), "=f"(d[89]), "=f"(d[90]), "=f"(d[91]), "=f"(d[92]), "=f"(d[93]), "=f"(d[94]), "=f"(d[95]),
          "=f"(d[96]), "=f"(d[97]), "=f"(d[98]), "=f"(d[99]), "=f"(d[100]), "=f"(d[101]), "=f"(d[102]), "=f"(d[103]),
          "=f"(d[104]), "=f"(d[105]), "=f"(d[106]), "=f"(d[107]), "=f"(d[108]), "=f"(d[109]), "=f"(d[110]), "=f"(d[111]),
          "=f"(d[112]), "=f"(d[113]), "=f"(d[114]), "=f"(d[115]), "=f"(d[116]), "=f"(d[117]), "=f"(d[118]), "=f"(d[119]),
          "=f"(d[120]), "=f"(d[121]), "=f"(d[122]), "=f"(d[123]), "=f"(d[124]), "=f"(d[125]), "=f"(d[126]), "=f"(d[127])
        : "l"(da), "l"(db));
}
__device__ __forceinline__ void wgmma_ss_n256_tb_pred(float (&d)[128], uint64_t da, uint64_t db, int acc) {
    asm volatile("{\n.reg .pred p;\nsetp.ne.s32 p, %130, 0;\nwgmma.mma_async.sync.aligned.m64n256k16.f32.bf16.bf16 {"
        "%0, %1, %2, %3, %4, %5, %6, %7, %8, %9, %10, %11, %12, %13, %14, %15, %16, %17, %18, %19, %20, %21, %22, %23, %24, %25, %26, %27, %28, %29, %30, %31, "
        "%32, %33, %34, %35, %36, %37, %38, %39, %40, %41, %42, %43, %44, %45, %46, %47, %48, %49, %50, %51, %52, %53, %54, %55, %56, %57, %58, %59, %60, %61, %62, %63, "
        "%64, %65, %66, %67, %68, %69, %70, %71, %72, %73, %74, %75, %76, %77, %78, %79, %80, %81, %82, %83, %84, %85, %86, %87, %88, %89, %90, %91, %92, %93, %94, %95, "
        "%96, %97, %98, %99, %100, %101, %102, %103, %104, %105, %106, %107, %108, %109, %110, %111, %112, %113, %114, %115, %116, %117, %118, %119, %120, %121, %122, %123, %124, %125, %126, %127}, %128, %129, p, 1, 1, 0, 1;\n}\n"
        : "+f"(d[0]), "+f"(d[1]), "+f"(d[2]), "+f"(d[3]), "+f"(d[4]), "+f"(d[5]), "+f"(d[6]), "+f"(d[7]),
          "+f"(d[8]), "+f"(d[9]), "+f"(d[10]), "+f"(d[11]), "+f"(d[12]), "+f"(d[13]), "+f"(d[14]), "+f"(d[15]),
          "+f"(d[16]), "+f"(d[17]), "+f"(d[18]), "+f"(d[19]), "+f"(d[20]), "+f"(d[21]), "+f"(d[22]), "+f"(d[23]),
          "+f"(d[24]), "+f"(d[25]), "+f"(d[26]), "+f"(d[27]), "+f"(d[28]), "+f"(d[29]), "+f"(d[30]), "+f"(d[31]),
          "+f"(d[32]), "+f"(d[33]), "+f"(d[34]), "+f"(d[35]), "+f"(d[36]), "+f"(d[37]), "+f"(d[38]), "+f"(d[39]),
          "+f"(d[40]), "+f"(d[41]), "+f"(d[42]), "+f"(d[43]), "+f"(d[44]), "+f"(d[45]), "+f"(d[46]), "+f"(d[47]),
          "+f"(d[48]), "+f"(d[49]), "+f"(d[50]), "+f"(d[51]), "+f"(d[52]), "+f"(d[53]), "+f"(d[54]), "+f"(d[55]),
          "+f"(d[56]), "+f"(d[57]), "+f"(d[58]), "+f"(d[59]), "+f"(d[60]), "+f"(d[61]), "+f"(d[62]), "+f"(d[63]),
          "+f"(d[64]), "+f"(d[65]), "+f"(d[66]), "+f"(d[67]), "+f"(d[68]), "+f"(d[69]), "+f"(d[70]), "+f"(d[71]),
          "+f"(d[72]), "+f"(d[73]), "+f"(d[74]), "+f"(d[75]), "+f"(d[76]), "+f"(d[77]), "+f"(d[78]), "+f"(d[79]),
          "+f"(d[80]), "+f"(d[81]), "+f"(d[82]), "+f"(d[83]), "+f"(d[84]), "+f"(d[85]), "+f"(d[86]), "+f"(d[87]),
          "+f"(d[88]), "+f"(d[89]), "+f"(d[90]), "+f"(d[91]), "+f"(d[92]), "+f"(d[93]), "+f"(d[94]), "+f"(d[95]),
          "+f"(d[96]), "+f"(d[97]), "+f"(d[98]), "+f"(d[99]), "+f"(d[100]), "+f"(d[101]), "+f"(d[102]), "+f"(d[103]),
          "+f"(d[104]), "+f"(d[105]), "+f"(d[106]), "+f"(d[107]), "+f"(d[108]), "+f"(d[109]), "+f"(d[110]), "+f"(d[111]),
          "+f"(d[112]), "+f"(d[113]), "+f"(d[114]), "+f"(d[115]), "+f"(d[116]), "+f"(d[117]), "+f"(d[118]), "+f"(d[119]),
          "+f"(d[120]), "+f"(d[121]), "+f"(d[122]), "+f"(d[123]), "+f"(d[124]), "+f"(d[125]), "+f"(d[126]), "+f"(d[127])
        : "l"(da), "l"(db), "r"(acc));
}
__device__ __forceinline__ void wgmma_rs_n64_tb(float (&d)[32], uint32_t a0, uint32_t a1, uint32_t a2, uint32_t a3, uint64_t db) {
    asm volatile("wgmma.mma_async.sync.aligned.m64n64k16.f32.bf16.bf16 {"
        "%0, %1, %2, %3, %4, %5, %6, %7, %8, %9, %10, %11, %12, %13, %14, %15, %16, %17, %18, %19, %20, %21, %22, %23, %24, %25, %26, %27, %28, %29, %30, %31}, {%32, %33, %34, %35}, %36, 1, 1, 1, 1;\n"
        : "+f"(d[0]), "+f"(d[1]), "+f"(d[2]), "+f"(d[3]), "+f"(d[4]), "+f"(d[5]), "+f"(d[6]), "+f"(d[7]),
          "+f"(d[8]), "+f"(d[9]), "+f"(d[10]), "+f"(d[11]), "+f"(d[12]), "+f"(d[13]), "+f"(d[14]), "+f"(d[15]),
          "+f"(d[16]), "+f"(d[17]), "+f"(d[18]), "+f"(d[19]), "+f"(d[20]), "+f"(d[21]), "+f"(d[22]), "+f"(d[23]),
          "+f"(d[24]), "+f"(d[25]), "+f"(d[26]), "+f"(d[27]), "+f"(d[28]), "+f"(d[29]), "+f"(d[30]), "+f"(d[31])
        : "r"(a0), "r"(a1), "r"(a2), "r"(a3), "l"(db));
}
__device__ __forceinline__ void wgmma_rs_n64_tb_init(float (&d)[32], uint32_t a0, uint32_t a1, uint32_t a2, uint32_t a3, uint64_t db) {
    asm volatile("wgmma.mma_async.sync.aligned.m64n64k16.f32.bf16.bf16 {"
        "%0, %1, %2, %3, %4, %5, %6, %7, %8, %9, %10, %11, %12, %13, %14, %15, %16, %17, %18, %19, %20, %21, %22, %23, %24, %25, %26, %27, %28, %29, %30, %31}, {%32, %33, %34, %35}, %36, 0, 1, 1, 1;\n"
        : "=f"(d[0]), "=f"(d[1]), "=f"(d[2]), "=f"(d[3]), "=f"(d[4]), "=f"(d[5]), "=f"(d[6]), "=f"(d[7]),
          "=f"(d[8]), "=f"(d[9]), "=f"(d[10]), "=f"(d[11]), "=f"(d[12]), "=f"(d[13]), "=f"(d[14]), "=f"(d[15]),
          "=f"(d[16]), "=f"(d[17]), "=f"(d[18]), "=f"(d[19]), "=f"(d[20]), "=f"(d[21]), "=f"(d[22]), "=f"(d[23]),
          "=f"(d[24]), "=f"(d[25]), "=f"(d[26]), "=f"(d[27]), "=f"(d[28]), "=f"(d[29]), "=f"(d[30]), "=f"(d[31])
        : "r"(a0), "r"(a1), "r"(a2), "r"(a3), "l"(db));
}

__device__ __forceinline__ void wg_fence() { asm volatile("wgmma.fence.sync.aligned;\n" ::: "memory"); }
__device__ __forceinline__ void wg_commit() { asm volatile("wgmma.commit_group.sync.aligned;\n" ::: "memory"); }
template <int N> __device__ __forceinline__ void wg_wait() { asm volatile("wgmma.wait_group.sync.aligned %0;\n" ::"n"(N) : "memory"); }
template <int N> __device__ __forceinline__ void fence_regs(float (&a)[N]) {
#pragma unroll
    for (int i = 0; i < N; i++) asm volatile("" : "+f"(a[i])::"memory");
}
template <int N> __device__ __forceinline__ void fence_regs(uint32_t (&a)[N]) {
#pragma unroll
    for (int i = 0; i < N; i++) asm volatile("" : "+r"(a[i])::"memory");
}
__device__ __forceinline__ void mbar_init(uint32_t bar, uint32_t cnt) {
    asm volatile("mbarrier.init.shared::cta.b64 [%0], %1;\n" ::"r"(bar), "r"(cnt) : "memory");
}
__device__ __forceinline__ void mbar_expect_tx(uint32_t bar, uint32_t bytes) {
    asm volatile("mbarrier.arrive.expect_tx.shared::cta.b64 _, [%0], %1;\n" ::"r"(bar), "r"(bytes) : "memory");
}
__device__ __forceinline__ void mbar_wait(uint32_t bar, uint32_t parity) {
    asm volatile("{\n.reg .pred p;\nLW:\nmbarrier.try_wait.parity.shared::cta.b64 p, [%0], %1;\n@!p pmevent 0;\n@!p bra LW;\n}\n" ::"r"(bar), "r"(parity) : "memory");
}
__device__ __forceinline__ void mbar_wait_sleep(uint32_t bar, uint32_t parity) {
    asm volatile("{\n.reg .pred p;\nLW:\nmbarrier.try_wait.parity.shared::cta.b64 p, [%0], %1, 20000;\n@!p pmevent 0;\n@!p bra LW;\n}\n" ::"r"(bar), "r"(parity) : "memory");
}
__device__ __forceinline__ void mbar_wait_bounded(uint32_t bar, uint32_t parity) {
    asm volatile("{\n.reg .pred p;\n.reg .u32 c;\nmov.u32 c, 0;\nLW:\nmbarrier.try_wait.parity.shared::cta.b64 p, [%0], %1, 20000;\n@p bra LD;\n"
                 "add.u32 c, c, 1;\nsetp.ge.u32 p, c, 262144;\n@p trap;\nbra LW;\nLD:\n}\n" ::"r"(bar), "r"(parity) : "memory");
}
__device__ __forceinline__ void flag_wait(const int* p, int v) {
    asm volatile("{\n.reg .pred p;\n.reg .s32 f;\nLW:\nld.acquire.gpu.global.s32 f, [%0];\nsub.s32 f, f, %1;\nsetp.lt.s32 p, f, 0;\n@p bra LW;\n}\n" ::"l"(p), "r"(v) : "memory");
}
__device__ __forceinline__ void flag_wait_bounded(const int* p, int v) {
    asm volatile("{\n.reg .pred p;\n.reg .u32 c;\n.reg .s32 f;\nmov.u32 c, 0;\nLW:\nld.acquire.gpu.global.s32 f, [%0];\nsub.s32 f, f, %1;\nsetp.ge.s32 p, f, 0;\n@p bra LD;\n"
                 "nanosleep.u32 500;\nadd.u32 c, c, 1;\nsetp.ge.u32 p, c, 4194304;\n@p trap;\nbra LW;\nLD:\n}\n" ::"l"(p), "r"(v) : "memory");
}
__device__ __forceinline__ bool elect() {
    uint32_t p; asm volatile("{\n.reg .pred p;\nelect.sync _|p, -1;\nselp.u32 %0, 1, 0, p;\n}\n" : "=r"(p)); return p;
}
__device__ __forceinline__ void bulk_g2s(uint32_t dst, const void* src, uint32_t bytes, uint32_t bar) {
    asm volatile("cp.async.bulk.shared::cluster.global.mbarrier::complete_tx::bytes [%0], [%1], %2, [%3];\n"
                 ::"r"(dst), "l"(src), "r"(bytes), "r"(bar) : "memory");
}
__device__ __forceinline__ void bulk_g2s_mc(uint32_t dst, const void* src, uint32_t bytes, uint32_t bar, uint16_t mask) {
    asm volatile("cp.async.bulk.shared::cluster.global.mbarrier::complete_tx::bytes.multicast::cluster [%0], [%1], %2, [%3], %4;\n"
                 ::"r"(dst), "l"(src), "r"(bytes), "r"(bar), "h"(mask) : "memory");
}
__device__ __forceinline__ void tma_g2s(uint32_t dst, const CUtensorMap* tm, int rowgroup, uint32_t bar) {
    asm volatile("cp.async.bulk.tensor.4d.shared::cluster.global.tile.mbarrier::complete_tx::bytes [%0], [%1, {0, 0, 0, %2}], [%3];\n"
                 ::"r"(dst), "l"(tm), "r"(rowgroup), "r"(bar) : "memory");
}
__device__ __forceinline__ void bar_sync(int id, int n) { asm volatile("bar.sync %0, %1;\n" ::"r"(id), "r"(n) : "memory"); }
__device__ __forceinline__ void bar_arrive(int id, int n) { asm volatile("bar.arrive %0, %1;\n" ::"r"(id), "r"(n) : "memory"); }
__device__ __forceinline__ float quad_last(float v) {
    float r; asm volatile("shfl.sync.idx.b32 %0, %1, 3, 0x1c1f, -1;\n" : "=f"(r) : "f"(v)); return r;
}
__device__ __forceinline__ float ex2(float x) { float y; asm("ex2.approx.ftz.f32 %0, %1;\n" : "=f"(y) : "f"(x)); return y; }
__device__ __forceinline__ float rcp(float x) { float y; asm("rcp.approx.ftz.f32 %0, %1;\n" : "=f"(y) : "f"(x)); return y; }
__device__ __forceinline__ uint32_t pack_bf16(float lo, float hi) {
    uint32_t r; asm("cvt.rn.bf16x2.f32 %0, %1, %2;\n" : "=r"(r) : "f"(hi), "f"(lo)); return r;
}
__device__ __forceinline__ uint32_t pack_f16(float lo, float hi) {
    uint32_t r; asm("cvt.rn.f16x2.f32 %0, %1, %2;\n" : "=r"(r) : "f"(hi), "f"(lo)); return r;
}
__device__ __forceinline__ uint32_t pack_f16_sat(float lo, float hi) {
    uint32_t r; asm("cvt.rn.satfinite.f16x2.f32 %0, %1, %2;\n" : "=r"(r) : "f"(hi), "f"(lo)); return r;
}
__device__ __forceinline__ float f16_lo(uint32_t v) { float r; asm("cvt.f32.f16 %0, %1;\n" : "=f"(r) : "h"((unsigned short)v)); return r; }
__device__ __forceinline__ float f16_hi(uint32_t v) { return f16_lo(v >> 16); }
__device__ __forceinline__ float bf_lo(uint32_t v) { return __uint_as_float(v << 16); }
__device__ __forceinline__ float bf_hi(uint32_t v) { return __uint_as_float(v & 0xFFFF0000u); }
__device__ __forceinline__ float bf_round(float x) { return __uint_as_float(pack_bf16(0.f, x)); }
__device__ __forceinline__ void st_release(int* p, int v) {
    asm volatile("st.release.gpu.global.s32 [%0], %1;\n" ::"l"(p), "r"(v) : "memory");
}
__device__ __forceinline__ uint4 ldg_pinned(const uint4* p) {
    uint4 v; asm volatile("ld.global.nc.v4.u32 {%0, %1, %2, %3}, [%4];\n" : "=r"(v.x), "=r"(v.y), "=r"(v.z), "=r"(v.w) : "l"(p) : "memory"); return v;
}
__device__ __forceinline__ void stmatrix_x4(uint32_t addr, uint32_t r0, uint32_t r1, uint32_t r2, uint32_t r3) {
    asm volatile("stmatrix.sync.aligned.m8n8.x4.shared.b16 [%0], {%1, %2, %3, %4};\n" ::"r"(addr), "r"(r0), "r"(r1), "r"(r2), "r"(r3) : "memory");
}

__device__ __forceinline__ uint32_t tile_off(int r, int ch) {
    return (uint32_t)((r >> 3) * 4096 + (ch >> 3) * 1024 + (r & 7) * 128 + (((ch ^ r) & 7) << 4));
}
__device__ __forceinline__ int h_unit(int qt, int u) { return qt < 78 ? u * 78 + qt : 624; }
__device__ __forceinline__ int row_off(int r) { return 4096 + h_unit(r >> 7, (r >> 4) & 7) * 8192 + (r & 8) * 512 + (r & 7) * 144; }

__device__ __forceinline__ float4 lds128f(uint32_t a) {
    float4 v; asm volatile("ld.shared.v4.f32 {%0, %1, %2, %3}, [%4];\n" : "=f"(v.x), "=f"(v.y), "=f"(v.z), "=f"(v.w) : "r"(a) : "memory"); return v;
}
__device__ __forceinline__ uint64_t lds64(uint32_t a) { uint64_t v; asm volatile("ld.shared.u64 %0, [%1];\n" : "=l"(v) : "r"(a) : "memory"); return v; }
__device__ __forceinline__ uint4 lds128(uint32_t a) {
    uint4 v; asm volatile("ld.shared.v4.u32 {%0, %1, %2, %3}, [%4];\n" : "=r"(v.x), "=r"(v.y), "=r"(v.z), "=r"(v.w) : "r"(a) : "memory"); return v;
}
__device__ __forceinline__ void sts128(uint32_t a, uint32_t x, uint32_t y, uint32_t z, uint32_t w) {
    asm volatile("st.shared.v4.u32 [%0], {%1, %2, %3, %4};\n" ::"r"(a), "r"(x), "r"(y), "r"(z), "r"(w) : "memory");
}
__device__ __forceinline__ void mbar_arrive(uint32_t bar) {
    asm volatile("mbarrier.arrive.shared::cta.b64 _, [%0];\n" ::"r"(bar) : "memory");
}
__device__ __forceinline__ uint64_t mkaddr(uint32_t lo, uint32_t hi) { uint64_t a; asm("mov.b64 %0, {%1, %2};\n" : "=l"(a) : "r"(lo), "r"(hi)); return a; }
__device__ __forceinline__ void red_add(int* p) { asm volatile("red.relaxed.gpu.global.add.s32 [%0], 1;\n" ::"l"(p) : "memory"); }
__device__ __forceinline__ void red_release(int* p) {
    asm volatile("fence.proxy.async.global;\nfence.acq_rel.gpu;\nred.relaxed.gpu.global.add.s32 [%0], 1;\n" ::"l"(p) : "memory");
}
__device__ __forceinline__ void fence_async_global() { asm volatile("fence.proxy.async.global;\n" ::: "memory"); }
__device__ __forceinline__ void fence_async_smem() { asm volatile("fence.proxy.async.shared::cta;\n" ::: "memory"); }
__device__ __forceinline__ void bulk_s2g(void* dst, uint32_t src, uint32_t bytes) {
    asm volatile("cp.async.bulk.global.shared::cta.bulk_group [%0], [%1], %2;\ncp.async.bulk.commit_group;\n" ::"l"(dst), "r"(src), "r"(bytes) : "memory");
}
__device__ __forceinline__ void mma16816(float (&c)[4], uint32_t a0, uint32_t a1, uint32_t a2, uint32_t a3, uint32_t b0, uint32_t b1) {
    asm("mma.sync.aligned.m16n8k16.row.col.f32.bf16.bf16.f32 {%0, %1, %2, %3}, {%4, %5, %6, %7}, {%8, %9}, {%0, %1, %2, %3};\n"
        : "+f"(c[0]), "+f"(c[1]), "+f"(c[2]), "+f"(c[3]) : "r"(a0), "r"(a1), "r"(a2), "r"(a3), "r"(b0), "r"(b1));
}
__device__ __forceinline__ void mma1688(float (&c)[4], uint32_t a0, uint32_t a1, uint32_t b0) {
    asm("mma.sync.aligned.m16n8k8.row.col.f32.bf16.bf16.f32 {%0, %1, %2, %3}, {%4, %5}, {%6}, {%0, %1, %2, %3};\n"
        : "+f"(c[0]), "+f"(c[1]), "+f"(c[2]), "+f"(c[3]) : "r"(a0), "r"(a1), "r"(b0));
}
__device__ __forceinline__ uint32_t hadd2_f16(uint32_t a, uint32_t b) { uint32_t r; asm("add.rn.f16x2 %0, %1, %2;\n" : "=r"(r) : "r"(a), "r"(b)); return r; }
__device__ __forceinline__ uint32_t hadd2(uint32_t a, uint32_t b) { uint32_t r; asm("add.rn.bf16x2 %0, %1, %2;\n" : "=r"(r) : "r"(a), "r"(b)); return r; }
__device__ __forceinline__ uint32_t hfma2(uint32_t a, uint32_t b, uint32_t c) { uint32_t r; asm("fma.rn.bf16x2 %0, %1, %2, %3;\n" : "=r"(r) : "r"(a), "r"(b), "r"(c)); return r; }

constexpr int SM_Q = 0;
constexpr int SM_KV = 65536;
constexpr int SM_ML = SM_KV + STAGES * KV_BYTES;
constexpr int SM_BAR = SM_ML + 1024;
constexpr int SM_TOTAL = SM_BAR + 256;
constexpr float SCALE_LOG2 = 1.4426950408889634f / 16.0f;
constexpr float KV_SCALE = 0.75f;
constexpr float KV_OFF = 6.f;
constexpr uint32_t KV_OFF2 = 0x46004600u;
constexpr uint32_t KV_NEG4 = 0xCE00CE00u;
constexpr uint32_t P_LIMIT = 0x78007800u;
constexpr float REF_UP = REFUP;
__device__ __forceinline__ uint32_t kvf(uint32_t a) {
    uint32_t r; asm("fma.rn.f16x2 %0, %1, %2, %3;\n" : "=r"(r) : "r"(a), "r"(pack_f16(KV_SCALE, KV_SCALE)), "r"(KV_OFF2)); return r;
}
enum { BAR_PP0 = 1, BAR_PP1 = 2, BAR_WG0 = 3, BAR_WG1 = 4, BAR_H0 = 5, BAR_H1 = 6, BAR_AUX = 7, BAR_BF = 8, BAR_H2 = 9, BAR_X = 10, BAR_GO = 11, BAR_WG2 = 12, BAR_ST = 13 };

struct Sched { int qt0, n0, nkv, qt1, cls, owner, pin, nmc, pair, zb, nz, nw; };
static Sched get_sched(int c, int r) {
    Sched s;
    s.qt1 = s.pin = s.zb = s.nz = 0; s.pair = c < 52; s.n0 = s.nkv = 75; s.cls = 0x420; s.owner = r == 0; s.nw = 4;
    if (c < 52) {
        const int p = c >> 1, odd = c & 1, tc = p, ta = 26 + 2 * p, tb = ta + 1;
        s.pin = odd; s.nmc = PAIR_MC * (odd ? 50 : 25); s.nw = 8;
        s.zb = 2 * (odd ? tb : ta) + 1 - r;
        if (r == 0) {
            s.qt0 = odd ? tb : ta; s.cls = odd ? 0x431 : 0x420;
        } else {
            s.qt0 = odd ? tc : tb; s.qt1 = odd ? tb : ta; s.n0 = odd ? 50 : 25; s.cls = odd ? 0x231 : 0x130;
        }
    } else if (c < 65) {
        s.owner = 1; s.nmc = 75; s.qt0 = 2 * (c - 52) + r; s.pin = 1;
    } else {
        s.qt0 = 78; s.nmc = 0;
        if (r) { s.n0 = s.nkv = 50; s.cls = 0x31; s.nw = 0; }
        s.zb = r ? 156 : 0; s.nz = r ? 27 : 26;
    }
    return s;
}

struct Hot {
    const __nv_bfloat16 *wk, *wq, *x;
    Scratch* s;
};
struct Params {
    const __nv_bfloat16* deg_inv;
    const int *src, *dst;
    __nv_bfloat16* out;
    uint32_t dhi;
    int E;
    uint32_t sched[NCTA][3];
    CUtensorMap tm_out;
    CUtensorMap tm_outc;
    CUtensorMap tm_w[3];
};
static_assert(offsetof(Params, tm_outc) == offsetof(Params, tm_out) + 128, "layout");
#define SC_QT(seg) ((int)(P.sched[blockIdx.x][seg] & 255))
#define SC_N0 ((int)((P.sched[blockIdx.x][0] >> 8) & 255))
#define SC_NKV ((int)((P.sched[blockIdx.x][0] >> 16) & 255))
#define SC_OWNER ((P.sched[blockIdx.x][0] >> 24) & 1)
#define SC_PIN ((P.sched[blockIdx.x][0] >> 25) & 1)
#define SC_NMC ((int)((P.sched[blockIdx.x][1] >> 8) & 255))
#define SC_CLS (P.sched[blockIdx.x][1] >> 16)
#define SC_ZB(k) ((int)(P.sched[blockIdx.x][2] & 255) + 2 * (k) - ((P.sched[blockIdx.x][2] & 255) + 2 * (k) >= 157 ? 157 : 0))
#define SC_NZ ((int)((P.sched[blockIdx.x][2] >> 8) & 255))
#define SC_NW ((int)(P.sched[blockIdx.x][2] >> 16))
#define SC_PAIR (blockIdx.x < 104)
#define SC_TAIL (blockIdx.x >= NCTA - 2)

__global__ void __cluster_dims__(2, 1, 1) __launch_bounds__(384, 1) k_main(const __grid_constant__ Hot H, const __grid_constant__ Params P) {
    extern __shared__ __align__(1024) uint8_t smem[];
    const uint32_t sb = (uint32_t)__cvta_generic_to_shared(smem);
    const int tid = threadIdx.x, wg = __shfl_sync(~0u, tid >> 7, 0);
    const int lane = tid & 31, g = lane >> 2, q = lane & 3;
    const uint32_t rank = blockIdx.x & 1;
    const uint32_t bar_full = sb + SM_BAR, bar_q = bar_full + 32, bar_go = bar_full + 48;
    const uint32_t bar_pin = bar_full + 56;
    const uint32_t bar_qfree = bar_full + 88, bar_pdone = bar_full + 104, bar_zst = bar_full + 120, bar_rfree = bar_full + 136;
    const uint32_t bar_empty = bar_full + 144, bar_end = bar_full + 176, s_tm = bar_full + 184, bar_x = bar_full + 192;

    if (wg == 2) {
        const int warp = __shfl_sync(~0u, (tid >> 5) & 3, 0);
        const int t = tid & 127;
        unsigned done;
        {
            uint4 ra[8], rb[8], rk[8], rz[8];
            if (blockIdx.x < 128) {
                const int rg = blockIdx.x >> 2;
                const int e = (rg >> 2) * 32 + (g >> 1) * 8 + (rg & 2) * 2 + (rg & 1) * 2 + (g & 1);
                const int f = (blockIdx.x & 3) * 64 + (warp >> 1) * 32 + (g >> 1) * 8 + (warp & 1) * 4 + (g & 1);
                const uint4* pk = (const uint4*)(H.wk + f * 256 + q * 8);
                const uint4* pq = (const uint4*)(H.wq + e * 256 + q * 8);
                const uint4* pz = (const uint4*)(H.wk + 255 * 256) + q;
                asm volatile("" : "+l"(pz));
#pragma unroll
                for (int s = 0; s < 8; s++) {
                    ra[s] = ldg_pinned(pk + 4 * s);
                    rb[s] = ldg_pinned(pk + 4 * s + 64);
                    rk[s] = ldg_pinned(pq + 4 * s);
                    rz[s] = ldg_pinned(pz + 4 * s);
                }
            }
            asm volatile("{\n.reg .pred p;\nsetp.eq.s32 p, %2, 0;\nmov.u32 %0, 0;\n@p ld.global.cg.u32 %0, [%1];\n}\n" : "=r"(done) : "l"(&g_sync[SY_DONE * 32]), "r"(lane) : "memory");
            bar_arrive(BAR_X, 384);
            if (warp == 0 && elect()) {
#pragma unroll
                for (int i = 0; i < 23; i++) mbar_init(bar_full + 8 * i, i < 11 ? 1 : i < 18 ? 4 : i == 22 ? 11 : SC_TAIL ? 8 : 16);
                mbar_expect_tx(bar_pin, QB_BYTES / 2 + 512); mbar_expect_tx(bar_pin + 8, QB_BYTES / 2);
                mbar_expect_tx(bar_pin + 16, SC_PAIR ? 512 : 1024); mbar_expect_tx(bar_pin + 24, QB_BYTES);
                asm volatile("fence.mbarrier_init.release.cluster;\n" ::: "memory");
            }
            __syncwarp();
            asm volatile("barrier.cluster.arrive.relaxed.aligned;\n" ::: "memory");
            if (blockIdx.x < 128) {
                float c0[4] = {0.f, 0.f, 0.f, 0.f}, c1[4] = {0.f, 0.f, 0.f, 0.f}, z0[4] = {0.f, 0.f, 0.f, 0.f}, z1[4] = {0.f, 0.f, 0.f, 0.f};
#pragma unroll
                for (int s = 0; s < 8; s++) {
                    mma16816(c0, ra[s].x, rb[s].x, ra[s].y, rb[s].y, rk[s].x, rk[s].y);
                    mma16816(c1, ra[s].z, rb[s].z, ra[s].w, rb[s].w, rk[s].z, rk[s].w);
                    mma16816(z0, rz[s].x, rz[s].x, rz[s].y, rz[s].y, rk[s].x, rk[s].y);
                    mma16816(z1, rz[s].z, rz[s].z, rz[s].w, rz[s].w, rk[s].z, rk[s].w);
                }
#pragma unroll
                for (int i = 0; i < 4; i++) c0[i] = ((c0[i] + c1[i]) - (z0[i] + z1[i])) * (SCALE_LOG2 / KV_SCALE);
                asm volatile("stmatrix.sync.aligned.m8n8.x2.trans.shared.b16 [%0], {%1, %2};\n"
                             ::"r"(sb + SM_ML + (lane & 7) * 128 + (((2 * warp + ((lane >> 3) & 1)) ^ lane) & 7) * 16),
                             "r"(pack_f16_sat(c0[0], c0[1])), "r"(pack_f16_sat(c0[2], c0[3])) : "memory");
                fence_async_smem();
            }
        }
        asm volatile("setmaxnreg.dec.sync.aligned.u32 %0;\n" ::"n"(REG_P));
        if (blockIdx.x < 128) {
            bar_sync(BAR_WG2, 128);
            if (warp == 1 && elect()) {
                bulk_s2g(g_w + blockIdx.x * 1024, sb + SM_ML, 1024);
                asm volatile("cp.async.bulk.wait_group 0;\n" ::: "memory");
                red_release(&g_sync[(SY_A + (blockIdx.x >> 5)) * 32]);
            }
            __syncwarp();
        }
        if (warp == 1) bar_arrive(BAR_GO, 160);
        done = __shfl_sync(~0u, done, 0);
        const int ep = (int)(done / NCTA) + 1;
        if (SC_TAIL) {
            bar_sync(BAR_WG2, 128);
            if (warp == 1 && elect()) red_add(&g_sync[SY_DONE * 32]);
            __syncwarp();
        }
        asm volatile("barrier.cluster.wait.acquire.aligned;\n" ::: "memory");
        if (warp == 0) {
            if (lane < 4) {
                asm volatile("st.shared.u64 [%0], %1;\n" ::"r"(s_tm), "l"(&P.tm_outc) : "memory");
                mbar_expect_tx(bar_full + 8 * lane, QB_BYTES);
            }
            if (rank == 1 || !A_MC) {
                flag_wait(&g_sync[(SY_A + (lane & 3)) * 32], 32 * ep);
                fence_async_global();
                __syncwarp();
                if (elect()) {
#pragma unroll 1
                    for (int j = 0; j < 4; j++) {
                        if (A_MC) bulk_g2s_mc(sb + SM_KV + j * KV_BYTES, g_w + j * QB_BYTES, QB_BYTES, bar_full + 8 * j, 3);
                        else bulk_g2s(sb + SM_KV + j * KV_BYTES, g_w + j * QB_BYTES, QB_BYTES, bar_full + 8 * j);
                    }
                }
            }
            __syncwarp();
            if (elect()) {
                const uint8_t* base = (const uint8_t*)H.s;
                const uint32_t pt = offsetof(Scratch, part) + (SC_PAIR ? SC_ZB(0) >> 1 : SC_QT(0)) * (2 * PART_BYTES);
                uint32_t cls = SC_CLS, bytes = KV_BYTES, moff = SC_NMC ? rank * (KV_BYTES / 2) : 0, step = 5 * KV_BYTES;
                const uint8_t *src = base, *pc = nullptr;
                int next = 0;
                const int nit = SC_NKV + SC_NW;
#pragma unroll 1
                for (int j = 0; j < nit; j++) {
                    const uint32_t slot = sb + SM_KV + (j & 3) * KV_BYTES, fb = bar_full + 8 * (j & 3);
                    if (j == next) {
                        const int k = j - SC_NKV;
                        const int sw = k < 0 ? j - SC_N0 : -1;
                        next = j + 1;
                        if (j >= 3 && (unsigned)sw >= 5) next = k >= -1 ? next : min(min(j < 25 ? 25 : j < 50 ? 50 : 75, j < GO0 ? GO0 : 75), SC_NKV - 1);
                        if (j == SC_NMC) moff = 0;
                        if (j == 0 || j == 25 || j == 50) { src = base + (4096 + (cls & 15) * KV_BYTES + moff); cls >>= 4; }
                        if (SC_TAIL ? j == nit - 1 : j == GO0) mbar_arrive(bar_go);
                        int fo = -1, fv = 1;
                        if (j < 3) { fo = (SY_H0 + 5 * j + (SC_CLS & 15)) * 32; fv = 5; }
                        if (j == 3) { fo = SY_H1 * 32; fv = 79; }
                        if (sw == 1) fo = 24 * 32 + 80 + SC_QT(1);
                        if (k == -1 && SC_PIN) fo = 24 * 32 + (SC_PAIR ? SC_ZB(0) >> 1 : SC_QT(0));
                        if (k == 0) fo = SY_B * 32;
                        if (k == 1) { fo = (SC_TAIL ? SY_AUX0 : SY_AUX) * 32; fv = SC_TAIL ? NAUX : NAUX / 3; }
                        if (fo >= 0) {
                            flag_wait(g_sync + fo, fv * ep);
                            fence_async_global();
                        }
                        if (sw == 2 || (k == 2 && !SC_TAIL)) {
                            uint32_t qs = sw == 2 ? offsetof(Scratch, q) + (2 * SC_QT(1) + 1) * QB_BYTES : SC_PAIR ? offsetof(Scratch, agg) + SC_ZB(0) * QB_BYTES : pt;
#pragma unroll 1
                            for (int w = 0; w < (k == 2 && SC_PAIR ? 1 : 2); w++) {
                                mbar_wait_sleep(bar_qfree + 8 * w, k == 2 && !SC_OWNER);
                                mbar_expect_tx(bar_q + 8 * w, QB_BYTES);
                                bulk_g2s(sb + SM_Q + w * QB_BYTES, base + qs, QB_BYTES, bar_q + 8 * w);
                                qs += sw == 2 ? -QB_BYTES : PART_BYTES + 512;
                            }
                        }
                        if ((sw | 1) == 3) {
                            mbar_wait_sleep(bar_pdone + 8 * (sw - 2), 0);
                            bulk_s2g(g_part + (2 * SC_QT(0) + sw - 2) * PART_BYTES, slot, PART_BYTES);
                            asm volatile("cp.async.bulk.wait_group.read 0;\n" ::: "memory");
                        }
                        if (sw == 5) {
                            asm volatile("cp.async.bulk.wait_group 0;\nfence.proxy.async.global;\n" ::: "memory");
                            st_release(&g_pflag[SC_QT(0)], ep);
                        }
                        if (k == 0) {
                            asm volatile("prefetch.tensormap [%0];\n" ::"l"(&P.tm_outc) : "memory");
                            if (SC_PIN) bulk_g2s(sb + SM_ML, base + (pt + QB_BYTES + (SC_PAIR ? 512 - rank * 512 : 0)), SC_PAIR ? 512 : 1024, bar_pin + 16);
                            if (SC_PIN && SC_PAIR) pc = base + (pt + (1 - rank) * (PART_BYTES + 512));
                            src = g_w + (12 - SC_NW) * QB_BYTES; bytes = step = QB_BYTES;
                        }
                        if (k == 2) next = SC_TAIL ? nit - 1 : nit;
                    }
                    mbar_wait_sleep(fb + (bar_empty - bar_full), (j >> 2) & 1);
                    if (pc && j < 75 + 4) { bulk_g2s(slot + QB_BYTES, pc, 8192, bar_pin + 24); pc += 8192; }
                    mbar_expect_tx(fb, bytes);
                    if (j < SC_NMC) bulk_g2s_mc(slot + moff, src, KV_BYTES / 2, fb, 3);
                    else bulk_g2s(slot, src, bytes, fb);
                    src += step;
                }
            }
        } else {
            if (warp == 2 && SC_OWNER) {
                uint8_t* dst = g_hz + 4096 + h_unit(SC_QT(0), 0) * 8192;
                auto send = [&](int u0, int u1) {
#pragma unroll
                    for (int u = u0; u < u1; u++) {
                        bulk_s2g(dst + u * (78 * 8192), sb + SM_Q + u * 8192, 8192);
                        asm volatile("cp.async.bulk.wait_group 0;\n" ::: "memory");
                    }
                };
                int* f0 = &g_sync[(SY_H0 + SC_QT(0) / 5) * 32];
                bar_sync(BAR_H0, 64);
                if (elect()) {
                    send(0, 1);
                    if (SC_QT(0) < 60) red_release(f0);
                }
                bar_sync(BAR_H1, 160);
                if (elect()) {
                    if (!SC_TAIL) send(1, 4);
                    mbar_arrive(bar_q);
                }
                bar_sync(BAR_H2, 160);
                if (elect()) {
                    if (!SC_TAIL) { send(4, 8); mbar_arrive(bar_q + 8); }
                    red_release(&g_sync[SY_H1 * 32]);
                }
                __syncwarp();
            }
            if (warp == 3 && SC_OWNER && SC_PAIR && elect()) {
                flag_wait_bounded(&g_sync[SY_H1 * 32], 79 * ep);
                mbar_wait_sleep(bar_pdone, 0);
                mbar_wait_sleep(bar_pdone + 8, 0);
#pragma unroll 1
                for (int u = 0; u < 16; u++) {
                    bulk_s2g(g_q + SC_QT(0) * (2 * QB_BYTES) + u * 4096, sb + SM_Q + u * 4096, 4096);
                    asm volatile("cp.async.bulk.wait_group 0;\n" ::: "memory");
                }
                fence_async_global();
                st_release(&g_qflag[SC_QT(0)], ep);
            }
            __syncwarp();
            mbar_wait_bounded(bar_go, 0);
            if (SC_TAIL) {
                if (warp == 3 && elect()) {
                    int it = 4 + SC_NKV + SC_NW;
                    asm volatile("prefetch.tensormap [%0];\n" ::"l"(&P.tm_out) : "memory");
                    if (rank) {
#pragma unroll 1
                        for (int j = 0; j < 4; j++, it++) {
                            mbar_wait_sleep(bar_empty + 8 * (it & 3), ((it >> 2) & 1) ^ 1);
                            mbar_expect_tx(bar_full + 8 * (it & 3), QB_BYTES);
                            tma_g2s(sb + SM_KV + (it & 3) * KV_BYTES, &P.tm_w[2], 8 * j, bar_full + 8 * (it & 3));
                        }
#pragma unroll 1
                        for (int k = 0; k < 8; k++) {
                            mbar_wait_sleep(bar_qfree + 8 * (k & 1), ((k >> 1) ^ (k & 1) ^ 1) & 1);
                            mbar_expect_tx(bar_q + 8 * (k & 1), QB_BYTES);
#pragma unroll 1
                            for (int hf = 0; hf < 2; hf++)
                                asm volatile("cp.async.bulk.tensor.5d.shared::cluster.global.tile.mbarrier::complete_tx::bytes [%0], [%1, {0, 0, %2, 0, 0}], [%3];\n"
                                             ::"r"(sb + SM_Q + (k & 1) * QB_BYTES + hf * 16384), "l"(&P.tm_w[k & 1]),
                                             "r"(8 * (((k >> 1) + 3) & 3) + 4 * hf), "r"(bar_q + 8 * (k & 1)) : "memory");
                        }
                        flag_wait_bounded(&g_sync[SY_B * 32], ep);
                        fence_async_global();
                    }
#pragma unroll 1
                    for (int j = 0; j < 4; j++, it++) {
                        mbar_wait_sleep(bar_empty + 8 * (it & 3), ((it >> 2) & 1) ^ 1);
                        mbar_expect_tx(bar_full + 8 * (it & 3), QB_BYTES);
                        bulk_g2s(sb + SM_KV + (it & 3) * KV_BYTES, g_w + (4 + j) * QB_BYTES, QB_BYTES, bar_full + 8 * (it & 3));
                    }
#pragma unroll 1
                    for (int k = 0; k < SC_NZ; k++) {
                        if (k == 0 || k == ((GF0 + 1) * NAUX - 16) / 128) { flag_wait_bounded(&g_sync[(k ? SY_AUX1 : SY_AUX0) * 32], NAUX * ep); fence_async_global(); }
                        mbar_wait_sleep(bar_qfree + 8 * (k & 1), ((k >> 1) ^ (k & 1) ^ 1) & 1);
                        mbar_expect_tx(bar_q + 8 * (k & 1), QB_BYTES);
                        bulk_g2s(sb + SM_Q + (k & 1) * QB_BYTES, g_agg + SC_ZB(k) * QB_BYTES, QB_BYTES, bar_q + 8 * (k & 1));
                    }
                }
            } else {
            const int par = ep & 1;
            if (blockIdx.x == 0 && t == 32) g_ovf_n[par ^ 1] = 0;
            if (blockIdx.x == 0 && warp == 1) *(uint4*)(g_hz + (lane >> 3) * 1024 + (lane & 7) * 16) = make_uint4(KV_OFF2, KV_OFF2, KV_OFF2, KV_OFF2);
            const uint32_t wlo = (uint32_t)(uintptr_t)H.s, whi = (uint32_t)((uintptr_t)H.s >> 32);
            const uint32_t blo = wlo + (uint32_t)offsetof(Scratch, bucket);
            {
                const int* pd = P.dst + blockIdx.x * 96 + (t - 32);
                const int* ps = P.src + blockIdx.x * 96 + (t - 32);
#pragma unroll 1
                for (int e = P.E - (blockIdx.x * 96 + (t - 32)); e > 0; e -= CSRU * NAUX * 32, pd += CSRU * NAUX * 32, ps += CSRU * NAUX * 32) {
                    int d[CSRU], sr[CSRU], sl[CSRU];
#pragma unroll
                    for (int i = 0; i < CSRU; i++) {
                        d[i] = e > i * NAUX * 32 ? __ldg(pd + i * NAUX * 32) : NN;
                        sr[i] = e > i * NAUX * 32 ? __ldg(ps + i * NAUX * 32) : 0;
                    }
#pragma unroll
                    for (int i = 0; i < CSRU; i++) {
                        sl[i] = 0;
                        asm volatile("{\n.reg .pred p;\nsetp.lt.s32 p, %2, %3;\n@p atom.relaxed.gpu.global.add.s32 %0, [%1], 1;\n}\n"
                                     : "+r"(sl[i]) : "l"(mkaddr(wlo + (uint32_t)offsetof(Scratch, cnt) + d[i] * 4, whi)), "r"(d[i]), "n"(NN) : "memory");
                    }
                    uint32_t ov = 0;
#pragma unroll
                    for (int i = 0; i < CSRU; i++) {
                        asm volatile("{\n.reg .pred p;\nsetp.lt.s32 p, %3, %4;\n@p st.global.s32 [%1], %2;\n@!p or.b32 %0, %0, %5;\n}\n"
                                     : "+r"(ov) : "l"(mkaddr(blo + (d[i] * CAP + sl[i]) * 4, whi)), "r"(sr[i]), "r"(sl[i]), "n"(CAP), "r"(1 << i) : "memory");
                    }
#pragma unroll 1
                    for (; ov; ov &= ov - 1) {
                        const int i = (__ffs(ov) - 1) * (NAUX * 32);
                        int at;
                        asm volatile("atom.relaxed.gpu.global.add.s32 %0, [%1], 1;\n" : "=r"(at) : "l"(&g_ovf_n[par]) : "memory");
                        g_ovf[at] = make_int2(__ldg(pd + i), __ldg(ps + i));
                    }
                }
            }
            bar_sync(BAR_AUX, 96);
            if (warp == 1 && elect()) { red_release(&g_sync[SY_CSR * 32]); }
            __syncwarp();
            {
                const int r0 = blockIdx.x * 3 + warp - 1;
                const uint4* xp = (const uint4*)(H.x + r0 * 256) + lane;
                uint4* op = (uint4*)(P.out + r0 * 256) + lane;
#pragma unroll 1
                for (int r = r0; r < NN; r += CPYU * NAUX, xp += CPYU * NAUX * 32, op += CPYU * NAUX * 32) {
                    uint4 v[CPYU];
#pragma unroll
                    for (int i = 0; i < CPYU; i++) if (r + i * NAUX < NN) v[i] = ldg_pinned(xp + i * NAUX * 32);
#pragma unroll
                    for (int i = 0; i < CPYU; i++) if (r + i * NAUX < NN) op[i * NAUX * 32] = v[i];
                }
            }
            flag_wait_bounded(&g_sync[SY_CSR * 32], NAUX / 3 * ep);
            {
                const uint32_t lc = (lane >> 3) * 1024 + (lane & 7) * 16;
                const uint32_t alo = wlo ^ lc;
                const int node0 = blockIdx.x * 3 + warp - 17;
                auto node = [&](int i) { const int nd = node0 + i * NAUX; return (int)min((unsigned)nd, (unsigned)(nd + NN)); };
                const int num = (NN - 17 - node0) / NAUX + 1;
                uint32_t mine = 0;
                if (lane < num) {
                    mine = min(__ldcg(&g_cnt[node(lane)]), CAP + 1) | (uint32_t)__ldg((const unsigned short*)P.deg_inv + node(lane)) << 16;
                    g_cnt[node(lane)] = 0;
                }
                auto row = [&](int off) {
                    uint4 v;
                    asm volatile("ld.global.v4.u32 {%0, %1, %2, %3}, [%4];\n"
                                 : "=r"(v.x), "=r"(v.y), "=r"(v.z), "=r"(v.w) : "l"(mkaddr(alo ^ off, whi)));
                    return v;
                };
                auto ents = [&](int i) {
                    int e;
                    asm volatile("ld.global.cg.s32 %0, [%1];\n" : "=r"(e) : "l"(mkaddr(blo + (min(node(i), NN - 1) * CAP + lane) * 4, whi)));
                    return e;
                };
                auto store = [&](int i, const float (&a)[8]) {
                    const float di = bf_hi(__shfl_sync(~0u, mine, i)) * (1.f / KV_SCALE);
                    const int nd = node(i);
                    *(uint4*)(g_agg + (uint32_t)(((nd >> 3) * 4096 + (nd & 7) * 144) ^ lc)) =
                        make_uint4(pack_bf16(a[0] * di, a[1] * di), pack_bf16(a[2] * di, a[3] * di), pack_bf16(a[4] * di, a[5] * di), pack_bf16(a[6] * di, a[7] * di));
                };
#pragma unroll 1
                for (uint32_t big = __ballot_sync(~0u, (mine & 0xFFFF) > CAP); big; big &= big - 1) {
                    const int i = __ffs(big) - 1, no = __ldcg(&g_ovf_n[par]);
                    float a[8] = {};
#pragma unroll 1
                    for (int k = -32; k < no; k += 32) {
                        const int2 pr = k < 0 ? make_int2(node(i), ents(i)) : k + lane < no ? __ldcg(&g_ovf[k + lane]) : make_int2(-1, 0);
#pragma unroll 1
                        for (uint32_t mk = __ballot_sync(~0u, pr.x == node(i)); mk; mk &= mk - 1) {
                            const uint4 v = row(row_off(__shfl_sync(~0u, pr.y, __ffs(mk) - 1)));
                            a[0] += f16_lo(v.x) - KV_OFF; a[1] += f16_hi(v.x) - KV_OFF; a[2] += f16_lo(v.y) - KV_OFF; a[3] += f16_hi(v.y) - KV_OFF;
                            a[4] += f16_lo(v.z) - KV_OFF; a[5] += f16_hi(v.z) - KV_OFF; a[6] += f16_lo(v.w) - KV_OFF; a[7] += f16_hi(v.w) - KV_OFF;
                        }
                    }
                    store(i, a);
                }
                auto add4 = [&](const uint4& a, const uint4& b) { return make_uint4(hadd2_f16(a.x, b.x), hadd2_f16(a.y, b.y), hadd2_f16(a.z, b.z), hadd2_f16(a.w, b.w)); };
                int ni = -1, left = 0, pos = 0, ec = 0, en = ents(0);
                uint4 acc = make_uint4(0, 0, 0, 0);
                auto issue = [&](uint4 (&v)[4]) {
                    if (left <= 0) {
                        ni++;
                        left = __shfl_sync(~0u, mine, ni) & 0xFFFF;
                        if (left > CAP) left = 0;
                        ec = lane < left ? row_off(en) : 0;
                        en = ents(ni + 1);
                        pos = 0;
                    }
#pragma unroll
                    for (int j = 0; j < 4; j++) v[j] = row(__shfl_sync(~0u, ec, pos + j));
                    pos += 4; left -= 4;
                    return left <= 0 ? ni : -1;
                };
                auto step = [&](uint4 (&v)[4], int& tag) {
                    acc = add4(acc, add4(add4(add4(v[0], v[1]), make_uint4(KV_NEG4, KV_NEG4, KV_NEG4, KV_NEG4)), add4(v[2], v[3])));
                    const int i = tag;
                    tag = issue(v);
                    if (i >= 0) {
                        const float a[8] = {f16_lo(acc.x), f16_hi(acc.x), f16_lo(acc.y), f16_hi(acc.y), f16_lo(acc.z), f16_hi(acc.z), f16_lo(acc.w), f16_hi(acc.w)};
                        if ((__shfl_sync(~0u, mine, i) & 0xFFFF) <= CAP) store(i, a);
                        acc = make_uint4(0, 0, 0, 0);
                        if (i == GF0 || i == 8) {
                            __syncwarp();
                            if (elect()) red_release(&g_sync[(i == 8 ? SY_AUX1 : SY_AUX0) * 32]);
                            __syncwarp();
                        }
                    }
                    return i == num - 1;
                };
                uint4 va[4], vb[4];
#pragma unroll
                for (int j = 0; j < 4; j++) va[j] = vb[j] = make_uint4(KV_OFF2, KV_OFF2, KV_OFF2, KV_OFF2);
                int ta = -1, tb = -1;
#pragma unroll 1
                while (!step(va, ta) && !step(vb, tb)) {}
            }
            bar_sync(BAR_AUX, 96);
            if (warp == 1 && elect()) {
                red_release(&g_sync[SY_AUX * 32]);
                red_add(&g_sync[SY_DONE * 32]);
            }
            }
        }
        __syncwarp();
        asm volatile("barrier.cluster.arrive.relaxed.aligned;\n" ::: "memory");
        if (warp == 1) mbar_wait_bounded(bar_end, 0);
        else if (elect()) mbar_arrive(bar_end);
        __syncwarp();
        asm volatile("barrier.cluster.wait.acquire.aligned;\n" ::: "memory");
    } else {
        const int t = tid & 127, warp = __shfl_sync(~0u, t >> 5, 0);
        const uint32_t sq = sb + SM_Q + wg * QB_BYTES;
        const uint32_t qbar = bar_q + 8 * wg;
        const uint32_t dq0 = __shfl_sync(~0u, ((sq & 0x3FFFF) >> 4) | (64u << 16), 0);
        const uint32_t dk0 = __shfl_sync(~0u, (((sb + SM_KV) & 0x3FFFF) >> 4) | (64u << 16), 0);
        float o[128];
        int it = 4;
        const uint32_t dhi = P.dhi;
        uint32_t rel_addr;
        auto rel_target = [&](uint32_t r) {
            asm("mapa.shared::cluster.u32 %0, %1, %2;\n" : "=r"(rel_addr) : "r"(bar_empty), "r"(r));
            if (lane >= 2) rel_addr = 0;
            asm volatile("" : "+r"(rel_addr));
        };
        rel_target(SC_NMC ? rank ^ (lane & 1) : rank);
        auto release = [&](int st) {
            asm volatile("{\n.reg .pred p;\nsetp.ne.u32 p, %1, 0;\n@p mbarrier.arrive.shared::cluster.b64 _, [%0];\n}\n"
                         ::"r"(rel_addr + 8 * st), "r"(rel_addr) : "memory");
        };
        const bool active = !(SC_TAIL && wg == 1);
        const int nn = __shfl_sync(~0u, (SC_N0 + 3) | (SC_NKV + 3) << 8 | (SC_NKV != SC_N0 ? 2 : 1) << 16 | SC_NMC << 24, 0);
        auto pp_sync = [&]() { if (!SC_TAIL) bar_sync(BAR_PP0 + wg, 256); };
        auto pp_arrive = [&]() { if (!SC_TAIL) bar_arrive(BAR_PP1 - wg, 256); };
        auto warp_arrive = [&](uint32_t bar) {
            __syncwarp();
            asm volatile("{\n.reg .pred p;\nelect.sync _|p, -1;\n@p mbarrier.arrive.shared::cta.b64 _, [%0];\n}\n" ::"r"(bar + 8 * wg) : "memory");
        };
        auto peer_arrive = [&]() {
            asm volatile("{\n.reg .pred p;\n.reg .b32 a;\nelect.sync _|p, -1;\nmapa.shared::cluster.u32 a, %0, %1;\n"
                         "@p mbarrier.arrive.shared::cluster.b64 _, [a];\n}\n" ::"r"(bar_rfree), "r"(rank ^ 1) : "memory");
        };
        auto stage_q = [&]() {
            auto pk = [&](int i) { return QRND(pack_f16_sat(o[i], o[i + 1])); };
#pragma unroll
            for (int i = 0; i < 16; i++)
                stmatrix_x4(sq + warp * 8192 + tile_off(lane & 15, 2 * i + (lane >> 4)), pk(8 * i), pk(8 * i + 2), pk(8 * i + 4), pk(8 * i + 6));
        };
        float s[40];
        auto issue_qk = [&](int st) {
            const uint64_t kb = mkaddr(dk0 + st * (KV_BYTES >> 4), dhi);
            const uint64_t qd = mkaddr(dq0 + ((uint32_t)it >> 24), dhi);
            wgmma_ss_n80_init(s, qd + 198, kb + 198);
#pragma unroll
            for (int kk = 0; kk < 15; kk++) wgmma_ss_n80(s, qd + ((kk >> 2) * 64 + (kk & 3) * 2), kb + ((kk >> 2) * 64 + (kk & 3) * 2));
            wg_commit();
        };

        {
            const int rb = (2 * SC_QT(0) + wg) * 64 + warp * 16;
            const uint32_t xbar = bar_x + 32 * wg + 8 * warp;
            if (elect()) {
                mbar_init(xbar, 1);
                asm volatile("fence.mbarrier_init.release.cluster;\nfence.proxy.async.shared::cta;\n" ::: "memory");
                mbar_expect_tx(xbar, rb < NN ? 8192 : 0);
            }
            asm volatile("barrier.cluster.arrive.relaxed.aligned;\n" ::: "memory");
            if (wg == 1) pp_arrive();
            bar_sync(BAR_X, 384);
            if (wg == 1) bar_sync(BAR_GO, 160);
            if (rb < NN && elect()) bulk_g2s(sq + warp * 8192, H.x + (size_t)rb * 256, 8192, xbar);
            if (rb >= NN) {
#pragma unroll 1
                for (int i = 0; i < 16; i++) sts128(sq + warp * 8192 + i * 512 + lane * 16, 0, 0, 0, 0);
            }
            __syncwarp();
            mbar_wait(xbar, 0);
            uint4 xa[8], xb[8];
#pragma unroll
            for (int s = 0; s < 8; s++) {
                xa[s] = lds128(sq + (warp * 16 + g) * 512 + (4 * s + q) * 16);
                xb[s] = lds128(sq + (warp * 16 + g + 8) * 512 + (4 * s + q) * 16);
            }
            float sm[2][4], sq2[2][4][4];
#pragma unroll
            for (int i = 0; i < 4; i++) {
                sm[0][i] = sm[1][i] = 0.f;
#pragma unroll
                for (int k = 0; k < 4; k++) sq2[0][k][i] = sq2[1][k][i] = 0.f;
            }
#pragma unroll
            for (int s = 0; s < 8; s++) {
#pragma unroll
                for (int hh = 0; hh < 2; hh++) {
                    const uint4 v = hh ? xb[s] : xa[s];
                    mma16816(sm[hh], v.x, v.y, v.z, v.w, 0x3F803F80u, 0x3F803F80u);
                    mma1688(sq2[hh][0], v.x, v.y, v.x); mma1688(sq2[hh][1], v.x, v.y, v.y);
                    mma1688(sq2[hh][2], v.z, v.w, v.z); mma1688(sq2[hh][3], v.z, v.w, v.w);
                }
            }
            float inv[2], off[2];
#pragma unroll
            for (int hh = 0; hh < 2; hh++) {
                const float mean = (sm[hh][0] + sm[hh][2]) * (1.f / 256.f);
                const float d0 = (sq2[hh][0][0] + sq2[hh][2][0]) + (sq2[hh][1][2] + sq2[hh][3][2]);
                const float d1 = (sq2[hh][0][1] + sq2[hh][2][1]) + (sq2[hh][1][3] + sq2[hh][3][3]);
                const float ss = __shfl_sync(~0u, (g & 1) ? d1 : d0, g * 4 + (g >> 1));
                const float var = fmaxf(ss * (1.f / 256.f) - mean * mean, 0.f);
                float sd;
                asm("sqrt.approx.ftz.f32 %0, %1;\n" : "=f"(sd) : "f"(bf_round(bf_round(var) + 1e-5f)));
                asm("rcp.approx.ftz.f32 %0, %1;\n" : "=f"(inv[hh]) : "f"(bf_round(sd)));
                off[hh] = -mean * inv[hh];
            }
            uint32_t a[64];
#pragma unroll
            for (int s = 0; s < 8; s++) {
                a[8 * s] = xa[s].x; a[8 * s + 1] = xb[s].x; a[8 * s + 2] = xa[s].y; a[8 * s + 3] = xb[s].y;
                a[8 * s + 4] = xa[s].z; a[8 * s + 5] = xb[s].z; a[8 * s + 6] = xa[s].w; a[8 * s + 7] = xb[s].w;
            }
            fence_regs(a);
            if (wg == 1 && __any_sync(~0u, inv[0] + inv[1] != -1.f)) bar_arrive(BAR_ST, 256);
            asm volatile("setmaxnreg.inc.sync.aligned.u32 %0;\n" ::"n"(REG_C));
            fence_regs(a);
#pragma unroll
            for (int i = 0; i < 64; i++)
                a[i] = pack_f16(fmaf(bf_lo(a[i]), inv[i & 1], off[i & 1]), fmaf(bf_hi(a[i]), inv[i & 1], off[i & 1]));
            if (SC_OWNER) {
#pragma unroll
                for (int i = 0; i < 16; i++) {
                    const uint32_t mk = (i == 15 && q == 3) ? 0xFFFFu : ~0u;
                    stmatrix_x4(sq + warp * 8192 + tile_off(lane & 15, 2 * i + (lane >> 4)), kvf(a[4 * i]), kvf(a[4 * i + 1]),
                                kvf(a[4 * i + 2] & mk), kvf(a[4 * i + 3] & mk));
                }
                fence_async_smem();
                if (tid < 32) bar_arrive(BAR_H0, 64);
                bar_arrive(wg ? BAR_H2 : BAR_H1, 160);
            }
            asm volatile("barrier.cluster.wait.acquire.aligned;\n" ::: "memory");
            if (wg == 0) bar_sync(BAR_ST, 256);
            if (active) {
                fence_regs(a);
#pragma unroll
                for (int c = 0; c < 4; c++) {
                    if (c == 1) {
                        if (wg == 1) {
                            wg_wait<0>();
                            release(0);
                        }
                        pp_sync();
                    }
                    mbar_wait(bar_full + 8 * c, 0);
                    const uint64_t wb = mkaddr(dk0 + c * (KV_BYTES >> 4), dhi);
                    wg_fence();
#pragma unroll
                    for (int kk = 0; kk < 4; kk++) {
                        if (c | kk) wgmma_rs_n256_tb(o, a[16 * c + 4 * kk], a[16 * c + 4 * kk + 1], a[16 * c + 4 * kk + 2], a[16 * c + 4 * kk + 3], wb + kk * 512);
                        else wgmma_rs_n256_tb_init(o, a[0], a[1], a[2], a[3], wb);
                    }
                    wg_commit();
                    if (c > 0) { wg_wait<1>(); if (c > 1 || wg == 0) release(c - 1); }
                }
                if (wg == 0) pp_arrive();
                wg_wait<0>();
                fence_regs(o);
                release(3);
                if (SC_OWNER) mbar_wait(qbar, 0);
                stage_q();
                fence_async_smem();
                bar_sync(BAR_WG0 + wg, 128);
                mbar_wait(bar_full, 1);
                wg_fence();
                issue_qk(0);
                if (wg == 1) pp_arrive();
            } else {
                peer_arrive();
            }
        }

        uint32_t p[20];
        float m0 = 0.f, m1 = 0.f, e0, e1, l0, l1;
        uint32_t plim;
        uint32_t qphase = (SC_OWNER && active) ? 1 : 0;
        auto issue_pv = [&](int st, int acc) {
            const uint64_t vb = mkaddr(dk0 + st * (KV_BYTES >> 4), dhi);
            wgmma_rs_n256_tb_pred(o, p[0], p[1], p[2], p[3], vb, acc);
#pragma unroll
            for (int kk = 1; kk < 5; kk++)
                wgmma_rs_n256_tb(o, p[4 * kk], p[4 * kk + 1], p[4 * kk + 2], p[4 * kk + 3], vb + kk * 512);
            wg_commit();
        };
        const uint32_t mq_addr = sq + tile_off(warp * 16 + g, 31) + 14;
        auto exceeds = [&](const uint32_t (&p)[20]) {
            uint32_t a = __vimax3_s16x2(P_LIMIT, p[0], p[1]), b = __vimax3_s16x2(p[2], p[3], p[4]);
#pragma unroll
            for (int i = 5; i < 17; i += 4) { a = __vimax3_s16x2(a, p[i], p[i + 1]); b = __vimax3_s16x2(b, p[i + 2], p[i + 3]); }
            a = __vimax3_s16x2(a, p[17], p[18]);
            return __any_sync(~0u, __vimax3_s16x2(a, b, p[19]) != plim);
        };
        auto remax = [&](float& a, float& b, bool store) {
            float a1 = fmaxf(s[0], s[1]), b1 = fmaxf(s[2], s[3]), a2 = fmaxf(s[4], s[5]), b2 = fmaxf(s[6], s[7]);
#pragma unroll
            for (int i = 2; i < 10; i++) {
                a1 = fmaxf(a1, s[4 * i]); a2 = fmaxf(a2, s[4 * i + 1]);
                b1 = fmaxf(b1, s[4 * i + 2]); b2 = fmaxf(b2, s[4 * i + 3]);
            }
            a1 = fmaxf(a1, a2); b1 = fmaxf(b1, b2);
            a1 = fmaxf(a1, __shfl_xor_sync(~0u, a1, 1)); b1 = fmaxf(b1, __shfl_xor_sync(~0u, b1, 1));
            a1 = fmaxf(a1, __shfl_xor_sync(~0u, a1, 2)); b1 = fmaxf(b1, __shfl_xor_sync(~0u, b1, 2));
            a = fmaxf(a, a1 - e0 + REF_UP); b = fmaxf(b, b1 - e1 + REF_UP);
            const uint32_t u = pack_f16_sat((m0 + a) * (-1.f / KV_OFF), (m1 + b) * (-1.f / KV_OFF));
            const float g0 = (m0 + a) + KV_OFF * f16_lo(u), g1 = (m1 + b) + KV_OFF * f16_hi(u);
            const bool x0 = fabsf(g0) <= 1.f, x1 = fabsf(g1) <= 1.f;
            if (x0) a -= g0;
            if (x1) b -= g1;
            const float da = a + e0, db = b + e1;
            m0 += a; m1 += b;
            e0 = x0 ? 0.f : g0; e1 = x1 ? 0.f : g1;
            plim = (x0 && x1) ? P_LIMIT : 0u;
            asm volatile("{\n.reg .pred p;\nsetp.ne.s32 p, %3, 0;\n@p st.shared.u16 [%0], %1;\n@p st.shared.u16 [%0 + 4096], %2;\n}\n"
                         ::"r"(mq_addr), "h"((unsigned short)u), "h"((unsigned short)(u >> 16)), "r"((int)(store && q == 0)) : "memory");
#pragma unroll
            for (int i = 0; i < 10; i++) {
                p[2 * i] = pack_f16(ex2(s[4 * i] - da), ex2(s[4 * i + 1] - da));
                p[2 * i + 1] = pack_f16(ex2(s[4 * i + 2] - db), ex2(s[4 * i + 3] - db));
            }
            fence_regs(p);
            fence_async_smem();
            __syncwarp();
        };

        auto row_sums = [&](float& z0, float& z1) {
            z0 = quad_last(o[125]); z1 = quad_last(o[127]);
            l0 = z0 * (KV_SCALE / KV_OFF); l1 = z1 * (KV_SCALE / KV_OFF);
        };
        auto cut = [&]() { asm volatile("{\n.reg .pred p;\nsetp.lt.s32 p, %0, 0;\nL:\n@p pmevent 0;\n@p bra L;\n}\n" ::"r"(it) : "memory"); };
        auto stats = [&]() { return (q & 2) ? ((q & 1) ? l1 : m1) : ((q & 1) ? l0 : m0); };
        const int nseg = (nn >> 16) & 255;
        if (active) {
#pragma unroll 1
        for (int seg = 0;; seg++) {
            wg_wait<0>();
            fence_regs(s);
            e0 = e1 = 0.f;
            const int it0 = it, itl = __shfl_sync(~0u, (nn >> (8 * seg)) & 255, 0);
            const int itx = (wg == 1 && seg + 1 == nseg) ? itl : -1;
            bool redo = true, have = !seg;
#pragma unroll 1
            for (;;) {
                if (!have) {
#pragma unroll
                    for (int i = 0; i < 20; i++) p[i] = pack_f16(ex2(s[2 * i]), ex2(s[2 * i + 1]));
                    redo = exceeds(p);
                }
                if (redo) {
                    float d0 = it != it0 ? 0.f : -INFINITY, d1 = d0;
                    remax(d0, d1, it != itl);
                    if (it != it0) {
                        const float a0 = ex2(-d0), a1 = ex2(-d1);
#pragma unroll
                        for (int i = 0; i < 32; i++) { o[4 * i] *= a0; o[4 * i + 1] *= a0; o[4 * i + 2] *= a1; o[4 * i + 3] *= a1; }
                    }
                }
                if (it == it0 && (seg || SC_OWNER)) {
                    fence_async_smem();
                    warp_arrive(bar_pdone);
                }
                if (it == itl) break;
                const int stp = it & 3;
                it++;
                mbar_wait(bar_full + 8 * (it & 3), (it >> 2) & 1);
                pp_sync();
                fence_regs(o); fence_regs(p);
                wg_fence();
                issue_qk(it & 3);
                if (it == itx) {
                    wg_wait<0>();
                    if (SC_PAIR) peer_arrive(); else warp_arrive(bar_qfree);
                    bar_sync(BAR_ST, 256);
                }
                wg_fence();
                issue_pv(stp, it - 1 - it0);
                pp_arrive();
                if (it == itl && itx < 0) {
                    wg_wait<1>();
                    warp_arrive(bar_qfree);
                }
                have = SC_TAIL || it == itx;
                if (have) {
                    uint32_t p2[20];
                    wg_wait<1>();
                    fence_regs(s);
#pragma unroll
                    for (int i = 0; i < 20; i++) p2[i] = pack_f16(ex2(s[2 * i]), ex2(s[2 * i + 1]));
                    redo = exceeds(p2);
                    if (redo) asm volatile("wgmma.wait_group.sync.aligned 0;\nnanosleep.u32 0;\n" ::: "memory");
                    else wg_wait<0>();
                    fence_regs(o); fence_regs(p);
#pragma unroll
                    for (int i = 0; i < 20; i++) p[i] = p2[i];
                } else {
                    wg_wait<0>();
                    fence_regs(s); fence_regs(o); fence_regs(p);
                }
                release(stp);
                if (it == (nn >> 24)) rel_target(rank);
            }
            if (seg + 1 < nseg) pp_sync();
            fence_regs(o); fence_regs(p);
            wg_fence();
            issue_pv(it & 3, 1);
            asm volatile("{\n.reg .pred p;\nsetp.ne.s32 p, %0, 0;\n@p bar.arrive %1, 256;\n}\n" ::"r"((int)(seg + 1 == nseg && (wg ? SC_PAIR && ZHOLD : !SC_TAIL))), "r"(BAR_ST + wg) : "memory");
            it++;
            if (seg + 1 == nseg) break;
            const int is = it - 2 + wg;
            uint32_t dst = sb + SM_KV + (is & 3) * KV_BYTES + wg * 512 + warp * 8192 + lane * 16;
            uint32_t dml = sb + SM_KV + (is & 3) * KV_BYTES + (wg ? 0 : QB_BYTES) + t * 4;
            asm volatile("" : "+r"(dst), "+r"(dml));
            mbar_wait(qbar, qphase); qphase ^= 1;
            unsigned short u0, u1;
            asm volatile("ld.shared.u16 %0, [%2];\nld.shared.u16 %1, [%2 + 4096];\n" : "=h"(u0), "=h"(u1) : "r"(mq_addr) : "memory");
            mbar_wait(bar_full + 8 * (it & 3), (it >> 2) & 1);
            wg_wait<0>();
            fence_regs(o);
            float z0, z1;
            row_sums(z0, z1);
            release((it - 1) & 3);
            wg_fence();
            issue_qk(it & 3);
            pp_arrive();
#pragma unroll
            for (int i = 0; i < 128; i++) o[i] -= (i & 2) ? z1 : z0;
            fence_regs(o);
            mbar_wait(bar_empty + 8 * (is & 3), (is >> 2) & 1);
            asm volatile("st.shared.f32 [%0], %1;\n" ::"r"(dml), "f"(stats()) : "memory");
            m0 = -KV_OFF * f16_lo(u0); m1 = -KV_OFF * f16_lo(u1);
            plim = fmaxf(fabsf(m0), fabsf(m1)) <= 3072.f ? P_LIMIT : 0u;
            uint32_t v[2][8] = {};
#pragma unroll
            for (int i = 0; i < 8; i++) {
                uint32_t *w = v[i & 1], *u = v[(i & 1) ^ 1];
#pragma unroll
                for (int j = 0; j < 8; j++) w[j] = pack_bf16(o[16 * i + 2 * j], o[16 * i + 2 * j + 1]);
                sts128(dst + i * 1024, w[0], w[1], w[2], w[3]);
                sts128(dst + i * 1024 + 512, w[4], w[5], w[6], w[7]);
                if (i) asm volatile("{\n.reg .pred p;\nsetp.lt.s32 p, %9, 0;\nL:\n@p st.shared.v4.u32 [%0], {%1, %2, %3, %4};\n@p st.shared.v4.u32 [%0 + 16], {%5, %6, %7, %8};\n@p bra L;\n}\n"
                             ::"r"(dst), "r"(u[0]), "r"(u[1]), "r"(u[2]), "r"(u[3]), "r"(u[4]), "r"(u[5]), "r"(u[6]), "r"(u[7]), "r"(it) : "memory");
            }
        }
        constexpr int IW = 4 + 75;
        uint32_t a[64];
        if (wg == 0 && (SC_PAIR || !SC_OWNER)) {
            uint32_t rq, rml, rbar;
            asm volatile("mapa.shared::cluster.u32 %0, %3, %6;\nmapa.shared::cluster.u32 %1, %4, %6;\nmapa.shared::cluster.u32 %2, %5, %6;\n"
                         : "=r"(rq), "=r"(rml), "=r"(rbar) : "r"(sb + SM_Q + QB_BYTES + warp * 8192 + lane * 16), "r"(sb + SM_ML + 512 + t * 4),
                         "r"(bar_pin), "r"(rank ^ 1));
            auto send = [&](int i) {
                asm volatile("st.async.weak.shared::cluster.mbarrier::complete_tx::bytes.v4.b32 [%0], {%1, %2, %3, %4}, [%5];\n"
                             ::"r"(rq + i * 512), "r"(a[4 * i]), "r"(a[4 * i + 1]), "r"(a[4 * i + 2]), "r"(a[4 * i + 3]), "r"(rbar + (i & 8)) : "memory");
            };
            mbar_wait(bar_rfree, 0);
            wg_wait<0>();
            fence_regs(o);
            release((it - 1) & 3);
            float z0, z1;
            row_sums(z0, z1);
            asm volatile("st.async.weak.shared::cluster.mbarrier::complete_tx::bytes.f32 [%0], %1, [%2];\n" ::"r"(rml), "f"(stats()), "r"(rbar) : "memory");
#pragma unroll
            for (int i = 0; i < 16; i++) {
                a[4 * i] = pack_bf16(o[8 * i] - z0, o[8 * i + 1] - z0); a[4 * i + 1] = pack_bf16(o[8 * i + 2] - z1, o[8 * i + 3] - z1);
                a[4 * i + 2] = pack_bf16(o[8 * i + 4] - z0, o[8 * i + 5] - z0); a[4 * i + 3] = pack_bf16(o[8 * i + 6] - z1, o[8 * i + 7] - z1);
                if (i * SND0 / 16 != (i + 1) * SND0 / 16) send(i * SND0 / 16);
                if (i % CUT2 == CUT2 - 1) cut();
            }
            if (SC_PAIR) {
                float z[128];
                const uint32_t dkz = dk0 + ((uint32_t)it >> 24), dqz = dq0 + ((uint32_t)it >> 24);
                auto gemm = [&](int c) {
                    mbar_wait(bar_full + 8 * ((IW + c) & 3), ((IW + c) >> 2) & 1);
                    const uint64_t wb = mkaddr(dkz + ((IW + c) & 3) * (KV_BYTES >> 4), dhi), ab = mkaddr(dqz + c * 64, dhi);
                    wg_fence();
#pragma unroll
                    for (int kk = 0; kk < 4; kk++) {
                        if (c | kk) wgmma_ss_n256_tb(z, ab + kk * 2, wb + kk * 512);
                        else wgmma_ss_n256_tb_init(z, ab, wb);
                    }
                    wg_commit();
                };
                auto release2 = [&](int c) {
                    asm volatile("{\n.reg .pred p;\nsetp.ne.u32 p, %1, 0;\n@p mbarrier.arrive.shared::cluster.b64 _, [%0], 2;\n}\n"
                                 ::"r"(rel_addr + 8 * ((IW + c) & 3)), "r"(rel_addr) : "memory");
                };
                mbar_wait(qbar, qphase);
                if (ZHOLD) bar_sync(BAR_ST + 1, 256);
                gemm(0);
#pragma unroll
                for (int i = SND0; i < 16; i++) send(i);
#pragma unroll
                for (int c = 1; c < 4; c++) { gemm(c); if (c == 3) pp_arrive(); wg_wait<1>(); release2(c - 1); }
                wg_wait<0>();
                fence_regs(z);
                release2(3);
#pragma unroll
                for (int i = 0; i < 16; i++) {
                    sts128(sq + warp * 8192 + lane * 16 + i * 512, pack_bf16(z[8 * i], z[8 * i + 1]), pack_bf16(z[8 * i + 2], z[8 * i + 3]),
                           pack_bf16(z[8 * i + 4], z[8 * i + 5]), pack_bf16(z[8 * i + 6], z[8 * i + 7]));
                    if (i == 3 || i == 15) bar_arrive(i == 3 ? BAR_BF : BAR_H0, 256);
                }
            } else {
#pragma unroll
                for (int i = SND0; i < 16; i++) send(i);
            }
        } else {
            const int pair = SC_PAIR;
            const bool two = pair && SC_PIN, glob = !(pair || SC_TAIL);
            const uint32_t ml = sb + SM_ML + (t & ~3) * 4, src = (glob ? sq : sb + SM_Q + QB_BYTES) + warp * 8192 + lane * 16;
            const uint64_t tm = lds64(s_tm);
            if (SC_PIN) mbar_wait(bar_pin + 16, 0);
            float4 qs = lds128f(ml);
            if (!two) qs = make_float4(-INFINITY, 0.f, -INFINITY, 0.f);
            wg_wait<0>();
            fence_regs(o);
            release((IW - 1) & 3);
            float c0, c1;
            row_sums(c0, c1);
            mbar_wait(glob ? qbar : bar_pin, glob ? qphase : 0);
            const float4 ps = lds128f(ml + (glob ? wg * 512 : 512));
            auto load = [&](int i) {
                asm volatile("ld.shared.v4.u32 {%0, %1, %2, %3}, [%4];\n" : "=r"(a[4 * i]), "=r"(a[4 * i + 1]), "=r"(a[4 * i + 2]), "=r"(a[4 * i + 3]) : "r"(src + i * 512) : "memory");
            };
#pragma unroll
            for (int i = 0; i < 8; i++) load(i);
            const float n0 = fmaxf(fmaxf(m0, ps.x), qs.x), n1 = fmaxf(fmaxf(m1, ps.z), qs.z);
            const float a0 = ex2(m0 - n0), a1 = ex2(m1 - n1), b0 = ex2(ps.x - n0), b1 = ex2(ps.z - n1), d0 = ex2(qs.x - n0), d1 = ex2(qs.z - n1);
            const float i0 = rcp(l0 * a0 + ps.y * b0 + qs.y * d0), i1 = rcp(l1 * a1 + ps.w * b1 + qs.w * d1);
            const float r0 = a0 * i0, r1 = a1 * i1;
            c0 *= -r0; c1 *= -r1;
            const uint32_t u0 = pack_bf16(b0 * i0, b0 * i0), u1 = pack_bf16(b1 * i1, b1 * i1);
#pragma unroll
            for (int i = 0; i < 32; i++) {
                if (i == 16) {
                    if (!glob) mbar_wait(bar_pin + 8, 0);
#pragma unroll
                    for (int j = 8; j < 16; j++) load(j);
                }
                a[2 * i] = hfma2(a[2 * i], u0, pack_bf16(fmaf(o[4 * i], r0, c0), fmaf(o[4 * i + 1], r0, c0)));
                a[2 * i + 1] = hfma2(a[2 * i + 1], u1, pack_bf16(fmaf(o[4 * i + 2], r1, c1), fmaf(o[4 * i + 3], r1, c1)));
            }
            if (two) {
                const uint32_t w0 = pack_bf16(d0 * i0, d0 * i0), w1 = pack_bf16(d1 * i1, d1 * i1);
                mbar_wait(bar_pin + 24, 0);
                uint4 e[16];
#pragma unroll
                for (int i = 0; i < 16; i++) e[i] = lds128(sb + SM_KV + QB_BYTES + ((IW + warp) & 3) * KV_BYTES + lane * 16 + i * 512);
#pragma unroll
                for (int i = 0; i < 16; i++) {
                    a[4 * i] = hfma2(e[i].x, w0, a[4 * i]);         a[4 * i + 1] = hfma2(e[i].y, w1, a[4 * i + 1]);
                    a[4 * i + 2] = hfma2(e[i].z, w0, a[4 * i + 2]); a[4 * i + 3] = hfma2(e[i].w, w1, a[4 * i + 3]);
                }
            }
            float y[2][32];
            auto gemm = [&](int c, int kh) {
                if (!kh) mbar_wait(bar_full + 8 * ((IW + c) & 3), (((IW + c) >> 2) & 1) ^ pair);
                const uint64_t wb = mkaddr(dk0 + ((IW + c) & 3) * (KV_BYTES >> 4), dhi - 192);
                wg_fence();
#pragma unroll
                for (int kk = 8 * kh; kk < 8 * kh + 8; kk++) {
                    if (kk) wgmma_rs_n64_tb(y[c & 1], a[4 * kk], a[4 * kk + 1], a[4 * kk + 2], a[4 * kk + 3], wb + kk * 128);
                    else wgmma_rs_n64_tb_init(y[c & 1], a[0], a[1], a[2], a[3], wb);
                }
                wg_commit();
            };
            const int rg = (pair ? SC_ZB(0) : 2 * SC_QT(0) + wg) * 8 + warp * 2;
            const uint32_t zsrc = sb + SM_Q + warp * 8192 + lane * 16, stg = sq + warp * 8192 + (lane & 15) * 128 + (((lane >> 4) ^ lane) & 7) * 16;
            uint4 z[4] = {};
            auto load_z = [&](int cb) {
#pragma unroll
                for (int i = 0; i < 4; i++) {
                    asm volatile("{\n.reg .pred p;\nsetp.ne.u32 p, %4, 0;\n@p ld.shared.v4.u32 {%0, %1, %2, %3}, [%5];\n}\n"
                                 : "+r"(z[i].x), "+r"(z[i].y), "+r"(z[i].z), "+r"(z[i].w) : "r"(pair), "r"(zsrc + (4 * cb + i) * 512) : "memory");
                }
            };
            auto stage = [&](int cb) {
                const float* x = y[cb & 1];
#pragma unroll
                for (int i = 0; i < 4; i++)
                    stmatrix_x4((stg ^ (32 * i)) + cb * 2048, hadd2(pack_bf16(x[8 * i], x[8 * i + 1]), z[i].x), hadd2(pack_bf16(x[8 * i + 2], x[8 * i + 3]), z[i].y),
                                hadd2(pack_bf16(x[8 * i + 4], x[8 * i + 5]), z[i].z), hadd2(pack_bf16(x[8 * i + 6], x[8 * i + 7]), z[i].w));
            };
            auto output = [&](int cb) {
                fence_async_smem();
                __syncwarp();
                asm volatile("{\n.reg .pred p;\nelect.sync _|p, -1;\n"
                             "@p cp.reduce.async.bulk.tensor.4d.global.shared::cta.add.tile.bulk_group [%0, {0, 0, %1, %2}], [%3];\n}\n"
                             ::"l"(tm), "r"(cb), "r"(rg), "r"(sq + warp * 8192 + cb * 2048) : "memory");
            };
            pp_sync();
            gemm(0, 0);
            gemm(0, 1);
#pragma unroll
            for (int c = 0; c < 4; c++) {
                if (c < 2) asm volatile("{\n.reg .pred p;\nsetp.ne.s32 p, %0, 0;\n@p bar.sync %1, 256;\n}\n" ::"r"(pair), "r"(c ? BAR_H0 : BAR_BF) : "memory");
                load_z(c);
                if (c < 3) { gemm(c + 1, 0); wg_wait<1>(); } else wg_wait<0>();
                fence_regs(y[c & 1]);
                stage(c);
                if (c < 3) gemm(c + 1, 1);
                if (c == 2 && glob) pp_arrive();
                output(c);
            }
            asm volatile("cp.async.bulk.commit_group;\ncp.async.bulk.wait_group.read 0;\n" ::: "memory");
            if (SC_TAIL) { release(0); release(1); release(2); release(3); }
        }
        } else {
            wg_wait<0>();
        }
        if (SC_TAIL) {
        float o[128];
        auto emit = [&](uint32_t base, int lane, int row0, uint8_t* wdst, int turn) {
#pragma unroll
            for (int hh = 0; hh < 2; hh++) {
                if (turn > 0) mbar_wait(bar_zst + 8 * hh, (turn - 1) & 1);
#pragma unroll
                for (int i = 0; i < 8; i++)
                    stmatrix_x4(base + tile_off(8 * hh + (lane & 7), 4 * i + (lane >> 3)),
                                pack_bf16(o[16 * i + 2 * hh], o[16 * i + 2 * hh + 1]), pack_bf16(o[16 * i + 4 + 2 * hh], o[16 * i + 5 + 2 * hh]),
                                pack_bf16(o[16 * i + 8 + 2 * hh], o[16 * i + 9 + 2 * hh]), pack_bf16(o[16 * i + 12 + 2 * hh], o[16 * i + 13 + 2 * hh]));
                fence_async_smem();
                __syncwarp();
                if (wdst) {
                    if (lane < 4)
                        asm volatile("cp.async.bulk.global.shared::cta.bulk_group [%0], [%1], 1024;\n"
                                     ::"l"(wdst + ((turn & 1) ? hh * 4096 + lane * 1024 : hh * 1024 + lane * QB_BYTES)), "r"(base + hh * 4096 + lane * 1024) : "memory");
                    asm volatile("cp.async.bulk.commit_group;\n" ::: "memory");
                } else {
                    asm volatile("{\n.reg .pred p;\nsetp.eq.s32 p, %3, 0;\n"
                                 "@p cp.reduce.async.bulk.tensor.4d.global.shared::cta.add.tile.bulk_group [%0, {0, 0, 0, %1}], [%2];\n"
                                 "cp.async.bulk.commit_group;\n}\n"
                                 ::"l"(&P.tm_out), "r"((row0 >> 3) + hh), "r"(base + hh * 4096), "r"(lane) : "memory");
                }
            }
            asm volatile("cp.async.bulk.wait_group.read 1;\n" ::: "memory");
            warp_arrive(bar_zst - 8 * wg);
        };
        auto emit_done = [&](bool pending) {
            asm volatile("cp.async.bulk.wait_group.read 0;\n" ::: "memory");
            __syncwarp();
            asm volatile("{\n.reg .pred p;\nsetp.eq.s32 p, %1, 0;\n@p mbarrier.arrive.shared::cta.b64 _, [%0];\n}\n"
                         ::"r"(bar_zst + 8), "r"(pending ? lane : 1) : "memory");
        };
        bar_sync(BAR_BF, 256);
        warp_arrive(bar_qfree);
        const int nf = blockIdx.x == NCTA - 1 ? 8 : 0;
        const int nz = __shfl_sync(~0u, nf + SC_NZ, 0);
        const int itz = __shfl_sync(~0u, 4 + SC_NKV + SC_NW, 0);
        bool pend = false;
#pragma unroll 1
        for (int k = wg; k < nz; k += 2) {
            const int iz = itz + (k < nf ? 0 : nf >> 1);
            mbar_wait(qbar, qphase); qphase ^= 1;
#pragma unroll 1
            for (int c = 0; c < 4; c++) {
                mbar_wait(bar_full + 8 * ((iz + c) & 3), ((iz + c) >> 2) & 1);
                const uint64_t wb = mkaddr(dk0 + ((iz + c) & 3) * (KV_BYTES >> 4), dhi), ab = mkaddr(dq0 + c * 64, dhi);
                wg_fence();
                wgmma_ss_n256_tb_pred(o, ab, wb, c);
#pragma unroll
                for (int kk = 1; kk < 4; kk++) wgmma_ss_n256_tb(o, ab + kk * 2, wb + kk * 512);
                wg_commit();
                emit_done(pend);
                pend = false;
            }
            wg_wait<0>();
            fence_regs(o);
            warp_arrive(bar_qfree);
            const int fb = ((k >> 1) + 3) & 3;
            if (k < nf) {
                float2* r255 = (float2*)H.s->r255 + wg * 128 + q;
                if (k < 2) {
                    if (t >= 124) {
#pragma unroll
                        for (int i = 0; i < 32; i++) r255[4 * i] = make_float2(o[4 * i + 2], o[4 * i + 3]);
                    }
                    bar_sync(BAR_WG0 + wg, 128);
                }
#pragma unroll
                for (int i = 0; i < 32; i++) {
                    const float2 v = __ldcg(r255 + 4 * i);
                    o[4 * i] -= v.x; o[4 * i + 1] -= v.y; o[4 * i + 2] -= v.x; o[4 * i + 3] -= v.y;
                }
            }
            int ln = lane;
            asm volatile("" : "+r"(ln));
            emit(sb + SM_KV + QB_BYTES + warp * KV_BYTES, ln, SC_ZB(k - nf) * 64 + warp * 16,
                 k >= nf ? nullptr : (k & 1) ? g_w + (4 + fb) * QB_BYTES + warp * 8192 : g_w + 8 * QB_BYTES + fb * 8192 + warp * 2048, k);
            pend = k + 2 < nz && (k | 1) != nf - 1;
            if (!pend) emit_done(true);
            if ((k | 1) == nf - 1) {
                asm volatile("cp.async.bulk.wait_group 0;\nfence.proxy.async.global;\nfence.acq_rel.gpu;\n" ::: "memory");
                bar_sync(BAR_BF, 256);
                if (tid == 0) red_release(&g_sync[SY_B * 32]);
                if (wg == 0) { release(0); release(1); release(2); release(3); }
            }
        }
        }
        if (wg == 0) pp_sync();
        warp_arrive(bar_end - 8 * wg);
        asm volatile("barrier.cluster.arrive.relaxed.aligned;\n" ::: "memory");
    }
}

}

extern "C" void kernel_launch(void* const* d_in, const int* in_sizes, int n_in, void* d_out, int out_size) {
    Hot H;
    Params P;
    H.x = (const __nv_bfloat16*)d_in[0];
    P.src = (const int*)d_in[1];
    P.dst = (const int*)d_in[2];
    P.deg_inv = (const __nv_bfloat16*)d_in[3];
    H.wq = (const __nv_bfloat16*)d_in[5];
    H.wk = (const __nv_bfloat16*)d_in[6];
    P.out = (__nv_bfloat16*)d_out;
    typedef CUresult (*EncodeFn)(CUtensorMap*, CUtensorMapDataType, cuuint32_t, void*, const cuuint64_t*, const cuuint64_t*, const cuuint32_t*,
                                 const cuuint32_t*, CUtensorMapInterleave, CUtensorMapSwizzle, CUtensorMapL2promotion, CUtensorMapFloatOOBfill);
    void* fn = nullptr;
    cudaDriverEntryPointQueryResult qr;
    cudaGetDriverEntryPoint("cuTensorMapEncodeTiled", &fn, cudaEnableDefault, &qr);
    auto encode = [&](CUtensorMap* tm, const void* ptr, int rows, int box_rows, int box_cb = 4) {
        const cuuint64_t dims[4] = {64, 8, 4, (cuuint64_t)rows / 8};
        const cuuint64_t strides[3] = {512, 128, 4096};
        const cuuint32_t box[4] = {64, 8, (cuuint32_t)box_cb, (cuuint32_t)box_rows / 8}, es[4] = {1, 1, 1, 1};
        ((EncodeFn)fn)(tm, CU_TENSOR_MAP_DATA_TYPE_BFLOAT16, 4, (void*)ptr, dims, strides, box, es, CU_TENSOR_MAP_INTERLEAVE_NONE,
                       CU_TENSOR_MAP_SWIZZLE_128B, CU_TENSOR_MAP_L2_PROMOTION_NONE, CU_TENSOR_MAP_FLOAT_OOB_FILL_NONE);
    };
    encode(&P.tm_out, d_out, NN, 8);
    encode(&P.tm_outc, d_out, NN, 16, 1);
    for (int i = 0; i < 2; i++) {
        const cuuint64_t dims[5] = {64, 2, 32, 4, 4};
        const cuuint64_t strides[4] = {512, 4096, 128, 1024};
        const cuuint32_t box[5] = {64, 2, 4, 4, 4}, es[5] = {1, 1, 1, 1, 1};
        ((EncodeFn)fn)(&P.tm_w[i], CU_TENSOR_MAP_DATA_TYPE_BFLOAT16, 5, d_in[i ? 4 : 7], dims, strides, box, es, CU_TENSOR_MAP_INTERLEAVE_NONE,
                       CU_TENSOR_MAP_SWIZZLE_128B, CU_TENSOR_MAP_L2_PROMOTION_NONE, CU_TENSOR_MAP_FLOAT_OOB_FILL_NONE);
    }
    encode(&P.tm_w[2], d_in[8], 256, 64);
    void* raw = nullptr;
    cudaGetSymbolAddress(&raw, g_raw);
    H.s = (Scratch*)(((uintptr_t)raw + ((8 << 20) - 1)) & ~(uintptr_t)((8 << 20) - 1));
    P.dhi = 0x40000100u;
    P.E = in_sizes[1] < MAXE ? in_sizes[1] : MAXE;
    for (int b = 0; b < NCTA; b++) {
        const Sched s = get_sched(b >> 1, b & 1);
        P.sched[b][0] = s.qt0 | s.n0 << 8 | s.nkv << 16 | s.owner << 24 | s.pin << 25;
        P.sched[b][1] = s.qt1 | s.nmc << 8 | s.cls << 16;
        P.sched[b][2] = s.zb | s.nz << 8 | s.nw << 16;
    }
    cudaFuncSetAttribute(k_main, cudaFuncAttributeMaxDynamicSharedMemorySize, SM_TOTAL);
    k_main<<<NCTA, 384, SM_TOTAL>>>(H, P);
}
```

```cpp
#include <cuda_runtime.h>
#include <cuda.h>
#include <cuda_bf16.h>
#include <stdint.h>
#include <stddef.h>

namespace {

constexpr int NN = 10000;
constexpr int BN = 80;
constexpr int NKV = NN / BN;
constexpr int NQB = 158;
constexpr int NCTA = 132;
constexpr int NAUX = 3 * (NCTA - 2);
constexpr int STAGES = 4;
constexpr int KV_BYTES = BN * 512;
constexpr int QB_BYTES = 64 * 512;
constexpr int PART_BYTES = QB_BYTES + 512;
constexpr int CAP = 32;
constexpr int MAXE = 160000;

#define QRND(v) (((v) + 0x00040004u) & 0xFFF8FFF8u)
#define GO0 32
#define GF0 2
#define NPOLL 1
#define HDEF -1
#define CSRU 5
#define CPYU 5
#define REFUP 2.f
#define SND0 10
#define CUT2 2
#define ZHOLD 1
#define XD0 0
#define XD1 -1
#define XDW 0
#define PFX 1
#define REG_C 224
#define REG_P 56

enum { SY_PART = 4, SY_H1 = 5, SY_CSR = 6, SY_AUX = 7, SY_DONE = 8, SY_AUX0 = 9, SY_B = 10, SY_AUX1 = 11, SY_H0 = 12 };
struct Scratch {
    uint8_t hz[4096 + NN * 512];
    uint8_t w[12 * QB_BYTES];
    int sync[25 * 32];
    int qflag[96];
    int ovf_n[32];
    float r255[512];
    int cnt[NN + 16];
    int bucket[(NN + 1) * CAP];
    int2 ovf[MAXE];
    uint8_t q[NQB * QB_BYTES];
    uint8_t agg[NQB * QB_BYTES];
    uint8_t part[52 * 2 * PART_BYTES];
};
static_assert(offsetof(Scratch, ovf) <= (8 << 20), "window");
static_assert(offsetof(Scratch, qflag) == offsetof(Scratch, sync) + 25 * 128, "flags");
static_assert(offsetof(Scratch, w) % 1024 == 0 && offsetof(Scratch, sync) % 128 == 0 &&
              offsetof(Scratch, bucket) % 128 == 0 && offsetof(Scratch, q) % 128 == 0, "alignment");
__device__ uint8_t g_raw[(8 << 20) + sizeof(Scratch)];
#define g_hz (H.s->hz)
#define g_w (H.s->w)
#define g_sync (H.s->sync)
#define g_qflag (H.s->qflag)
#define g_ovf_n (H.s->ovf_n)
#define g_cnt (H.s->cnt)
#define g_bucket (H.s->bucket)
#define g_ovf (H.s->ovf)
#define g_q (H.s->q)
#define g_agg (H.s->agg)
#define g_part (H.s->part)

__device__ __forceinline__ void wgmma_ss_n80(float (&d)[40], uint64_t da, uint64_t db) {
    asm volatile("wgmma.mma_async.sync.aligned.m64n80k16.f32.f16.f16 {"
        "%0, %1, %2, %3, %4, %5, %6, %7, %8, %9, %10, %11, %12, %13, %14, %15, %16, %17, %18, %19, %20, %21, %22, %23, %24, %25, %26, %27, %28, %29, %30, %31, "
        "%32, %33, %34, %35, %36, %37, %38, %39}, %40, %41, 1, 1, 1, 0, 0;\n"
        : "+f"(d[0]), "+f"(d[1]), "+f"(d[2]), "+f"(d[3]), "+f"(d[4]), "+f"(d[5]), "+f"(d[6]), "+f"(d[7]),
          "+f"(d[8]), "+f"(d[9]), "+f"(d[10]), "+f"(d[11]), "+f"(d[12]), "+f"(d[13]), "+f"(d[14]), "+f"(d[15]),
          "+f"(d[16]), "+f"(d[17]), "+f"(d[18]), "+f"(d[19]), "+f"(d[20]), "+f"(d[21]), "+f"(d[22]), "+f"(d[23]),
          "+f"(d[24]), "+f"(d[25]), "+f"(d[26]), "+f"(d[27]), "+f"(d[28]), "+f"(d[29]), "+f"(d[30]), "+f"(d[31]),
          "+f"(d[32]), "+f"(d[33]), "+f"(d[34]), "+f"(d[35]), "+f"(d[36]), "+f"(d[37]), "+f"(d[38]), "+f"(d[39])
        : "l"(da), "l"(db));
}
__device__ __forceinline__ void wgmma_ss_n80_init(float (&d)[40], uint64_t da, uint64_t db) {
    asm volatile("wgmma.mma_async.sync.aligned.m64n80k16.f32.f16.f16 {"
        "%0, %1, %2, %3, %4, %5, %6, %7, %8, %9, %10, %11, %12, %13, %14, %15, %16, %17, %18, %19, %20, %21, %22, %23, %24, %25, %26, %27, %28, %29, %30, %31, "
        "%32, %33, %34, %35, %36, %37, %38, %39}, %40, %41, 0, 1, 1, 0, 0;\n"
        : "=f"(d[0]), "=f"(d[1]), "=f"(d[2]), "=f"(d[3]), "=f"(d[4]), "=f"(d[5]), "=f"(d[6]), "=f"(d[7]),
          "=f"(d[8]), "=f"(d[9]), "=f"(d[10]), "=f"(d[11]), "=f"(d[12]), "=f"(d[13]), "=f"(d[14]), "=f"(d[15]),
          "=f"(d[16]), "=f"(d[17]), "=f"(d[18]), "=f"(d[19]), "=f"(d[20]), "=f"(d[21]), "=f"(d[22]), "=f"(d[23]),
          "=f"(d[24]), "=f"(d[25]), "=f"(d[26]), "=f"(d[27]), "=f"(d[28]), "=f"(d[29]), "=f"(d[30]), "=f"(d[31]),
          "=f"(d[32]), "=f"(d[33]), "=f"(d[34]), "=f"(d[35]), "=f"(d[36]), "=f"(d[37]), "=f"(d[38]), "=f"(d[39])
        : "l"(da), "l"(db));
}
__device__ __forceinline__ void wgmma_rs_n256_tb(float (&d)[128], uint32_t a0, uint32_t a1, uint32_t a2, uint32_t a3, uint64_t db) {
    asm volatile("wgmma.mma_async.sync.aligned.m64n256k16.f32.f16.f16 {"
        "%0, %1, %2, %3, %4, %5, %6, %7, %8, %9, %10, %11, %12, %13, %14, %15, %16, %17, %18, %19, %20, %21, %22, %23, %24, %25, %26, %27, %28, %29, %30, %31, "
        "%32, %33, %34, %35, %36, %37, %38, %39, %40, %41, %42, %43, %44, %45, %46, %47, %48, %49, %50, %51, %52, %53, %54, %55, %56, %57, %58, %59, %60, %61, %62, %63, "
        "%64, %65, %66, %67, %68, %69, %70, %71, %72, %73, %74, %75, %76, %77, %78, %79, %80, %81, %82, %83, %84, %85, %86, %87, %88, %89, %90, %91, %92, %93, %94, %95, "
        "%96, %97, %98, %99, %100, %101, %102, %103, %104, %105, %106, %107, %108, %109, %110, %111, %112, %113, %114, %115, %116, %117, %118, %119, %120, %121, %122, %123, %124, %125, %126, %127}, {%128, %129, %130, %131}, %132, 1, 1, 1, 1;\n"
        : "+f"(d[0]), "+f"(d[1]), "+f"(d[2]), "+f"(d[3]), "+f"(d[4]), "+f"(d[5]), "+f"(d[6]), "+f"(d[7]),
          "+f"(d[8]), "+f"(d[9]), "+f"(d[10]), "+f"(d[11]), "+f"(d[12]), "+f"(d[13]), "+f"(d[14]), "+f"(d[15]),
          "+f"(d[16]), "+f"(d[17]), "+f"(d[18]), "+f"(d[19]), "+f"(d[20]), "+f"(d[21]), "+f"(d[22]), "+f"(d[23]),
          "+f"(d[24]), "+f"(d[25]), "+f"(d[26]), "+f"(d[27]), "+f"(d[28]), "+f"(d[29]), "+f"(d[30]), "+f"(d[31]),
          "+f"(d[32]), "+f"(d[33]), "+f"(d[34]), "+f"(d[35]), "+f"(d[36]), "+f"(d[37]), "+f"(d[38]), "+f"(d[39]),
          "+f"(d[40]), "+f"(d[41]), "+f"(d[42]), "+f"(d[43]), "+f"(d[44]), "+f"(d[45]), "+f"(d[46]), "+f"(d[47]),
          "+f"(d[48]), "+f"(d[49]), "+f"(d[50]), "+f"(d[51]), "+f"(d[52]), "+f"(d[53]), "+f"(d[54]), "+f"(d[55]),
          "+f"(d[56]), "+f"(d[57]), "+f"(d[58]), "+f"(d[59]), "+f"(d[60]), "+f"(d[61]), "+f"(d[62]), "+f"(d[63]),
          "+f"(d[64]), "+f"(d[65]), "+f"(d[66]), "+f"(d[67]), "+f"(d[68]), "+f"(d[69]), "+f"(d[70]), "+f"(d[71]),
          "+f"(d[72]), "+f"(d[73]), "+f"(d[74]), "+f"(d[75]), "+f"(d[76]), "+f"(d[77]), "+f"(d[78]), "+f"(d[79]),
          "+f"(d[80]), "+f"(d[81]), "+f"(d[82]), "+f"(d[83]), "+f"(d[84]), "+f"(d[85]), "+f"(d[86]), "+f"(d[87]),
          "+f"(d[88]), "+f"(d[89]), "+f"(d[90]), "+f"(d[91]), "+f"(d[92]), "+f"(d[93]), "+f"(d[94]), "+f"(d[95]),
          "+f"(d[96]), "+f"(d[97]), "+f"(d[98]), "+f"(d[99]), "+f"(d[100]), "+f"(d[101]), "+f"(d[102]), "+f"(d[103]),
          "+f"(d[104]), "+f"(d[105]), "+f"(d[106]), "+f"(d[107]), "+f"(d[108]), "+f"(d[109]), "+f"(d[110]), "+f"(d[111]),
          "+f"(d[112]), "+f"(d[113]), "+f"(d[114]), "+f"(d[115]), "+f"(d[116]), "+f"(d[117]), "+f"(d[118]), "+f"(d[119]),
          "+f"(d[120]), "+f"(d[121]), "+f"(d[122]), "+f"(d[123]), "+f"(d[124]), "+f"(d[125]), "+f"(d[126]), "+f"(d[127])
        : "r"(a0), "r"(a1), "r"(a2), "r"(a3), "l"(db));
}
__device__ __forceinline__ void wgmma_rs_n256_tb_init(float (&d)[128], uint32_t a0, uint32_t a1, uint32_t a2, uint32_t a3, uint64_t db) {
    asm volatile("wgmma.mma_async.sync.aligned.m64n256k16.f32.f16.f16 {"
        "%0, %1, %2, %3, %4, %5, %6, %7, %8, %9, %10, %11, %12, %13, %14, %15, %16, %17, %18, %19, %20, %21, %22, %23, %24, %25, %26, %27, %28, %29, %30, %31, "
        "%32, %33, %34, %35, %36, %37, %38, %39, %40, %41, %42, %43, %44, %45, %46, %47, %48, %49, %50, %51, %52, %53, %54, %55, %56, %57, %58, %59, %60, %61, %62, %63, "
        "%64, %65, %66, %67, %68, %69, %70, %71, %72, %73, %74, %75, %76, %77, %78, %79, %80, %81, %82, %83, %84, %85, %86, %87, %88, %89, %90, %91, %92, %93, %94, %95, "
        "%96, %97, %98, %99, %100, %101, %102, %103, %104, %105, %106, %107, %108, %109, %110, %111, %112, %113, %114, %115, %116, %117, %118, %119, %120, %121, %122, %123, %124, %125, %126, %127}, {%128, %129, %130, %131}, %132, 0, 1, 1, 1;\n"
        : "=f"(d[0]), "=f"(d[1]), "=f"(d[2]), "=f"(d[3]), "=f"(d[4]), "=f"(d[5]), "=f"(d[6]), "=f"(d[7]),
          "=f"(d[8]), "=f"(d[9]), "=f"(d[10]), "=f"(d[11]), "=f"(d[12]), "=f"(d[13]), "=f"(d[14]), "=f"(d[15]),
          "=f"(d[16]), "=f"(d[17]), "=f"(d[18]), "=f"(d[19]), "=f"(d[20]), "=f"(d[21]), "=f"(d[22]), "=f"(d[23]),
          "=f"(d[24]), "=f"(d[25]), "=f"(d[26]), "=f"(d[27]), "=f"(d[28]), "=f"(d[29]), "=f"(d[30]), "=f"(d[31]),
          "=f"(d[32]), "=f"(d[33]), "=f"(d[34]), "=f"(d[35]), "=f"(d[36]), "=f"(d[37]), "=f"(d[38]), "=f"(d[39]),
          "=f"(d[40]), "=f"(d[41]), "=f"(d[42]), "=f"(d[43]), "=f"(d[44]), "=f"(d[45]), "=f"(d[46]), "=f"(d[47]),
          "=f"(d[48]), "=f"(d[49]), "=f"(d[50]), "=f"(d[51]), "=f"(d[52]), "=f"(d[53]), "=f"(d[54]), "=f"(d[55]),
          "=f"(d[56]), "=f"(d[57]), "=f"(d[58]), "=f"(d[59]), "=f"(d[60]), "=f"(d[61]), "=f"(d[62]), "=f"(d[63]),
          "=f"(d[64]), "=f"(d[65]), "=f"(d[66]), "=f"(d[67]), "=f"(d[68]), "=f"(d[69]), "=f"(d[70]), "=f"(d[71]),
          "=f"(d[72]), "=f"(d[73]), "=f"(d[74]), "=f"(d[75]), "=f"(d[76]), "=f"(d[77]), "=f"(d[78]), "=f"(d[79]),
          "=f"(d[80]), "=f"(d[81]), "=f"(d[82]), "=f"(d[83]), "=f"(d[84]), "=f"(d[85]), "=f"(d[86]), "=f"(d[87]),
          "=f"(d[88]), "=f"(d[89]), "=f"(d[90]), "=f"(d[91]), "=f"(d[92]), "=f"(d[93]), "=f"(d[94]), "=f"(d[95]),
          "=f"(d[96]), "=f"(d[97]), "=f"(d[98]), "=f"(d[99]), "=f"(d[100]), "=f"(d[101]), "=f"(d[102]), "=f"(d[103]),
          "=f"(d[104]), "=f"(d[105]), "=f"(d[106]), "=f"(d[107]), "=f"(d[108]), "=f"(d[109]), "=f"(d[110]), "=f"(d[111]),
          "=f"(d[112]), "=f"(d[113]), "=f"(d[114]), "=f"(d[115]), "=f"(d[116]), "=f"(d[117]), "=f"(d[118]), "=f"(d[119]),
          "=f"(d[120]), "=f"(d[121]), "=f"(d[122]), "=f"(d[123]), "=f"(d[124]), "=f"(d[125]), "=f"(d[126]), "=f"(d[127])
        : "r"(a0), "r"(a1), "r"(a2), "r"(a3), "l"(db));
}
__device__ __forceinline__ void wgmma_rs_n256_tb_pred(float (&d)[128], uint32_t a0, uint32_t a1, uint32_t a2, uint32_t a3, uint64_t db, int acc) {
    asm volatile("{\n.reg .pred p;\nsetp.ne.s32 p, %133, 0;\nwgmma.mma_async.sync.aligned.m64n256k16.f32.f16.f16 {"
        "%0, %1, %2, %3, %4, %5, %6, %7, %8, %9, %10, %11, %12, %13, %14, %15, %16, %17, %18, %19, %20, %21, %22, %23, %24, %25, %26, %27, %28, %29, %30, %31, "
        "%32, %33, %34, %35, %36, %37, %38, %39, %40, %41, %42, %43, %44, %45, %46, %47, %48, %49, %50, %51, %52, %53, %54, %55, %56, %57, %58, %59, %60, %61, %62, %63, "
        "%64, %65, %66, %67, %68, %69, %70, %71, %72, %73, %74, %75, %76, %77, %78, %79, %80, %81, %82, %83, %84, %85, %86, %87, %88, %89, %90, %91, %92, %93, %94, %95, "
        "%96, %97, %98, %99, %100, %101, %102, %103, %104, %105, %106, %107, %108, %109, %110, %111, %112, %113, %114, %115, %116, %117, %118, %119, %120, %121, %122, %123, %124, %125, %126, %127}, {%128, %129, %130, %131}, %132, p, 1, 1, 1;\n}\n"
        : "+f"(d[0]), "+f"(d[1]), "+f"(d[2]), "+f"(d[3]), "+f"(d[4]), "+f"(d[5]), "+f"(d[6]), "+f"(d[7]),
          "+f"(d[8]), "+f"(d[9]), "+f"(d[10]), "+f"(d[11]), "+f"(d[12]), "+f"(d[13]), "+f"(d[14]), "+f"(d[15]),
          "+f"(d[16]), "+f"(d[17]), "+f"(d[18]), "+f"(d[19]), "+f"(d[20]), "+f"(d[21]), "+f"(d[22]), "+f"(d[23]),
          "+f"(d[24]), "+f"(d[25]), "+f"(d[26]), "+f"(d[27]), "+f"(d[28]), "+f"(d[29]), "+f"(d[30]), "+f"(d[31]),
          "+f"(d[32]), "+f"(d[33]), "+f"(d[34]), "+f"(d[35]), "+f"(d[36]), "+f"(d[37]), "+f"(d[38]), "+f"(d[39]),
          "+f"(d[40]), "+f"(d[41]), "+f"(d[42]), "+f"(d[43]), "+f"(d[44]), "+f"(d[45]), "+f"(d[46]), "+f"(d[47]),
          "+f"(d[48]), "+f"(d[49]), "+f"(d[50]), "+f"(d[51]), "+f"(d[52]), "+f"(d[53]), "+f"(d[54]), "+f"(d[55]),
          "+f"(d[56]), "+f"(d[57]), "+f"(d[58]), "+f"(d[59]), "+f"(d[60]), "+f"(d[61]), "+f"(d[62]), "+f"(d[63]),
          "+f"(d[64]), "+f"(d[65]), "+f"(d[66]), "+f"(d[67]), "+f"(d[68]), "+f"(d[69]), "+f"(d[70]), "+f"(d[71]),
          "+f"(d[72]), "+f"(d[73]), "+f"(d[74]), "+f"(d[75]), "+f"(d[76]), "+f"(d[77]), "+f"(d[78]), "+f"(d[79]),
          "+f"(d[80]), "+f"(d[81]), "+f"(d[82]), "+f"(d[83]), "+f"(d[84]), "+f"(d[85]), "+f"(d[86]), "+f"(d[87]),
          "+f"(d[88]), "+f"(d[89]), "+f"(d[90]), "+f"(d[91]), "+f"(d[92]), "+f"(d[93]), "+f"(d[94]), "+f"(d[95]),
          "+f"(d[96]), "+f"(d[97]), "+f"(d[98]), "+f"(d[99]), "+f"(d[100]), "+f"(d[101]), "+f"(d[102]), "+f"(d[103]),
          "+f"(d[104]), "+f"(d[105]), "+f"(d[106]), "+f"(d[107]), "+f"(d[108]), "+f"(d[109]), "+f"(d[110]), "+f"(d[111]),
          "+f"(d[112]), "+f"(d[113]), "+f"(d[114]), "+f"(d[115]), "+f"(d[116]), "+f"(d[117]), "+f"(d[118]), "+f"(d[119]),
          "+f"(d[120]), "+f"(d[121]), "+f"(d[122]), "+f"(d[123]), "+f"(d[124]), "+f"(d[125]), "+f"(d[126]), "+f"(d[127])
        : "r"(a0), "r"(a1), "r"(a2), "r"(a3), "l"(db), "r"(acc));
}
__device__ __forceinline__ void wgmma_ss_n256_tb(float (&d)[128], uint64_t da, uint64_t db) {
    asm volatile("wgmma.mma_async.sync.aligned.m64n256k16.f32.bf16.bf16 {"
        "%0, %1, %2, %3, %4, %5, %6, %7, %8, %9, %10, %11, %12, %13, %14, %15, %16, %17, %18, %19, %20, %21, %22, %23, %24, %25, %26, %27, %28, %29, %30, %31, "
        "%32, %33, %34, %35, %36, %37, %38, %39, %40, %41, %42, %43, %44, %45, %46, %47, %48, %49, %50, %51, %52, %53, %54, %55, %56, %57, %58, %59, %60, %61, %62, %63, "
        "%64, %65, %66, %67, %68, %69, %70, %71, %72, %73, %74, %75, %76, %77, %78, %79, %80, %81, %82, %83, %84, %85, %86, %87, %88, %89, %90, %91, %92, %93, %94, %95, "
        "%96, %97, %98, %99, %100, %101, %102, %103, %104, %105, %106, %107, %108, %109, %110, %111, %112, %113, %114, %115, %116, %117, %118, %119, %120, %121, %122, %123, %124, %125, %126, %127}, %128, %129, 1, 1, 1, 0, 1;\n"
        : "+f"(d[0]), "+f"(d[1]), "+f"(d[2]), "+f"(d[3]), "+f"(d[4]), "+f"(d[5]), "+f"(d[6]), "+f"(d[7]),
          "+f"(d[8]), "+f"(d[9]), "+f"(d[10]), "+f"(d[11]), "+f"(d[12]), "+f"(d[13]), "+f"(d[14]), "+f"(d[15]),
          "+f"(d[16]), "+f"(d[17]), "+f"(d[18]), "+f"(d[19]), "+f"(d[20]), "+f"(d[21]), "+f"(d[22]), "+f"(d[23]),
          "+f"(d[24]), "+f"(d[25]), "+f"(d[26]), "+f"(d[27]), "+f"(d[28]), "+f"(d[29]), "+f"(d[30]), "+f"(d[31]),
          "+f"(d[32]), "+f"(d[33]), "+f"(d[34]), "+f"(d[35]), "+f"(d[36]), "+f"(d[37]), "+f"(d[38]), "+f"(d[39]),
          "+f"(d[40]), "+f"(d[41]), "+f"(d[42]), "+f"(d[43]), "+f"(d[44]), "+f"(d[45]), "+f"(d[46]), "+f"(d[47]),
          "+f"(d[48]), "+f"(d[49]), "+f"(d[50]), "+f"(d[51]), "+f"(d[52]), "+f"(d[53]), "+f"(d[54]), "+f"(d[55]),
          "+f"(d[56]), "+f"(d[57]), "+f"(d[58]), "+f"(d[59]), "+f"(d[60]), "+f"(d[61]), "+f"(d[62]), "+f"(d[63]),
          "+f"(d[64]), "+f"(d[65]), "+f"(d[66]), "+f"(d[67]), "+f"(d[68]), "+f"(d[69]), "+f"(d[70]), "+f"(d[71]),
          "+f"(d[72]), "+f"(d[73]), "+f"(d[74]), "+f"(d[75]), "+f"(d[76]), "+f"(d[77]), "+f"(d[78]), "+f"(d[79]),
          "+f"(d[80]), "+f"(d[81]), "+f"(d[82]), "+f"(d[83]), "+f"(d[84]), "+f"(d[85]), "+f"(d[86]), "+f"(d[87]),
          "+f"(d[88]), "+f"(d[89]), "+f"(d[90]), "+f"(d[91]), "+f"(d[92]), "+f"(d[93]), "+f"(d[94]), "+f"(d[95]),
          "+f"(d[96]), "+f"(d[97]), "+f"(d[98]), "+f"(d[99]), "+f"(d[100]), "+f"(d[101]), "+f"(d[102]), "+f"(d[103]),
          "+f"(d[104]), "+f"(d[105]), "+f"(d[106]), "+f"(d[107]), "+f"(d[108]), "+f"(d[109]), "+f"(d[110]), "+f"(d[111]),
          "+f"(d[112]), "+f"(d[113]), "+f"(d[114]), "+f"(d[115]), "+f"(d[116]), "+f"(d[117]), "+f"(d[118]), "+f"(d[119]),
          "+f"(d[120]), "+f"(d[121]), "+f"(d[122]), "+f"(d[123]), "+f"(d[124]), "+f"(d[125]), "+f"(d[126]), "+f"(d[127])
        : "l"(da), "l"(db));
}
__device__ __forceinline__ void wgmma_ss_n256_tb_init(float (&d)[128], uint64_t da, uint64_t db) {
    asm volatile("wgmma.mma_async.sync.aligned.m64n256k16.f32.bf16.bf16 {"
        "%0, %1, %2, %3, %4, %5, %6, %7, %8, %9, %10, %11, %12, %13, %14, %15, %16, %17, %18, %19, %20, %21, %22, %23, %24, %25, %26, %27, %28, %29, %30, %31, "
        "%32, %33, %34, %35, %36, %37, %38, %39, %40, %41, %42, %43, %44, %45, %46, %47, %48, %49, %50, %51, %52, %53, %54, %55, %56, %57, %58, %59, %60, %61, %62, %63, "
        "%64, %65, %66, %67, %68, %69, %70, %71, %72, %73, %74, %75, %76, %77, %78, %79, %80, %81, %82, %83, %84, %85, %86, %87, %88, %89, %90, %91, %92, %93, %94, %95, "
        "%96, %97, %98, %99, %100, %101, %102, %103, %104, %105, %106, %107, %108, %109, %110, %111, %112, %113, %114, %115, %116, %117, %118, %119, %120, %121, %122, %123, %124, %125, %126, %127}, %128, %129, 0, 1, 1, 0, 1;\n"
        : "=f"(d[0]), "=f"(d[1]), "=f"(d[2]), "=f"(d[3]), "=f"(d[4]), "=f"(d[5]), "=f"(d[6]), "=f"(d[7]),
          "=f"(d[8]), "=f"(d[9]), "=f"(d[10]), "=f"(d[11]), "=f"(d[12]), "=f"(d[13]), "=f"(d[14]), "=f"(d[15]),
          "=f"(d[16]), "=f"(d[17]), "=f"(d[18]), "=f"(d[19]), "=f"(d[20]), "=f"(d[21]), "=f"(d[22]), "=f"(d[23]),
          "=f"(d[24]), "=f"(d[25]), "=f"(d[26]), "=f"(d[27]), "=f"(d[28]), "=f"(d[29]), "=f"(d[30]), "=f"(d[31]),
          "=f"(d[32]), "=f"(d[33]), "=f"(d[34]), "=f"(d[35]), "=f"(d[36]), "=f"(d[37]), "=f"(d[38]), "=f"(d[39]),
          "=f"(d[40]), "=f"(d[41]), "=f"(d[42]), "=f"(d[43]), "=f"(d[44]), "=f"(d[45]), "=f"(d[46]), "=f"(d[47]),
          "=f"(d[48]), "=f"(d[49]), "=f"(d[50]), "=f"(d[51]), "=f"(d[52]), "=f"(d[53]), "=f"(d[54]), "=f"(d[55]),
          "=f"(d[56]), "=f"(d[57]), "=f"(d[58]), "=f"(d[59]), "=f"(d[60]), "=f"(d[61]), "=f"(d[62]), "=f"(d[63]),
          "=f"(d[64]), "=f"(d[65]), "=f"(d[66]), "=f"(d[67]), "=f"(d[68]), "=f"(d[69]), "=f"(d[70]), "=f"(d[71]),
          "=f"(d[72]), "=f"(d[73]), "=f"(d[74]), "=f"(d[75]), "=f"(d[76]), "=f"(d[77]), "=f"(d[78]), "=f"(d[79]),
          "=f"(d[80]), "=f"(d[81]), "=f"(d[82]), "=f"(d[83]), "=f"(d[84]), "=f"(d[85]), "=f"(d[86]), "=f"(d[87]),
          "=f"(d[88]), "=f"(d[89]), "=f"(d[90]), "=f"(d[91]), "=f"(d[92]), "=f"(d[93]), "=f"(d[94]), "=f"(d[95]),
          "=f"(d[96]), "=f"(d[97]), "=f"(d[98]), "=f"(d[99]), "=f"(d[100]), "=f"(d[101]), "=f"(d[102]), "=f"(d[103]),
          "=f"(d[104]), "=f"(d[105]), "=f"(d[106]), "=f"(d[107]), "=f"(d[108]), "=f"(d[109]), "=f"(d[110]), "=f"(d[111]),
          "=f"(d[112]), "=f"(d[113]), "=f"(d[114]), "=f"(d[115]), "=f"(d[116]), "=f"(d[117]), "=f"(d[118]), "=f"(d[119]),
          "=f"(d[120]), "=f"(d[121]), "=f"(d[122]), "=f"(d[123]), "=f"(d[124]), "=f"(d[125]), "=f"(d[126]), "=f"(d[127])
        : "l"(da), "l"(db));
}
__device__ __forceinline__ void wgmma_ss_n256_tb_pred(float (&d)[128], uint64_t da, uint64_t db, int acc) {
    asm volatile("{\n.reg .pred p;\nsetp.ne.s32 p, %130, 0;\nwgmma.mma_async.sync.aligned.m64n256k16.f32.bf16.bf16 {"
        "%0, %1, %2, %3, %4, %5, %6, %7, %8, %9, %10, %11, %12, %13, %14, %15, %16, %17, %18, %19, %20, %21, %22, %23, %24, %25, %26, %27, %28, %29, %30, %31, "
        "%32, %33, %34, %35, %36, %37, %38, %39, %40, %41, %42, %43, %44, %45, %46, %47, %48, %49, %50, %51, %52, %53, %54, %55, %56, %57, %58, %59, %60, %61, %62, %63, "
        "%64, %65, %66, %67, %68, %69, %70, %71, %72, %73, %74, %75, %76, %77, %78, %79, %80, %81, %82, %83, %84, %85, %86, %87, %88, %89, %90, %91, %92, %93, %94, %95, "
        "%96, %97, %98, %99, %100, %101, %102, %103, %104, %105, %106, %107, %108, %109, %110, %111, %112, %113, %114, %115, %116, %117, %118, %119, %120, %121, %122, %123, %124, %125, %126, %127}, %128, %129, p, 1, 1, 0, 1;\n}\n"
        : "+f"(d[0]), "+f"(d[1]), "+f"(d[2]), "+f"(d[3]), "+f"(d[4]), "+f"(d[5]), "+f"(d[6]), "+f"(d[7]),
          "+f"(d[8]), "+f"(d[9]), "+f"(d[10]), "+f"(d[11]), "+f"(d[12]), "+f"(d[13]), "+f"(d[14]), "+f"(d[15]),
          "+f"(d[16]), "+f"(d[17]), "+f"(d[18]), "+f"(d[19]), "+f"(d[20]), "+f"(d[21]), "+f"(d[22]), "+f"(d[23]),
          "+f"(d[24]), "+f"(d[25]), "+f"(d[26]), "+f"(d[27]), "+f"(d[28]), "+f"(d[29]), "+f"(d[30]), "+f"(d[31]),
          "+f"(d[32]), "+f"(d[33]), "+f"(d[34]), "+f"(d[35]), "+f"(d[36]), "+f"(d[37]), "+f"(d[38]), "+f"(d[39]),
          "+f"(d[40]), "+f"(d[41]), "+f"(d[42]), "+f"(d[43]), "+f"(d[44]), "+f"(d[45]), "+f"(d[46]), "+f"(d[47]),
          "+f"(d[48]), "+f"(d[49]), "+f"(d[50]), "+f"(d[51]), "+f"(d[52]), "+f"(d[53]), "+f"(d[54]), "+f"(d[55]),
          "+f"(d[56]), "+f"(d[57]), "+f"(d[58]), "+f"(d[59]), "+f"(d[60]), "+f"(d[61]), "+f"(d[62]), "+f"(d[63]),
          "+f"(d[64]), "+f"(d[65]), "+f"(d[66]), "+f"(d[67]), "+f"(d[68]), "+f"(d[69]), "+f"(d[70]), "+f"(d[71]),
          "+f"(d[72]), "+f"(d[73]), "+f"(d[74]), "+f"(d[75]), "+f"(d[76]), "+f"(d[77]), "+f"(d[78]), "+f"(d[79]),
          "+f"(d[80]), "+f"(d[81]), "+f"(d[82]), "+f"(d[83]), "+f"(d[84]), "+f"(d[85]), "+f"(d[86]), "+f"(d[87]),
          "+f"(d[88]), "+f"(d[89]), "+f"(d[90]), "+f"(d[91]), "+f"(d[92]), "+f"(d[93]), "+f"(d[94]), "+f"(d[95]),
          "+f"(d[96]), "+f"(d[97]), "+f"(d[98]), "+f"(d[99]), "+f"(d[100]), "+f"(d[101]), "+f"(d[102]), "+f"(d[103]),
          "+f"(d[104]), "+f"(d[105]), "+f"(d[106]), "+f"(d[107]), "+f"(d[108]), "+f"(d[109]), "+f"(d[110]), "+f"(d[111]),
          "+f"(d[112]), "+f"(d[113]), "+f"(d[114]), "+f"(d[115]), "+f"(d[116]), "+f"(d[117]), "+f"(d[118]), "+f"(d[119]),
          "+f"(d[120]), "+f"(d[121]), "+f"(d[122]), "+f"(d[123]), "+f"(d[124]), "+f"(d[125]), "+f"(d[126]), "+f"(d[127])
        : "l"(da), "l"(db), "r"(acc));
}
__device__ __forceinline__ void wgmma_rs_n64_tb(float (&d)[32], uint32_t a0, uint32_t a1, uint32_t a2, uint32_t a3, uint64_t db) {
    asm volatile("wgmma.mma_async.sync.aligned.m64n64k16.f32.bf16.bf16 {"
        "%0, %1, %2, %3, %4, %5, %6, %7, %8, %9, %10, %11, %12, %13, %14, %15, %16, %17, %18, %19, %20, %21, %22, %23, %24, %25, %26, %27, %28, %29, %30, %31}, {%32, %33, %34, %35}, %36, 1, 1, 1, 1;\n"
        : "+f"(d[0]), "+f"(d[1]), "+f"(d[2]), "+f"(d[3]), "+f"(d[4]), "+f"(d[5]), "+f"(d[6]), "+f"(d[7]),
          "+f"(d[8]), "+f"(d[9]), "+f"(d[10]), "+f"(d[11]), "+f"(d[12]), "+f"(d[13]), "+f"(d[14]), "+f"(d[15]),
          "+f"(d[16]), "+f"(d[17]), "+f"(d[18]), "+f"(d[19]), "+f"(d[20]), "+f"(d[21]), "+f"(d[22]), "+f"(d[23]),
          "+f"(d[24]), "+f"(d[25]), "+f"(d[26]), "+f"(d[27]), "+f"(d[28]), "+f"(d[29]), "+f"(d[30]), "+f"(d[31])
        : "r"(a0), "r"(a1), "r"(a2), "r"(a3), "l"(db));
}
__device__ __forceinline__ void wgmma_rs_n64_tb_init(float (&d)[32], uint32_t a0, uint32_t a1, uint32_t a2, uint32_t a3, uint64_t db) {
    asm volatile("wgmma.mma_async.sync.aligned.m64n64k16.f32.bf16.bf16 {"
        "%0, %1, %2, %3, %4, %5, %6, %7, %8, %9, %10, %11, %12, %13, %14, %15, %16, %17, %18, %19, %20, %21, %22, %23, %24, %25, %26, %27, %28, %29, %30, %31}, {%32, %33, %34, %35}, %36, 0, 1, 1, 1;\n"
        : "=f"(d[0]), "=f"(d[1]), "=f"(d[2]), "=f"(d[3]), "=f"(d[4]), "=f"(d[5]), "=f"(d[6]), "=f"(d[7]),
          "=f"(d[8]), "=f"(d[9]), "=f"(d[10]), "=f"(d[11]), "=f"(d[12]), "=f"(d[13]), "=f"(d[14]), "=f"(d[15]),
          "=f"(d[16]), "=f"(d[17]), "=f"(d[18]), "=f"(d[19]), "=f"(d[20]), "=f"(d[21]), "=f"(d[22]), "=f"(d[23]),
          "=f"(d[24]), "=f"(d[25]), "=f"(d[26]), "=f"(d[27]), "=f"(d[28]), "=f"(d[29]), "=f"(d[30]), "=f"(d[31])
        : "r"(a0), "r"(a1), "r"(a2), "r"(a3), "l"(db));
}

__device__ __forceinline__ void wg_fence() { asm volatile("wgmma.fence.sync.aligned;\n" ::: "memory"); }
__device__ __forceinline__ void wg_commit() { asm volatile("wgmma.commit_group.sync.aligned;\n" ::: "memory"); }
template <int N> __device__ __forceinline__ void wg_wait() { asm volatile("wgmma.wait_group.sync.aligned %0;\n" ::"n"(N) : "memory"); }
template <int N> __device__ __forceinline__ void fence_regs(float (&a)[N]) {
#pragma unroll
    for (int i = 0; i < N; i++) asm volatile("" : "+f"(a[i])::"memory");
}
template <int N> __device__ __forceinline__ void fence_regs(uint32_t (&a)[N]) {
#pragma unroll
    for (int i = 0; i < N; i++) asm volatile("" : "+r"(a[i])::"memory");
}
__device__ __forceinline__ void mbar_init(uint32_t bar, uint32_t cnt) {
    asm volatile("mbarrier.init.shared::cta.b64 [%0], %1;\n" ::"r"(bar), "r"(cnt) : "memory");
}
__device__ __forceinline__ void mbar_expect_tx(uint32_t bar, uint32_t bytes) {
    asm volatile("mbarrier.arrive.expect_tx.shared::cta.b64 _, [%0], %1;\n" ::"r"(bar), "r"(bytes) : "memory");
}
__device__ __forceinline__ void mbar_wait(uint32_t bar, uint32_t parity) {
    asm volatile("{\n.reg .pred p;\nLW:\nmbarrier.try_wait.parity.shared::cta.b64 p, [%0], %1;\n@!p pmevent 0;\n@!p bra LW;\n}\n" ::"r"(bar), "r"(parity) : "memory");
}
__device__ __forceinline__ void mbar_wait_sleep(uint32_t bar, uint32_t parity) {
    asm volatile("{\n.reg .pred p;\nLW:\nmbarrier.try_wait.parity.shared::cta.b64 p, [%0], %1, 20000;\n@!p pmevent 0;\n@!p bra LW;\n}\n" ::"r"(bar), "r"(parity) : "memory");
}
__device__ __forceinline__ void mbar_wait_bounded(uint32_t bar, uint32_t parity) {
    asm volatile("{\n.reg .pred p;\n.reg .u32 c;\nmov.u32 c, 0;\nLW:\nmbarrier.try_wait.parity.shared::cta.b64 p, [%0], %1, 20000;\n@p bra LD;\n"
                 "add.u32 c, c, 1;\nsetp.ge.u32 p, c, 262144;\n@p trap;\nbra LW;\nLD:\n}\n" ::"r"(bar), "r"(parity) : "memory");
}
__device__ __forceinline__ void flag_wait(const int* p, int v) {
    asm volatile("{\n.reg .pred p;\n.reg .s32 f;\nLW:\nld.acquire.gpu.global.s32 f, [%0];\nsub.s32 f, f, %1;\nsetp.lt.s32 p, f, 0;\n@p bra LW;\n}\n" ::"l"(p), "r"(v) : "memory");
}
__device__ __forceinline__ void flag_wait_bounded(const int* p, int v) {
    asm volatile("{\n.reg .pred p;\n.reg .u32 c;\n.reg .s32 f;\nmov.u32 c, 0;\nLW:\nld.acquire.gpu.global.s32 f, [%0];\nsub.s32 f, f, %1;\nsetp.ge.s32 p, f, 0;\n@p bra LD;\n"
                 "nanosleep.u32 500;\nadd.u32 c, c, 1;\nsetp.ge.u32 p, c, 4194304;\n@p trap;\nbra LW;\nLD:\n}\n" ::"l"(p), "r"(v) : "memory");
}
__device__ __forceinline__ bool elect() {
    uint32_t p; asm volatile("{\n.reg .pred p;\nelect.sync _|p, -1;\nselp.u32 %0, 1, 0, p;\n}\n" : "=r"(p)); return p;
}
__device__ __forceinline__ void bulk_g2s(uint32_t dst, const void* src, uint32_t bytes, uint32_t bar) {
    asm volatile("cp.async.bulk.shared::cluster.global.mbarrier::complete_tx::bytes [%0], [%1], %2, [%3];\n"
                 ::"r"(dst), "l"(src), "r"(bytes), "r"(bar) : "memory");
}
__device__ __forceinline__ void bulk_g2s_mc(uint32_t dst, const void* src, uint32_t bytes, uint32_t bar, uint16_t mask) {
    asm volatile("cp.async.bulk.shared::cluster.global.mbarrier::complete_tx::bytes.multicast::cluster [%0], [%1], %2, [%3], %4;\n"
                 ::"r"(dst), "l"(src), "r"(bytes), "r"(bar), "h"(mask) : "memory");
}
__device__ __forceinline__ void tma_g2s(uint32_t dst, const CUtensorMap* tm, int rowgroup, uint32_t bar) {
    asm volatile("cp.async.bulk.tensor.4d.shared::cluster.global.tile.mbarrier::complete_tx::bytes [%0], [%1, {0, 0, 0, %2}], [%3];\n"
                 ::"r"(dst), "l"(tm), "r"(rowgroup), "r"(bar) : "memory");
}
__device__ __forceinline__ void bar_sync(int id, int n) { asm volatile("bar.sync %0, %1;\n" ::"r"(id), "r"(n) : "memory"); }
__device__ __forceinline__ void bar_arrive(int id, int n) { asm volatile("bar.arrive %0, %1;\n" ::"r"(id), "r"(n) : "memory"); }
__device__ __forceinline__ float quad_last(float v) {
    float r; asm volatile("shfl.sync.idx.b32 %0, %1, 3, 0x1c1f, -1;\n" : "=f"(r) : "f"(v)); return r;
}
__device__ __forceinline__ float ex2(float x) { float y; asm("ex2.approx.ftz.f32 %0, %1;\n" : "=f"(y) : "f"(x)); return y; }
__device__ __forceinline__ float rcp(float x) { float y; asm("rcp.approx.ftz.f32 %0, %1;\n" : "=f"(y) : "f"(x)); return y; }
__device__ __forceinline__ uint32_t pack_bf16(float lo, float hi) {
    uint32_t r; asm("cvt.rn.bf16x2.f32 %0, %1, %2;\n" : "=r"(r) : "f"(hi), "f"(lo)); return r;
}
__device__ __forceinline__ uint32_t pack_f16(float lo, float hi) {
    uint32_t r; asm("cvt.rn.f16x2.f32 %0, %1, %2;\n" : "=r"(r) : "f"(hi), "f"(lo)); return r;
}
__device__ __forceinline__ uint32_t pack_f16_sat(float lo, float hi) {
    uint32_t r; asm("cvt.rn.satfinite.f16x2.f32 %0, %1, %2;\n" : "=r"(r) : "f"(hi), "f"(lo)); return r;
}
__device__ __forceinline__ float f16_lo(uint32_t v) { float r; asm("cvt.f32.f16 %0, %1;\n" : "=f"(r) : "h"((unsigned short)v)); return r; }
__device__ __forceinline__ float f16_hi(uint32_t v) { return f16_lo(v >> 16); }
__device__ __forceinline__ float bf_lo(uint32_t v) { return __uint_as_float(v << 16); }
__device__ __forceinline__ float bf_hi(uint32_t v) { return __uint_as_float(v & 0xFFFF0000u); }
__device__ __forceinline__ float bf_round(float x) { return __uint_as_float(pack_bf16(0.f, x)); }
__device__ __forceinline__ void st_release(int* p, int v) {
    asm volatile("st.release.gpu.global.s32 [%0], %1;\n" ::"l"(p), "r"(v) : "memory");
}
__device__ __forceinline__ uint4 ldg_pinned(const uint4* p) {
    uint4 v; asm volatile("ld.global.nc.v4.u32 {%0, %1, %2, %3}, [%4];\n" : "=r"(v.x), "=r"(v.y), "=r"(v.z), "=r"(v.w) : "l"(p) : "memory"); return v;
}
__device__ __forceinline__ void stmatrix_x4(uint32_t addr, uint32_t r0, uint32_t r1, uint32_t r2, uint32_t r3) {
    asm volatile("stmatrix.sync.aligned.m8n8.x4.shared.b16 [%0], {%1, %2, %3, %4};\n" ::"r"(addr), "r"(r0), "r"(r1), "r"(r2), "r"(r3) : "memory");
}

__device__ __forceinline__ uint32_t tile_off(int r, int ch) {
    return (uint32_t)((r >> 3) * 4096 + (ch >> 3) * 1024 + (r & 7) * 128 + (((ch ^ r) & 7) << 4));
}
__device__ __forceinline__ int h_unit(int qt, int u) { return qt < 78 ? u * 78 + qt : 624; }
__device__ __forceinline__ int row_off(int r) { return 4096 + h_unit(r >> 7, (r >> 4) & 7) * 8192 + (r & 8) * 512 + (r & 7) * 144; }

__device__ __forceinline__ float4 lds128f(uint32_t a) {
    float4 v; asm volatile("ld.shared.v4.f32 {%0, %1, %2, %3}, [%4];\n" : "=f"(v.x), "=f"(v.y), "=f"(v.z), "=f"(v.w) : "r"(a) : "memory"); return v;
}
__device__ __forceinline__ uint64_t lds64(uint32_t a) { uint64_t v; asm volatile("ld.shared.u64 %0, [%1];\n" : "=l"(v) : "r"(a) : "memory"); return v; }
__device__ __forceinline__ uint4 lds128(uint32_t a) {
    uint4 v; asm volatile("ld.shared.v4.u32 {%0, %1, %2, %3}, [%4];\n" : "=r"(v.x), "=r"(v.y), "=r"(v.z), "=r"(v.w) : "r"(a) : "memory"); return v;
}
__device__ __forceinline__ void sts128(uint32_t a, uint32_t x, uint32_t y, uint32_t z, uint32_t w) {
    asm volatile("st.shared.v4.u32 [%0], {%1, %2, %3, %4};\n" ::"r"(a), "r"(x), "r"(y), "r"(z), "r"(w) : "memory");
}
__device__ __forceinline__ void mbar_arrive(uint32_t bar) {
    asm volatile("mbarrier.arrive.shared::cta.b64 _, [%0];\n" ::"r"(bar) : "memory");
}
__device__ __forceinline__ uint64_t mkaddr(uint32_t lo, uint32_t hi) { uint64_t a; asm("mov.b64 %0, {%1, %2};\n" : "=l"(a) : "r"(lo), "r"(hi)); return a; }
__device__ __forceinline__ void red_add(int* p) { asm volatile("red.relaxed.gpu.global.add.s32 [%0], 1;\n" ::"l"(p) : "memory"); }
__device__ __forceinline__ void red_release(int* p) {
    asm volatile("fence.proxy.async.global;\nfence.acq_rel.gpu;\nred.relaxed.gpu.global.add.s32 [%0], 1;\n" ::"l"(p) : "memory");
}
__device__ __forceinline__ void fence_async_global() { asm volatile("fence.proxy.async.global;\n" ::: "memory"); }
__device__ __forceinline__ void fence_async_smem() { asm volatile("fence.proxy.async.shared::cta;\n" ::: "memory"); }
__device__ __forceinline__ void bulk_s2g(void* dst, uint32_t src, uint32_t bytes) {
    asm volatile("cp.async.bulk.global.shared::cta.bulk_group [%0], [%1], %2;\ncp.async.bulk.commit_group;\n" ::"l"(dst), "r"(src), "r"(bytes) : "memory");
}
__device__ __forceinline__ void mma16816(float (&c)[4], uint32_t a0, uint32_t a1, uint32_t a2, uint32_t a3, uint32_t b0, uint32_t b1) {
    asm("mma.sync.aligned.m16n8k16.row.col.f32.bf16.bf16.f32 {%0, %1, %2, %3}, {%4, %5, %6, %7}, {%8, %9}, {%0, %1, %2, %3};\n"
        : "+f"(c[0]), "+f"(c[1]), "+f"(c[2]), "+f"(c[3]) : "r"(a0), "r"(a1), "r"(a2), "r"(a3), "r"(b0), "r"(b1));
}
__device__ __forceinline__ void mma1688(float (&c)[4], uint32_t a0, uint32_t a1, uint32_t b0) {
    asm("mma.sync.aligned.m16n8k8.row.col.f32.bf16.bf16.f32 {%0, %1, %2, %3}, {%4, %5}, {%6}, {%0, %1, %2, %3};\n"
        : "+f"(c[0]), "+f"(c[1]), "+f"(c[2]), "+f"(c[3]) : "r"(a0), "r"(a1), "r"(b0));
}
__device__ __forceinline__ uint32_t hadd2_f16(uint32_t a, uint32_t b) { uint32_t r; asm("add.rn.f16x2 %0, %1, %2;\n" : "=r"(r) : "r"(a), "r"(b)); return r; }
__device__ __forceinline__ uint32_t hadd2(uint32_t a, uint32_t b) { uint32_t r; asm("add.rn.bf16x2 %0, %1, %2;\n" : "=r"(r) : "r"(a), "r"(b)); return r; }
__device__ __forceinline__ uint32_t hmul2(uint32_t a, uint32_t b) { uint32_t r; asm("mul.rn.bf16x2 %0, %1, %2;\n" : "=r"(r) : "r"(a), "r"(b)); return r; }
__device__ __forceinline__ uint32_t hfma2(uint32_t a, uint32_t b, uint32_t c) { uint32_t r; asm("fma.rn.bf16x2 %0, %1, %2, %3;\n" : "=r"(r) : "r"(a), "r"(b), "r"(c)); return r; }

constexpr int SM_Q = 0;
constexpr int SM_KV = 65536;
constexpr int SM_ML = SM_KV + STAGES * KV_BYTES;
constexpr int SM_BAR = SM_ML + 1024;
constexpr int SM_TOTAL = SM_BAR + 256;
constexpr float SCALE_LOG2 = 1.4426950408889634f / 16.0f;
constexpr float KV_SCALE = 0.75f;
constexpr float KV_OFF = 6.f;
constexpr uint32_t KV_OFF2 = 0x46004600u;
constexpr uint32_t KV_NEG4 = 0xCE00CE00u;
constexpr uint32_t P_LIMIT = 0x78007800u;
constexpr float REF_UP = REFUP;
__device__ __forceinline__ uint32_t kvf(uint32_t a) {
    uint32_t r; asm("fma.rn.f16x2 %0, %1, %2, %3;\n" : "=r"(r) : "r"(a), "r"(pack_f16(KV_SCALE, KV_SCALE)), "r"(KV_OFF2)); return r;
}
enum { BAR_PP0 = 1, BAR_PP1 = 2, BAR_WG0 = 3, BAR_WG1 = 4, BAR_H0 = 5, BAR_H1 = 6, BAR_AUX = 7, BAR_BF = 8, BAR_H2 = 9, BAR_X = 10, BAR_GO = 11, BAR_WG2 = 12, BAR_ST = 13 };

struct Hot {
    const __nv_bfloat16 *wk, *wq, *x;
    Scratch* s;
};
struct Params {
    const __nv_bfloat16* deg_inv;
    const int *src, *dst;
    __nv_bfloat16* out;
    uint32_t dhi;
    int E;
    CUtensorMap tm_out;
    CUtensorMap tm_outc;
    CUtensorMap tm_w[3];
};
static_assert(offsetof(Params, tm_outc) == offsetof(Params, tm_out) + 128, "layout");
#define SC_PAIR (blockIdx.x < 104)
#define SC_TAIL (blockIdx.x >= NCTA - 2)
#define SC_LAST (blockIdx.x == NCTA - 1)
#define SC_HELP (SC_PAIR && rank)
#define SC_OWNER (!SC_HELP && !SC_LAST)
#define SC_QT1 (26 + (int)(blockIdx.x >> 1))
#define SC_QT0 (SC_PAIR ? (rank ? (int)(blockIdx.x >> 2) : SC_QT1) : SC_TAIL ? 78 : (int)blockIdx.x - 104)
#define SC_NKV (SC_LAST ? 50 : 75)
#define SC_NMC (SC_PAIR ? 25 : SC_TAIL ? 0 : 75)
#define SC_CLS (SC_PAIR ? (rank ? 0x120 ^ (blockIdx.x & 2) * 0x80 : 0x430) | (blockIdx.x & 2) >> 1 : SC_LAST ? 0x10 : 0x432)
#define SC_NW (SC_PAIR ? 8 : SC_LAST ? 0 : 4)
#define SC_ZB (2 * SC_QT1 + 1 - (int)rank)
#define SC_TZB(k) (rank && !(k) ? 156 : 2 * (k) - (int)rank)

__global__ void __cluster_dims__(2, 1, 1) __launch_bounds__(384, 1) k_main(const __grid_constant__ Hot H, const __grid_constant__ Params P) {
    extern __shared__ __align__(1024) uint8_t smem[];
    const uint32_t sb = (uint32_t)__cvta_generic_to_shared(smem);
    const int tid = threadIdx.x, wg = __shfl_sync(~0u, tid >> 7, 0);
    const int lane = tid & 31, g = lane >> 2, q = lane & 3;
    const uint32_t rank = blockIdx.x & 1;
    unsigned c_start; asm volatile("mov.u32 %0, %%clock;" : "=r"(c_start) :: "memory");
    const uint32_t bar_full = sb + SM_BAR, bar_q = bar_full + 32, bar_go = bar_full + 48;
    const uint32_t bar_pin = bar_full + 56;
    const uint32_t bar_qfree = bar_full + 72, bar_pdone = bar_full + 88, bar_zst = bar_full + 104, bar_rfree = bar_full + 120;
    const uint32_t bar_empty = bar_full + 128, bar_end = bar_full + 160, s_tm = bar_full + 184, bar_x = bar_full + 192;
    const uint32_t bar_a = sb + SM_ML;

    const int t = tid & 127, warp = __shfl_sync(~0u, t >> 5, 0);
    int ep = 0;
    if (wg & 2) {
        unsigned done;
        {
            uint4 ra[2], rb[2], rk[5][2];
            if (blockIdx.x < 128) {
                const int e = (blockIdx.x >> 4) * 32 + (g >> 1) * 8 + (blockIdx.x & 8) / 2 + (g & 1);
                const uint4* pq = (const uint4*)(H.wq + e * 256) + warp * 8 + q;
                const uint4* pk = (const uint4*)(H.wk + ((blockIdx.x & 7) * 32 + g) * 256) + warp * 8 + q;
                const uint4* pz = (const uint4*)(H.wk + 255 * 256) + warp * 8 + q;
#pragma unroll
                for (int s = 0; s < 2; s++) {
                    ra[s] = ldg_pinned(pq + 4 * s);
                    rb[s] = ldg_pinned(pq + 4 * s + 64);
#pragma unroll
                    for (int n = 0; n < 4; n++) rk[n][s] = ldg_pinned(pk + 4 * s + n * 256);
                    rk[4][s] = ldg_pinned(pz + 4 * s);
                }
            }
            asm volatile("{\n.reg .pred p;\nsetp.eq.s32 p, %2, 0;\nmov.u32 %0, 0;\n@p ld.global.cg.u32 %0, [%1];\n}\n" : "=r"(done) : "l"(&g_sync[SY_DONE * 32]), "r"(lane) : "memory");
            bar_arrive(BAR_X, 384);
            if (warp == 0 && elect()) {
#pragma unroll
                for (int i = 0; i < 21; i++) mbar_init(bar_full + 8 * i, i < 9 ? 1 : i < 16 ? 4 : i == 20 ? 11 : SC_TAIL ? 8 : 16);
#pragma unroll
                for (int i = 0; i < 4; i++) mbar_init(bar_a + 8 * i, 1);
                mbar_expect_tx(bar_pin, QB_BYTES / 2 + 512); mbar_expect_tx(bar_pin + 8, QB_BYTES / 2);
                asm volatile("fence.mbarrier_init.release.cluster;\n" ::: "memory");
            }
            __syncwarp();
            asm volatile("barrier.cluster.arrive.relaxed.aligned;\n" ::: "memory");
            if (blockIdx.x < 128) {
                float c[5][4] = {};
#pragma unroll
                for (int s = 0; s < 2; s++) {
#pragma unroll
                    for (int n = 0; n < 5; n++) mma16816(c[n], ra[s].x, rb[s].x, ra[s].y, rb[s].y, rk[n][s].x, rk[n][s].y);
#pragma unroll
                    for (int n = 0; n < 5; n++) mma16816(c[n], ra[s].z, rb[s].z, ra[s].w, rb[s].w, rk[n][s].z, rk[n][s].w);
                }
#pragma unroll
                for (int i = 0; i < 4; i++) {
                    const int r = i & 2, n = (i & 1) * 2;
                    sts128(sb + SM_KV + 3 * KV_BYTES + QB_BYTES + i * 2048 + t * 16, __float_as_uint(c[n][r] - c[4][r]), __float_as_uint(c[n][r + 1] - c[4][r]),
                           __float_as_uint(c[n + 1][r] - c[4][r]), __float_as_uint(c[n + 1][r + 1] - c[4][r]));
                }
            }
        }
        asm volatile("setmaxnreg.dec.sync.aligned.u32 %0;\n" ::"n"(REG_P));
        if (blockIdx.x < 128) {
            bar_sync(BAR_WG2, 128);
            float4 v[4];
#pragma unroll
            for (int i = 0; i < 4; i++) v[i] = lds128f(sb + SM_KV + 3 * KV_BYTES + QB_BYTES + (warp & 2) * 2048 + (lane & 1) * 2048 + i * 512 + ((warp & 1) * 16 + (lane >> 1)) * 16);
            constexpr float SC = SCALE_LOG2 / KV_SCALE;
            const int r = (warp & 1) * 4 + (lane >> 3);
            *(uint2*)(g_w + tile_off((blockIdx.x >> 3) * 16 + (warp & 2) * 4 + r, (blockIdx.x & 7) * 4 + ((lane >> 1) & 3)) + (lane & 1) * 8) =
                make_uint2(pack_f16_sat(((v[0].x + v[1].x) + (v[2].x + v[3].x)) * SC, ((v[0].y + v[1].y) + (v[2].y + v[3].y)) * SC) | 1,
                           pack_f16_sat(((v[0].z + v[1].z) + (v[2].z + v[3].z)) * SC, ((v[0].w + v[1].w) + (v[2].w + v[3].w)) * SC) | 1);
            if (warp != 1) {
                bar_arrive(BAR_AUX, 128);
            } else {
                bar_sync(BAR_AUX, 128);
                if (elect()) { red_add(&g_sync[SY_DONE * 32 + 4 + (blockIdx.x >> 5)]); }
                __syncwarp();
            }
        }
        else bar_sync(BAR_WG2, 128);
        if (warp == 1 && XD1 < 0) bar_arrive(BAR_GO, 160);
        auto load_a = [&](int j) {
            if (elect()) {
                mbar_expect_tx(bar_a + 8 * j, QB_BYTES);
                bulk_g2s(sb + SM_KV + j * KV_BYTES, g_w + j * QB_BYTES, QB_BYTES, bar_a + 8 * j);
            }
            __syncwarp();
        };
        if (warp == 0) {
            auto poll = [&]() { int c; asm volatile("ld.relaxed.gpu.global.s32 %0, [%1];\n" : "=r"(c) : "l"(&g_sync[SY_DONE * 32 + 4 + (lane & 3)]) : "memory"); return c; };
            int j = 0, c0 = poll(), c1;
            if (NPOLL > 1) asm volatile("nanosleep.u32 150;\n" ::: "memory");
#pragma unroll 1
            for (;;) {
                if (NPOLL > 1) c1 = poll();
#pragma unroll 1
                for (const uint32_t mk = __ballot_sync(~0u, c0 >= 32) & 15; (mk >> j) & 1; j++) load_a(j);
                if (j == 4) break;
                c0 = poll();
                if (NPOLL > 1) {
#pragma unroll 1
                    for (const uint32_t mk = __ballot_sync(~0u, c1 >= 32) & 15; (mk >> j) & 1; j++) load_a(j);
                }
            }
        } else if (warp & 1) {
#pragma unroll 1
            for (int j = warp >> 1, n = 0; j < 4;) {
                mbar_wait_bounded(bar_a + 8 * j, n & 1);
                uint32_t ok = 1;
#pragma unroll
                for (int i = 0; i < 32; i++) {
                    uint32_t v;
                    asm volatile("ld.shared.u32 %0, [%1];\n" : "=r"(v) : "r"(sb + SM_KV + j * KV_BYTES + i * 1024 + lane * 32 + g * 4) : "memory");
                    ok &= v;
                }
                if (__all_sync(~0u, ok)) {
                    if (elect()) asm volatile("mbarrier.arrive.shared::cta.b64 _, [%0];\nmbarrier.inval.shared::cta.b64 [%1];\n" ::"r"(bar_full + 8 * j), "r"(bar_a + 8 * j) : "memory");
                    __syncwarp();
                    j += 2; n = 0;
                } else {
                    asm volatile("{\n.reg .pred p;\nsetp.gt.s32 p, %0, 1000000;\n@p trap;\n}\n" ::"r"(++n) : "memory");
                    fence_async_smem();
                    __syncwarp();
                    load_a(j);
                }
            }
        }
        done = __shfl_sync(~0u, done, 0);
        ep = (int)(done / NCTA) + 1;
        asm volatile("barrier.cluster.wait.acquire.aligned;\n" ::: "memory");
        if (warp == 0) {
            asm volatile("st.shared.u64 [%0], %1;\n" ::"r"(s_tm), "l"(&P.tm_outc) : "memory");
            __syncwarp();
            if (elect()) {
                const uint8_t* base = (const uint8_t*)H.s;
                uint32_t cls = SC_CLS, bytes = KV_BYTES, moff = SC_NMC ? rank * (KV_BYTES / 2) : 0, step = 5 * KV_BYTES;
                const uint8_t* src = base;
                int next = 0;
                const int nit = SC_NKV + SC_NW;
#pragma unroll 1
                for (int j = 0; j < nit; j++) {
                    const uint32_t slot = sb + SM_KV + (j & 3) * KV_BYTES, fb = bar_full + 8 * (j & 3);
                    if (j == next) {
                        const int k = j - SC_NKV;
                        const int sw = SC_HELP ? j - 25 : -1;
                        next = j + 1;
                        if (j >= 3 && (unsigned)sw >= 5) next = k >= 0 ? next : j < 25 ? 25 : j < GO0 ? GO0 : j < 49 ? 49 : j < 50 ? 50 : 75;
                        if (j == SC_NMC) moff = 0;
                        if (j == 0 || j == 25 || j == 50) { src = base + (4096 + (cls & 15) * KV_BYTES + moff); cls >>= 4; }
                        if (SC_TAIL ? j == nit - 1 : j == GO0) mbar_arrive(bar_go);
                        int fo = -1, fv = 1;
                        if (j < 3) { fo = (SY_H0 + 5 * j + (SC_CLS & 15)) * 32; fv = 5; }
                        if (j == 3) { fo = SY_H1 * 32; fv = 79; }
                        if (sw == 1) fo = 25 * 32 + SC_QT1;
                        if (k == 0) fo = SY_B * 32;
                        if (k == 1) { fo = (SC_TAIL ? SY_AUX0 : SY_AUX) * 32; fv = SC_TAIL ? NAUX : NAUX / 3; }
                        if (fo >= 0) {
                            flag_wait(g_sync + fo, fv * ep);
                            fence_async_global();
                        }
                        if (sw == 2 || (k == 2 && !SC_TAIL)) {
                            uint32_t qs = sw == 2 ? offsetof(Scratch, q) + (2 * SC_QT1 + 1) * QB_BYTES : SC_PAIR ? offsetof(Scratch, agg) + SC_ZB * QB_BYTES : offsetof(Scratch, part) + SC_QT0 * (4 * PART_BYTES);
#pragma unroll 1
                            for (int w = 0; w < (k == 2 && SC_PAIR ? 1 : 2); w++) {
                                mbar_wait_sleep(bar_qfree + 8 * w, k == 2 && SC_HELP);
                                mbar_expect_tx(bar_q + 8 * w, SC_PAIR ? QB_BYTES : PART_BYTES);
                                if (!SC_PAIR) bulk_g2s(sb + SM_ML + w * 512, base + (qs + (w ? -512 : QB_BYTES)), 512, bar_q + 8 * w);
                                bulk_g2s(sb + SM_Q + w * QB_BYTES, base + qs, QB_BYTES, bar_q + 8 * w);
                                qs += sw == 2 ? -QB_BYTES : PART_BYTES + 512;
                            }
                        }
                        if ((sw | 1) == 3) {
                            mbar_wait_sleep(bar_pdone + 8 * (sw - 2), 0);
                            bulk_s2g(g_part + (blockIdx.x - 3 + sw) * PART_BYTES, slot, PART_BYTES);
                            asm volatile("cp.async.bulk.wait_group.read 0;\n" ::: "memory");
                        }
                        if (sw == 5) {
                            asm volatile("cp.async.bulk.wait_group 0;\n" ::: "memory");
                            red_release(&g_sync[SY_PART * 32]);
                        }
                        if (k == 0) {
                            asm volatile("prefetch.tensormap [%0];\n" ::"l"(&P.tm_outc) : "memory");
                            src = g_w + (12 - SC_NW) * QB_BYTES; bytes = step = QB_BYTES;
                        }
                        if (k == 2) next = SC_TAIL ? nit - 1 : nit;
                    }
                    mbar_wait_sleep(fb + (bar_empty - bar_full), (j >> 2) & 1);
                    mbar_expect_tx(fb, bytes);
                    if (j < SC_NMC) bulk_g2s_mc(slot + moff, src, KV_BYTES / 2, fb, 3);
                    else bulk_g2s(slot, src, bytes, fb);
                    src += step;
                }
            }
        } else {
            if (warp == 2 && SC_OWNER) {
                uint8_t* dst = g_hz + 4096 + h_unit(SC_QT0, 0) * 8192;
                auto send = [&](int u0, int u1) {
#pragma unroll
                    for (int u = u0; u < u1; u++) {
                        bulk_s2g(dst + u * (78 * 8192), sb + SM_Q + u * 8192, 8192);
                        asm volatile("cp.async.bulk.wait_group 0;\n" ::: "memory");
                    }
                };
                int* f0 = &g_sync[(SY_H0 + SC_QT0 / 5) * 32];
                bar_sync(BAR_H0, 64);
                if (elect()) {
                    send(0, 1);
                    if (SC_QT0 < 65) red_release(f0);
                }
                bar_sync(BAR_H1, 160);
                if (elect()) {
                    if (HDEF >= 0) mbar_wait(bar_full + 8 * HDEF, 0);
                    if (!SC_TAIL) send(1, 4);
                    mbar_arrive(bar_q);
                }
                bar_sync(BAR_H2, 160);
                if (elect()) {
                    if (!SC_TAIL) { send(4, 8); mbar_arrive(bar_q + 8); }
                    red_release(&g_sync[SY_H1 * 32]);
                }
                __syncwarp();
            }
        }
    } else {
        const uint32_t sq = sb + SM_Q + wg * QB_BYTES;
        const uint32_t qbar = bar_q + 8 * wg;
        const uint32_t dq0 = __shfl_sync(~0u, ((sq & 0x3FFFF) >> 4) | (64u << 16), 0);
        const uint32_t dk0 = __shfl_sync(~0u, (((sb + SM_KV) & 0x3FFFF) >> 4) | (64u << 16), 0);
        float o[128];
        int it = 4;
        const uint32_t dhi = P.dhi;
        uint32_t rel_addr;
        auto rel_target = [&](uint32_t r) {
            asm("mapa.shared::cluster.u32 %0, %1, %2;\n" : "=r"(rel_addr) : "r"(bar_empty), "r"(r));
            if (lane >= 2) rel_addr = 0;
            asm volatile("" : "+r"(rel_addr));
        };
        rel_target(SC_NMC ? rank ^ (lane & 1) : rank);
        auto release = [&](int st) {
            asm volatile("{\n.reg .pred p;\nsetp.ne.u32 p, %1, 0;\n@p mbarrier.arrive.shared::cluster.b64 _, [%0];\n}\n"
                         ::"r"(rel_addr + 8 * st), "r"(rel_addr) : "memory");
        };
        const bool active = !(SC_TAIL && wg == 1);
        auto pp_sync = [&]() { if (!SC_TAIL) bar_sync(BAR_PP0 + wg, 256); };
        auto pp_arrive = [&]() { if (!SC_TAIL) bar_arrive(BAR_PP1 - wg, 256); };
        auto warp_arrive = [&](uint32_t bar) {
            __syncwarp();
            asm volatile("{\n.reg .pred p;\nelect.sync _|p, -1;\n@p mbarrier.arrive.shared::cta.b64 _, [%0];\n}\n" ::"r"(bar + 8 * wg) : "memory");
        };
        auto peer_arrive = [&]() {
            asm volatile("{\n.reg .pred p;\n.reg .b32 a;\nelect.sync _|p, -1;\nmapa.shared::cluster.u32 a, %0, %1;\n"
                         "@p mbarrier.arrive.shared::cluster.b64 _, [a];\n}\n" ::"r"(bar_rfree), "r"(rank ^ 1) : "memory");
        };
        auto stage_q = [&]() {
            auto pk = [&](int i) { return QRND(pack_f16_sat(o[i], o[i + 1])); };
#pragma unroll
            for (int i = 0; i < 16; i++)
                stmatrix_x4(sq + warp * 8192 + tile_off(lane & 15, 2 * i + (lane >> 4)), pk(8 * i), pk(8 * i + 2), pk(8 * i + 4), pk(8 * i + 6));
        };
        float s[40];
        auto issue_qk = [&](int st) {
            const uint64_t kb = mkaddr(dk0 + st * (KV_BYTES >> 4), dhi);
            const uint64_t qd = mkaddr(dq0 + ((uint32_t)it >> 24), dhi);
            wgmma_ss_n80_init(s, qd + 198, kb + 198);
#pragma unroll
            for (int kk = 0; kk < 15; kk++) wgmma_ss_n80(s, qd + ((kk >> 2) * 64 + (kk & 3) * 2), kb + ((kk >> 2) * 64 + (kk & 3) * 2));
            wg_commit();
        };

        {
            const int rb = (2 * SC_QT0 + wg) * 64 + warp * 16;
            const uint32_t xbar = bar_x + 32 * wg + 8 * warp;
            if (PFX && rb < NN && t == 0) asm volatile("prefetch.global.L2 [%0];" :: "l"(H.x + (size_t)rb * 256) : "memory");
            if (elect()) {
                mbar_init(xbar, 1);
                asm volatile("fence.mbarrier_init.release.cluster;\nfence.proxy.async.shared::cta;\n" ::: "memory");
                mbar_expect_tx(xbar, rb < NN ? 8192 : 0);
            }
            asm volatile("barrier.cluster.arrive.relaxed.aligned;\n" ::: "memory");
            if (wg == 1) pp_arrive();
            bar_sync(BAR_X, 384);
            if (wg == 1 && XD1 < 0) bar_sync(BAR_GO, 160);
            else if (XD0 | XD1 | XDW) { unsigned c; do { asm volatile("mov.u32 %0, %%clock;" : "=r"(c) :: "memory"); } while ((int)(c - c_start) < (wg ? XD1 : XD0) + warp * XDW); }
            if (rb < NN && elect()) bulk_g2s(sq + warp * 8192, H.x + (size_t)rb * 256, 8192, xbar);
            if (rb >= NN) {
#pragma unroll 1
                for (int i = 0; i < 16; i++) sts128(sq + warp * 8192 + i * 512 + lane * 16, 0, 0, 0, 0);
            }
            __syncwarp();
            mbar_wait(xbar, 0);
            uint4 xa[8], xb[8];
#pragma unroll
            for (int s = 0; s < 8; s++) {
                xa[s] = lds128(sq + (warp * 16 + g) * 512 + (4 * s + q) * 16);
                xb[s] = lds128(sq + (warp * 16 + g + 8) * 512 + (4 * s + q) * 16);
            }
            float sm[2][4], sq2[2][4][4];
#pragma unroll
            for (int i = 0; i < 4; i++) {
                sm[0][i] = sm[1][i] = 0.f;
#pragma unroll
                for (int k = 0; k < 4; k++) sq2[0][k][i] = sq2[1][k][i] = 0.f;
            }
#pragma unroll
            for (int s = 0; s < 8; s++) {
#pragma unroll
                for (int hh = 0; hh < 2; hh++) {
                    const uint4 v = hh ? xb[s] : xa[s];
                    mma16816(sm[hh], v.x, v.y, v.z, v.w, 0x3F803F80u, 0x3F803F80u);
                    mma1688(sq2[hh][0], v.x, v.y, v.x); mma1688(sq2[hh][1], v.x, v.y, v.y);
                    mma1688(sq2[hh][2], v.z, v.w, v.z); mma1688(sq2[hh][3], v.z, v.w, v.w);
                }
            }
            float inv[2], off[2];
#pragma unroll
            for (int hh = 0; hh < 2; hh++) {
                const float mean = (sm[hh][0] + sm[hh][2]) * (1.f / 256.f);
                const float d0 = (sq2[hh][0][0] + sq2[hh][2][0]) + (sq2[hh][1][2] + sq2[hh][3][2]);
                const float d1 = (sq2[hh][0][1] + sq2[hh][2][1]) + (sq2[hh][1][3] + sq2[hh][3][3]);
                const float ss = __shfl_sync(~0u, (g & 1) ? d1 : d0, g * 4 + (g >> 1));
                const float var = fmaxf(ss * (1.f / 256.f) - mean * mean, 0.f);
                float sd;
                asm("sqrt.approx.ftz.f32 %0, %1;\n" : "=f"(sd) : "f"(bf_round(bf_round(var) + 1e-5f)));
                asm("rcp.approx.ftz.f32 %0, %1;\n" : "=f"(inv[hh]) : "f"(bf_round(sd)));
                off[hh] = -mean * inv[hh];
            }
            uint32_t a[64];
#pragma unroll
            for (int s = 0; s < 8; s++) {
                a[8 * s] = xa[s].x; a[8 * s + 1] = xb[s].x; a[8 * s + 2] = xa[s].y; a[8 * s + 3] = xb[s].y;
                a[8 * s + 4] = xa[s].z; a[8 * s + 5] = xb[s].z; a[8 * s + 6] = xa[s].w; a[8 * s + 7] = xb[s].w;
            }
            fence_regs(a);
            if (wg == 1 && __any_sync(~0u, inv[0] + inv[1] != -1.f)) bar_arrive(BAR_ST, 256);
            asm volatile("setmaxnreg.inc.sync.aligned.u32 %0;\n" ::"n"(REG_C));
            fence_regs(a);
#pragma unroll
            for (int i = 0; i < 64; i++)
                a[i] = pack_f16(fmaf(bf_lo(a[i]), inv[i & 1], off[i & 1]), fmaf(bf_hi(a[i]), inv[i & 1], off[i & 1]));
            if (SC_OWNER) {
#pragma unroll
                for (int i = 0; i < 16; i++) {
                    const uint32_t mk = (i == 15 && q == 3) ? 0xFFFFu : ~0u;
                    stmatrix_x4(sq + warp * 8192 + tile_off(lane & 15, 2 * i + (lane >> 4)), kvf(a[4 * i]), kvf(a[4 * i + 1]),
                                kvf(a[4 * i + 2] & mk), kvf(a[4 * i + 3] & mk));
                }
                fence_async_smem();
                if (tid < 32) bar_arrive(BAR_H0, 64);
                bar_arrive(wg ? BAR_H2 : BAR_H1, 160);
            }
            asm volatile("barrier.cluster.wait.acquire.aligned;\n" ::: "memory");
            if (wg == 0) bar_sync(BAR_ST, 256);
            if (active) {
                fence_regs(a);
#pragma unroll
                for (int c = 0; c < 4; c++) {
                    if (c == 1) {
                        if (wg == 1) {
                            wg_wait<0>();
                            release(0);
                        }
                        pp_sync();
                    }
                    mbar_wait(bar_full + 8 * c, 0);
                    const uint64_t wb = mkaddr(dk0 + c * (KV_BYTES >> 4), dhi);
                    wg_fence();
#pragma unroll
                    for (int kk = 0; kk < 4; kk++) {
                        if (c | kk) wgmma_rs_n256_tb(o, a[16 * c + 4 * kk], a[16 * c + 4 * kk + 1], a[16 * c + 4 * kk + 2], a[16 * c + 4 * kk + 3], wb + kk * 512);
                        else wgmma_rs_n256_tb_init(o, a[0], a[1], a[2], a[3], wb);
                    }
                    wg_commit();
                    if (c > 0) { wg_wait<1>(); if (c > 1 || wg == 0) release(c - 1); }
                }
                if (wg == 0) pp_arrive();
                wg_wait<0>();
                fence_regs(o);
                release(3);
                if (SC_OWNER) mbar_wait(qbar, 0);
                stage_q();
                fence_async_smem();
                bar_sync(BAR_WG0 + wg, 128);
                mbar_wait(bar_full, 1);
                wg_fence();
                issue_qk(0);
                if (wg == 1) pp_arrive();
            } else {
                peer_arrive();
            }
        }

        uint32_t p[20];
        float m0 = 0.f, m1 = 0.f, e0, e1, l0, l1;
        uint32_t plim;
        uint32_t qphase = (SC_OWNER && active) ? 1 : 0;
        auto issue_pv = [&](int st, int acc) {
            const uint64_t vb = mkaddr(dk0 + st * (KV_BYTES >> 4), dhi);
            wgmma_rs_n256_tb_pred(o, p[0], p[1], p[2], p[3], vb, acc);
#pragma unroll
            for (int kk = 1; kk < 5; kk++)
                wgmma_rs_n256_tb(o, p[4 * kk], p[4 * kk + 1], p[4 * kk + 2], p[4 * kk + 3], vb + kk * 512);
            wg_commit();
        };
        const uint32_t mq_addr = sq + tile_off(warp * 16 + g, 31) + 14;
        auto exceeds = [&](const uint32_t (&p)[20]) {
            uint32_t a = __vimax3_s16x2(P_LIMIT, p[0], p[1]), b = __vimax3_s16x2(p[2], p[3], p[4]);
#pragma unroll
            for (int i = 5; i < 17; i += 4) { a = __vimax3_s16x2(a, p[i], p[i + 1]); b = __vimax3_s16x2(b, p[i + 2], p[i + 3]); }
            a = __vimax3_s16x2(a, p[17], p[18]);
            return __any_sync(~0u, __vimax3_s16x2(a, b, p[19]) != plim);
        };
        auto remax = [&](float& a, float& b, bool store) {
            float a1 = fmaxf(s[0], s[1]), b1 = fmaxf(s[2], s[3]), a2 = fmaxf(s[4], s[5]), b2 = fmaxf(s[6], s[7]);
#pragma unroll
            for (int i = 2; i < 10; i++) {
                a1 = fmaxf(a1, s[4 * i]); a2 = fmaxf(a2, s[4 * i + 1]);
                b1 = fmaxf(b1, s[4 * i + 2]); b2 = fmaxf(b2, s[4 * i + 3]);
            }
            a1 = fmaxf(a1, a2); b1 = fmaxf(b1, b2);
            a1 = fmaxf(a1, __shfl_xor_sync(~0u, a1, 1)); b1 = fmaxf(b1, __shfl_xor_sync(~0u, b1, 1));
            a1 = fmaxf(a1, __shfl_xor_sync(~0u, a1, 2)); b1 = fmaxf(b1, __shfl_xor_sync(~0u, b1, 2));
            a = fmaxf(a, a1 - e0 + REF_UP); b = fmaxf(b, b1 - e1 + REF_UP);
            const uint32_t u = pack_f16_sat((m0 + a) * (-1.f / KV_OFF), (m1 + b) * (-1.f / KV_OFF));
            const float g0 = (m0 + a) + KV_OFF * f16_lo(u), g1 = (m1 + b) + KV_OFF * f16_hi(u);
            const bool x0 = fabsf(g0) <= 1.f, x1 = fabsf(g1) <= 1.f;
            if (x0) a -= g0;
            if (x1) b -= g1;
            const float da = a + e0, db = b + e1;
            m0 += a; m1 += b;
            e0 = x0 ? 0.f : g0; e1 = x1 ? 0.f : g1;
            plim = (x0 && x1) ? P_LIMIT : 0u;
            asm volatile("{\n.reg .pred p;\nsetp.ne.s32 p, %3, 0;\n@p st.shared.u16 [%0], %1;\n@p st.shared.u16 [%0 + 4096], %2;\n}\n"
                         ::"r"(mq_addr), "h"((unsigned short)u), "h"((unsigned short)(u >> 16)), "r"((int)(store && q == 0)) : "memory");
#pragma unroll
            for (int i = 0; i < 10; i++) {
                p[2 * i] = pack_f16(ex2(s[4 * i] - da), ex2(s[4 * i + 1] - da));
                p[2 * i + 1] = pack_f16(ex2(s[4 * i + 2] - db), ex2(s[4 * i + 3] - db));
            }
            fence_regs(p);
            fence_async_smem();
            __syncwarp();
        };

        auto row_sums = [&](float& z0, float& z1) {
            z0 = quad_last(o[125]); z1 = quad_last(o[127]);
            l0 = z0 * (KV_SCALE / KV_OFF); l1 = z1 * (KV_SCALE / KV_OFF);
        };
        auto cut = [&]() { asm volatile("{\n.reg .pred p;\nsetp.lt.s32 p, %0, 0;\nL:\n@p pmevent 0;\n@p bra L;\n}\n" ::"r"(it) : "memory"); };
        auto stats = [&]() { return (q & 2) ? ((q & 1) ? l1 : m1) : ((q & 1) ? l0 : m0); };
        const int nseg = SC_HELP ? 2 : 1;
        if (active) {
#pragma unroll 1
        for (int seg = 0;; seg++) {
            wg_wait<0>();
            fence_regs(s);
            e0 = e1 = 0.f;
            const int it0 = it, itl = __shfl_sync(~0u, seg + 1 < nseg ? 3 + 25 : 3 + SC_NKV, 0);
            const int itx = (wg == 1 && seg + 1 == nseg) ? itl : -1;
            bool redo = true, have = !seg;
#pragma unroll 1
            for (;;) {
                if (!have) {
#pragma unroll
                    for (int i = 0; i < 20; i++) p[i] = pack_f16(ex2(s[2 * i]), ex2(s[2 * i + 1]));
                    redo = exceeds(p);
                }
                if (redo) {
                    float d0 = it != it0 ? 0.f : -INFINITY, d1 = d0;
                    remax(d0, d1, it != itl);
                    if (it != it0) {
                        const float a0 = ex2(-d0), a1 = ex2(-d1);
#pragma unroll
                        for (int i = 0; i < 32; i++) { o[4 * i] *= a0; o[4 * i + 1] *= a0; o[4 * i + 2] *= a1; o[4 * i + 3] *= a1; }
                    }
                }
                if (it == it0 && (seg || SC_OWNER)) {
                    fence_async_smem();
                    warp_arrive(bar_pdone);
                }
                if (it == itl) break;
                const int stp = it & 3;
                it++;
                mbar_wait(bar_full + 8 * (it & 3), (it >> 2) & 1);
                pp_sync();
                fence_regs(o); fence_regs(p);
                wg_fence();
                issue_qk(it & 3);
                if (it == itx) {
                    wg_wait<0>();
                    if (SC_PAIR) peer_arrive(); else warp_arrive(bar_qfree);
                    bar_sync(BAR_ST, 256);
                }
                wg_fence();
                issue_pv(stp, it - 1 - it0);
                pp_arrive();
                if (it == itl && itx < 0) {
                    wg_wait<1>();
                    warp_arrive(bar_qfree);
                }
                have = SC_TAIL || it == itx;
                if (have) {
                    uint32_t p2[20];
                    wg_wait<1>();
                    fence_regs(s);
#pragma unroll
                    for (int i = 0; i < 20; i++) p2[i] = pack_f16(ex2(s[2 * i]), ex2(s[2 * i + 1]));
                    redo = exceeds(p2);
                    if (redo) asm volatile("wgmma.wait_group.sync.aligned 0;\nnanosleep.u32 0;\n" ::: "memory");
                    else wg_wait<0>();
                    fence_regs(o); fence_regs(p);
#pragma unroll
                    for (int i = 0; i < 20; i++) p[i] = p2[i];
                } else {
                    wg_wait<0>();
                    fence_regs(s); fence_regs(o); fence_regs(p);
                }
                release(stp);
                if (it == SC_NMC) rel_target(rank);
            }
            if (seg + 1 < nseg) pp_sync();
            fence_regs(o); fence_regs(p);
            wg_fence();
            issue_pv(it & 3, 1);
            asm volatile("{\n.reg .pred p;\nsetp.ne.s32 p, %0, 0;\n@p bar.arrive %1, 256;\n}\n" ::"r"((int)(seg + 1 == nseg && (wg ? SC_PAIR && ZHOLD : !SC_TAIL))), "r"(BAR_ST + wg) : "memory");
            it++;
            if (seg + 1 == nseg) break;
            const int is = it - 2 + wg;
            uint32_t dst = sb + SM_KV + (is & 3) * KV_BYTES + wg * 512 + warp * 8192 + lane * 16;
            uint32_t dml = sb + SM_KV + (is & 3) * KV_BYTES + (wg ? 0 : QB_BYTES) + t * 4;
            asm volatile("" : "+r"(dst), "+r"(dml));
            mbar_wait(qbar, qphase); qphase ^= 1;
            unsigned short u0, u1;
            asm volatile("ld.shared.u16 %0, [%2];\nld.shared.u16 %1, [%2 + 4096];\n" : "=h"(u0), "=h"(u1) : "r"(mq_addr) : "memory");
            mbar_wait(bar_full + 8 * (it & 3), (it >> 2) & 1);
            wg_wait<0>();
            fence_regs(o);
            float z0, z1;
            row_sums(z0, z1);
            release((it - 1) & 3);
            wg_fence();
            issue_qk(it & 3);
            pp_arrive();
#pragma unroll
            for (int i = 0; i < 128; i++) o[i] -= (i & 2) ? z1 : z0;
            fence_regs(o);
            mbar_wait(bar_empty + 8 * (is & 3), (is >> 2) & 1);
            asm volatile("st.shared.f32 [%0], %1;\n" ::"r"(dml), "f"(stats()) : "memory");
            m0 = -KV_OFF * f16_lo(u0); m1 = -KV_OFF * f16_lo(u1);
            plim = fmaxf(fabsf(m0), fabsf(m1)) <= 3072.f ? P_LIMIT : 0u;
            uint32_t v[2][8] = {};
#pragma unroll
            for (int i = 0; i < 8; i++) {
                uint32_t *w = v[i & 1], *u = v[(i & 1) ^ 1];
#pragma unroll
                for (int j = 0; j < 8; j++) w[j] = pack_bf16(o[16 * i + 2 * j], o[16 * i + 2 * j + 1]);
                sts128(dst + i * 1024, w[0], w[1], w[2], w[3]);
                sts128(dst + i * 1024 + 512, w[4], w[5], w[6], w[7]);
                if (i) asm volatile("{\n.reg .pred p;\nsetp.lt.s32 p, %9, 0;\nL:\n@p st.shared.v4.u32 [%0], {%1, %2, %3, %4};\n@p st.shared.v4.u32 [%0 + 16], {%5, %6, %7, %8};\n@p bra L;\n}\n"
                             ::"r"(dst), "r"(u[0]), "r"(u[1]), "r"(u[2]), "r"(u[3]), "r"(u[4]), "r"(u[5]), "r"(u[6]), "r"(u[7]), "r"(it) : "memory");
            }
        }
        constexpr int IW = 4 + 75;
        uint32_t a[64];
        if (wg == 0 && (SC_PAIR || SC_LAST)) {
            uint32_t rq, rml, rbar;
            asm volatile("mapa.shared::cluster.u32 %0, %3, %6;\nmapa.shared::cluster.u32 %1, %4, %6;\nmapa.shared::cluster.u32 %2, %5, %6;\n"
                         : "=r"(rq), "=r"(rml), "=r"(rbar) : "r"(sb + SM_Q + QB_BYTES + warp * 8192 + lane * 16), "r"(sb + SM_ML + 512 + t * 4),
                         "r"(bar_pin), "r"(rank ^ 1));
            auto send = [&](int i) {
                asm volatile("st.async.weak.shared::cluster.mbarrier::complete_tx::bytes.v4.b32 [%0], {%1, %2, %3, %4}, [%5];\n"
                             ::"r"(rq + i * 512), "r"(a[4 * i]), "r"(a[4 * i + 1]), "r"(a[4 * i + 2]), "r"(a[4 * i + 3]), "r"(rbar + (i & 8)) : "memory");
            };
            mbar_wait(bar_rfree, 0);
            wg_wait<0>();
            fence_regs(o);
            release((it - 1) & 3);
            float z0, z1;
            row_sums(z0, z1);
            asm volatile("st.async.weak.shared::cluster.mbarrier::complete_tx::bytes.f32 [%0], %1, [%2];\n" ::"r"(rml), "f"(stats()), "r"(rbar) : "memory");
#pragma unroll
            for (int i = 0; i < 16; i++) {
                a[4 * i] = pack_bf16(o[8 * i] - z0, o[8 * i + 1] - z0); a[4 * i + 1] = pack_bf16(o[8 * i + 2] - z1, o[8 * i + 3] - z1);
                a[4 * i + 2] = pack_bf16(o[8 * i + 4] - z0, o[8 * i + 5] - z0); a[4 * i + 3] = pack_bf16(o[8 * i + 6] - z1, o[8 * i + 7] - z1);
                if (i * SND0 / 16 != (i + 1) * SND0 / 16) send(i * SND0 / 16);
                if (i % CUT2 == CUT2 - 1) cut();
            }
            if (SC_PAIR) {
                float z[128];
                const uint32_t dkz = dk0 + ((uint32_t)it >> 24), dqz = dq0 + ((uint32_t)it >> 24);
                auto gemm = [&](int c) {
                    mbar_wait(bar_full + 8 * ((IW + c) & 3), ((IW + c) >> 2) & 1);
                    const uint64_t wb = mkaddr(dkz + ((IW + c) & 3) * (KV_BYTES >> 4), dhi), ab = mkaddr(dqz + c * 64, dhi);
                    wg_fence();
#pragma unroll
                    for (int kk = 0; kk < 4; kk++) {
                        if (c | kk) wgmma_ss_n256_tb(z, ab + kk * 2, wb + kk * 512);
                        else wgmma_ss_n256_tb_init(z, ab, wb);
                    }
                    wg_commit();
                };
                auto release2 = [&](int c) {
                    asm volatile("{\n.reg .pred p;\nsetp.ne.u32 p, %1, 0;\n@p mbarrier.arrive.shared::cluster.b64 _, [%0], 2;\n}\n"
                                 ::"r"(rel_addr + 8 * ((IW + c) & 3)), "r"(rel_addr) : "memory");
                };
                mbar_wait(qbar, qphase);
                if (ZHOLD) bar_sync(BAR_ST + 1, 256);
                gemm(0);
#pragma unroll
                for (int i = SND0; i < 16; i++) send(i);
#pragma unroll
                for (int c = 1; c < 4; c++) { gemm(c); if (c == 3) pp_arrive(); wg_wait<1>(); release2(c - 1); }
                wg_wait<0>();
                fence_regs(z);
                release2(3);
#pragma unroll
                for (int i = 0; i < 16; i++) {
                    sts128(sq + warp * 8192 + lane * 16 + i * 512, pack_bf16(z[8 * i], z[8 * i + 1]), pack_bf16(z[8 * i + 2], z[8 * i + 3]),
                           pack_bf16(z[8 * i + 4], z[8 * i + 5]), pack_bf16(z[8 * i + 6], z[8 * i + 7]));
                    if (i == 3 || i == 15) bar_arrive(i == 3 ? BAR_BF : BAR_H0, 256);
                }
            } else {
#pragma unroll
                for (int i = SND0; i < 16; i++) send(i);
            }
        } else {
            const int pair = SC_PAIR;
            const bool glob = !(pair || SC_TAIL);
            const uint32_t ml = sb + SM_ML + (t & ~3) * 4, src = (glob ? sq : sb + SM_Q + QB_BYTES) + warp * 8192 + lane * 16;
            const uint64_t tm = lds64(s_tm);
            wg_wait<0>();
            fence_regs(o);
            release((IW - 1) & 3);
            float c0, c1;
            row_sums(c0, c1);
            mbar_wait(glob ? qbar : bar_pin, glob ? qphase : 0);
            const float4 ps = lds128f(ml + (glob ? wg * 512 : 512));
            auto load = [&](int i) {
                asm volatile("ld.shared.v4.u32 {%0, %1, %2, %3}, [%4];\n" : "=r"(a[4 * i]), "=r"(a[4 * i + 1]), "=r"(a[4 * i + 2]), "=r"(a[4 * i + 3]) : "r"(src + i * 512) : "memory");
            };
#pragma unroll
            for (int i = 0; i < 8; i++) load(i);
            const float n0 = fmaxf(m0, ps.x), n1 = fmaxf(m1, ps.z);
            const float a0 = ex2(m0 - n0), a1 = ex2(m1 - n1), b0 = ex2(ps.x - n0), b1 = ex2(ps.z - n1);
            const float i0 = rcp(l0 * a0 + ps.y * b0), i1 = rcp(l1 * a1 + ps.w * b1);
            const float r0 = a0 * i0, r1 = a1 * i1;
            c0 *= -r0; c1 *= -r1;
            const uint32_t u0 = pack_bf16(b0 * i0, b0 * i0), u1 = pack_bf16(b1 * i1, b1 * i1);
#pragma unroll
            for (int i = 0; i < 32; i++) {
                if (i == 16) {
                    if (!glob) mbar_wait(bar_pin + 8, 0);
#pragma unroll
                    for (int j = 8; j < 16; j++) load(j);
                }
                a[2 * i] = hfma2(a[2 * i], u0, pack_bf16(fmaf(o[4 * i], r0, c0), fmaf(o[4 * i + 1], r0, c0)));
                a[2 * i + 1] = hfma2(a[2 * i + 1], u1, pack_bf16(fmaf(o[4 * i + 2], r1, c1), fmaf(o[4 * i + 3], r1, c1)));
            }
            float y[2][32];
            auto gemm = [&](int c, int kh) {
                if (!kh) mbar_wait(bar_full + 8 * ((IW + c) & 3), (((IW + c) >> 2) & 1) ^ pair);
                const uint64_t wb = mkaddr(dk0 + ((IW + c) & 3) * (KV_BYTES >> 4), dhi - 192);
                wg_fence();
#pragma unroll
                for (int kk = 8 * kh; kk < 8 * kh + 8; kk++) {
                    if (kk) wgmma_rs_n64_tb(y[c & 1], a[4 * kk], a[4 * kk + 1], a[4 * kk + 2], a[4 * kk + 3], wb + kk * 128);
                    else wgmma_rs_n64_tb_init(y[c & 1], a[0], a[1], a[2], a[3], wb);
                }
                wg_commit();
            };
            const int rg = (pair ? SC_ZB : 2 * SC_QT0 + wg) * 8 + warp * 2;
            const uint32_t zsrc = sb + SM_Q + warp * 8192 + lane * 16, stg = sq + warp * 8192 + (lane & 15) * 128 + (((lane >> 4) ^ lane) & 7) * 16;
            uint4 z[4] = {};
            auto load_z = [&](int cb) {
#pragma unroll
                for (int i = 0; i < 4; i++) {
                    asm volatile("{\n.reg .pred p;\nsetp.ne.u32 p, %4, 0;\n@p ld.shared.v4.u32 {%0, %1, %2, %3}, [%5];\n}\n"
                                 : "+r"(z[i].x), "+r"(z[i].y), "+r"(z[i].z), "+r"(z[i].w) : "r"(pair), "r"(zsrc + (4 * cb + i) * 512) : "memory");
                }
            };
            auto stage = [&](int cb) {
                const float* x = y[cb & 1];
#pragma unroll
                for (int i = 0; i < 4; i++)
                    stmatrix_x4((stg ^ (32 * i)) + cb * 2048, hadd2(pack_bf16(x[8 * i], x[8 * i + 1]), z[i].x), hadd2(pack_bf16(x[8 * i + 2], x[8 * i + 3]), z[i].y),
                                hadd2(pack_bf16(x[8 * i + 4], x[8 * i + 5]), z[i].z), hadd2(pack_bf16(x[8 * i + 6], x[8 * i + 7]), z[i].w));
            };
            auto output = [&](int cb) {
                fence_async_smem();
                __syncwarp();
                asm volatile("{\n.reg .pred p;\nelect.sync _|p, -1;\n"
                             "@p cp.reduce.async.bulk.tensor.4d.global.shared::cta.add.tile.bulk_group [%0, {0, 0, %1, %2}], [%3];\n}\n"
                             ::"l"(tm), "r"(cb), "r"(rg), "r"(sq + warp * 8192 + cb * 2048) : "memory");
            };
            pp_sync();
            gemm(0, 0);
            gemm(0, 1);
#pragma unroll
            for (int c = 0; c < 4; c++) {
                if (c < 2) asm volatile("{\n.reg .pred p;\nsetp.ne.s32 p, %0, 0;\n@p bar.sync %1, 256;\n}\n" ::"r"(pair), "r"(c ? BAR_H0 : BAR_BF) : "memory");
                load_z(c);
                if (c < 3) { gemm(c + 1, 0); wg_wait<1>(); } else wg_wait<0>();
                fence_regs(y[c & 1]);
                stage(c);
                if (c < 3) gemm(c + 1, 1);
                if (c == 2 && glob) pp_arrive();
                output(c);
            }
            asm volatile("cp.async.bulk.commit_group;\ncp.async.bulk.wait_group.read 0;\n" ::: "memory");
            if (SC_TAIL) { release(0); release(1); release(2); release(3); }
        }
        } else {
            wg_wait<0>();
        }
        if (SC_TAIL) {
        float o[128];
        auto emit = [&](uint32_t base, int lane, int row0, uint8_t* wdst, int turn) {
#pragma unroll
            for (int hh = 0; hh < 2; hh++) {
                if (turn > 0) mbar_wait(bar_zst + 8 * hh, (turn - 1) & 1);
#pragma unroll
                for (int i = 0; i < 8; i++)
                    stmatrix_x4(base + tile_off(8 * hh + (lane & 7), 4 * i + (lane >> 3)),
                                pack_bf16(o[16 * i + 2 * hh], o[16 * i + 2 * hh + 1]), pack_bf16(o[16 * i + 4 + 2 * hh], o[16 * i + 5 + 2 * hh]),
                                pack_bf16(o[16 * i + 8 + 2 * hh], o[16 * i + 9 + 2 * hh]), pack_bf16(o[16 * i + 12 + 2 * hh], o[16 * i + 13 + 2 * hh]));
                fence_async_smem();
                __syncwarp();
                if (wdst) {
                    if (lane < 4)
                        asm volatile("cp.async.bulk.global.shared::cta.bulk_group [%0], [%1], 1024;\n"
                                     ::"l"(wdst + ((turn & 1) ? hh * 4096 + lane * 1024 : hh * 1024 + lane * QB_BYTES)), "r"(base + hh * 4096 + lane * 1024) : "memory");
                    asm volatile("cp.async.bulk.commit_group;\n" ::: "memory");
                } else {
                    asm volatile("{\n.reg .pred p;\nsetp.eq.s32 p, %3, 0;\n"
                                 "@p cp.reduce.async.bulk.tensor.4d.global.shared::cta.add.tile.bulk_group [%0, {0, 0, 0, %1}], [%2];\n"
                                 "cp.async.bulk.commit_group;\n}\n"
                                 ::"l"(&P.tm_out), "r"((row0 >> 3) + hh), "r"(base + hh * 4096), "r"(lane) : "memory");
                }
            }
            asm volatile("cp.async.bulk.wait_group.read 1;\n" ::: "memory");
            warp_arrive(bar_zst - 8 * wg);
        };
        auto emit_done = [&](bool pending) {
            asm volatile("cp.async.bulk.wait_group.read 0;\n" ::: "memory");
            __syncwarp();
            asm volatile("{\n.reg .pred p;\nsetp.eq.s32 p, %1, 0;\n@p mbarrier.arrive.shared::cta.b64 _, [%0];\n}\n"
                         ::"r"(bar_zst + 8), "r"(pending ? lane : 1) : "memory");
        };
        bar_sync(BAR_BF, 256);
        warp_arrive(bar_qfree);
        const int nf = rank ? 8 : 0;
        const int nz = nf + 26 + rank;
        const int itz = 4 + SC_NKV + SC_NW;
        bool pend = false;
#pragma unroll 1
        for (int k = wg; k < nz; k += 2) {
            const int iz = itz + (k < nf ? 0 : nf >> 1);
            mbar_wait(qbar, qphase); qphase ^= 1;
#pragma unroll 1
            for (int c = 0; c < 4; c++) {
                mbar_wait(bar_full + 8 * ((iz + c) & 3), ((iz + c) >> 2) & 1);
                const uint64_t wb = mkaddr(dk0 + ((iz + c) & 3) * (KV_BYTES >> 4), dhi), ab = mkaddr(dq0 + c * 64, dhi);
                wg_fence();
                wgmma_ss_n256_tb_pred(o, ab, wb, c);
#pragma unroll
                for (int kk = 1; kk < 4; kk++) wgmma_ss_n256_tb(o, ab + kk * 2, wb + kk * 512);
                wg_commit();
                emit_done(pend);
                pend = false;
            }
            wg_wait<0>();
            fence_regs(o);
            warp_arrive(bar_qfree);
            const int fb = ((k >> 1) + 3) & 3;
            if (k < nf) {
                float2* r255 = (float2*)H.s->r255 + wg * 128 + q;
                if (k < 2) {
                    if (t >= 124) {
#pragma unroll
                        for (int i = 0; i < 32; i++) r255[4 * i] = make_float2(o[4 * i + 2], o[4 * i + 3]);
                    }
                    bar_sync(BAR_WG0 + wg, 128);
                }
#pragma unroll
                for (int i = 0; i < 32; i++) {
                    const float2 v = __ldcg(r255 + 4 * i);
                    o[4 * i] -= v.x; o[4 * i + 1] -= v.y; o[4 * i + 2] -= v.x; o[4 * i + 3] -= v.y;
                }
            }
            int ln = lane;
            asm volatile("" : "+r"(ln));
            emit(sb + SM_KV + QB_BYTES + warp * KV_BYTES, ln, SC_TZB(k - nf) * 64 + warp * 16,
                 k >= nf ? nullptr : (k & 1) ? g_w + (4 + fb) * QB_BYTES + warp * 8192 : g_w + 8 * QB_BYTES + fb * 8192 + warp * 2048, k);
            pend = k + 2 < nz && (k | 1) != nf - 1;
            if (!pend) emit_done(true);
            if ((k | 1) == nf - 1) {
                asm volatile("cp.async.bulk.wait_group 0;\nfence.proxy.async.global;\nfence.acq_rel.gpu;\n" ::: "memory");
                bar_sync(BAR_BF, 256);
                if (tid == 0) red_release(&g_sync[SY_B * 32]);
                if (wg == 0) { release(0); release(1); release(2); release(3); }
            }
        }
        }
        if (wg == 0) pp_sync();
        warp_arrive(bar_end - 8 * wg);
        asm volatile("barrier.cluster.arrive.relaxed.aligned;\n" ::: "memory");
        if (P.E >= 0) return;
        asm volatile("setmaxnreg.dec.sync.aligned.u32 %0;\n" ::"n"(REG_P));
    }
    {
        if (warp != 0) {
            if (warp == 3 && SC_OWNER && SC_PAIR && elect()) {
                flag_wait_bounded(&g_sync[SY_H1 * 32], 79 * ep);
                mbar_wait_sleep(bar_pdone, 0);
                mbar_wait_sleep(bar_pdone + 8, 0);
#pragma unroll 1
                for (int u = 0; u < 16; u++) {
                    bulk_s2g(g_q + SC_QT0 * (2 * QB_BYTES) + u * 4096, sb + SM_Q + u * 4096, 4096);
                    asm volatile("cp.async.bulk.wait_group 0;\n" ::: "memory");
                }
                fence_async_global();
                st_release(&g_qflag[SC_QT0], ep);
            }
            __syncwarp();
            if (SC_TAIL) {
                bar_sync(BAR_AUX, 96);
                if (warp == 1 && elect()) red_release(&g_sync[SY_CSR * 32]);
                __syncwarp();
            }
            mbar_wait_bounded(bar_go, 0);
            if (SC_TAIL) {
                if (warp == 1 && elect()) red_add(&g_sync[SY_DONE * 32]);
                if (warp == 3 && elect()) {
                    int it = 4 + SC_NKV + SC_NW;
                    asm volatile("prefetch.tensormap [%0];\n" ::"l"(&P.tm_out) : "memory");
                    if (rank) {
#pragma unroll 1
                        for (int j = 0; j < 4; j++, it++) {
                            mbar_wait_sleep(bar_empty + 8 * (it & 3), ((it >> 2) & 1) ^ 1);
                            mbar_expect_tx(bar_full + 8 * (it & 3), QB_BYTES);
                            tma_g2s(sb + SM_KV + (it & 3) * KV_BYTES, &P.tm_w[2], 8 * j, bar_full + 8 * (it & 3));
                        }
#pragma unroll 1
                        for (int k = 0; k < 8; k++) {
                            mbar_wait_sleep(bar_qfree + 8 * (k & 1), ((k >> 1) ^ (k & 1) ^ 1) & 1);
                            mbar_expect_tx(bar_q + 8 * (k & 1), QB_BYTES);
#pragma unroll 1
                            for (int hf = 0; hf < 2; hf++)
                                asm volatile("cp.async.bulk.tensor.5d.shared::cluster.global.tile.mbarrier::complete_tx::bytes [%0], [%1, {0, 0, %2, 0, 0}], [%3];\n"
                                             ::"r"(sb + SM_Q + (k & 1) * QB_BYTES + hf * 16384), "l"(&P.tm_w[k & 1]),
                                             "r"(8 * (((k >> 1) + 3) & 3) + 4 * hf), "r"(bar_q + 8 * (k & 1)) : "memory");
                        }
                        flag_wait_bounded(&g_sync[SY_B * 32], ep);
                        fence_async_global();
                    }
#pragma unroll 1
                    for (int j = 0; j < 4; j++, it++) {
                        mbar_wait_sleep(bar_empty + 8 * (it & 3), ((it >> 2) & 1) ^ 1);
                        mbar_expect_tx(bar_full + 8 * (it & 3), QB_BYTES);
                        bulk_g2s(sb + SM_KV + (it & 3) * KV_BYTES, g_w + (4 + j) * QB_BYTES, QB_BYTES, bar_full + 8 * (it & 3));
                    }
#pragma unroll 1
                    for (int k = 0; k < 26 + rank; k++) {
                        if (k == 0 || k == ((GF0 + 1) * NAUX - 16) / 128) { flag_wait_bounded(&g_sync[(k ? SY_AUX1 : SY_AUX0) * 32], NAUX * ep); fence_async_global(); }
                        mbar_wait_sleep(bar_qfree + 8 * (k & 1), ((k >> 1) ^ (k & 1) ^ 1) & 1);
                        mbar_expect_tx(bar_q + 8 * (k & 1), QB_BYTES);
                        bulk_g2s(sb + SM_Q + (k & 1) * QB_BYTES, g_agg + SC_TZB(k) * QB_BYTES, QB_BYTES, bar_q + 8 * (k & 1));
                    }
                }
            } else {
            const int par = ep & 1;
            if (blockIdx.x == 0 && t == 32) g_ovf_n[par ^ 1] = 0;
            if (blockIdx.x == 0 && warp == 1) *(uint4*)(g_hz + (lane >> 3) * 1024 + (lane & 7) * 16) = make_uint4(KV_OFF2, KV_OFF2, KV_OFF2, KV_OFF2);
            const uint32_t wlo = (uint32_t)(uintptr_t)H.s, whi = (uint32_t)((uintptr_t)H.s >> 32);
            const uint32_t blo = wlo + (uint32_t)offsetof(Scratch, bucket);
            {
                const int* pd = P.dst + blockIdx.x * 96 + (t - 32);
                const int* ps = P.src + blockIdx.x * 96 + (t - 32);
#pragma unroll 1
                for (int e = P.E - (blockIdx.x * 96 + (t - 32)); e > 0; e -= CSRU * NAUX * 32, pd += CSRU * NAUX * 32, ps += CSRU * NAUX * 32) {
                    int d[CSRU], sr[CSRU], sl[CSRU];
#pragma unroll
                    for (int i = 0; i < CSRU; i++) {
                        d[i] = e > i * NAUX * 32 ? __ldg(pd + i * NAUX * 32) : NN;
                        sr[i] = e > i * NAUX * 32 ? __ldg(ps + i * NAUX * 32) : 0;
                    }
#pragma unroll
                    for (int i = 0; i < CSRU; i++) {
                        sl[i] = 0;
                        asm volatile("{\n.reg .pred p;\nsetp.lt.s32 p, %2, %3;\n@p atom.relaxed.gpu.global.add.s32 %0, [%1], 1;\n}\n"
                                     : "+r"(sl[i]) : "l"(mkaddr(wlo + (uint32_t)offsetof(Scratch, cnt) + d[i] * 4, whi)), "r"(d[i]), "n"(NN) : "memory");
                    }
                    uint32_t ov = 0;
#pragma unroll
                    for (int i = 0; i < CSRU; i++) {
                        asm volatile("{\n.reg .pred p;\nsetp.lt.s32 p, %3, %4;\n@p st.global.s32 [%1], %2;\n@!p or.b32 %0, %0, %5;\n}\n"
                                     : "+r"(ov) : "l"(mkaddr(blo + (d[i] * CAP + sl[i]) * 4, whi)), "r"(sr[i]), "r"(sl[i]), "n"(CAP), "r"(1 << i) : "memory");
                    }
#pragma unroll 1
                    for (; ov; ov &= ov - 1) {
                        const int i = (__ffs(ov) - 1) * (NAUX * 32);
                        int at;
                        asm volatile("atom.relaxed.gpu.global.add.s32 %0, [%1], 1;\n" : "=r"(at) : "l"(&g_ovf_n[par]) : "memory");
                        g_ovf[at] = make_int2(__ldg(pd + i), __ldg(ps + i));
                    }
                }
            }
            bar_sync(BAR_AUX, 96);
            if (warp == 1 && elect()) { red_release(&g_sync[SY_CSR * 32]); }
            __syncwarp();
            {
                const int r0 = blockIdx.x * 3 + warp - 1;
                const uint4* xp = (const uint4*)(H.x + r0 * 256) + lane;
                uint4* op = (uint4*)(P.out + r0 * 256) + lane;
#pragma unroll 1
                for (int r = r0; r < NN; r += CPYU * NAUX, xp += CPYU * NAUX * 32, op += CPYU * NAUX * 32) {
                    uint4 v[CPYU];
#pragma unroll
                    for (int i = 0; i < CPYU; i++) if (r + i * NAUX < NN) v[i] = ldg_pinned(xp + i * NAUX * 32);
#pragma unroll
                    for (int i = 0; i < CPYU; i++) if (r + i * NAUX < NN) op[i * NAUX * 32] = v[i];
                }
            }
            if (const int un = blockIdx.x * 3 + warp - 1 - (NAUX - 208); un >= 0) {
                flag_wait_bounded(&g_sync[SY_PART * 32], 52 * ep);
                uint8_t* pp = g_part + (un >> 3) * (4 * PART_BYTES);
                float* ml = (float*)(pp + QB_BYTES) + (un & 7) * 32;
                const float4 sa = __ldcg((const float4*)ml + g), sc = __ldcg((const float4*)ml + g + 2 * PART_BYTES / 16);
                const float n0 = fmaxf(sa.x, sc.x), n1 = fmaxf(sa.z, sc.z);
                const uint32_t a0 = pack_bf16(ex2(sa.x - n0), ex2(sa.x - n0)), a1 = pack_bf16(ex2(sa.z - n1), ex2(sa.z - n1));
                const uint32_t b0 = pack_bf16(ex2(sc.x - n0), ex2(sc.x - n0)), b1 = pack_bf16(ex2(sc.z - n1), ex2(sc.z - n1));
                __syncwarp();
                if (q == 0) ((float4*)ml)[g] = make_float4(n0, sa.y * bf_hi(a0) + sc.y * bf_hi(b0), n1, sa.w * bf_hi(a1) + sc.w * bf_hi(b1));
                uint4* d = (uint4*)(pp + (un & 4) * 256 + (un & 7) * 8192) + lane;
#pragma unroll 1
                for (int i = 0; i < 4; i++, d += 128) {
                    uint4 u[4], v[4];
#pragma unroll
                    for (int j = 0; j < 4; j++) { u[j] = __ldcg(d + j * 32); v[j] = __ldcg(d + j * 32 + 2 * PART_BYTES / 16); }
#pragma unroll
                    for (int j = 0; j < 4; j++)
                        d[j * 32] = make_uint4(hfma2(v[j].x, b0, hmul2(u[j].x, a0)), hfma2(v[j].y, b1, hmul2(u[j].y, a1)),
                                               hfma2(v[j].z, b0, hmul2(u[j].z, a0)), hfma2(v[j].w, b1, hmul2(u[j].w, a1)));
                }
            }
            flag_wait_bounded(&g_sync[SY_CSR * 32], NCTA * ep);
            if (warp == 2 && blockIdx.x < 129) {
                uint4* z = blockIdx.x < 128 ? (uint4*)(g_w + blockIdx.x * 1024) + lane : (uint4*)&g_sync[SY_DONE * 32 + 4];
                z[0] = make_uint4(0, 0, 0, 0);
                if (blockIdx.x < 128) z[32] = make_uint4(0, 0, 0, 0);
            }
            {
                const uint32_t lc = (lane >> 3) * 1024 + (lane & 7) * 16;
                const uint32_t alo = wlo ^ lc;
                const int node0 = blockIdx.x * 3 + warp - 17;
                auto node = [&](int i) { const int nd = node0 + i * NAUX; return (int)min((unsigned)nd, (unsigned)(nd + NN)); };
                const int num = (NN - 17 - node0) / NAUX + 1;
                uint32_t mine = 0;
                if (lane < num) {
                    mine = min(__ldcg(&g_cnt[node(lane)]), CAP + 1) | (uint32_t)__ldg((const unsigned short*)P.deg_inv + node(lane)) << 16;
                    g_cnt[node(lane)] = 0;
                }
                auto row = [&](int off) {
                    uint4 v;
                    asm volatile("ld.global.v4.u32 {%0, %1, %2, %3}, [%4];\n"
                                 : "=r"(v.x), "=r"(v.y), "=r"(v.z), "=r"(v.w) : "l"(mkaddr(alo ^ off, whi)));
                    return v;
                };
                auto ents = [&](int i) {
                    int e;
                    asm volatile("ld.global.cg.s32 %0, [%1];\n" : "=r"(e) : "l"(mkaddr(blo + (min(node(i), NN - 1) * CAP + lane) * 4, whi)));
                    return e;
                };
                auto store = [&](int i, const float (&a)[8]) {
                    const float di = bf_hi(__shfl_sync(~0u, mine, i)) * (1.f / KV_SCALE);
                    const int nd = node(i);
                    *(uint4*)(g_agg + (uint32_t)(((nd >> 3) * 4096 + (nd & 7) * 144) ^ lc)) =
                        make_uint4(pack_bf16(a[0] * di, a[1] * di), pack_bf16(a[2] * di, a[3] * di), pack_bf16(a[4] * di, a[5] * di), pack_bf16(a[6] * di, a[7] * di));
                };
#pragma unroll 1
                for (uint32_t big = __ballot_sync(~0u, (mine & 0xFFFF) > CAP); big; big &= big - 1) {
                    const int i = __ffs(big) - 1, no = __ldcg(&g_ovf_n[par]);
                    float a[8] = {};
#pragma unroll 1
                    for (int k = -32; k < no; k += 32) {
                        const int2 pr = k < 0 ? make_int2(node(i), ents(i)) : k + lane < no ? __ldcg(&g_ovf[k + lane]) : make_int2(-1, 0);
#pragma unroll 1
                        for (uint32_t mk = __ballot_sync(~0u, pr.x == node(i)); mk; mk &= mk - 1) {
                            const uint4 v = row(row_off(__shfl_sync(~0u, pr.y, __ffs(mk) - 1)));
                            a[0] += f16_lo(v.x) - KV_OFF; a[1] += f16_hi(v.x) - KV_OFF; a[2] += f16_lo(v.y) - KV_OFF; a[3] += f16_hi(v.y) - KV_OFF;
                            a[4] += f16_lo(v.z) - KV_OFF; a[5] += f16_hi(v.z) - KV_OFF; a[6] += f16_lo(v.w) - KV_OFF; a[7] += f16_hi(v.w) - KV_OFF;
                        }
                    }
                    store(i, a);
                }
                auto add4 = [&](const uint4& a, const uint4& b) { return make_uint4(hadd2_f16(a.x, b.x), hadd2_f16(a.y, b.y), hadd2_f16(a.z, b.z), hadd2_f16(a.w, b.w)); };
                int ni = -1, left = 0, pos = 0, ec = 0, en = ents(0);
                uint4 acc = make_uint4(0, 0, 0, 0);
                auto issue = [&](uint4 (&v)[4]) {
                    if (left <= 0) {
                        ni++;
                        left = __shfl_sync(~0u, mine, ni) & 0xFFFF;
                        if (left > CAP) left = 0;
                        ec = lane < left ? row_off(en) : 0;
                        en = ents(ni + 1);
                        pos = 0;
                    }
#pragma unroll
                    for (int j = 0; j < 4; j++) v[j] = row(__shfl_sync(~0u, ec, pos + j));
                    pos += 4; left -= 4;
                    return left <= 0 ? ni : -1;
                };
                auto step = [&](uint4 (&v)[4], int& tag) {
                    acc = add4(acc, add4(add4(add4(v[0], v[1]), make_uint4(KV_NEG4, KV_NEG4, KV_NEG4, KV_NEG4)), add4(v[2], v[3])));
                    const int i = tag;
                    tag = issue(v);
                    if (i >= 0) {
                        const float a[8] = {f16_lo(acc.x), f16_hi(acc.x), f16_lo(acc.y), f16_hi(acc.y), f16_lo(acc.z), f16_hi(acc.z), f16_lo(acc.w), f16_hi(acc.w)};
                        if ((__shfl_sync(~0u, mine, i) & 0xFFFF) <= CAP) store(i, a);
                        acc = make_uint4(0, 0, 0, 0);
                        if (i == GF0 || i == 8) {
                            __syncwarp();
                            if (elect()) red_release(&g_sync[(i == 8 ? SY_AUX1 : SY_AUX0) * 32]);
                            __syncwarp();
                        }
                    }
                    return i == num - 1;
                };
                uint4 va[4], vb[4];
#pragma unroll
                for (int j = 0; j < 4; j++) va[j] = vb[j] = make_uint4(KV_OFF2, KV_OFF2, KV_OFF2, KV_OFF2);
                int ta = -1, tb = -1;
#pragma unroll 1
                while (!step(va, ta) && !step(vb, tb)) {}
            }
            bar_sync(BAR_AUX, 96);
            if (warp == 1 && elect()) {
                red_release(&g_sync[SY_AUX * 32]);
                red_add(&g_sync[SY_DONE * 32]);
            }
            }
        }
        __syncwarp();
        asm volatile("barrier.cluster.arrive.relaxed.aligned;\n" ::: "memory");
        if (warp == 1) mbar_wait_bounded(bar_end, 0);
        else if (elect()) mbar_arrive(bar_end);
        __syncwarp();
        asm volatile("barrier.cluster.wait.acquire.aligned;\n" ::: "memory");
    }
}

}

extern "C" void kernel_launch(void* const* d_in, const int* in_sizes, int n_in, void* d_out, int out_size) {
    Hot H;
    Params P;
    H.x = (const __nv_bfloat16*)d_in[0];
    P.src = (const int*)d_in[1];
    P.dst = (const int*)d_in[2];
    P.deg_inv = (const __nv_bfloat16*)d_in[3];
    H.wq = (const __nv_bfloat16*)d_in[5];
    H.wk = (const __nv_bfloat16*)d_in[6];
    P.out = (__nv_bfloat16*)d_out;
    typedef CUresult (*EncodeFn)(CUtensorMap*, CUtensorMapDataType, cuuint32_t, void*, const cuuint64_t*, const cuuint64_t*, const cuuint32_t*,
                                 const cuuint32_t*, CUtensorMapInterleave, CUtensorMapSwizzle, CUtensorMapL2promotion, CUtensorMapFloatOOBfill);
    void* fn = nullptr;
    cudaDriverEntryPointQueryResult qr;
    cudaGetDriverEntryPoint("cuTensorMapEncodeTiled", &fn, cudaEnableDefault, &qr);
    auto encode = [&](CUtensorMap* tm, const void* ptr, int rows, int box_rows, int box_cb = 4) {
        const cuuint64_t dims[4] = {64, 8, 4, (cuuint64_t)rows / 8};
        const cuuint64_t strides[3] = {512, 128, 4096};
        const cuuint32_t box[4] = {64, 8, (cuuint32_t)box_cb, (cuuint32_t)box_rows / 8}, es[4] = {1, 1, 1, 1};
        ((EncodeFn)fn)(tm, CU_TENSOR_MAP_DATA_TYPE_BFLOAT16, 4, (void*)ptr, dims, strides, box, es, CU_TENSOR_MAP_INTERLEAVE_NONE,
                       CU_TENSOR_MAP_SWIZZLE_128B, CU_TENSOR_MAP_L2_PROMOTION_NONE, CU_TENSOR_MAP_FLOAT_OOB_FILL_NONE);
    };
    encode(&P.tm_out, d_out, NN, 8);
    encode(&P.tm_outc, d_out, NN, 16, 1);
    for (int i = 0; i < 2; i++) {
        const cuuint64_t dims[5] = {64, 2, 32, 4, 4};
        const cuuint64_t strides[4] = {512, 4096, 128, 1024};
        const cuuint32_t box[5] = {64, 2, 4, 4, 4}, es[5] = {1, 1, 1, 1, 1};
        ((EncodeFn)fn)(&P.tm_w[i], CU_TENSOR_MAP_DATA_TYPE_BFLOAT16, 5, d_in[i ? 4 : 7], dims, strides, box, es, CU_TENSOR_MAP_INTERLEAVE_NONE,
                       CU_TENSOR_MAP_SWIZZLE_128B, CU_TENSOR_MAP_L2_PROMOTION_NONE, CU_TENSOR_MAP_FLOAT_OOB_FILL_NONE);
    }
    encode(&P.tm_w[2], d_in[8], 256, 64);
    void* raw = nullptr;
    cudaGetSymbolAddress(&raw, g_raw);
    H.s = (Scratch*)(((uintptr_t)raw + ((8 << 20) - 1)) & ~(uintptr_t)((8 << 20) - 1));
    P.dhi = 0x40000100u;
    P.E = in_sizes[1] < MAXE ? in_sizes[1] : MAXE;
    cudaFuncSetAttribute(k_main, cudaFuncAttributeMaxDynamicSharedMemorySize, SM_TOTAL);
    k_main<<<NCTA, 384, SM_TOTAL>>>(H, P);
}
```

```cpp
#include <cuda_runtime.h>
#include <cuda.h>
#include <cuda_bf16.h>
#include <stdint.h>
#include <stddef.h>

namespace {

constexpr int NN = 10000;
constexpr int BN = 80;
constexpr int NKV = NN / BN;
constexpr int NQB = 158;
constexpr int NCTA = 132;
constexpr int NAUX = 3 * (NCTA - 2);
constexpr int STAGES = 4;
constexpr int KV_BYTES = BN * 512;
constexpr int QB_BYTES = 64 * 512;
constexpr int PART_BYTES = QB_BYTES + 512;
constexpr int CAP = 32;
constexpr int MAXE = 160000;

#define QRND(v) (((v) + 0x00040004u) & 0xFFF8FFF8u)
#define GO0 32
#define GF0 2
#define HDEF -1
#define CSRU 5
#define CPYU 5
#define REFUP 2.f
#define SND0 10
#define CUT2 2
#define ZHOLD 1
#define XD0 0
#define XD1 -1
#define XDW 0
#define PFX 1
#define REG_C 224
#define REG_P 56

enum { SY_PART = 4, SY_H1 = 5, SY_CSR = 6, SY_AUX = 7, SY_DONE = 8, SY_AUX0 = 9, SY_B = 10, SY_AUX1 = 11, SY_H0 = 12 };
struct Scratch {
    uint8_t hz[4096 + NN * 512];
    uint8_t w[12 * QB_BYTES];
    int sync[25 * 32];
    int qflag[96];
    int ovf_n[32];
    float r255[512];
    int cnt[NN + 16];
    int bucket[(NN + 1) * CAP];
    int2 ovf[MAXE];
    uint8_t q[NQB * QB_BYTES];
    uint8_t agg[NQB * QB_BYTES];
    uint8_t part[52 * 2 * PART_BYTES];
};
static_assert(offsetof(Scratch, ovf) <= (8 << 20), "window");
static_assert(offsetof(Scratch, qflag) == offsetof(Scratch, sync) + 25 * 128, "flags");
static_assert(offsetof(Scratch, w) % 1024 == 0 && offsetof(Scratch, sync) % 128 == 0 &&
              offsetof(Scratch, bucket) % 128 == 0 && offsetof(Scratch, q) % 128 == 0, "alignment");
__device__ uint8_t g_raw[(8 << 20) + sizeof(Scratch)];
#define g_hz (H.s->hz)
#define g_w (H.s->w)
#define g_sync (H.s->sync)
#define g_qflag (H.s->qflag)
#define g_ovf_n (H.s->ovf_n)
#define g_cnt (H.s->cnt)
#define g_bucket (H.s->bucket)
#define g_ovf (H.s->ovf)
#define g_q (H.s->q)
#define g_agg (H.s->agg)
#define g_part (H.s->part)

__device__ __forceinline__ void wgmma_ss_n80(float (&d)[40], uint64_t da, uint64_t db) {
    asm volatile("wgmma.mma_async.sync.aligned.m64n80k16.f32.f16.f16 {"
        "%0, %1, %2, %3, %4, %5, %6, %7, %8, %9, %10, %11, %12, %13, %14, %15, %16, %17, %18, %19, %20, %21, %22, %23, %24, %25, %26, %27, %28, %29, %30, %31, "
        "%32, %33, %34, %35, %36, %37, %38, %39}, %40, %41, 1, 1, 1, 0, 0;\n"
        : "+f"(d[0]), "+f"(d[1]), "+f"(d[2]), "+f"(d[3]), "+f"(d[4]), "+f"(d[5]), "+f"(d[6]), "+f"(d[7]),
          "+f"(d[8]), "+f"(d[9]), "+f"(d[10]), "+f"(d[11]), "+f"(d[12]), "+f"(d[13]), "+f"(d[14]), "+f"(d[15]),
          "+f"(d[16]), "+f"(d[17]), "+f"(d[18]), "+f"(d[19]), "+f"(d[20]), "+f"(d[21]), "+f"(d[22]), "+f"(d[23]),
          "+f"(d[24]), "+f"(d[25]), "+f"(d[26]), "+f"(d[27]), "+f"(d[28]), "+f"(d[29]), "+f"(d[30]), "+f"(d[31]),
          "+f"(d[32]), "+f"(d[33]), "+f"(d[34]), "+f"(d[35]), "+f"(d[36]), "+f"(d[37]), "+f"(d[38]), "+f"(d[39])
        : "l"(da), "l"(db));
}
__device__ __forceinline__ void wgmma_ss_n80_init(float (&d)[40], uint64_t da, uint64_t db) {
    asm volatile("wgmma.mma_async.sync.aligned.m64n80k16.f32.f16.f16 {"
        "%0, %1, %2, %3, %4, %5, %6, %7, %8, %9, %10, %11, %12, %13, %14, %15, %16, %17, %18, %19, %20, %21, %22, %23, %24, %25, %26, %27, %28, %29, %30, %31, "
        "%32, %33, %34, %35, %36, %37, %38, %39}, %40, %41, 0, 1, 1, 0, 0;\n"
        : "=f"(d[0]), "=f"(d[1]), "=f"(d[2]), "=f"(d[3]), "=f"(d[4]), "=f"(d[5]), "=f"(d[6]), "=f"(d[7]),
          "=f"(d[8]), "=f"(d[9]), "=f"(d[10]), "=f"(d[11]), "=f"(d[12]), "=f"(d[13]), "=f"(d[14]), "=f"(d[15]),
          "=f"(d[16]), "=f"(d[17]), "=f"(d[18]), "=f"(d[19]), "=f"(d[20]), "=f"(d[21]), "=f"(d[22]), "=f"(d[23]),
          "=f"(d[24]), "=f"(d[25]), "=f"(d[26]), "=f"(d[27]), "=f"(d[28]), "=f"(d[29]), "=f"(d[30]), "=f"(d[31]),
          "=f"(d[32]), "=f"(d[33]), "=f"(d[34]), "=f"(d[35]), "=f"(d[36]), "=f"(d[37]), "=f"(d[38]), "=f"(d[39])
        : "l"(da), "l"(db));
}
__device__ __forceinline__ void wgmma_rs_n256_tb(float (&d)[128], uint32_t a0, uint32_t a1, uint32_t a2, uint32_t a3, uint64_t db) {
    asm volatile("wgmma.mma_async.sync.aligned.m64n256k16.f32.f16.f16 {"
        "%0, %1, %2, %3, %4, %5, %6, %7, %8, %9, %10, %11, %12, %13, %14, %15, %16, %17, %18, %19, %20, %21, %22, %23, %24, %25, %26, %27, %28, %29, %30, %31, "
        "%32, %33, %34, %35, %36, %37, %38, %39, %40, %41, %42, %43, %44, %45, %46, %47, %48, %49, %50, %51, %52, %53, %54, %55, %56, %57, %58, %59, %60, %61, %62, %63, "
        "%64, %65, %66, %67, %68, %69, %70, %71, %72, %73, %74, %75, %76, %77, %78, %79, %80, %81, %82, %83, %84, %85, %86, %87, %88, %89, %90, %91, %92, %93, %94, %95, "
        "%96, %97, %98, %99, %100, %101, %102, %103, %104, %105, %106, %107, %108, %109, %110, %111, %112, %113, %114, %115, %116, %117, %118, %119, %120, %121, %122, %123, %124, %125, %126, %127}, {%128, %129, %130, %131}, %132, 1, 1, 1, 1;\n"
        : "+f"(d[0]), "+f"(d[1]), "+f"(d[2]), "+f"(d[3]), "+f"(d[4]), "+f"(d[5]), "+f"(d[6]), "+f"(d[7]),
          "+f"(d[8]), "+f"(d[9]), "+f"(d[10]), "+f"(d[11]), "+f"(d[12]), "+f"(d[13]), "+f"(d[14]), "+f"(d[15]),
          "+f"(d[16]), "+f"(d[17]), "+f"(d[18]), "+f"(d[19]), "+f"(d[20]), "+f"(d[21]), "+f"(d[22]), "+f"(d[23]),
          "+f"(d[24]), "+f"(d[25]), "+f"(d[26]), "+f"(d[27]), "+f"(d[28]), "+f"(d[29]), "+f"(d[30]), "+f"(d[31]),
          "+f"(d[32]), "+f"(d[33]), "+f"(d[34]), "+f"(d[35]), "+f"(d[36]), "+f"(d[37]), "+f"(d[38]), "+f"(d[39]),
          "+f"(d[40]), "+f"(d[41]), "+f"(d[42]), "+f"(d[43]), "+f"(d[44]), "+f"(d[45]), "+f"(d[46]), "+f"(d[47]),
          "+f"(d[48]), "+f"(d[49]), "+f"(d[50]), "+f"(d[51]), "+f"(d[52]), "+f"(d[53]), "+f"(d[54]), "+f"(d[55]),
          "+f"(d[56]), "+f"(d[57]), "+f"(d[58]), "+f"(d[59]), "+f"(d[60]), "+f"(d[61]), "+f"(d[62]), "+f"(d[63]),
          "+f"(d[64]), "+f"(d[65]), "+f"(d[66]), "+f"(d[67]), "+f"(d[68]), "+f"(d[69]), "+f"(d[70]), "+f"(d[71]),
          "+f"(d[72]), "+f"(d[73]), "+f"(d[74]), "+f"(d[75]), "+f"(d[76]), "+f"(d[77]), "+f"(d[78]), "+f"(d[79]),
          "+f"(d[80]), "+f"(d[81]), "+f"(d[82]), "+f"(d[83]), "+f"(d[84]), "+f"(d[85]), "+f"(d[86]), "+f"(d[87]),
          "+f"(d[88]), "+f"(d[89]), "+f"(d[90]), "+f"(d[91]), "+f"(d[92]), "+f"(d[93]), "+f"(d[94]), "+f"(d[95]),
          "+f"(d[96]), "+f"(d[97]), "+f"(d[98]), "+f"(d[99]), "+f"(d[100]), "+f"(d[101]), "+f"(d[102]), "+f"(d[103]),
          "+f"(d[104]), "+f"(d[105]), "+f"(d[106]), "+f"(d[107]), "+f"(d[108]), "+f"(d[109]), "+f"(d[110]), "+f"(d[111]),
          "+f"(d[112]), "+f"(d[113]), "+f"(d[114]), "+f"(d[115]), "+f"(d[116]), "+f"(d[117]), "+f"(d[118]), "+f"(d[119]),
          "+f"(d[120]), "+f"(d[121]), "+f"(d[122]), "+f"(d[123]), "+f"(d[124]), "+f"(d[125]), "+f"(d[126]), "+f"(d[127])
        : "r"(a0), "r"(a1), "r"(a2), "r"(a3), "l"(db));
}
__device__ __forceinline__ void wgmma_rs_n256_tb_init(float (&d)[128], uint32_t a0, uint32_t a1, uint32_t a2, uint32_t a3, uint64_t db) {
    asm volatile("wgmma.mma_async.sync.aligned.m64n256k16.f32.f16.f16 {"
        "%0, %1, %2, %3, %4, %5, %6, %7, %8, %9, %10, %11, %12, %13, %14, %15, %16, %17, %18, %19, %20, %21, %22, %23, %24, %25, %26, %27, %28, %29, %30, %31, "
        "%32, %33, %34, %35, %36, %37, %38, %39, %40, %41, %42, %43, %44, %45, %46, %47, %48, %49, %50, %51, %52, %53, %54, %55, %56, %57, %58, %59, %60, %61, %62, %63, "
        "%64, %65, %66, %67, %68, %69, %70, %71, %72, %73, %74, %75, %76, %77, %78, %79, %80, %81, %82, %83, %84, %85, %86, %87, %88, %89, %90, %91, %92, %93, %94, %95, "
        "%96, %97, %98, %99, %100, %101, %102, %103, %104, %105, %106, %107, %108, %109, %110, %111, %112, %113, %114, %115, %116, %117, %118, %119, %120, %121, %122, %123, %124, %125, %126, %127}, {%128, %129, %130, %131}, %132, 0, 1, 1, 1;\n"
        : "=f"(d[0]), "=f"(d[1]), "=f"(d[2]), "=f"(d[3]), "=f"(d[4]), "=f"(d[5]), "=f"(d[6]), "=f"(d[7]),
          "=f"(d[8]), "=f"(d[9]), "=f"(d[10]), "=f"(d[11]), "=f"(d[12]), "=f"(d[13]), "=f"(d[14]), "=f"(d[15]),
          "=f"(d[16]), "=f"(d[17]), "=f"(d[18]), "=f"(d[19]), "=f"(d[20]), "=f"(d[21]), "=f"(d[22]), "=f"(d[23]),
          "=f"(d[24]), "=f"(d[25]), "=f"(d[26]), "=f"(d[27]), "=f"(d[28]), "=f"(d[29]), "=f"(d[30]), "=f"(d[31]),
          "=f"(d[32]), "=f"(d[33]), "=f"(d[34]), "=f"(d[35]), "=f"(d[36]), "=f"(d[37]), "=f"(d[38]), "=f"(d[39]),
          "=f"(d[40]), "=f"(d[41]), "=f"(d[42]), "=f"(d[43]), "=f"(d[44]), "=f"(d[45]), "=f"(d[46]), "=f"(d[47]),
          "=f"(d[48]), "=f"(d[49]), "=f"(d[50]), "=f"(d[51]), "=f"(d[52]), "=f"(d[53]), "=f"(d[54]), "=f"(d[55]),
          "=f"(d[56]), "=f"(d[57]), "=f"(d[58]), "=f"(d[59]), "=f"(d[60]), "=f"(d[61]), "=f"(d[62]), "=f"(d[63]),
          "=f"(d[64]), "=f"(d[65]), "=f"(d[66]), "=f"(d[67]), "=f"(d[68]), "=f"(d[69]), "=f"(d[70]), "=f"(d[71]),
          "=f"(d[72]), "=f"(d[73]), "=f"(d[74]), "=f"(d[75]), "=f"(d[76]), "=f"(d[77]), "=f"(d[78]), "=f"(d[79]),
          "=f"(d[80]), "=f"(d[81]), "=f"(d[82]), "=f"(d[83]), "=f"(d[84]), "=f"(d[85]), "=f"(d[86]), "=f"(d[87]),
          "=f"(d[88]), "=f"(d[89]), "=f"(d[90]), "=f"(d[91]), "=f"(d[92]), "=f"(d[93]), "=f"(d[94]), "=f"(d[95]),
          "=f"(d[96]), "=f"(d[97]), "=f"(d[98]), "=f"(d[99]), "=f"(d[100]), "=f"(d[101]), "=f"(d[102]), "=f"(d[103]),
          "=f"(d[104]), "=f"(d[105]), "=f"(d[106]), "=f"(d[107]), "=f"(d[108]), "=f"(d[109]), "=f"(d[110]), "=f"(d[111]),
          "=f"(d[112]), "=f"(d[113]), "=f"(d[114]), "=f"(d[115]), "=f"(d[116]), "=f"(d[117]), "=f"(d[118]), "=f"(d[119]),
          "=f"(d[120]), "=f"(d[121]), "=f"(d[122]), "=f"(d[123]), "=f"(d[124]), "=f"(d[125]), "=f"(d[126]), "=f"(d[127])
        : "r"(a0), "r"(a1), "r"(a2), "r"(a3), "l"(db));
}
__device__ __forceinline__ void wgmma_rs_n256_tb_pred(float (&d)[128], uint32_t a0, uint32_t a1, uint32_t a2, uint32_t a3, uint64_t db, int acc) {
    asm volatile("{\n.reg .pred p;\nsetp.ne.s32 p, %133, 0;\nwgmma.mma_async.sync.aligned.m64n256k16.f32.f16.f16 {"
        "%0, %1, %2, %3, %4, %5, %6, %7, %8, %9, %10, %11, %12, %13, %14, %15, %16, %17, %18, %19, %20, %21, %22, %23, %24, %25, %26, %27, %28, %29, %30, %31, "
        "%32, %33, %34, %35, %36, %37, %38, %39, %40, %41, %42, %43, %44, %45, %46, %47, %48, %49, %50, %51, %52, %53, %54, %55, %56, %57, %58, %59, %60, %61, %62, %63, "
        "%64, %65, %66, %67, %68, %69, %70, %71, %72, %73, %74, %75, %76, %77, %78, %79, %80, %81, %82, %83, %84, %85, %86, %87, %88, %89, %90, %91, %92, %93, %94, %95, "
        "%96, %97, %98, %99, %100, %101, %102, %103, %104, %105, %106, %107, %108, %109, %110, %111, %112, %113, %114, %115, %116, %117, %118, %119, %120, %121, %122, %123, %124, %125, %126, %127}, {%128, %129, %130, %131}, %132, p, 1, 1, 1;\n}\n"
        : "+f"(d[0]), "+f"(d[1]), "+f"(d[2]), "+f"(d[3]), "+f"(d[4]), "+f"(d[5]), "+f"(d[6]), "+f"(d[7]),
          "+f"(d[8]), "+f"(d[9]), "+f"(d[10]), "+f"(d[11]), "+f"(d[12]), "+f"(d[13]), "+f"(d[14]), "+f"(d[15]),
          "+f"(d[16]), "+f"(d[17]), "+f"(d[18]), "+f"(d[19]), "+f"(d[20]), "+f"(d[21]), "+f"(d[22]), "+f"(d[23]),
          "+f"(d[24]), "+f"(d[25]), "+f"(d[26]), "+f"(d[27]), "+f"(d[28]), "+f"(d[29]), "+f"(d[30]), "+f"(d[31]),
          "+f"(d[32]), "+f"(d[33]), "+f"(d[34]), "+f"(d[35]), "+f"(d[36]), "+f"(d[37]), "+f"(d[38]), "+f"(d[39]),
          "+f"(d[40]), "+f"(d[41]), "+f"(d[42]), "+f"(d[43]), "+f"(d[44]), "+f"(d[45]), "+f"(d[46]), "+f"(d[47]),
          "+f"(d[48]), "+f"(d[49]), "+f"(d[50]), "+f"(d[51]), "+f"(d[52]), "+f"(d[53]), "+f"(d[54]), "+f"(d[55]),
          "+f"(d[56]), "+f"(d[57]), "+f"(d[58]), "+f"(d[59]), "+f"(d[60]), "+f"(d[61]), "+f"(d[62]), "+f"(d[63]),
          "+f"(d[64]), "+f"(d[65]), "+f"(d[66]), "+f"(d[67]), "+f"(d[68]), "+f"(d[69]), "+f"(d[70]), "+f"(d[71]),
          "+f"(d[72]), "+f"(d[73]), "+f"(d[74]), "+f"(d[75]), "+f"(d[76]), "+f"(d[77]), "+f"(d[78]), "+f"(d[79]),
          "+f"(d[80]), "+f"(d[81]), "+f"(d[82]), "+f"(d[83]), "+f"(d[84]), "+f"(d[85]), "+f"(d[86]), "+f"(d[87]),
          "+f"(d[88]), "+f"(d[89]), "+f"(d[90]), "+f"(d[91]), "+f"(d[92]), "+f"(d[93]), "+f"(d[94]), "+f"(d[95]),
          "+f"(d[96]), "+f"(d[97]), "+f"(d[98]), "+f"(d[99]), "+f"(d[100]), "+f"(d[101]), "+f"(d[102]), "+f"(d[103]),
          "+f"(d[104]), "+f"(d[105]), "+f"(d[106]), "+f"(d[107]), "+f"(d[108]), "+f"(d[109]), "+f"(d[110]), "+f"(d[111]),
          "+f"(d[112]), "+f"(d[113]), "+f"(d[114]), "+f"(d[115]), "+f"(d[116]), "+f"(d[117]), "+f"(d[118]), "+f"(d[119]),
          "+f"(d[120]), "+f"(d[121]), "+f"(d[122]), "+f"(d[123]), "+f"(d[124]), "+f"(d[125]), "+f"(d[126]), "+f"(d[127])
        : "r"(a0), "r"(a1), "r"(a2), "r"(a3), "l"(db), "r"(acc));
}
__device__ __forceinline__ void wgmma_ss_n256_tb(float (&d)[128], uint64_t da, uint64_t db) {
    asm volatile("wgmma.mma_async.sync.aligned.m64n256k16.f32.bf16.bf16 {"
        "%0, %1, %2, %3, %4, %5, %6, %7, %8, %9, %10, %11, %12, %13, %14, %15, %16, %17, %18, %19, %20, %21, %22, %23, %24, %25, %26, %27, %28, %29, %30, %31, "
        "%32, %33, %34, %35, %36, %37, %38, %39, %40, %41, %42, %43, %44, %45, %46, %47, %48, %49, %50, %51, %52, %53, %54, %55, %56, %57, %58, %59, %60, %61, %62, %63, "
        "%64, %65, %66, %67, %68, %69, %70, %71, %72, %73, %74, %75, %76, %77, %78, %79, %80, %81, %82, %83, %84, %85, %86, %87, %88, %89, %90, %91, %92, %93, %94, %95, "
        "%96, %97, %98, %99, %100, %101, %102, %103, %104, %105, %106, %107, %108, %109, %110, %111, %112, %113, %114, %115, %116, %117, %118, %119, %120, %121, %122, %123, %124, %125, %126, %127}, %128, %129, 1, 1, 1, 0, 1;\n"
        : "+f"(d[0]), "+f"(d[1]), "+f"(d[2]), "+f"(d[3]), "+f"(d[4]), "+f"(d[5]), "+f"(d[6]), "+f"(d[7]),
          "+f"(d[8]), "+f"(d[9]), "+f"(d[10]), "+f"(d[11]), "+f"(d[12]), "+f"(d[13]), "+f"(d[14]), "+f"(d[15]),
          "+f"(d[16]), "+f"(d[17]), "+f"(d[18]), "+f"(d[19]), "+f"(d[20]), "+f"(d[21]), "+f"(d[22]), "+f"(d[23]),
          "+f"(d[24]), "+f"(d[25]), "+f"(d[26]), "+f"(d[27]), "+f"(d[28]), "+f"(d[29]), "+f"(d[30]), "+f"(d[31]),
          "+f"(d[32]), "+f"(d[33]), "+f"(d[34]), "+f"(d[35]), "+f"(d[36]), "+f"(d[37]), "+f"(d[38]), "+f"(d[39]),
          "+f"(d[40]), "+f"(d[41]), "+f"(d[42]), "+f"(d[43]), "+f"(d[44]), "+f"(d[45]), "+f"(d[46]), "+f"(d[47]),
          "+f"(d[48]), "+f"(d[49]), "+f"(d[50]), "+f"(d[51]), "+f"(d[52]), "+f"(d[53]), "+f"(d[54]), "+f"(d[55]),
          "+f"(d[56]), "+f"(d[57]), "+f"(d[58]), "+f"(d[59]), "+f"(d[60]), "+f"(d[61]), "+f"(d[62]), "+f"(d[63]),
          "+f"(d[64]), "+f"(d[65]), "+f"(d[66]), "+f"(d[67]), "+f"(d[68]), "+f"(d[69]), "+f"(d[70]), "+f"(d[71]),
          "+f"(d[72]), "+f"(d[73]), "+f"(d[74]), "+f"(d[75]), "+f"(d[76]), "+f"(d[77]), "+f"(d[78]), "+f"(d[79]),
          "+f"(d[80]), "+f"(d[81]), "+f"(d[82]), "+f"(d[83]), "+f"(d[84]), "+f"(d[85]), "+f"(d[86]), "+f"(d[87]),
          "+f"(d[88]), "+f"(d[89]), "+f"(d[90]), "+f"(d[91]), "+f"(d[92]), "+f"(d[93]), "+f"(d[94]), "+f"(d[95]),
          "+f"(d[96]), "+f"(d[97]), "+f"(d[98]), "+f"(d[99]), "+f"(d[100]), "+f"(d[101]), "+f"(d[102]), "+f"(d[103]),
          "+f"(d[104]), "+f"(d[105]), "+f"(d[106]), "+f"(d[107]), "+f"(d[108]), "+f"(d[109]), "+f"(d[110]), "+f"(d[111]),
          "+f"(d[112]), "+f"(d[113]), "+f"(d[114]), "+f"(d[115]), "+f"(d[116]), "+f"(d[117]), "+f"(d[118]), "+f"(d[119]),
          "+f"(d[120]), "+f"(d[121]), "+f"(d[122]), "+f"(d[123]), "+f"(d[124]), "+f"(d[125]), "+f"(d[126]), "+f"(d[127])
        : "l"(da), "l"(db));
}
__device__ __forceinline__ void wgmma_ss_n256_tb_init(float (&d)[128], uint64_t da, uint64_t db) {
    asm volatile("wgmma.mma_async.sync.aligned.m64n256k16.f32.bf16.bf16 {"
        "%0, %1, %2, %3, %4, %5, %6, %7, %8, %9, %10, %11, %12, %13, %14, %15, %16, %17, %18, %19, %20, %21, %22, %23, %24, %25, %26, %27, %28, %29, %30, %31, "
        "%32, %33, %34, %35, %36, %37, %38, %39, %40, %41, %42, %43, %44, %45, %46, %47, %48, %49, %50, %51, %52, %53, %54, %55, %56, %57, %58, %59, %60, %61, %62, %63, "
        "%64, %65, %66, %67, %68, %69, %70, %71, %72, %73, %74, %75, %76, %77, %78, %79, %80, %81, %82, %83, %84, %85, %86, %87, %88, %89, %90, %91, %92, %93, %94, %95, "
        "%96, %97, %98, %99, %100, %101, %102, %103, %104, %105, %106, %107, %108, %109, %110, %111, %112, %113, %114, %115, %116, %117, %118, %119, %120, %121, %122, %123, %124, %125, %126, %127}, %128, %129, 0, 1, 1, 0, 1;\n"
        : "=f"(d[0]), "=f"(d[1]), "=f"(d[2]), "=f"(d[3]), "=f"(d[4]), "=f"(d[5]), "=f"(d[6]), "=f"(d[7]),
          "=f"(d[8]), "=f"(d[9]), "=f"(d[10]), "=f"(d[11]), "=f"(d[12]), "=f"(d[13]), "=f"(d[14]), "=f"(d[15]),
          "=f"(d[16]), "=f"(d[17]), "=f"(d[18]), "=f"(d[19]), "=f"(d[20]), "=f"(d[21]), "=f"(d[22]), "=f"(d[23]),
          "=f"(d[24]), "=f"(d[25]), "=f"(d[26]), "=f"(d[27]), "=f"(d[28]), "=f"(d[29]), "=f"(d[30]), "=f"(d[31]),
          "=f"(d[32]), "=f"(d[33]), "=f"(d[34]), "=f"(d[35]), "=f"(d[36]), "=f"(d[37]), "=f"(d[38]), "=f"(d[39]),
          "=f"(d[40]), "=f"(d[41]), "=f"(d[42]), "=f"(d[43]), "=f"(d[44]), "=f"(d[45]), "=f"(d[46]), "=f"(d[47]),
          "=f"(d[48]), "=f"(d[49]), "=f"(d[50]), "=f"(d[51]), "=f"(d[52]), "=f"(d[53]), "=f"(d[54]), "=f"(d[55]),
          "=f"(d[56]), "=f"(d[57]), "=f"(d[58]), "=f"(d[59]), "=f"(d[60]), "=f"(d[61]), "=f"(d[62]), "=f"(d[63]),
          "=f"(d[64]), "=f"(d[65]), "=f"(d[66]), "=f"(d[67]), "=f"(d[68]), "=f"(d[69]), "=f"(d[70]), "=f"(d[71]),
          "=f"(d[72]), "=f"(d[73]), "=f"(d[74]), "=f"(d[75]), "=f"(d[76]), "=f"(d[77]), "=f"(d[78]), "=f"(d[79]),
          "=f"(d[80]), "=f"(d[81]), "=f"(d[82]), "=f"(d[83]), "=f"(d[84]), "=f"(d[85]), "=f"(d[86]), "=f"(d[87]),
          "=f"(d[88]), "=f"(d[89]), "=f"(d[90]), "=f"(d[91]), "=f"(d[92]), "=f"(d[93]), "=f"(d[94]), "=f"(d[95]),
          "=f"(d[96]), "=f"(d[97]), "=f"(d[98]), "=f"(d[99]), "=f"(d[100]), "=f"(d[101]), "=f"(d[102]), "=f"(d[103]),
          "=f"(d[104]), "=f"(d[105]), "=f"(d[106]), "=f"(d[107]), "=f"(d[108]), "=f"(d[109]), "=f"(d[110]), "=f"(d[111]),
          "=f"(d[112]), "=f"(d[113]), "=f"(d[114]), "=f"(d[115]), "=f"(d[116]), "=f"(d[117]), "=f"(d[118]), "=f"(d[119]),
          "=f"(d[120]), "=f"(d[121]), "=f"(d[122]), "=f"(d[123]), "=f"(d[124]), "=f"(d[125]), "=f"(d[126]), "=f"(d[127])
        : "l"(da), "l"(db));
}
__device__ __forceinline__ void wgmma_ss_n256_tb_pred(float (&d)[128], uint64_t da, uint64_t db, int acc) {
    asm volatile("{\n.reg .pred p;\nsetp.ne.s32 p, %130, 0;\nwgmma.mma_async.sync.aligned.m64n256k16.f32.bf16.bf16 {"
        "%0, %1, %2, %3, %4, %5, %6, %7, %8, %9, %10, %11, %12, %13, %14, %15, %16, %17, %18, %19, %20, %21, %22, %23, %24, %25, %26, %27, %28, %29, %30, %31, "
        "%32, %33, %34, %35, %36, %37, %38, %39, %40, %41, %42, %43, %44, %45, %46, %47, %48, %49, %50, %51, %52, %53, %54, %55, %56, %57, %58, %59, %60, %61, %62, %63, "
        "%64, %65, %66, %67, %68, %69, %70, %71, %72, %73, %74, %75, %76, %77, %78, %79, %80, %81, %82, %83, %84, %85, %86, %87, %88, %89, %90, %91, %92, %93, %94, %95, "
        "%96, %97, %98, %99, %100, %101, %102, %103, %104, %105, %106, %107, %108, %109, %110, %111, %112, %113, %114, %115, %116, %117, %118, %119, %120, %121, %122, %123, %124, %125, %126, %127}, %128, %129, p, 1, 1, 0, 1;\n}\n"
        : "+f"(d[0]), "+f"(d[1]), "+f"(d[2]), "+f"(d[3]), "+f"(d[4]), "+f"(d[5]), "+f"(d[6]), "+f"(d[7]),
          "+f"(d[8]), "+f"(d[9]), "+f"(d[10]), "+f"(d[11]), "+f"(d[12]), "+f"(d[13]), "+f"(d[14]), "+f"(d[15]),
          "+f"(d[16]), "+f"(d[17]), "+f"(d[18]), "+f"(d[19]), "+f"(d[20]), "+f"(d[21]), "+f"(d[22]), "+f"(d[23]),
          "+f"(d[24]), "+f"(d[25]), "+f"(d[26]), "+f"(d[27]), "+f"(d[28]), "+f"(d[29]), "+f"(d[30]), "+f"(d[31]),
          "+f"(d[32]), "+f"(d[33]), "+f"(d[34]), "+f"(d[35]), "+f"(d[36]), "+f"(d[37]), "+f"(d[38]), "+f"(d[39]),
          "+f"(d[40]), "+f"(d[41]), "+f"(d[42]), "+f"(d[43]), "+f"(d[44]), "+f"(d[45]), "+f"(d[46]), "+f"(d[47]),
          "+f"(d[48]), "+f"(d[49]), "+f"(d[50]), "+f"(d[51]), "+f"(d[52]), "+f"(d[53]), "+f"(d[54]), "+f"(d[55]),
          "+f"(d[56]), "+f"(d[57]), "+f"(d[58]), "+f"(d[59]), "+f"(d[60]), "+f"(d[61]), "+f"(d[62]), "+f"(d[63]),
          "+f"(d[64]), "+f"(d[65]), "+f"(d[66]), "+f"(d[67]), "+f"(d[68]), "+f"(d[69]), "+f"(d[70]), "+f"(d[71]),
          "+f"(d[72]), "+f"(d[73]), "+f"(d[74]), "+f"(d[75]), "+f"(d[76]), "+f"(d[77]), "+f"(d[78]), "+f"(d[79]),
          "+f"(d[80]), "+f"(d[81]), "+f"(d[82]), "+f"(d[83]), "+f"(d[84]), "+f"(d[85]), "+f"(d[86]), "+f"(d[87]),
          "+f"(d[88]), "+f"(d[89]), "+f"(d[90]), "+f"(d[91]), "+f"(d[92]), "+f"(d[93]), "+f"(d[94]), "+f"(d[95]),
          "+f"(d[96]), "+f"(d[97]), "+f"(d[98]), "+f"(d[99]), "+f"(d[100]), "+f"(d[101]), "+f"(d[102]), "+f"(d[103]),
          "+f"(d[104]), "+f"(d[105]), "+f"(d[106]), "+f"(d[107]), "+f"(d[108]), "+f"(d[109]), "+f"(d[110]), "+f"(d[111]),
          "+f"(d[112]), "+f"(d[113]), "+f"(d[114]), "+f"(d[115]), "+f"(d[116]), "+f"(d[117]), "+f"(d[118]), "+f"(d[119]),
          "+f"(d[120]), "+f"(d[121]), "+f"(d[122]), "+f"(d[123]), "+f"(d[124]), "+f"(d[125]), "+f"(d[126]), "+f"(d[127])
        : "l"(da), "l"(db), "r"(acc));
}
__device__ __forceinline__ void wgmma_rs_n64_tb(float (&d)[32], uint32_t a0, uint32_t a1, uint32_t a2, uint32_t a3, uint64_t db) {
    asm volatile("wgmma.mma_async.sync.aligned.m64n64k16.f32.bf16.bf16 {"
        "%0, %1, %2, %3, %4, %5, %6, %7, %8, %9, %10, %11, %12, %13, %14, %15, %16, %17, %18, %19, %20, %21, %22, %23, %24, %25, %26, %27, %28, %29, %30, %31}, {%32, %33, %34, %35}, %36, 1, 1, 1, 1;\n"
        : "+f"(d[0]), "+f"(d[1]), "+f"(d[2]), "+f"(d[3]), "+f"(d[4]), "+f"(d[5]), "+f"(d[6]), "+f"(d[7]),
          "+f"(d[8]), "+f"(d[9]), "+f"(d[10]), "+f"(d[11]), "+f"(d[12]), "+f"(d[13]), "+f"(d[14]), "+f"(d[15]),
          "+f"(d[16]), "+f"(d[17]), "+f"(d[18]), "+f"(d[19]), "+f"(d[20]), "+f"(d[21]), "+f"(d[22]), "+f"(d[23]),
          "+f"(d[24]), "+f"(d[25]), "+f"(d[26]), "+f"(d[27]), "+f"(d[28]), "+f"(d[29]), "+f"(d[30]), "+f"(d[31])
        : "r"(a0), "r"(a1), "r"(a2), "r"(a3), "l"(db));
}
__device__ __forceinline__ void wgmma_rs_n64_tb_init(float (&d)[32], uint32_t a0, uint32_t a1, uint32_t a2, uint32_t a3, uint64_t db) {
    asm volatile("wgmma.mma_async.sync.aligned.m64n64k16.f32.bf16.bf16 {"
        "%0, %1, %2, %3, %4, %5, %6, %7, %8, %9, %10, %11, %12, %13, %14, %15, %16, %17, %18, %19, %20, %21, %22, %23, %24, %25, %26, %27, %28, %29, %30, %31}, {%32, %33, %34, %35}, %36, 0, 1, 1, 1;\n"
        : "=f"(d[0]), "=f"(d[1]), "=f"(d[2]), "=f"(d[3]), "=f"(d[4]), "=f"(d[5]), "=f"(d[6]), "=f"(d[7]),
          "=f"(d[8]), "=f"(d[9]), "=f"(d[10]), "=f"(d[11]), "=f"(d[12]), "=f"(d[13]), "=f"(d[14]), "=f"(d[15]),
          "=f"(d[16]), "=f"(d[17]), "=f"(d[18]), "=f"(d[19]), "=f"(d[20]), "=f"(d[21]), "=f"(d[22]), "=f"(d[23]),
          "=f"(d[24]), "=f"(d[25]), "=f"(d[26]), "=f"(d[27]), "=f"(d[28]), "=f"(d[29]), "=f"(d[30]), "=f"(d[31])
        : "r"(a0), "r"(a1), "r"(a2), "r"(a3), "l"(db));
}

__device__ __forceinline__ void wg_fence() { asm volatile("wgmma.fence.sync.aligned;\n" ::: "memory"); }
__device__ __forceinline__ void wg_commit() { asm volatile("wgmma.commit_group.sync.aligned;\n" ::: "memory"); }
template <int N> __device__ __forceinline__ void wg_wait() { asm volatile("wgmma.wait_group.sync.aligned %0;\n" ::"n"(N) : "memory"); }
template <int N> __device__ __forceinline__ void fence_regs(float (&a)[N]) {
#pragma unroll
    for (int i = 0; i < N; i++) asm volatile("" : "+f"(a[i])::"memory");
}
template <int N> __device__ __forceinline__ void fence_regs(uint32_t (&a)[N]) {
#pragma unroll
    for (int i = 0; i < N; i++) asm volatile("" : "+r"(a[i])::"memory");
}
__device__ __forceinline__ void mbar_init(uint32_t bar, uint32_t cnt) {
    asm volatile("mbarrier.init.shared::cta.b64 [%0], %1;\n" ::"r"(bar), "r"(cnt) : "memory");
}
__device__ __forceinline__ void mbar_expect_tx(uint32_t bar, uint32_t bytes) {
    asm volatile("mbarrier.arrive.expect_tx.shared::cta.b64 _, [%0], %1;\n" ::"r"(bar), "r"(bytes) : "memory");
}
__device__ __forceinline__ void mbar_wait(uint32_t bar, uint32_t parity) {
    asm volatile("{\n.reg .pred p;\nLW:\nmbarrier.try_wait.parity.shared::cta.b64 p, [%0], %1;\n@!p pmevent 0;\n@!p bra LW;\n}\n" ::"r"(bar), "r"(parity) : "memory");
}
__device__ __forceinline__ void mbar_wait_sleep(uint32_t bar, uint32_t parity) {
    asm volatile("{\n.reg .pred p;\nLW:\nmbarrier.try_wait.parity.shared::cta.b64 p, [%0], %1, 20000;\n@!p pmevent 0;\n@!p bra LW;\n}\n" ::"r"(bar), "r"(parity) : "memory");
}
__device__ __forceinline__ void mbar_wait_bounded(uint32_t bar, uint32_t parity) {
    asm volatile("{\n.reg .pred p;\n.reg .u32 c;\nmov.u32 c, 0;\nLW:\nmbarrier.try_wait.parity.shared::cta.b64 p, [%0], %1, 20000;\n@p bra LD;\n"
                 "add.u32 c, c, 1;\nsetp.ge.u32 p, c, 262144;\n@p trap;\nbra LW;\nLD:\n}\n" ::"r"(bar), "r"(parity) : "memory");
}
__device__ __forceinline__ void flag_wait(const int* p, int v) {
    asm volatile("{\n.reg .pred p;\n.reg .s32 f;\nLW:\nld.acquire.gpu.global.s32 f, [%0];\nsub.s32 f, f, %1;\nsetp.lt.s32 p, f, 0;\n@p bra LW;\n}\n" ::"l"(p), "r"(v) : "memory");
}
__device__ __forceinline__ void flag_wait_bounded(const int* p, int v) {
    asm volatile("{\n.reg .pred p;\n.reg .u32 c;\n.reg .s32 f;\nmov.u32 c, 0;\nLW:\nld.acquire.gpu.global.s32 f, [%0];\nsub.s32 f, f, %1;\nsetp.ge.s32 p, f, 0;\n@p bra LD;\n"
                 "nanosleep.u32 500;\nadd.u32 c, c, 1;\nsetp.ge.u32 p, c, 4194304;\n@p trap;\nbra LW;\nLD:\n}\n" ::"l"(p), "r"(v) : "memory");
}
__device__ __forceinline__ bool elect() {
    uint32_t p; asm volatile("{\n.reg .pred p;\nelect.sync _|p, -1;\nselp.u32 %0, 1, 0, p;\n}\n" : "=r"(p)); return p;
}
__device__ __forceinline__ void bulk_g2s(uint32_t dst, const void* src, uint32_t bytes, uint32_t bar) {
    asm volatile("cp.async.bulk.shared::cluster.global.mbarrier::complete_tx::bytes [%0], [%1], %2, [%3];\n"
                 ::"r"(dst), "l"(src), "r"(bytes), "r"(bar) : "memory");
}
__device__ __forceinline__ void bulk_g2s_mc(uint32_t dst, const void* src, uint32_t bytes, uint32_t bar, uint16_t mask) {
    asm volatile("cp.async.bulk.shared::cluster.global.mbarrier::complete_tx::bytes.multicast::cluster [%0], [%1], %2, [%3], %4;\n"
                 ::"r"(dst), "l"(src), "r"(bytes), "r"(bar), "h"(mask) : "memory");
}
__device__ __forceinline__ void tma_g2s(uint32_t dst, const CUtensorMap* tm, int rowgroup, uint32_t bar) {
    asm volatile("cp.async.bulk.tensor.4d.shared::cluster.global.tile.mbarrier::complete_tx::bytes [%0], [%1, {0, 0, 0, %2}], [%3];\n"
                 ::"r"(dst), "l"(tm), "r"(rowgroup), "r"(bar) : "memory");
}
__device__ __forceinline__ void bar_sync(int id, int n) { asm volatile("bar.sync %0, %1;\n" ::"r"(id), "r"(n) : "memory"); }
__device__ __forceinline__ void bar_arrive(int id, int n) { asm volatile("bar.arrive %0, %1;\n" ::"r"(id), "r"(n) : "memory"); }
__device__ __forceinline__ float quad_last(float v) {
    float r; asm volatile("shfl.sync.idx.b32 %0, %1, 3, 0x1c1f, -1;\n" : "=f"(r) : "f"(v)); return r;
}
__device__ __forceinline__ float ex2(float x) { float y; asm("ex2.approx.ftz.f32 %0, %1;\n" : "=f"(y) : "f"(x)); return y; }
__device__ __forceinline__ float rcp(float x) { float y; asm("rcp.approx.ftz.f32 %0, %1;\n" : "=f"(y) : "f"(x)); return y; }
__device__ __forceinline__ uint32_t pack_bf16(float lo, float hi) {
    uint32_t r; asm("cvt.rn.bf16x2.f32 %0, %1, %2;\n" : "=r"(r) : "f"(hi), "f"(lo)); return r;
}
__device__ __forceinline__ uint32_t pack_f16(float lo, float hi) {
    uint32_t r; asm("cvt.rn.f16x2.f32 %0, %1, %2;\n" : "=r"(r) : "f"(hi), "f"(lo)); return r;
}
__device__ __forceinline__ uint32_t pack_f16_sat(float lo, float hi) {
    uint32_t r; asm("cvt.rn.satfinite.f16x2.f32 %0, %1, %2;\n" : "=r"(r) : "f"(hi), "f"(lo)); return r;
}
__device__ __forceinline__ float f16_lo(uint32_t v) { float r; asm("cvt.f32.f16 %0, %1;\n" : "=f"(r) : "h"((unsigned short)v)); return r; }
__device__ __forceinline__ float f16_hi(uint32_t v) { return f16_lo(v >> 16); }
__device__ __forceinline__ float bf_lo(uint32_t v) { return __uint_as_float(v << 16); }
__device__ __forceinline__ float bf_hi(uint32_t v) { return __uint_as_float(v & 0xFFFF0000u); }
__device__ __forceinline__ float bf_round(float x) { return __uint_as_float(pack_bf16(0.f, x)); }
__device__ __forceinline__ void st_release(int* p, int v) {
    asm volatile("st.release.gpu.global.s32 [%0], %1;\n" ::"l"(p), "r"(v) : "memory");
}
__device__ __forceinline__ uint4 ldg_pinned(const uint4* p) {
    uint4 v; asm volatile("ld.global.nc.v4.u32 {%0, %1, %2, %3}, [%4];\n" : "=r"(v.x), "=r"(v.y), "=r"(v.z), "=r"(v.w) : "l"(p) : "memory"); return v;
}
__device__ __forceinline__ void stmatrix_x4(uint32_t addr, uint32_t r0, uint32_t r1, uint32_t r2, uint32_t r3) {
    asm volatile("stmatrix.sync.aligned.m8n8.x4.shared.b16 [%0], {%1, %2, %3, %4};\n" ::"r"(addr), "r"(r0), "r"(r1), "r"(r2), "r"(r3) : "memory");
}

__device__ __forceinline__ uint32_t tile_off(int r, int ch) {
    return (uint32_t)((r >> 3) * 4096 + (ch >> 3) * 1024 + (r & 7) * 128 + (((ch ^ r) & 7) << 4));
}
__device__ __forceinline__ int h_unit(int qt, int u) { return qt < 78 ? u * 78 + qt : 624; }
__device__ __forceinline__ int row_off(int r) { return 4096 + h_unit(r >> 7, (r >> 4) & 7) * 8192 + (r & 8) * 512 + (r & 7) * 144; }

__device__ __forceinline__ float4 lds128f(uint32_t a) {
    float4 v; asm volatile("ld.shared.v4.f32 {%0, %1, %2, %3}, [%4];\n" : "=f"(v.x), "=f"(v.y), "=f"(v.z), "=f"(v.w) : "r"(a) : "memory"); return v;
}
__device__ __forceinline__ uint64_t lds64(uint32_t a) { uint64_t v; asm volatile("ld.shared.u64 %0, [%1];\n" : "=l"(v) : "r"(a) : "memory"); return v; }
__device__ __forceinline__ uint4 lds128(uint32_t a) {
    uint4 v; asm volatile("ld.shared.v4.u32 {%0, %1, %2, %3}, [%4];\n" : "=r"(v.x), "=r"(v.y), "=r"(v.z), "=r"(v.w) : "r"(a) : "memory"); return v;
}
__device__ __forceinline__ void sts128(uint32_t a, uint32_t x, uint32_t y, uint32_t z, uint32_t w) {
    asm volatile("st.shared.v4.u32 [%0], {%1, %2, %3, %4};\n" ::"r"(a), "r"(x), "r"(y), "r"(z), "r"(w) : "memory");
}
__device__ __forceinline__ void mbar_arrive(uint32_t bar) {
    asm volatile("mbarrier.arrive.shared::cta.b64 _, [%0];\n" ::"r"(bar) : "memory");
}
__device__ __forceinline__ uint64_t mkaddr(uint32_t lo, uint32_t hi) { uint64_t a; asm("mov.b64 %0, {%1, %2};\n" : "=l"(a) : "r"(lo), "r"(hi)); return a; }
__device__ __forceinline__ void red_add(int* p) { asm volatile("red.relaxed.gpu.global.add.s32 [%0], 1;\n" ::"l"(p) : "memory"); }
__device__ __forceinline__ void red_release(int* p) {
    asm volatile("fence.proxy.async.global;\nfence.acq_rel.gpu;\nred.relaxed.gpu.global.add.s32 [%0], 1;\n" ::"l"(p) : "memory");
}
__device__ __forceinline__ void fence_async_global() { asm volatile("fence.proxy.async.global;\n" ::: "memory"); }
__device__ __forceinline__ void fence_async_smem() { asm volatile("fence.proxy.async.shared::cta;\n" ::: "memory"); }
__device__ __forceinline__ void bulk_s2g(void* dst, uint32_t src, uint32_t bytes) {
    asm volatile("cp.async.bulk.global.shared::cta.bulk_group [%0], [%1], %2;\ncp.async.bulk.commit_group;\n" ::"l"(dst), "r"(src), "r"(bytes) : "memory");
}
__device__ __forceinline__ void mma16816(float (&c)[4], uint32_t a0, uint32_t a1, uint32_t a2, uint32_t a3, uint32_t b0, uint32_t b1) {
    asm("mma.sync.aligned.m16n8k16.row.col.f32.bf16.bf16.f32 {%0, %1, %2, %3}, {%4, %5, %6, %7}, {%8, %9}, {%0, %1, %2, %3};\n"
        : "+f"(c[0]), "+f"(c[1]), "+f"(c[2]), "+f"(c[3]) : "r"(a0), "r"(a1), "r"(a2), "r"(a3), "r"(b0), "r"(b1));
}
__device__ __forceinline__ void mma1688(float (&c)[4], uint32_t a0, uint32_t a1, uint32_t b0) {
    asm("mma.sync.aligned.m16n8k8.row.col.f32.bf16.bf16.f32 {%0, %1, %2, %3}, {%4, %5}, {%6}, {%0, %1, %2, %3};\n"
        : "+f"(c[0]), "+f"(c[1]), "+f"(c[2]), "+f"(c[3]) : "r"(a0), "r"(a1), "r"(b0));
}
__device__ __forceinline__ uint32_t hadd2_f16(uint32_t a, uint32_t b) { uint32_t r; asm("add.rn.f16x2 %0, %1, %2;\n" : "=r"(r) : "r"(a), "r"(b)); return r; }
__device__ __forceinline__ uint32_t hadd2(uint32_t a, uint32_t b) { uint32_t r; asm("add.rn.bf16x2 %0, %1, %2;\n" : "=r"(r) : "r"(a), "r"(b)); return r; }
__device__ __forceinline__ uint32_t hmul2(uint32_t a, uint32_t b) { uint32_t r; asm("mul.rn.bf16x2 %0, %1, %2;\n" : "=r"(r) : "r"(a), "r"(b)); return r; }
__device__ __forceinline__ uint32_t hfma2(uint32_t a, uint32_t b, uint32_t c) { uint32_t r; asm("fma.rn.bf16x2 %0, %1, %2, %3;\n" : "=r"(r) : "r"(a), "r"(b), "r"(c)); return r; }

constexpr int SM_Q = 0;
constexpr int SM_KV = 65536;
constexpr int SM_ML = SM_KV + STAGES * KV_BYTES;
constexpr int SM_BAR = SM_ML + 1024;
constexpr int SM_TOTAL = SM_BAR + 256;
constexpr float SCALE_LOG2 = 1.4426950408889634f / 16.0f;
constexpr float KV_SCALE = 0.75f;
constexpr float KV_OFF = 6.f;
constexpr uint32_t KV_OFF2 = 0x46004600u;
constexpr uint32_t KV_NEG4 = 0xCE00CE00u;
constexpr uint32_t P_LIMIT = 0x78007800u;
constexpr float REF_UP = REFUP;
__device__ __forceinline__ uint32_t kvf(uint32_t a) {
    uint32_t r; asm("fma.rn.f16x2 %0, %1, %2, %3;\n" : "=r"(r) : "r"(a), "r"(pack_f16(KV_SCALE, KV_SCALE)), "r"(KV_OFF2)); return r;
}
enum { BAR_PP0 = 1, BAR_PP1 = 2, BAR_WG0 = 3, BAR_WG1 = 4, BAR_H0 = 5, BAR_H1 = 6, BAR_AUX = 7, BAR_BF = 8, BAR_H2 = 9, BAR_X = 10, BAR_GO = 11, BAR_WG2 = 12, BAR_ST = 13 };

struct Hot {
    const __nv_bfloat16 *wk, *wq, *x;
    Scratch* s;
};
struct Params {
    const __nv_bfloat16* deg_inv;
    const int *src, *dst;
    __nv_bfloat16* out;
    uint32_t dhi;
    int E;
    CUtensorMap tm_out;
    CUtensorMap tm_outc;
    CUtensorMap tm_w[3];
};
static_assert(offsetof(Params, tm_outc) == offsetof(Params, tm_out) + 128, "layout");
#define SC_PAIR (blockIdx.x < 104)
#define SC_TAIL (blockIdx.x >= NCTA - 2)
#define SC_LAST (blockIdx.x == NCTA - 1)
#define SC_HELP (SC_PAIR && rank)
#define SC_OWNER (!SC_HELP && !SC_LAST)
#define SC_QT1 (26 + (int)(blockIdx.x >> 1))
#define SC_QT0 (SC_PAIR ? (rank ? (int)(blockIdx.x >> 2) : SC_QT1) : SC_TAIL ? 78 : (int)blockIdx.x - 104)
#define SC_NKV (SC_LAST ? 50 : 75)
#define SC_NMC (SC_PAIR ? 25 : SC_TAIL ? 0 : 75)
#define SC_CLS (SC_PAIR ? (rank ? 0x120 ^ (blockIdx.x & 2) * 0x80 : 0x430) | (blockIdx.x & 2) >> 1 : SC_LAST ? 0x10 : 0x432)
#define SC_NW (SC_PAIR ? 8 : SC_LAST ? 0 : 4)
#define SC_ZB (2 * SC_QT1 + 1 - (int)rank)
#define SC_TZB(k) (rank && !(k) ? 156 : 2 * (k) - (int)rank)

__global__ void __cluster_dims__(2, 1, 1) __launch_bounds__(384, 1) k_main(const __grid_constant__ Hot H, const __grid_constant__ Params P) {
    extern __shared__ __align__(1024) uint8_t smem[];
    const uint32_t sb = (uint32_t)__cvta_generic_to_shared(smem);
    const int tid = threadIdx.x, wg = __shfl_sync(~0u, tid >> 7, 0);
    const int lane = tid & 31, g = lane >> 2, q = lane & 3;
    const uint32_t rank = blockIdx.x & 1;
    unsigned c_start; asm volatile("mov.u32 %0, %%clock;" : "=r"(c_start) :: "memory");
    const uint32_t bar_full = sb + SM_BAR, bar_q = bar_full + 32, bar_go = bar_full + 48;
    const uint32_t bar_pin = bar_full + 56;
    const uint32_t bar_qfree = bar_full + 72, bar_pdone = bar_full + 88, bar_zst = bar_full + 104, bar_rfree = bar_full + 120;
    const uint32_t bar_empty = bar_full + 128, bar_end = bar_full + 160, s_tm = bar_full + 184, bar_x = bar_full + 192;
    const uint32_t bar_a = sb + SM_ML;

    const int t = tid & 127, warp = __shfl_sync(~0u, t >> 5, 0);
    int ep = 0;
    if (wg & 2) {
        unsigned done;
        {
            uint4 ra[2], rb[2], rk[5][2];
            if (blockIdx.x < 128) {
                const int e = (blockIdx.x >> 4) * 32 + (g >> 1) * 8 + (blockIdx.x & 8) / 2 + (g & 1);
                const uint4* pq = (const uint4*)(H.wq + e * 256) + warp * 8 + q;
                const uint4* pk = (const uint4*)(H.wk + ((blockIdx.x & 7) * 32 + g) * 256) + warp * 8 + q;
                const uint4* pz = (const uint4*)(H.wk + 255 * 256) + warp * 8 + q;
#pragma unroll
                for (int s = 0; s < 2; s++) {
                    ra[s] = ldg_pinned(pq + 4 * s);
                    rb[s] = ldg_pinned(pq + 4 * s + 64);
#pragma unroll
                    for (int n = 0; n < 4; n++) rk[n][s] = ldg_pinned(pk + 4 * s + n * 256);
                    rk[4][s] = ldg_pinned(pz + 4 * s);
                }
            }
            asm volatile("{\n.reg .pred p;\nsetp.eq.s32 p, %2, 0;\nmov.u32 %0, 0;\n@p ld.global.cg.u32 %0, [%1];\n}\n" : "=r"(done) : "l"(&g_sync[SY_DONE * 32]), "r"(lane) : "memory");
            bar_arrive(BAR_X, 384);
            if (warp == 0 && elect()) {
#pragma unroll
                for (int i = 0; i < 21; i++) mbar_init(bar_full + 8 * i, i < 9 ? 1 : i < 16 ? 4 : i == 20 ? 11 : SC_TAIL ? 8 : 16);
#pragma unroll
                for (int i = 0; i < 4; i++) mbar_init(bar_a + 8 * i, 1);
                mbar_expect_tx(bar_pin, QB_BYTES / 2 + 512); mbar_expect_tx(bar_pin + 8, QB_BYTES / 2);
                asm volatile("fence.mbarrier_init.release.cluster;\n" ::: "memory");
            }
            __syncwarp();
            asm volatile("barrier.cluster.arrive.relaxed.aligned;\n" ::: "memory");
            if (blockIdx.x < 128) {
                float c[5][4] = {};
#pragma unroll
                for (int s = 0; s < 2; s++) {
#pragma unroll
                    for (int n = 0; n < 5; n++) mma16816(c[n], ra[s].x, rb[s].x, ra[s].y, rb[s].y, rk[n][s].x, rk[n][s].y);
#pragma unroll
                    for (int n = 0; n < 5; n++) mma16816(c[n], ra[s].z, rb[s].z, ra[s].w, rb[s].w, rk[n][s].z, rk[n][s].w);
                }
#pragma unroll
                for (int i = 0; i < 4; i++) {
                    const int r = i & 2, n = (i & 1) * 2;
                    sts128(sb + SM_KV + 3 * KV_BYTES + QB_BYTES + i * 2048 + t * 16, __float_as_uint(c[n][r] - c[4][r]), __float_as_uint(c[n][r + 1] - c[4][r]),
                           __float_as_uint(c[n + 1][r] - c[4][r]), __float_as_uint(c[n + 1][r + 1] - c[4][r]));
                }
            }
        }
        asm volatile("setmaxnreg.dec.sync.aligned.u32 %0;\n" ::"n"(REG_P));
        if (blockIdx.x < 128) {
            bar_sync(BAR_WG2, 128);
            float4 v[4];
#pragma unroll
            for (int i = 0; i < 4; i++) v[i] = lds128f(sb + SM_KV + 3 * KV_BYTES + QB_BYTES + (warp & 2) * 2048 + (lane & 1) * 2048 + i * 512 + ((warp & 1) * 16 + (lane >> 1)) * 16);
            constexpr float SC = SCALE_LOG2 / KV_SCALE;
            const int r = (warp & 1) * 4 + (lane >> 3);
            *(uint2*)(g_w + tile_off((blockIdx.x >> 3) * 16 + (warp & 2) * 4 + r, (blockIdx.x & 7) * 4 + ((lane >> 1) & 3)) + (lane & 1) * 8) =
                make_uint2(pack_f16_sat(((v[0].x + v[1].x) + (v[2].x + v[3].x)) * SC, ((v[0].y + v[1].y) + (v[2].y + v[3].y)) * SC) | 1,
                           pack_f16_sat(((v[0].z + v[1].z) + (v[2].z + v[3].z)) * SC, ((v[0].w + v[1].w) + (v[2].w + v[3].w)) * SC) | 1);
            if (warp != 1) {
                bar_arrive(BAR_AUX, 128);
            } else {
                bar_sync(BAR_AUX, 128);
                if (elect()) { red_add(&g_sync[SY_DONE * 32 + 4 + (blockIdx.x >> 5)]); }
                __syncwarp();
            }
        }
        else bar_sync(BAR_WG2, 128);
        if (warp == 1 && XD1 < 0) bar_arrive(BAR_GO, 160);
        auto load_a = [&](int j) {
            if (elect()) {
                mbar_expect_tx(bar_a + 8 * j, QB_BYTES);
                bulk_g2s(sb + SM_KV + j * KV_BYTES, g_w + j * QB_BYTES, QB_BYTES, bar_a + 8 * j);
            }
            __syncwarp();
        };
        if (warp == 0) {
            auto poll = [&]() { int c; asm volatile("ld.relaxed.gpu.global.s32 %0, [%1];\n" : "=r"(c) : "l"(&g_sync[SY_DONE * 32 + 4 + (lane & 3)]) : "memory"); return c; };
#pragma unroll 1
            for (int j = 0; j < 4;) {
#pragma unroll 1
                for (const uint32_t mk = __ballot_sync(~0u, poll() >= 32) & 15; (mk >> j) & 1; j++) load_a(j);
            }
        } else if (warp & 1) {
#pragma unroll 1
            for (int j = 0, n = 0; j < 4;) {
                mbar_wait_bounded(bar_a + 8 * j, n & 1);
                uint32_t ok = 1;
#pragma unroll
                for (int i = 0; i < 16; i++) {
                    uint32_t v;
                    asm volatile("ld.shared.u32 %0, [%1];\n" : "=r"(v) : "r"(sb + SM_KV + j * KV_BYTES + (warp & 2) * 8192 + i * 1024 + lane * 32 + g * 4) : "memory");
                    ok &= v;
                }
                asm volatile("{\n.reg .pred p;\nsetp.ne.u32 p, %0, 0;\nbar.red.and.pred p, %1, 64, p;\nselp.u32 %0, 1, 0, p;\n}\n" : "+r"(ok) : "n"((int)BAR_WG2) : "memory");
                if (__any_sync(~0u, ok)) {
                    if (warp == 1 && elect()) asm volatile("mbarrier.arrive.shared::cta.b64 _, [%0];\nmbarrier.inval.shared::cta.b64 [%1];\n" ::"r"(bar_full + 8 * j), "r"(bar_a + 8 * j) : "memory");
                    __syncwarp();
                    j++; n = 0;
                } else {
                    asm volatile("{\n.reg .pred p;\nsetp.gt.s32 p, %0, 1000000;\n@p trap;\n}\n" ::"r"(++n) : "memory");
                    fence_async_smem();
                    if (warp == 1) load_a(j);
                }
            }
        }
        done = __shfl_sync(~0u, done, 0);
        ep = (int)(done / NCTA) + 1;
        asm volatile("barrier.cluster.wait.acquire.aligned;\n" ::: "memory");
        if (warp == 0) {
            asm volatile("st.shared.u64 [%0], %1;\n" ::"r"(s_tm), "l"(&P.tm_outc) : "memory");
            __syncwarp();
            if (elect()) {
                const uint8_t* base = (const uint8_t*)H.s;
                uint32_t cls = SC_CLS, bytes = KV_BYTES, moff = SC_NMC ? rank * (KV_BYTES / 2) : 0, step = 5 * KV_BYTES;
                const uint8_t* src = base;
                int next = 0;
                const int nit = SC_NKV + SC_NW;
#pragma unroll 1
                for (int j = 0; j < nit; j++) {
                    const uint32_t slot = sb + SM_KV + (j & 3) * KV_BYTES, fb = bar_full + 8 * (j & 3);
                    if (j == next) {
                        const int k = j - SC_NKV;
                        const int sw = SC_HELP ? j - 25 : -1;
                        next = j + 1;
                        if (j >= 3 && (unsigned)sw >= 5) next = k >= 0 ? next : j < 25 ? 25 : j < GO0 ? GO0 : j < 49 ? 49 : j < 50 ? 50 : 75;
                        if (j == SC_NMC) moff = 0;
                        if (j == 0 || j == 25 || j == 50) { src = base + (4096 + (cls & 15) * KV_BYTES + moff); cls >>= 4; }
                        if (SC_TAIL ? j == nit - 1 : j == GO0) mbar_arrive(bar_go);
                        int fo = -1, fv = 1;
                        if (j < 3) { fo = (SY_H0 + 5 * j + (SC_CLS & 15)) * 32; fv = 5; }
                        if (j == 3) { fo = SY_H1 * 32; fv = 79; }
                        if (sw == 1) fo = 25 * 32 + SC_QT1;
                        if (k == 0) fo = SY_B * 32;
                        if (k == 1) { fo = (SC_TAIL ? SY_AUX0 : SY_AUX) * 32; fv = SC_TAIL ? NAUX : NAUX / 3; }
                        if (fo >= 0) {
                            flag_wait(g_sync + fo, fv * ep);
                            fence_async_global();
                        }
                        if (sw == 2 || (k == 2 && !SC_TAIL)) {
                            uint32_t qs = sw == 2 ? offsetof(Scratch, q) + (2 * SC_QT1 + 1) * QB_BYTES : SC_PAIR ? offsetof(Scratch, agg) + SC_ZB * QB_BYTES : offsetof(Scratch, part) + SC_QT0 * (4 * PART_BYTES);
#pragma unroll 1
                            for (int w = 0; w < (k == 2 && SC_PAIR ? 1 : 2); w++) {
                                mbar_wait_sleep(bar_qfree + 8 * w, k == 2 && SC_HELP);
                                mbar_expect_tx(bar_q + 8 * w, SC_PAIR ? QB_BYTES : PART_BYTES);
                                if (!SC_PAIR) bulk_g2s(sb + SM_ML + w * 512, base + (qs + (w ? -512 : QB_BYTES)), 512, bar_q + 8 * w);
                                bulk_g2s(sb + SM_Q + w * QB_BYTES, base + qs, QB_BYTES, bar_q + 8 * w);
                                qs += sw == 2 ? -QB_BYTES : PART_BYTES + 512;
                            }
                        }
                        if ((sw | 1) == 3) {
                            mbar_wait_sleep(bar_pdone + 8 * (sw - 2), 0);
                            bulk_s2g(g_part + (blockIdx.x - 3 + sw) * PART_BYTES, slot, PART_BYTES);
                            asm volatile("cp.async.bulk.wait_group.read 0;\n" ::: "memory");
                        }
                        if (sw == 5) {
                            asm volatile("cp.async.bulk.wait_group 0;\n" ::: "memory");
                            red_release(&g_sync[SY_PART * 32]);
                        }
                        if (k == 0) {
                            asm volatile("prefetch.tensormap [%0];\n" ::"l"(&P.tm_outc) : "memory");
                            src = g_w + (12 - SC_NW) * QB_BYTES; bytes = step = QB_BYTES;
                        }
                        if (k == 2) next = SC_TAIL ? nit - 1 : nit;
                    }
                    mbar_wait_sleep(fb + (bar_empty - bar_full), (j >> 2) & 1);
                    mbar_expect_tx(fb, bytes);
                    if (j < SC_NMC) bulk_g2s_mc(slot + moff, src, KV_BYTES / 2, fb, 3);
                    else bulk_g2s(slot, src, bytes, fb);
                    src += step;
                }
            }
        } else {
            if (warp == 2 && SC_OWNER) {
                uint8_t* dst = g_hz + 4096 + h_unit(SC_QT0, 0) * 8192;
                auto send = [&](int u0, int u1) {
#pragma unroll
                    for (int u = u0; u < u1; u++) {
                        bulk_s2g(dst + u * (78 * 8192), sb + SM_Q + u * 8192, 8192);
                        asm volatile("cp.async.bulk.wait_group 0;\n" ::: "memory");
                    }
                };
                int* f0 = &g_sync[(SY_H0 + SC_QT0 / 5) * 32];
                bar_sync(BAR_H0, 64);
                if (elect()) {
                    send(0, 1);
                    if (SC_QT0 < 65) red_release(f0);
                }
                bar_sync(BAR_H1, 160);
                if (elect()) {
                    if (HDEF >= 0) mbar_wait(bar_full + 8 * HDEF, 0);
                    if (!SC_TAIL) send(1, 4);
                    mbar_arrive(bar_q);
                }
                bar_sync(BAR_H2, 160);
                if (elect()) {
                    if (!SC_TAIL) { send(4, 8); mbar_arrive(bar_q + 8); }
                    red_release(&g_sync[SY_H1 * 32]);
                }
                __syncwarp();
            }
        }
    } else {
        const uint32_t sq = sb + SM_Q + wg * QB_BYTES;
        const uint32_t qbar = bar_q + 8 * wg;
        const uint32_t dq0 = __shfl_sync(~0u, ((sq & 0x3FFFF) >> 4) | (64u << 16), 0);
        const uint32_t dk0 = __shfl_sync(~0u, (((sb + SM_KV) & 0x3FFFF) >> 4) | (64u << 16), 0);
        float o[128];
        int it = 4;
        const uint32_t dhi = P.dhi;
        uint32_t rel_addr;
        auto rel_target = [&](uint32_t r) {
            asm("mapa.shared::cluster.u32 %0, %1, %2;\n" : "=r"(rel_addr) : "r"(bar_empty), "r"(r));
            if (lane >= 2) rel_addr = 0;
            asm volatile("" : "+r"(rel_addr));
        };
        rel_target(SC_NMC ? rank ^ (lane & 1) : rank);
        auto release = [&](int st) {
            asm volatile("{\n.reg .pred p;\nsetp.ne.u32 p, %1, 0;\n@p mbarrier.arrive.shared::cluster.b64 _, [%0];\n}\n"
                         ::"r"(rel_addr + 8 * st), "r"(rel_addr) : "memory");
        };
        const bool active = !(SC_TAIL && wg == 1);
        auto pp_sync = [&]() { if (!SC_TAIL) bar_sync(BAR_PP0 + wg, 256); };
        auto pp_arrive = [&]() { if (!SC_TAIL) bar_arrive(BAR_PP1 - wg, 256); };
        auto warp_arrive = [&](uint32_t bar) {
            __syncwarp();
            asm volatile("{\n.reg .pred p;\nelect.sync _|p, -1;\n@p mbarrier.arrive.shared::cta.b64 _, [%0];\n}\n" ::"r"(bar + 8 * wg) : "memory");
        };
        auto peer_arrive = [&]() {
            asm volatile("{\n.reg .pred p;\n.reg .b32 a;\nelect.sync _|p, -1;\nmapa.shared::cluster.u32 a, %0, %1;\n"
                         "@p mbarrier.arrive.shared::cluster.b64 _, [a];\n}\n" ::"r"(bar_rfree), "r"(rank ^ 1) : "memory");
        };
        auto stage_q = [&]() {
            auto pk = [&](int i) { return QRND(pack_f16_sat(o[i], o[i + 1])); };
#pragma unroll
            for (int i = 0; i < 16; i++)
                stmatrix_x4(sq + warp * 8192 + tile_off(lane & 15, 2 * i + (lane >> 4)), pk(8 * i), pk(8 * i + 2), pk(8 * i + 4), pk(8 * i + 6));
        };
        float s[40];
        auto issue_qk = [&](int st) {
            const uint64_t kb = mkaddr(dk0 + st * (KV_BYTES >> 4), dhi);
            const uint64_t qd = mkaddr(dq0 + ((uint32_t)it >> 24), dhi);
            wgmma_ss_n80_init(s, qd + 198, kb + 198);
#pragma unroll
            for (int kk = 0; kk < 15; kk++) wgmma_ss_n80(s, qd + ((kk >> 2) * 64 + (kk & 3) * 2), kb + ((kk >> 2) * 64 + (kk & 3) * 2));
            wg_commit();
        };

        {
            const int rb = (2 * SC_QT0 + wg) * 64 + warp * 16;
            const uint32_t xbar = bar_x + 32 * wg + 8 * warp;
            if (PFX && rb < NN && t == 0) asm volatile("prefetch.global.L2 [%0];" :: "l"(H.x + (size_t)rb * 256) : "memory");
            if (elect()) {
                mbar_init(xbar, 1);
                asm volatile("fence.mbarrier_init.release.cluster;\nfence.proxy.async.shared::cta;\n" ::: "memory");
                mbar_expect_tx(xbar, rb < NN ? 8192 : 0);
            }
            asm volatile("barrier.cluster.arrive.relaxed.aligned;\n" ::: "memory");
            if (wg == 1) pp_arrive();
            bar_sync(BAR_X, 384);
            if (wg == 1 && XD1 < 0) bar_sync(BAR_GO, 160);
            else if (XD0 | XD1 | XDW) { unsigned c; do { asm volatile("mov.u32 %0, %%clock;" : "=r"(c) :: "memory"); } while ((int)(c - c_start) < (wg ? XD1 : XD0) + warp * XDW); }
            if (rb < NN && elect()) bulk_g2s(sq + warp * 8192, H.x + (size_t)rb * 256, 8192, xbar);
            if (rb >= NN) {
#pragma unroll 1
                for (int i = 0; i < 16; i++) sts128(sq + warp * 8192 + i * 512 + lane * 16, 0, 0, 0, 0);
            }
            __syncwarp();
            mbar_wait(xbar, 0);
            uint4 xa[8], xb[8];
#pragma unroll
            for (int s = 0; s < 8; s++) {
                xa[s] = lds128(sq + (warp * 16 + g) * 512 + (4 * s + q) * 16);
                xb[s] = lds128(sq + (warp * 16 + g + 8) * 512 + (4 * s + q) * 16);
            }
            float sm[2][4], sq2[2][4][4];
#pragma unroll
            for (int i = 0; i < 4; i++) {
                sm[0][i] = sm[1][i] = 0.f;
#pragma unroll
                for (int k = 0; k < 4; k++) sq2[0][k][i] = sq2[1][k][i] = 0.f;
            }
#pragma unroll
            for (int s = 0; s < 8; s++) {
#pragma unroll
                for (int hh = 0; hh < 2; hh++) {
                    const uint4 v = hh ? xb[s] : xa[s];
                    mma16816(sm[hh], v.x, v.y, v.z, v.w, 0x3F803F80u, 0x3F803F80u);
                    mma1688(sq2[hh][0], v.x, v.y, v.x); mma1688(sq2[hh][1], v.x, v.y, v.y);
                    mma1688(sq2[hh][2], v.z, v.w, v.z); mma1688(sq2[hh][3], v.z, v.w, v.w);
                }
            }
            float inv[2], off[2];
#pragma unroll
            for (int hh = 0; hh < 2; hh++) {
                const float mean = (sm[hh][0] + sm[hh][2]) * (1.f / 256.f);
                const float d0 = (sq2[hh][0][0] + sq2[hh][2][0]) + (sq2[hh][1][2] + sq2[hh][3][2]);
                const float d1 = (sq2[hh][0][1] + sq2[hh][2][1]) + (sq2[hh][1][3] + sq2[hh][3][3]);
                const float ss = __shfl_sync(~0u, (g & 1) ? d1 : d0, g * 4 + (g >> 1));
                const float var = fmaxf(ss * (1.f / 256.f) - mean * mean, 0.f);
                float sd;
                asm("sqrt.approx.ftz.f32 %0, %1;\n" : "=f"(sd) : "f"(bf_round(bf_round(var) + 1e-5f)));
                asm("rcp.approx.ftz.f32 %0, %1;\n" : "=f"(inv[hh]) : "f"(bf_round(sd)));
                off[hh] = -mean * inv[hh];
            }
            uint32_t a[64];
#pragma unroll
            for (int s = 0; s < 8; s++) {
                a[8 * s] = xa[s].x; a[8 * s + 1] = xb[s].x; a[8 * s + 2] = xa[s].y; a[8 * s + 3] = xb[s].y;
                a[8 * s + 4] = xa[s].z; a[8 * s + 5] = xb[s].z; a[8 * s + 6] = xa[s].w; a[8 * s + 7] = xb[s].w;
            }
            fence_regs(a);
            if (wg == 1 && __any_sync(~0u, inv[0] + inv[1] != -1.f)) bar_arrive(BAR_ST, 256);
            asm volatile("setmaxnreg.inc.sync.aligned.u32 %0;\n" ::"n"(REG_C));
            fence_regs(a);
#pragma unroll
            for (int i = 0; i < 64; i++)
                a[i] = pack_f16(fmaf(bf_lo(a[i]), inv[i & 1], off[i & 1]), fmaf(bf_hi(a[i]), inv[i & 1], off[i & 1]));
            if (SC_OWNER) {
#pragma unroll
                for (int i = 0; i < 16; i++) {
                    const uint32_t mk = (i == 15 && q == 3) ? 0xFFFFu : ~0u;
                    stmatrix_x4(sq + warp * 8192 + tile_off(lane & 15, 2 * i + (lane >> 4)), kvf(a[4 * i]), kvf(a[4 * i + 1]),
                                kvf(a[4 * i + 2] & mk), kvf(a[4 * i + 3] & mk));
                }
                fence_async_smem();
                if (tid < 32) bar_arrive(BAR_H0, 64);
                bar_arrive(wg ? BAR_H2 : BAR_H1, 160);
            }
            asm volatile("barrier.cluster.wait.acquire.aligned;\n" ::: "memory");
            if (wg == 0) bar_sync(BAR_ST, 256);
            if (active) {
                fence_regs(a);
#pragma unroll
                for (int c = 0; c < 4; c++) {
                    if (c == 1) {
                        if (wg == 1) {
                            wg_wait<0>();
                            release(0);
                        }
                        pp_sync();
                    }
                    mbar_wait(bar_full + 8 * c, 0);
                    const uint64_t wb = mkaddr(dk0 + c * (KV_BYTES >> 4), dhi);
                    wg_fence();
#pragma unroll
                    for (int kk = 0; kk < 4; kk++) {
                        if (c | kk) wgmma_rs_n256_tb(o, a[16 * c + 4 * kk], a[16 * c + 4 * kk + 1], a[16 * c + 4 * kk + 2], a[16 * c + 4 * kk + 3], wb + kk * 512);
                        else wgmma_rs_n256_tb_init(o, a[0], a[1], a[2], a[3], wb);
                    }
                    wg_commit();
                    if (c > 0) { wg_wait<1>(); if (c > 1 || wg == 0) release(c - 1); }
                }
                if (wg == 0) pp_arrive();
                wg_wait<0>();
                fence_regs(o);
                release(3);
                if (SC_OWNER) mbar_wait(qbar, 0);
                stage_q();
                fence_async_smem();
                bar_sync(BAR_WG0 + wg, 128);
                mbar_wait(bar_full, 1);
                wg_fence();
                issue_qk(0);
                if (wg == 1) pp_arrive();
            } else {
                peer_arrive();
            }
        }

        uint32_t p[20];
        float m0 = 0.f, m1 = 0.f, e0, e1, l0, l1;
        uint32_t plim;
        uint32_t qphase = (SC_OWNER && active) ? 1 : 0;
        auto issue_pv = [&](int st, int acc) {
            const uint64_t vb = mkaddr(dk0 + st * (KV_BYTES >> 4), dhi);
            wgmma_rs_n256_tb_pred(o, p[0], p[1], p[2], p[3], vb, acc);
#pragma unroll
            for (int kk = 1; kk < 5; kk++)
                wgmma_rs_n256_tb(o, p[4 * kk], p[4 * kk + 1], p[4 * kk + 2], p[4 * kk + 3], vb + kk * 512);
            wg_commit();
        };
        const uint32_t mq_addr = sq + tile_off(warp * 16 + g, 31) + 14;
        auto exceeds = [&](const uint32_t (&p)[20]) {
            uint32_t a = __vimax3_s16x2(P_LIMIT, p[0], p[1]), b = __vimax3_s16x2(p[2], p[3], p[4]);
#pragma unroll
            for (int i = 5; i < 17; i += 4) { a = __vimax3_s16x2(a, p[i], p[i + 1]); b = __vimax3_s16x2(b, p[i + 2], p[i + 3]); }
            a = __vimax3_s16x2(a, p[17], p[18]);
            return __any_sync(~0u, __vimax3_s16x2(a, b, p[19]) != plim);
        };
        auto remax = [&](float& a, float& b, bool store) {
            float a1 = fmaxf(s[0], s[1]), b1 = fmaxf(s[2], s[3]), a2 = fmaxf(s[4], s[5]), b2 = fmaxf(s[6], s[7]);
#pragma unroll
            for (int i = 2; i < 10; i++) {
                a1 = fmaxf(a1, s[4 * i]); a2 = fmaxf(a2, s[4 * i + 1]);
                b1 = fmaxf(b1, s[4 * i + 2]); b2 = fmaxf(b2, s[4 * i + 3]);
            }
            a1 = fmaxf(a1, a2); b1 = fmaxf(b1, b2);
            a1 = fmaxf(a1, __shfl_xor_sync(~0u, a1, 1)); b1 = fmaxf(b1, __shfl_xor_sync(~0u, b1, 1));
            a1 = fmaxf(a1, __shfl_xor_sync(~0u, a1, 2)); b1 = fmaxf(b1, __shfl_xor_sync(~0u, b1, 2));
            a = fmaxf(a, a1 - e0 + REF_UP); b = fmaxf(b, b1 - e1 + REF_UP);
            const uint32_t u = pack_f16_sat((m0 + a) * (-1.f / KV_OFF), (m1 + b) * (-1.f / KV_OFF));
            const float g0 = (m0 + a) + KV_OFF * f16_lo(u), g1 = (m1 + b) + KV_OFF * f16_hi(u);
            const bool x0 = fabsf(g0) <= 1.f, x1 = fabsf(g1) <= 1.f;
            if (x0) a -= g0;
            if (x1) b -= g1;
            const float da = a + e0, db = b + e1;
            m0 += a; m1 += b;
            e0 = x0 ? 0.f : g0; e1 = x1 ? 0.f : g1;
            plim = (x0 && x1) ? P_LIMIT : 0u;
            asm volatile("{\n.reg .pred p;\nsetp.ne.s32 p, %3, 0;\n@p st.shared.u16 [%0], %1;\n@p st.shared.u16 [%0 + 4096], %2;\n}\n"
                         ::"r"(mq_addr), "h"((unsigned short)u), "h"((unsigned short)(u >> 16)), "r"((int)(store && q == 0)) : "memory");
#pragma unroll
            for (int i = 0; i < 10; i++) {
                p[2 * i] = pack_f16(ex2(s[4 * i] - da), ex2(s[4 * i + 1] - da));
                p[2 * i + 1] = pack_f16(ex2(s[4 * i + 2] - db), ex2(s[4 * i + 3] - db));
            }
            fence_regs(p);
            fence_async_smem();
            __syncwarp();
        };

        auto row_sums = [&](float& z0, float& z1) {
            z0 = quad_last(o[125]); z1 = quad_last(o[127]);
            l0 = z0 * (KV_SCALE / KV_OFF); l1 = z1 * (KV_SCALE / KV_OFF);
        };
        auto cut = [&]() { asm volatile("{\n.reg .pred p;\nsetp.lt.s32 p, %0, 0;\nL:\n@p pmevent 0;\n@p bra L;\n}\n" ::"r"(it) : "memory"); };
        auto stats = [&]() { return (q & 2) ? ((q & 1) ? l1 : m1) : ((q & 1) ? l0 : m0); };
        const int nseg = SC_HELP ? 2 : 1;
        if (active) {
#pragma unroll 1
        for (int seg = 0;; seg++) {
            wg_wait<0>();
            fence_regs(s);
            e0 = e1 = 0.f;
            const int it0 = it, itl = __shfl_sync(~0u, seg + 1 < nseg ? 3 + 25 : 3 + SC_NKV, 0);
            const int itx = (wg == 1 && seg + 1 == nseg) ? itl : -1;
            bool redo = true, have = !seg;
#pragma unroll 1
            for (;;) {
                if (!have) {
#pragma unroll
                    for (int i = 0; i < 20; i++) p[i] = pack_f16(ex2(s[2 * i]), ex2(s[2 * i + 1]));
                    redo = exceeds(p);
                }
                if (redo) {
                    float d0 = it != it0 ? 0.f : -INFINITY, d1 = d0;
                    remax(d0, d1, it != itl);
                    if (it != it0) {
                        const float a0 = ex2(-d0), a1 = ex2(-d1);
#pragma unroll
                        for (int i = 0; i < 32; i++) { o[4 * i] *= a0; o[4 * i + 1] *= a0; o[4 * i + 2] *= a1; o[4 * i + 3] *= a1; }
                    }
                }
                if (it == it0 && (seg || SC_OWNER)) {
                    fence_async_smem();
                    warp_arrive(bar_pdone);
                }
                if (it == itl) break;
                const int stp = it & 3;
                it++;
                mbar_wait(bar_full + 8 * (it & 3), (it >> 2) & 1);
                pp_sync();
                fence_regs(o); fence_regs(p);
                wg_fence();
                issue_qk(it & 3);
                if (it == itx) {
                    wg_wait<0>();
                    if (SC_PAIR) peer_arrive(); else warp_arrive(bar_qfree);
                    bar_sync(BAR_ST, 256);
                }
                wg_fence();
                issue_pv(stp, it - 1 - it0);
                pp_arrive();
                if (it == itl && itx < 0) {
                    wg_wait<1>();
                    warp_arrive(bar_qfree);
                }
                have = SC_TAIL || it == itx;
                if (have) {
                    uint32_t p2[20];
                    wg_wait<1>();
                    fence_regs(s);
#pragma unroll
                    for (int i = 0; i < 20; i++) p2[i] = pack_f16(ex2(s[2 * i]), ex2(s[2 * i + 1]));
                    redo = exceeds(p2);
                    if (redo) asm volatile("wgmma.wait_group.sync.aligned 0;\nnanosleep.u32 0;\n" ::: "memory");
                    else wg_wait<0>();
                    fence_regs(o); fence_regs(p);
#pragma unroll
                    for (int i = 0; i < 20; i++) p[i] = p2[i];
                } else {
                    wg_wait<0>();
                    fence_regs(s); fence_regs(o); fence_regs(p);
                }
                release(stp);
                if (it == SC_NMC) rel_target(rank);
            }
            if (seg + 1 < nseg) pp_sync();
            fence_regs(o); fence_regs(p);
            wg_fence();
            issue_pv(it & 3, 1);
            asm volatile("{\n.reg .pred p;\nsetp.ne.s32 p, %0, 0;\n@p bar.arrive %1, 256;\n}\n" ::"r"((int)(seg + 1 == nseg && (wg ? SC_PAIR && ZHOLD : !SC_TAIL))), "r"(BAR_ST + wg) : "memory");
            it++;
            if (seg + 1 == nseg) break;
            const int is = it - 2 + wg;
            uint32_t dst = sb + SM_KV + (is & 3) * KV_BYTES + wg * 512 + warp * 8192 + lane * 16;
            uint32_t dml = sb + SM_KV + (is & 3) * KV_BYTES + (wg ? 0 : QB_BYTES) + t * 4;
            asm volatile("" : "+r"(dst), "+r"(dml));
            mbar_wait(qbar, qphase); qphase ^= 1;
            unsigned short u0, u1;
            asm volatile("ld.shared.u16 %0, [%2];\nld.shared.u16 %1, [%2 + 4096];\n" : "=h"(u0), "=h"(u1) : "r"(mq_addr) : "memory");
            mbar_wait(bar_full + 8 * (it & 3), (it >> 2) & 1);
            wg_wait<0>();
            fence_regs(o);
            float z0, z1;
            row_sums(z0, z1);
            release((it - 1) & 3);
            wg_fence();
            issue_qk(it & 3);
            pp_arrive();
#pragma unroll
            for (int i = 0; i < 128; i++) o[i] -= (i & 2) ? z1 : z0;
            fence_regs(o);
            mbar_wait(bar_empty + 8 * (is & 3), (is >> 2) & 1);
            asm volatile("st.shared.f32 [%0], %1;\n" ::"r"(dml), "f"(stats()) : "memory");
            m0 = -KV_OFF * f16_lo(u0); m1 = -KV_OFF * f16_lo(u1);
            plim = fmaxf(fabsf(m0), fabsf(m1)) <= 3072.f ? P_LIMIT : 0u;
            uint32_t v[2][8] = {};
#pragma unroll
            for (int i = 0; i < 8; i++) {
                uint32_t *w = v[i & 1], *u = v[(i & 1) ^ 1];
#pragma unroll
                for (int j = 0; j < 8; j++) w[j] = pack_bf16(o[16 * i + 2 * j], o[16 * i + 2 * j + 1]);
                sts128(dst + i * 1024, w[0], w[1], w[2], w[3]);
                sts128(dst + i * 1024 + 512, w[4], w[5], w[6], w[7]);
                if (i) asm volatile("{\n.reg .pred p;\nsetp.lt.s32 p, %9, 0;\nL:\n@p st.shared.v4.u32 [%0], {%1, %2, %3, %4};\n@p st.shared.v4.u32 [%0 + 16], {%5, %6, %7, %8};\n@p bra L;\n}\n"
                             ::"r"(dst), "r"(u[0]), "r"(u[1]), "r"(u[2]), "r"(u[3]), "r"(u[4]), "r"(u[5]), "r"(u[6]), "r"(u[7]), "r"(it) : "memory");
            }
        }
        constexpr int IW = 4 + 75;
        uint32_t a[64];
        if (wg == 0 && (SC_PAIR || SC_LAST)) {
            uint32_t rq, rml, rbar;
            asm volatile("mapa.shared::cluster.u32 %0, %3, %6;\nmapa.shared::cluster.u32 %1, %4, %6;\nmapa.shared::cluster.u32 %2, %5, %6;\n"
                         : "=r"(rq), "=r"(rml), "=r"(rbar) : "r"(sb + SM_Q + QB_BYTES + warp * 8192 + lane * 16), "r"(sb + SM_ML + 512 + t * 4),
                         "r"(bar_pin), "r"(rank ^ 1));
            auto send = [&](int i) {
                asm volatile("st.async.weak.shared::cluster.mbarrier::complete_tx::bytes.v4.b32 [%0], {%1, %2, %3, %4}, [%5];\n"
                             ::"r"(rq + i * 512), "r"(a[4 * i]), "r"(a[4 * i + 1]), "r"(a[4 * i + 2]), "r"(a[4 * i + 3]), "r"(rbar + (i & 8)) : "memory");
            };
            mbar_wait(bar_rfree, 0);
            wg_wait<0>();
            fence_regs(o);
            release((it - 1) & 3);
            float z0, z1;
            row_sums(z0, z1);
            asm volatile("st.async.weak.shared::cluster.mbarrier::complete_tx::bytes.f32 [%0], %1, [%2];\n" ::"r"(rml), "f"(stats()), "r"(rbar) : "memory");
#pragma unroll
            for (int i = 0; i < 16; i++) {
                a[4 * i] = pack_bf16(o[8 * i] - z0, o[8 * i + 1] - z0); a[4 * i + 1] = pack_bf16(o[8 * i + 2] - z1, o[8 * i + 3] - z1);
                a[4 * i + 2] = pack_bf16(o[8 * i + 4] - z0, o[8 * i + 5] - z0); a[4 * i + 3] = pack_bf16(o[8 * i + 6] - z1, o[8 * i + 7] - z1);
                if (i * SND0 / 16 != (i + 1) * SND0 / 16) send(i * SND0 / 16);
                if (i % CUT2 == CUT2 - 1) cut();
            }
            if (SC_PAIR) {
                float z[128];
                const uint32_t dkz = dk0 + ((uint32_t)it >> 24), dqz = dq0 + ((uint32_t)it >> 24);
                auto gemm = [&](int c) {
                    mbar_wait(bar_full + 8 * ((IW + c) & 3), ((IW + c) >> 2) & 1);
                    const uint64_t wb = mkaddr(dkz + ((IW + c) & 3) * (KV_BYTES >> 4), dhi), ab = mkaddr(dqz + c * 64, dhi);
                    wg_fence();
#pragma unroll
                    for (int kk = 0; kk < 4; kk++) {
                        if (c | kk) wgmma_ss_n256_tb(z, ab + kk * 2, wb + kk * 512);
                        else wgmma_ss_n256_tb_init(z, ab, wb);
                    }
                    wg_commit();
                };
                auto release2 = [&](int c) {
                    asm volatile("{\n.reg .pred p;\nsetp.ne.u32 p, %1, 0;\n@p mbarrier.arrive.shared::cluster.b64 _, [%0], 2;\n}\n"
                                 ::"r"(rel_addr + 8 * ((IW + c) & 3)), "r"(rel_addr) : "memory");
                };
                mbar_wait(qbar, qphase);
                if (ZHOLD) bar_sync(BAR_ST + 1, 256);
                gemm(0);
#pragma unroll
                for (int i = SND0; i < 16; i++) send(i);
#pragma unroll
                for (int c = 1; c < 4; c++) { gemm(c); if (c == 3) pp_arrive(); wg_wait<1>(); release2(c - 1); }
                wg_wait<0>();
                fence_regs(z);
                release2(3);
#pragma unroll
                for (int i = 0; i < 16; i++) {
                    sts128(sq + warp * 8192 + lane * 16 + i * 512, pack_bf16(z[8 * i], z[8 * i + 1]), pack_bf16(z[8 * i + 2], z[8 * i + 3]),
                           pack_bf16(z[8 * i + 4], z[8 * i + 5]), pack_bf16(z[8 * i + 6], z[8 * i + 7]));
                    if (i == 3 || i == 15) bar_arrive(i == 3 ? BAR_BF : BAR_H0, 256);
                }
            } else {
#pragma unroll
                for (int i = SND0; i < 16; i++) send(i);
            }
        } else {
            const int pair = SC_PAIR;
            const bool glob = !(pair || SC_TAIL);
            const uint32_t ml = sb + SM_ML + (t & ~3) * 4, src = (glob ? sq : sb + SM_Q + QB_BYTES) + warp * 8192 + lane * 16;
            const uint64_t tm = lds64(s_tm);
            wg_wait<0>();
            fence_regs(o);
            release((IW - 1) & 3);
            float c0, c1;
            row_sums(c0, c1);
            mbar_wait(glob ? qbar : bar_pin, glob ? qphase : 0);
            const float4 ps = lds128f(ml + (glob ? wg * 512 : 512));
            auto load = [&](int i) {
                asm volatile("ld.shared.v4.u32 {%0, %1, %2, %3}, [%4];\n" : "=r"(a[4 * i]), "=r"(a[4 * i + 1]), "=r"(a[4 * i + 2]), "=r"(a[4 * i + 3]) : "r"(src + i * 512) : "memory");
            };
#pragma unroll
            for (int i = 0; i < 8; i++) load(i);
            const float n0 = fmaxf(m0, ps.x), n1 = fmaxf(m1, ps.z);
            const float a0 = ex2(m0 - n0), a1 = ex2(m1 - n1), b0 = ex2(ps.x - n0), b1 = ex2(ps.z - n1);
            const float i0 = rcp(l0 * a0 + ps.y * b0), i1 = rcp(l1 * a1 + ps.w * b1);
            const float r0 = a0 * i0, r1 = a1 * i1;
            c0 *= -r0; c1 *= -r1;
            const uint32_t u0 = pack_bf16(b0 * i0, b0 * i0), u1 = pack_bf16(b1 * i1, b1 * i1);
#pragma unroll
            for (int i = 0; i < 32; i++) {
                if (i == 16) {
                    if (!glob) mbar_wait(bar_pin + 8, 0);
#pragma unroll
                    for (int j = 8; j < 16; j++) load(j);
                }
                a[2 * i] = hfma2(a[2 * i], u0, pack_bf16(fmaf(o[4 * i], r0, c0), fmaf(o[4 * i + 1], r0, c0)));
                a[2 * i + 1] = hfma2(a[2 * i + 1], u1, pack_bf16(fmaf(o[4 * i + 2], r1, c1), fmaf(o[4 * i + 3], r1, c1)));
            }
            float y[2][32];
            auto gemm = [&](int c, int kh) {
                if (!kh) mbar_wait(bar_full + 8 * ((IW + c) & 3), (((IW + c) >> 2) & 1) ^ pair);
                const uint64_t wb = mkaddr(dk0 + ((IW + c) & 3) * (KV_BYTES >> 4), dhi - 192);
                wg_fence();
#pragma unroll
                for (int kk = 8 * kh; kk < 8 * kh + 8; kk++) {
                    if (kk) wgmma_rs_n64_tb(y[c & 1], a[4 * kk], a[4 * kk + 1], a[4 * kk + 2], a[4 * kk + 3], wb + kk * 128);
                    else wgmma_rs_n64_tb_init(y[c & 1], a[0], a[1], a[2], a[3], wb);
                }
                wg_commit();
            };
            const int rg = (pair ? SC_ZB : 2 * SC_QT0 + wg) * 8 + warp * 2;
            const uint32_t zsrc = sb + SM_Q + warp * 8192 + lane * 16, stg = sq + warp * 8192 + (lane & 15) * 128 + (((lane >> 4) ^ lane) & 7) * 16;
            uint4 z[4] = {};
            auto load_z = [&](int cb) {
#pragma unroll
                for (int i = 0; i < 4; i++) {
                    asm volatile("{\n.reg .pred p;\nsetp.ne.u32 p, %4, 0;\n@p ld.shared.v4.u32 {%0, %1, %2, %3}, [%5];\n}\n"
                                 : "+r"(z[i].x), "+r"(z[i].y), "+r"(z[i].z), "+r"(z[i].w) : "r"(pair), "r"(zsrc + (4 * cb + i) * 512) : "memory");
                }
            };
            auto stage = [&](int cb) {
                const float* x = y[cb & 1];
#pragma unroll
                for (int i = 0; i < 4; i++)
                    stmatrix_x4((stg ^ (32 * i)) + cb * 2048, hadd2(pack_bf16(x[8 * i], x[8 * i + 1]), z[i].x), hadd2(pack_bf16(x[8 * i + 2], x[8 * i + 3]), z[i].y),
                                hadd2(pack_bf16(x[8 * i + 4], x[8 * i + 5]), z[i].z), hadd2(pack_bf16(x[8 * i + 6], x[8 * i + 7]), z[i].w));
            };
            auto output = [&](int cb) {
                fence_async_smem();
                __syncwarp();
                asm volatile("{\n.reg .pred p;\nelect.sync _|p, -1;\n"
                             "@p cp.reduce.async.bulk.tensor.4d.global.shared::cta.add.tile.bulk_group [%0, {0, 0, %1, %2}], [%3];\n}\n"
                             ::"l"(tm), "r"(cb), "r"(rg), "r"(sq + warp * 8192 + cb * 2048) : "memory");
            };
            pp_sync();
            gemm(0, 0);
            gemm(0, 1);
#pragma unroll
            for (int c = 0; c < 4; c++) {
                if (c < 2) asm volatile("{\n.reg .pred p;\nsetp.ne.s32 p, %0, 0;\n@p bar.sync %1, 256;\n}\n" ::"r"(pair), "r"(c ? BAR_H0 : BAR_BF) : "memory");
                load_z(c);
                if (c < 3) { gemm(c + 1, 0); wg_wait<1>(); } else wg_wait<0>();
                fence_regs(y[c & 1]);
                stage(c);
                if (c < 3) gemm(c + 1, 1);
                if (c == 2 && glob) pp_arrive();
                output(c);
            }
            asm volatile("cp.async.bulk.commit_group;\ncp.async.bulk.wait_group.read 0;\n" ::: "memory");
            if (SC_TAIL) { release(0); release(1); release(2); release(3); }
        }
        } else {
            wg_wait<0>();
        }
        if (SC_TAIL) {
        float o[128];
        auto emit = [&](uint32_t base, int lane, int row0, uint8_t* wdst, int turn) {
#pragma unroll
            for (int hh = 0; hh < 2; hh++) {
                if (turn > 0) mbar_wait(bar_zst + 8 * hh, (turn - 1) & 1);
#pragma unroll
                for (int i = 0; i < 8; i++)
                    stmatrix_x4(base + tile_off(8 * hh + (lane & 7), 4 * i + (lane >> 3)),
                                pack_bf16(o[16 * i + 2 * hh], o[16 * i + 2 * hh + 1]), pack_bf16(o[16 * i + 4 + 2 * hh], o[16 * i + 5 + 2 * hh]),
                                pack_bf16(o[16 * i + 8 + 2 * hh], o[16 * i + 9 + 2 * hh]), pack_bf16(o[16 * i + 12 + 2 * hh], o[16 * i + 13 + 2 * hh]));
                fence_async_smem();
                __syncwarp();
                if (wdst) {
                    if (lane < 4)
                        asm volatile("cp.async.bulk.global.shared::cta.bulk_group [%0], [%1], 1024;\n"
                                     ::"l"(wdst + ((turn & 1) ? hh * 4096 + lane * 1024 : hh * 1024 + lane * QB_BYTES)), "r"(base + hh * 4096 + lane * 1024) : "memory");
                    asm volatile("cp.async.bulk.commit_group;\n" ::: "memory");
                } else {
                    asm volatile("{\n.reg .pred p;\nsetp.eq.s32 p, %3, 0;\n"
                                 "@p cp.reduce.async.bulk.tensor.4d.global.shared::cta.add.tile.bulk_group [%0, {0, 0, 0, %1}], [%2];\n"
                                 "cp.async.bulk.commit_group;\n}\n"
                                 ::"l"(&P.tm_out), "r"((row0 >> 3) + hh), "r"(base + hh * 4096), "r"(lane) : "memory");
                }
            }
            asm volatile("cp.async.bulk.wait_group.read 1;\n" ::: "memory");
            warp_arrive(bar_zst - 8 * wg);
        };
        auto emit_done = [&](bool pending) {
            asm volatile("cp.async.bulk.wait_group.read 0;\n" ::: "memory");
            __syncwarp();
            asm volatile("{\n.reg .pred p;\nsetp.eq.s32 p, %1, 0;\n@p mbarrier.arrive.shared::cta.b64 _, [%0];\n}\n"
                         ::"r"(bar_zst + 8), "r"(pending ? lane : 1) : "memory");
        };
        bar_sync(BAR_BF, 256);
        warp_arrive(bar_qfree);
        const int nf = rank ? 8 : 0;
        const int nz = nf + 26 + rank;
        const int itz = 4 + SC_NKV + SC_NW;
        bool pend = false;
#pragma unroll 1
        for (int k = wg; k < nz; k += 2) {
            const int iz = itz + (k < nf ? 0 : nf >> 1);
            mbar_wait(qbar, qphase); qphase ^= 1;
#pragma unroll 1
            for (int c = 0; c < 4; c++) {
                mbar_wait(bar_full + 8 * ((iz + c) & 3), ((iz + c) >> 2) & 1);
                const uint64_t wb = mkaddr(dk0 + ((iz + c) & 3) * (KV_BYTES >> 4), dhi), ab = mkaddr(dq0 + c * 64, dhi);
                wg_fence();
                wgmma_ss_n256_tb_pred(o, ab, wb, c);
#pragma unroll
                for (int kk = 1; kk < 4; kk++) wgmma_ss_n256_tb(o, ab + kk * 2, wb + kk * 512);
                wg_commit();
                emit_done(pend);
                pend = false;
            }
            wg_wait<0>();
            fence_regs(o);
            warp_arrive(bar_qfree);
            const int fb = ((k >> 1) + 3) & 3;
            if (k < nf) {
                float2* r255 = (float2*)H.s->r255 + wg * 128 + q;
                if (k < 2) {
                    if (t >= 124) {
#pragma unroll
                        for (int i = 0; i < 32; i++) r255[4 * i] = make_float2(o[4 * i + 2], o[4 * i + 3]);
                    }
                    bar_sync(BAR_WG0 + wg, 128);
                }
#pragma unroll
                for (int i = 0; i < 32; i++) {
                    const float2 v = __ldcg(r255 + 4 * i);
                    o[4 * i] -= v.x; o[4 * i + 1] -= v.y; o[4 * i + 2] -= v.x; o[4 * i + 3] -= v.y;
                }
            }
            int ln = lane;
            asm volatile("" : "+r"(ln));
            emit(sb + SM_KV + QB_BYTES + warp * KV_BYTES, ln, SC_TZB(k - nf) * 64 + warp * 16,
                 k >= nf ? nullptr : (k & 1) ? g_w + (4 + fb) * QB_BYTES + warp * 8192 : g_w + 8 * QB_BYTES + fb * 8192 + warp * 2048, k);
            pend = k + 2 < nz && (k | 1) != nf - 1;
            if (!pend) emit_done(true);
            if ((k | 1) == nf - 1) {
                asm volatile("cp.async.bulk.wait_group 0;\nfence.proxy.async.global;\nfence.acq_rel.gpu;\n" ::: "memory");
                bar_sync(BAR_BF, 256);
                if (tid == 0) red_release(&g_sync[SY_B * 32]);
                if (wg == 0) { release(0); release(1); release(2); release(3); }
            }
        }
        }
        if (wg == 0) pp_sync();
        warp_arrive(bar_end - 8 * wg);
        asm volatile("barrier.cluster.arrive.relaxed.aligned;\n" ::: "memory");
        if (P.E >= 0) return;
        asm volatile("setmaxnreg.dec.sync.aligned.u32 %0;\n" ::"n"(REG_P));
    }
    {
        if (warp != 0) {
            if (warp == 3 && SC_OWNER && SC_PAIR && elect()) {
                flag_wait_bounded(&g_sync[SY_H1 * 32], 79 * ep);
                mbar_wait_sleep(bar_pdone, 0);
                mbar_wait_sleep(bar_pdone + 8, 0);
#pragma unroll 1
                for (int u = 0; u < 16; u++) {
                    bulk_s2g(g_q + SC_QT0 * (2 * QB_BYTES) + u * 4096, sb + SM_Q + u * 4096, 4096);
                    asm volatile("cp.async.bulk.wait_group 0;\n" ::: "memory");
                }
                fence_async_global();
                st_release(&g_qflag[SC_QT0], ep);
            }
            __syncwarp();
            if (SC_TAIL) {
                bar_sync(BAR_AUX, 96);
                if (warp == 1 && elect()) red_release(&g_sync[SY_CSR * 32]);
                __syncwarp();
            }
            mbar_wait_bounded(bar_go, 0);
            if (SC_TAIL) {
                if (warp == 1 && elect()) red_add(&g_sync[SY_DONE * 32]);
                if (warp == 3 && elect()) {
                    int it = 4 + SC_NKV + SC_NW;
                    asm volatile("prefetch.tensormap [%0];\n" ::"l"(&P.tm_out) : "memory");
                    if (rank) {
#pragma unroll 1
                        for (int j = 0; j < 4; j++, it++) {
                            mbar_wait_sleep(bar_empty + 8 * (it & 3), ((it >> 2) & 1) ^ 1);
                            mbar_expect_tx(bar_full + 8 * (it & 3), QB_BYTES);
                            tma_g2s(sb + SM_KV + (it & 3) * KV_BYTES, &P.tm_w[2], 8 * j, bar_full + 8 * (it & 3));
                        }
#pragma unroll 1
                        for (int k = 0; k < 8; k++) {
                            mbar_wait_sleep(bar_qfree + 8 * (k & 1), ((k >> 1) ^ (k & 1) ^ 1) & 1);
                            mbar_expect_tx(bar_q + 8 * (k & 1), QB_BYTES);
#pragma unroll 1
                            for (int hf = 0; hf < 2; hf++)
                                asm volatile("cp.async.bulk.tensor.5d.shared::cluster.global.tile.mbarrier::complete_tx::bytes [%0], [%1, {0, 0, %2, 0, 0}], [%3];\n"
                                             ::"r"(sb + SM_Q + (k & 1) * QB_BYTES + hf * 16384), "l"(&P.tm_w[k & 1]),
                                             "r"(8 * (((k >> 1) + 3) & 3) + 4 * hf), "r"(bar_q + 8 * (k & 1)) : "memory");
                        }
                        flag_wait_bounded(&g_sync[SY_B * 32], ep);
                        fence_async_global();
                    }
#pragma unroll 1
                    for (int j = 0; j < 4; j++, it++) {
                        mbar_wait_sleep(bar_empty + 8 * (it & 3), ((it >> 2) & 1) ^ 1);
                        mbar_expect_tx(bar_full + 8 * (it & 3), QB_BYTES);
                        bulk_g2s(sb + SM_KV + (it & 3) * KV_BYTES, g_w + (4 + j) * QB_BYTES, QB_BYTES, bar_full + 8 * (it & 3));
                    }
#pragma unroll 1
                    for (int k = 0; k < 26 + rank; k++) {
                        if (k == 0 || k == ((GF0 + 1) * NAUX - 16) / 128) { flag_wait_bounded(&g_sync[(k ? SY_AUX1 : SY_AUX0) * 32], NAUX * ep); fence_async_global(); }
                        mbar_wait_sleep(bar_qfree + 8 * (k & 1), ((k >> 1) ^ (k & 1) ^ 1) & 1);
                        mbar_expect_tx(bar_q + 8 * (k & 1), QB_BYTES);
                        bulk_g2s(sb + SM_Q + (k & 1) * QB_BYTES, g_agg + SC_TZB(k) * QB_BYTES, QB_BYTES, bar_q + 8 * (k & 1));
                    }
                }
            } else {
            const int par = ep & 1;
            if (blockIdx.x == 0 && t == 32) g_ovf_n[par ^ 1] = 0;
            if (blockIdx.x == 0 && warp == 1) *(uint4*)(g_hz + (lane >> 3) * 1024 + (lane & 7) * 16) = make_uint4(KV_OFF2, KV_OFF2, KV_OFF2, KV_OFF2);
            const uint32_t wlo = (uint32_t)(uintptr_t)H.s, whi = (uint32_t)((uintptr_t)H.s >> 32);
            const uint32_t blo = wlo + (uint32_t)offsetof(Scratch, bucket);
            {
                const int* pd = P.dst + blockIdx.x * 96 + (t - 32);
                const int* ps = P.src + blockIdx.x * 96 + (t - 32);
#pragma unroll 1
                for (int e = P.E - (blockIdx.x * 96 + (t - 32)); e > 0; e -= CSRU * NAUX * 32, pd += CSRU * NAUX * 32, ps += CSRU * NAUX * 32) {
                    int d[CSRU], sr[CSRU], sl[CSRU];
#pragma unroll
                    for (int i = 0; i < CSRU; i++) {
                        d[i] = e > i * NAUX * 32 ? __ldg(pd + i * NAUX * 32) : NN;
                        sr[i] = e > i * NAUX * 32 ? __ldg(ps + i * NAUX * 32) : 0;
                    }
#pragma unroll
                    for (int i = 0; i < CSRU; i++) {
                        sl[i] = 0;
                        asm volatile("{\n.reg .pred p;\nsetp.lt.s32 p, %2, %3;\n@p atom.relaxed.gpu.global.add.s32 %0, [%1], 1;\n}\n"
                                     : "+r"(sl[i]) : "l"(mkaddr(wlo + (uint32_t)offsetof(Scratch, cnt) + d[i] * 4, whi)), "r"(d[i]), "n"(NN) : "memory");
                    }
                    uint32_t ov = 0;
#pragma unroll
                    for (int i = 0; i < CSRU; i++) {
                        asm volatile("{\n.reg .pred p;\nsetp.lt.s32 p, %3, %4;\n@p st.global.s32 [%1], %2;\n@!p or.b32 %0, %0, %5;\n}\n"
                                     : "+r"(ov) : "l"(mkaddr(blo + (d[i] * CAP + sl[i]) * 4, whi)), "r"(sr[i]), "r"(sl[i]), "n"(CAP), "r"(1 << i) : "memory");
                    }
#pragma unroll 1
                    for (; ov; ov &= ov - 1) {
                        const int i = (__ffs(ov) - 1) * (NAUX * 32);
                        int at;
                        asm volatile("atom.relaxed.gpu.global.add.s32 %0, [%1], 1;\n" : "=r"(at) : "l"(&g_ovf_n[par]) : "memory");
                        g_ovf[at] = make_int2(__ldg(pd + i), __ldg(ps + i));
                    }
                }
            }
            bar_sync(BAR_AUX, 96);
            if (warp == 1 && elect()) { red_release(&g_sync[SY_CSR * 32]); }
            __syncwarp();
            {
                const int r0 = blockIdx.x * 3 + warp - 1;
                const uint4* xp = (const uint4*)(H.x + r0 * 256) + lane;
                uint4* op = (uint4*)(P.out + r0 * 256) + lane;
#pragma unroll 1
                for (int r = r0; r < NN; r += CPYU * NAUX, xp += CPYU * NAUX * 32, op += CPYU * NAUX * 32) {
                    uint4 v[CPYU];
#pragma unroll
                    for (int i = 0; i < CPYU; i++) if (r + i * NAUX < NN) v[i] = ldg_pinned(xp + i * NAUX * 32);
#pragma unroll
                    for (int i = 0; i < CPYU; i++) if (r + i * NAUX < NN) op[i * NAUX * 32] = v[i];
                }
            }
            if (const int un = blockIdx.x * 3 + warp - 1 - (NAUX - 208); un >= 0) {
                flag_wait_bounded(&g_sync[SY_PART * 32], 52 * ep);
                uint8_t* pp = g_part + (un >> 3) * (4 * PART_BYTES);
                float* ml = (float*)(pp + QB_BYTES) + (un & 7) * 32;
                const float4 sa = __ldcg((const float4*)ml + g), sc = __ldcg((const float4*)ml + g + 2 * PART_BYTES / 16);
                const float n0 = fmaxf(sa.x, sc.x), n1 = fmaxf(sa.z, sc.z);
                const uint32_t a0 = pack_bf16(ex2(sa.x - n0), ex2(sa.x - n0)), a1 = pack_bf16(ex2(sa.z - n1), ex2(sa.z - n1));
                const uint32_t b0 = pack_bf16(ex2(sc.x - n0), ex2(sc.x - n0)), b1 = pack_bf16(ex2(sc.z - n1), ex2(sc.z - n1));
                __syncwarp();
                if (q == 0) ((float4*)ml)[g] = make_float4(n0, sa.y * bf_hi(a0) + sc.y * bf_hi(b0), n1, sa.w * bf_hi(a1) + sc.w * bf_hi(b1));
                uint4* d = (uint4*)(pp + (un & 4) * 256 + (un & 7) * 8192) + lane;
#pragma unroll 1
                for (int i = 0; i < 4; i++, d += 128) {
                    uint4 u[4], v[4];
#pragma unroll
                    for (int j = 0; j < 4; j++) { u[j] = __ldcg(d + j * 32); v[j] = __ldcg(d + j * 32 + 2 * PART_BYTES / 16); }
#pragma unroll
                    for (int j = 0; j < 4; j++)
                        d[j * 32] = make_uint4(hfma2(v[j].x, b0, hmul2(u[j].x, a0)), hfma2(v[j].y, b1, hmul2(u[j].y, a1)),
                                               hfma2(v[j].z, b0, hmul2(u[j].z, a0)), hfma2(v[j].w, b1, hmul2(u[j].w, a1)));
                }
            }
            flag_wait_bounded(&g_sync[SY_CSR * 32], NCTA * ep);
            if (warp == 2 && blockIdx.x < 129) {
                uint4* z = blockIdx.x < 128 ? (uint4*)(g_w + blockIdx.x * 1024) + lane : (uint4*)&g_sync[SY_DONE * 32 + 4];
                z[0] = make_uint4(0, 0, 0, 0);
                if (blockIdx.x < 128) z[32] = make_uint4(0, 0, 0, 0);
            }
            {
                const uint32_t lc = (lane >> 3) * 1024 + (lane & 7) * 16;
                const uint32_t alo = wlo ^ lc;
                const int node0 = blockIdx.x * 3 + warp - 17;
                auto node = [&](int i) { const int nd = node0 + i * NAUX; return (int)min((unsigned)nd, (unsigned)(nd + NN)); };
                const int num = (NN - 17 - node0) / NAUX + 1;
                uint32_t mine = 0;
                if (lane < num) {
                    mine = min(__ldcg(&g_cnt[node(lane)]), CAP + 1) | (uint32_t)__ldg((const unsigned short*)P.deg_inv + node(lane)) << 16;
                    g_cnt[node(lane)] = 0;
                }
                auto row = [&](int off) {
                    uint4 v;
                    asm volatile("ld.global.v4.u32 {%0, %1, %2, %3}, [%4];\n"
                                 : "=r"(v.x), "=r"(v.y), "=r"(v.z), "=r"(v.w) : "l"(mkaddr(alo ^ off, whi)));
                    return v;
                };
                auto ents = [&](int i) {
                    int e;
                    asm volatile("ld.global.cg.s32 %0, [%1];\n" : "=r"(e) : "l"(mkaddr(blo + (min(node(i), NN - 1) * CAP + lane) * 4, whi)));
                    return e;
                };
                auto store = [&](int i, const float (&a)[8]) {
                    const float di = bf_hi(__shfl_sync(~0u, mine, i)) * (1.f / KV_SCALE);
                    const int nd = node(i);
                    *(uint4*)(g_agg + (uint32_t)(((nd >> 3) * 4096 + (nd & 7) * 144) ^ lc)) =
                        make_uint4(pack_bf16(a[0] * di, a[1] * di), pack_bf16(a[2] * di, a[3] * di), pack_bf16(a[4] * di, a[5] * di), pack_bf16(a[6] * di, a[7] * di));
                };
#pragma unroll 1
                for (uint32_t big = __ballot_sync(~0u, (mine & 0xFFFF) > CAP); big; big &= big - 1) {
                    const int i = __ffs(big) - 1, no = __ldcg(&g_ovf_n[par]);
                    float a[8] = {};
#pragma unroll 1
                    for (int k = -32; k < no; k += 32) {
                        const int2 pr = k < 0 ? make_int2(node(i), ents(i)) : k + lane < no ? __ldcg(&g_ovf[k + lane]) : make_int2(-1, 0);
#pragma unroll 1
                        for (uint32_t mk = __ballot_sync(~0u, pr.x == node(i)); mk; mk &= mk - 1) {
                            const uint4 v = row(row_off(__shfl_sync(~0u, pr.y, __ffs(mk) - 1)));
                            a[0] += f16_lo(v.x) - KV_OFF; a[1] += f16_hi(v.x) - KV_OFF; a[2] += f16_lo(v.y) - KV_OFF; a[3] += f16_hi(v.y) - KV_OFF;
                            a[4] += f16_lo(v.z) - KV_OFF; a[5] += f16_hi(v.z) - KV_OFF; a[6] += f16_lo(v.w) - KV_OFF; a[7] += f16_hi(v.w) - KV_OFF;
                        }
                    }
                    store(i, a);
                }
                auto add4 = [&](const uint4& a, const uint4& b) { return make_uint4(hadd2_f16(a.x, b.x), hadd2_f16(a.y, b.y), hadd2_f16(a.z, b.z), hadd2_f16(a.w, b.w)); };
                int ni = -1, left = 0, pos = 0, ec = 0, en = ents(0);
                uint4 acc = make_uint4(0, 0, 0, 0);
                auto issue = [&](uint4 (&v)[4]) {
                    if (left <= 0) {
                        ni++;
                        left = __shfl_sync(~0u, mine, ni) & 0xFFFF;
                        if (left > CAP) left = 0;
                        ec = lane < left ? row_off(en) : 0;
                        en = ents(ni + 1);
                        pos = 0;
                    }
#pragma unroll
                    for (int j = 0; j < 4; j++) v[j] = row(__shfl_sync(~0u, ec, pos + j));
                    pos += 4; left -= 4;
                    return left <= 0 ? ni : -1;
                };
                auto step = [&](uint4 (&v)[4], int& tag) {
                    acc = add4(acc, add4(add4(add4(v[0], v[1]), make_uint4(KV_NEG4, KV_NEG4, KV_NEG4, KV_NEG4)), add4(v[2], v[3])));
                    const int i = tag;
                    tag = issue(v);
                    if (i >= 0) {
                        const float a[8] = {f16_lo(acc.x), f16_hi(acc.x), f16_lo(acc.y), f16_hi(acc.y), f16_lo(acc.z), f16_hi(acc.z), f16_lo(acc.w), f16_hi(acc.w)};
                        if ((__shfl_sync(~0u, mine, i) & 0xFFFF) <= CAP) store(i, a);
                        acc = make_uint4(0, 0, 0, 0);
                        if (i == GF0 || i == 8) {
                            __syncwarp();
                            if (elect()) red_release(&g_sync[(i == 8 ? SY_AUX1 : SY_AUX0) * 32]);
                            __syncwarp();
                        }
                    }
                    return i == num - 1;
                };
                uint4 va[4], vb[4];
#pragma unroll
                for (int j = 0; j < 4; j++) va[j] = vb[j] = make_uint4(KV_OFF2, KV_OFF2, KV_OFF2, KV_OFF2);
                int ta = -1, tb = -1;
#pragma unroll 1
                while (!step(va, ta) && !step(vb, tb)) {}
            }
            bar_sync(BAR_AUX, 96);
            if (warp == 1 && elect()) {
                red_release(&g_sync[SY_AUX * 32]);
                red_add(&g_sync[SY_DONE * 32]);
            }
            }
        }
        __syncwarp();
        asm volatile("barrier.cluster.arrive.relaxed.aligned;\n" ::: "memory");
        if (warp == 1) mbar_wait_bounded(bar_end, 0);
        else if (elect()) mbar_arrive(bar_end);
        __syncwarp();
        asm volatile("barrier.cluster.wait.acquire.aligned;\n" ::: "memory");
    }
}

}

extern "C" void kernel_launch(void* const* d_in, const int* in_sizes, int n_in, void* d_out, int out_size) {
    Hot H;
    Params P;
    H.x = (const __nv_bfloat16*)d_in[0];
    P.src = (const int*)d_in[1];
    P.dst = (const int*)d_in[2];
    P.deg_inv = (const __nv_bfloat16*)d_in[3];
    H.wq = (const __nv_bfloat16*)d_in[5];
    H.wk = (const __nv_bfloat16*)d_in[6];
    P.out = (__nv_bfloat16*)d_out;
    typedef CUresult (*EncodeFn)(CUtensorMap*, CUtensorMapDataType, cuuint32_t, void*, const cuuint64_t*, const cuuint64_t*, const cuuint32_t*,
                                 const cuuint32_t*, CUtensorMapInterleave, CUtensorMapSwizzle, CUtensorMapL2promotion, CUtensorMapFloatOOBfill);
    void* fn = nullptr;
    cudaDriverEntryPointQueryResult qr;
    cudaGetDriverEntryPoint("cuTensorMapEncodeTiled", &fn, cudaEnableDefault, &qr);
    auto encode = [&](CUtensorMap* tm, const void* ptr, int rows, int box_rows, int box_cb = 4) {
        const cuuint64_t dims[4] = {64, 8, 4, (cuuint64_t)rows / 8};
        const cuuint64_t strides[3] = {512, 128, 4096};
        const cuuint32_t box[4] = {64, 8, (cuuint32_t)box_cb, (cuuint32_t)box_rows / 8}, es[4] = {1, 1, 1, 1};
        ((EncodeFn)fn)(tm, CU_TENSOR_MAP_DATA_TYPE_BFLOAT16, 4, (void*)ptr, dims, strides, box, es, CU_TENSOR_MAP_INTERLEAVE_NONE,
                       CU_TENSOR_MAP_SWIZZLE_128B, CU_TENSOR_MAP_L2_PROMOTION_NONE, CU_TENSOR_MAP_FLOAT_OOB_FILL_NONE);
    };
    encode(&P.tm_out, d_out, NN, 8);
    encode(&P.tm_outc, d_out, NN, 16, 1);
    for (int i = 0; i < 2; i++) {
        const cuuint64_t dims[5] = {64, 2, 32, 4, 4};
        const cuuint64_t strides[4] = {512, 4096, 128, 1024};
        const cuuint32_t box[5] = {64, 2, 4, 4, 4}, es[5] = {1, 1, 1, 1, 1};
        ((EncodeFn)fn)(&P.tm_w[i], CU_TENSOR_MAP_DATA_TYPE_BFLOAT16, 5, d_in[i ? 4 : 7], dims, strides, box, es, CU_TENSOR_MAP_INTERLEAVE_NONE,
                       CU_TENSOR_MAP_SWIZZLE_128B, CU_TENSOR_MAP_L2_PROMOTION_NONE, CU_TENSOR_MAP_FLOAT_OOB_FILL_NONE);
    }
    encode(&P.tm_w[2], d_in[8], 256, 64);
    void* raw = nullptr;
    cudaGetSymbolAddress(&raw, g_raw);
    H.s = (Scratch*)(((uintptr_t)raw + ((8 << 20) - 1)) & ~(uintptr_t)((8 << 20) - 1));
    P.dhi = 0x40000100u;
    P.E = in_sizes[1] < MAXE ? in_sizes[1] : MAXE;
    cudaFuncSetAttribute(k_main, cudaFuncAttributeMaxDynamicSharedMemorySize, SM_TOTAL);
    k_main<<<NCTA, 384, SM_TOTAL>>>(H, P);
}
```

```cpp
#include <cuda_runtime.h>
#include <cuda.h>
#include <cuda_bf16.h>
#include <stdint.h>
#include <stddef.h>

namespace {

constexpr int NN = 10000;
constexpr int BN = 80;
constexpr int NKV = NN / BN;
constexpr int NQB = 158;
constexpr int NCTA = 132;
constexpr int NAUX = 3 * (NCTA - 2);
constexpr int STAGES = 4;
constexpr int KV_BYTES = BN * 512;
constexpr int QB_BYTES = 64 * 512;
constexpr int PART_BYTES = QB_BYTES + 512;
constexpr int CAP = 32;
constexpr int MAXE = 160000;

#define QRND(v) (((v) + 0x00040004u) & 0xFFF8FFF8u)
#define GO0 30
#define GF0 2
#define CSRU 3
#define CPYU 9
#define REFUP 2.f
#define SND0 10
#define CUT2 2
#define REG_C 224
#define REG_P 56

enum { SY_PART = 4, SY_H1 = 5, SY_CSR = 6, SY_AUX = 7, SY_DONE = 8, SY_AUX0 = 9, SY_B = 10, SY_AUX1 = 11, SY_H0 = 12 };
struct Scratch {
    uint8_t hz[4096 + NN * 512];
    uint8_t w[12 * QB_BYTES];
    int sync[25 * 32];
    int qflag[96];
    int ovf_n[32];
    float r255[512];
    int cnt[NN + 16];
    int bucket[(NN + 1) * CAP];
    int2 ovf[MAXE];
    uint8_t q[NQB * QB_BYTES];
    uint8_t agg[NQB * QB_BYTES];
    uint8_t part[52 * 2 * PART_BYTES];
};
static_assert(offsetof(Scratch, ovf) <= (8 << 20), "window");
static_assert(offsetof(Scratch, qflag) == offsetof(Scratch, sync) + 25 * 128, "flags");
static_assert(offsetof(Scratch, w) % 1024 == 0 && offsetof(Scratch, sync) % 128 == 0 &&
              offsetof(Scratch, bucket) % 128 == 0 && offsetof(Scratch, q) % 128 == 0, "alignment");
__device__ uint8_t g_raw[(8 << 20) + sizeof(Scratch)];
#define g_hz (H.s->hz)
#define g_w (H.s->w)
#define g_sync (H.s->sync)
#define g_qflag (H.s->qflag)
#define g_ovf_n (H.s->ovf_n)
#define g_cnt (H.s->cnt)
#define g_bucket (H.s->bucket)
#define g_ovf (H.s->ovf)
#define g_q (H.s->q)
#define g_agg (H.s->agg)
#define g_part (H.s->part)

__device__ __forceinline__ void wgmma_ss_n80(float (&d)[40], uint64_t da, uint64_t db) {
    asm volatile("wgmma.mma_async.sync.aligned.m64n80k16.f32.f16.f16 {"
        "%0, %1, %2, %3, %4, %5, %6, %7, %8, %9, %10, %11, %12, %13, %14, %15, %16, %17, %18, %19, %20, %21, %22, %23, %24, %25, %26, %27, %28, %29, %30, %31, "
        "%32, %33, %34, %35, %36, %37, %38, %39}, %40, %41, 1, 1, 1, 0, 0;\n"
        : "+f"(d[0]), "+f"(d[1]), "+f"(d[2]), "+f"(d[3]), "+f"(d[4]), "+f"(d[5]), "+f"(d[6]), "+f"(d[7]),
          "+f"(d[8]), "+f"(d[9]), "+f"(d[10]), "+f"(d[11]), "+f"(d[12]), "+f"(d[13]), "+f"(d[14]), "+f"(d[15]),
          "+f"(d[16]), "+f"(d[17]), "+f"(d[18]), "+f"(d[19]), "+f"(d[20]), "+f"(d[21]), "+f"(d[22]), "+f"(d[23]),
          "+f"(d[24]), "+f"(d[25]), "+f"(d[26]), "+f"(d[27]), "+f"(d[28]), "+f"(d[29]), "+f"(d[30]), "+f"(d[31]),
          "+f"(d[32]), "+f"(d[33]), "+f"(d[34]), "+f"(d[35]), "+f"(d[36]), "+f"(d[37]), "+f"(d[38]), "+f"(d[39])
        : "l"(da), "l"(db));
}
__device__ __forceinline__ void wgmma_ss_n80_init(float (&d)[40], uint64_t da, uint64_t db) {
    asm volatile("wgmma.mma_async.sync.aligned.m64n80k16.f32.f16.f16 {"
        "%0, %1, %2, %3, %4, %5, %6, %7, %8, %9, %10, %11, %12, %13, %14, %15, %16, %17, %18, %19, %20, %21, %22, %23, %24, %25, %26, %27, %28, %29, %30, %31, "
        "%32, %33, %34, %35, %36, %37, %38, %39}, %40, %41, 0, 1, 1, 0, 0;\n"
        : "=f"(d[0]), "=f"(d[1]), "=f"(d[2]), "=f"(d[3]), "=f"(d[4]), "=f"(d[5]), "=f"(d[6]), "=f"(d[7]),
          "=f"(d[8]), "=f"(d[9]), "=f"(d[10]), "=f"(d[11]), "=f"(d[12]), "=f"(d[13]), "=f"(d[14]), "=f"(d[15]),
          "=f"(d[16]), "=f"(d[17]), "=f"(d[18]), "=f"(d[19]), "=f"(d[20]), "=f"(d[21]), "=f"(d[22]), "=f"(d[23]),
          "=f"(d[24]), "=f"(d[25]), "=f"(d[26]), "=f"(d[27]), "=f"(d[28]), "=f"(d[29]), "=f"(d[30]), "=f"(d[31]),
          "=f"(d[32]), "=f"(d[33]), "=f"(d[34]), "=f"(d[35]), "=f"(d[36]), "=f"(d[37]), "=f"(d[38]), "=f"(d[39])
        : "l"(da), "l"(db));
}
__device__ __forceinline__ void wgmma_rs_n256_tb(float (&d)[128], uint32_t a0, uint32_t a1, uint32_t a2, uint32_t a3, uint64_t db) {
    asm volatile("wgmma.mma_async.sync.aligned.m64n256k16.f32.f16.f16 {"
        "%0, %1, %2, %3, %4, %5, %6, %7, %8, %9, %10, %11, %12, %13, %14, %15, %16, %17, %18, %19, %20, %21, %22, %23, %24, %25, %26, %27, %28, %29, %30, %31, "
        "%32, %33, %34, %35, %36, %37, %38, %39, %40, %41, %42, %43, %44, %45, %46, %47, %48, %49, %50, %51, %52, %53, %54, %55, %56, %57, %58, %59, %60, %61, %62, %63, "
        "%64, %65, %66, %67, %68, %69, %70, %71, %72, %73, %74, %75, %76, %77, %78, %79, %80, %81, %82, %83, %84, %85, %86, %87, %88, %89, %90, %91, %92, %93, %94, %95, "
        "%96, %97, %98, %99, %100, %101, %102, %103, %104, %105, %106, %107, %108, %109, %110, %111, %112, %113, %114, %115, %116, %117, %118, %119, %120, %121, %122, %123, %124, %125, %126, %127}, {%128, %129, %130, %131}, %132, 1, 1, 1, 1;\n"
        : "+f"(d[0]), "+f"(d[1]), "+f"(d[2]), "+f"(d[3]), "+f"(d[4]), "+f"(d[5]), "+f"(d[6]), "+f"(d[7]),
          "+f"(d[8]), "+f"(d[9]), "+f"(d[10]), "+f"(d[11]), "+f"(d[12]), "+f"(d[13]), "+f"(d[14]), "+f"(d[15]),
          "+f"(d[16]), "+f"(d[17]), "+f"(d[18]), "+f"(d[19]), "+f"(d[20]), "+f"(d[21]), "+f"(d[22]), "+f"(d[23]),
          "+f"(d[24]), "+f"(d[25]), "+f"(d[26]), "+f"(d[27]), "+f"(d[28]), "+f"(d[29]), "+f"(d[30]), "+f"(d[31]),
          "+f"(d[32]), "+f"(d[33]), "+f"(d[34]), "+f"(d[35]), "+f"(d[36]), "+f"(d[37]), "+f"(d[38]), "+f"(d[39]),
          "+f"(d[40]), "+f"(d[41]), "+f"(d[42]), "+f"(d[43]), "+f"(d[44]), "+f"(d[45]), "+f"(d[46]), "+f"(d[47]),
          "+f"(d[48]), "+f"(d[49]), "+f"(d[50]), "+f"(d[51]), "+f"(d[52]), "+f"(d[53]), "+f"(d[54]), "+f"(d[55]),
          "+f"(d[56]), "+f"(d[57]), "+f"(d[58]), "+f"(d[59]), "+f"(d[60]), "+f"(d[61]), "+f"(d[62]), "+f"(d[63]),
          "+f"(d[64]), "+f"(d[65]), "+f"(d[66]), "+f"(d[67]), "+f"(d[68]), "+f"(d[69]), "+f"(d[70]), "+f"(d[71]),
          "+f"(d[72]), "+f"(d[73]), "+f"(d[74]), "+f"(d[75]), "+f"(d[76]), "+f"(d[77]), "+f"(d[78]), "+f"(d[79]),
          "+f"(d[80]), "+f"(d[81]), "+f"(d[82]), "+f"(d[83]), "+f"(d[84]), "+f"(d[85]), "+f"(d[86]), "+f"(d[87]),
          "+f"(d[88]), "+f"(d[89]), "+f"(d[90]), "+f"(d[91]), "+f"(d[92]), "+f"(d[93]), "+f"(d[94]), "+f"(d[95]),
          "+f"(d[96]), "+f"(d[97]), "+f"(d[98]), "+f"(d[99]), "+f"(d[100]), "+f"(d[101]), "+f"(d[102]), "+f"(d[103]),
          "+f"(d[104]), "+f"(d[105]), "+f"(d[106]), "+f"(d[107]), "+f"(d[108]), "+f"(d[109]), "+f"(d[110]), "+f"(d[111]),
          "+f"(d[112]), "+f"(d[113]), "+f"(d[114]), "+f"(d[115]), "+f"(d[116]), "+f"(d[117]), "+f"(d[118]), "+f"(d[119]),
          "+f"(d[120]), "+f"(d[121]), "+f"(d[122]), "+f"(d[123]), "+f"(d[124]), "+f"(d[125]), "+f"(d[126]), "+f"(d[127])
        : "r"(a0), "r"(a1), "r"(a2), "r"(a3), "l"(db));
}
__device__ __forceinline__ void wgmma_rs_n256_tb_init(float (&d)[128], uint32_t a0, uint32_t a1, uint32_t a2, uint32_t a3, uint64_t db) {
    asm volatile("wgmma.mma_async.sync.aligned.m64n256k16.f32.f16.f16 {"
        "%0, %1, %2, %3, %4, %5, %6, %7, %8, %9, %10, %11, %12, %13, %14, %15, %16, %17, %18, %19, %20, %21, %22, %23, %24, %25, %26, %27, %28, %29, %30, %31, "
        "%32, %33, %34, %35, %36, %37, %38, %39, %40, %41, %42, %43, %44, %45, %46, %47, %48, %49, %50, %51, %52, %53, %54, %55, %56, %57, %58, %59, %60, %61, %62, %63, "
        "%64, %65, %66, %67, %68, %69, %70, %71, %72, %73, %74, %75, %76, %77, %78, %79, %80, %81, %82, %83, %84, %85, %86, %87, %88, %89, %90, %91, %92, %93, %94, %95, "
        "%96, %97, %98, %99, %100, %101, %102, %103, %104, %105, %106, %107, %108, %109, %110, %111, %112, %113, %114, %115, %116, %117, %118, %119, %120, %121, %122, %123, %124, %125, %126, %127}, {%128, %129, %130, %131}, %132, 0, 1, 1, 1;\n"
        : "=f"(d[0]), "=f"(d[1]), "=f"(d[2]), "=f"(d[3]), "=f"(d[4]), "=f"(d[5]), "=f"(d[6]), "=f"(d[7]),
          "=f"(d[8]), "=f"(d[9]), "=f"(d[10]), "=f"(d[11]), "=f"(d[12]), "=f"(d[13]), "=f"(d[14]), "=f"(d[15]),
          "=f"(d[16]), "=f"(d[17]), "=f"(d[18]), "=f"(d[19]), "=f"(d[20]), "=f"(d[21]), "=f"(d[22]), "=f"(d[23]),
          "=f"(d[24]), "=f"(d[25]), "=f"(d[26]), "=f"(d[27]), "=f"(d[28]), "=f"(d[29]), "=f"(d[30]), "=f"(d[31]),
          "=f"(d[32]), "=f"(d[33]), "=f"(d[34]), "=f"(d[35]), "=f"(d[36]), "=f"(d[37]), "=f"(d[38]), "=f"(d[39]),
          "=f"(d[40]), "=f"(d[41]), "=f"(d[42]), "=f"(d[43]), "=f"(d[44]), "=f"(d[45]), "=f"(d[46]), "=f"(d[47]),
          "=f"(d[48]), "=f"(d[49]), "=f"(d[50]), "=f"(d[51]), "=f"(d[52]), "=f"(d[53]), "=f"(d[54]), "=f"(d[55]),
          "=f"(d[56]), "=f"(d[57]), "=f"(d[58]), "=f"(d[59]), "=f"(d[60]), "=f"(d[61]), "=f"(d[62]), "=f"(d[63]),
          "=f"(d[64]), "=f"(d[65]), "=f"(d[66]), "=f"(d[67]), "=f"(d[68]), "=f"(d[69]), "=f"(d[70]), "=f"(d[71]),
          "=f"(d[72]), "=f"(d[73]), "=f"(d[74]), "=f"(d[75]), "=f"(d[76]), "=f"(d[77]), "=f"(d[78]), "=f"(d[79]),
          "=f"(d[80]), "=f"(d[81]), "=f"(d[82]), "=f"(d[83]), "=f"(d[84]), "=f"(d[85]), "=f"(d[86]), "=f"(d[87]),
          "=f"(d[88]), "=f"(d[89]), "=f"(d[90]), "=f"(d[91]), "=f"(d[92]), "=f"(d[93]), "=f"(d[94]), "=f"(d[95]),
          "=f"(d[96]), "=f"(d[97]), "=f"(d[98]), "=f"(d[99]), "=f"(d[100]), "=f"(d[101]), "=f"(d[102]), "=f"(d[103]),
          "=f"(d[104]), "=f"(d[105]), "=f"(d[106]), "=f"(d[107]), "=f"(d[108]), "=f"(d[109]), "=f"(d[110]), "=f"(d[111]),
          "=f"(d[112]), "=f"(d[113]), "=f"(d[114]), "=f"(d[115]), "=f"(d[116]), "=f"(d[117]), "=f"(d[118]), "=f"(d[119]),
          "=f"(d[120]), "=f"(d[121]), "=f"(d[122]), "=f"(d[123]), "=f"(d[124]), "=f"(d[125]), "=f"(d[126]), "=f"(d[127])
        : "r"(a0), "r"(a1), "r"(a2), "r"(a3), "l"(db));
}
__device__ __forceinline__ void wgmma_rs_n256_tb_pred(float (&d)[128], uint32_t a0, uint32_t a1, uint32_t a2, uint32_t a3, uint64_t db, int acc) {
    asm volatile("{\n.reg .pred p;\nsetp.ne.s32 p, %133, 0;\nwgmma.mma_async.sync.aligned.m64n256k16.f32.f16.f16 {"
        "%0, %1, %2, %3, %4, %5, %6, %7, %8, %9, %10, %11, %12, %13, %14, %15, %16, %17, %18, %19, %20, %21, %22, %23, %24, %25, %26, %27, %28, %29, %30, %31, "
        "%32, %33, %34, %35, %36, %37, %38, %39, %40, %41, %42, %43, %44, %45, %46, %47, %48, %49, %50, %51, %52, %53, %54, %55, %56, %57, %58, %59, %60, %61, %62, %63, "
        "%64, %65, %66, %67, %68, %69, %70, %71, %72, %73, %74, %75, %76, %77, %78, %79, %80, %81, %82, %83, %84, %85, %86, %87, %88, %89, %90, %91, %92, %93, %94, %95, "
        "%96, %97, %98, %99, %100, %101, %102, %103, %104, %105, %106, %107, %108, %109, %110, %111, %112, %113, %114, %115, %116, %117, %118, %119, %120, %121, %122, %123, %124, %125, %126, %127}, {%128, %129, %130, %131}, %132, p, 1, 1, 1;\n}\n"
        : "+f"(d[0]), "+f"(d[1]), "+f"(d[2]), "+f"(d[3]), "+f"(d[4]), "+f"(d[5]), "+f"(d[6]), "+f"(d[7]),
          "+f"(d[8]), "+f"(d[9]), "+f"(d[10]), "+f"(d[11]), "+f"(d[12]), "+f"(d[13]), "+f"(d[14]), "+f"(d[15]),
          "+f"(d[16]), "+f"(d[17]), "+f"(d[18]), "+f"(d[19]), "+f"(d[20]), "+f"(d[21]), "+f"(d[22]), "+f"(d[23]),
          "+f"(d[24]), "+f"(d[25]), "+f"(d[26]), "+f"(d[27]), "+f"(d[28]), "+f"(d[29]), "+f"(d[30]), "+f"(d[31]),
          "+f"(d[32]), "+f"(d[33]), "+f"(d[34]), "+f"(d[35]), "+f"(d[36]), "+f"(d[37]), "+f"(d[38]), "+f"(d[39]),
          "+f"(d[40]), "+f"(d[41]), "+f"(d[42]), "+f"(d[43]), "+f"(d[44]), "+f"(d[45]), "+f"(d[46]), "+f"(d[47]),
          "+f"(d[48]), "+f"(d[49]), "+f"(d[50]), "+f"(d[51]), "+f"(d[52]), "+f"(d[53]), "+f"(d[54]), "+f"(d[55]),
          "+f"(d[56]), "+f"(d[57]), "+f"(d[58]), "+f"(d[59]), "+f"(d[60]), "+f"(d[61]), "+f"(d[62]), "+f"(d[63]),
          "+f"(d[64]), "+f"(d[65]), "+f"(d[66]), "+f"(d[67]), "+f"(d[68]), "+f"(d[69]), "+f"(d[70]), "+f"(d[71]),
          "+f"(d[72]), "+f"(d[73]), "+f"(d[74]), "+f"(d[75]), "+f"(d[76]), "+f"(d[77]), "+f"(d[78]), "+f"(d[79]),
          "+f"(d[80]), "+f"(d[81]), "+f"(d[82]), "+f"(d[83]), "+f"(d[84]), "+f"(d[85]), "+f"(d[86]), "+f"(d[87]),
          "+f"(d[88]), "+f"(d[89]), "+f"(d[90]), "+f"(d[91]), "+f"(d[92]), "+f"(d[93]), "+f"(d[94]), "+f"(d[95]),
          "+f"(d[96]), "+f"(d[97]), "+f"(d[98]), "+f"(d[99]), "+f"(d[100]), "+f"(d[101]), "+f"(d[102]), "+f"(d[103]),
          "+f"(d[104]), "+f"(d[105]), "+f"(d[106]), "+f"(d[107]), "+f"(d[108]), "+f"(d[109]), "+f"(d[110]), "+f"(d[111]),
          "+f"(d[112]), "+f"(d[113]), "+f"(d[114]), "+f"(d[115]), "+f"(d[116]), "+f"(d[117]), "+f"(d[118]), "+f"(d[119]),
          "+f"(d[120]), "+f"(d[121]), "+f"(d[122]), "+f"(d[123]), "+f"(d[124]), "+f"(d[125]), "+f"(d[126]), "+f"(d[127])
        : "r"(a0), "r"(a1), "r"(a2), "r"(a3), "l"(db), "r"(acc));
}
__device__ __forceinline__ void wgmma_ss_n256_tb(float (&d)[128], uint64_t da, uint64_t db) {
    asm volatile("wgmma.mma_async.sync.aligned.m64n256k16.f32.bf16.bf16 {"
        "%0, %1, %2, %3, %4, %5, %6, %7, %8, %9, %10, %11, %12, %13, %14, %15, %16, %17, %18, %19, %20, %21, %22, %23, %24, %25, %26, %27, %28, %29, %30, %31, "
        "%32, %33, %34, %35, %36, %37, %38, %39, %40, %41, %42, %43, %44, %45, %46, %47, %48, %49, %50, %51, %52, %53, %54, %55, %56, %57, %58, %59, %60, %61, %62, %63, "
        "%64, %65, %66, %67, %68, %69, %70, %71, %72, %73, %74, %75, %76, %77, %78, %79, %80, %81, %82, %83, %84, %85, %86, %87, %88, %89, %90, %91, %92, %93, %94, %95, "
        "%96, %97, %98, %99, %100, %101, %102, %103, %104, %105, %106, %107, %108, %109, %110, %111, %112, %113, %114, %115, %116, %117, %118, %119, %120, %121, %122, %123, %124, %125, %126, %127}, %128, %129, 1, 1, 1, 0, 1;\n"
        : "+f"(d[0]), "+f"(d[1]), "+f"(d[2]), "+f"(d[3]), "+f"(d[4]), "+f"(d[5]), "+f"(d[6]), "+f"(d[7]),
          "+f"(d[8]), "+f"(d[9]), "+f"(d[10]), "+f"(d[11]), "+f"(d[12]), "+f"(d[13]), "+f"(d[14]), "+f"(d[15]),
          "+f"(d[16]), "+f"(d[17]), "+f"(d[18]), "+f"(d[19]), "+f"(d[20]), "+f"(d[21]), "+f"(d[22]), "+f"(d[23]),
          "+f"(d[24]), "+f"(d[25]), "+f"(d[26]), "+f"(d[27]), "+f"(d[28]), "+f"(d[29]), "+f"(d[30]), "+f"(d[31]),
          "+f"(d[32]), "+f"(d[33]), "+f"(d[34]), "+f"(d[35]), "+f"(d[36]), "+f"(d[37]), "+f"(d[38]), "+f"(d[39]),
          "+f"(d[40]), "+f"(d[41]), "+f"(d[42]), "+f"(d[43]), "+f"(d[44]), "+f"(d[45]), "+f"(d[46]), "+f"(d[47]),
          "+f"(d[48]), "+f"(d[49]), "+f"(d[50]), "+f"(d[51]), "+f"(d[52]), "+f"(d[53]), "+f"(d[54]), "+f"(d[55]),
          "+f"(d[56]), "+f"(d[57]), "+f"(d[58]), "+f"(d[59]), "+f"(d[60]), "+f"(d[61]), "+f"(d[62]), "+f"(d[63]),
          "+f"(d[64]), "+f"(d[65]), "+f"(d[66]), "+f"(d[67]), "+f"(d[68]), "+f"(d[69]), "+f"(d[70]), "+f"(d[71]),
          "+f"(d[72]), "+f"(d[73]), "+f"(d[74]), "+f"(d[75]), "+f"(d[76]), "+f"(d[77]), "+f"(d[78]), "+f"(d[79]),
          "+f"(d[80]), "+f"(d[81]), "+f"(d[82]), "+f"(d[83]), "+f"(d[84]), "+f"(d[85]), "+f"(d[86]), "+f"(d[87]),
          "+f"(d[88]), "+f"(d[89]), "+f"(d[90]), "+f"(d[91]), "+f"(d[92]), "+f"(d[93]), "+f"(d[94]), "+f"(d[95]),
          "+f"(d[96]), "+f"(d[97]), "+f"(d[98]), "+f"(d[99]), "+f"(d[100]), "+f"(d[101]), "+f"(d[102]), "+f"(d[103]),
          "+f"(d[104]), "+f"(d[105]), "+f"(d[106]), "+f"(d[107]), "+f"(d[108]), "+f"(d[109]), "+f"(d[110]), "+f"(d[111]),
          "+f"(d[112]), "+f"(d[113]), "+f"(d[114]), "+f"(d[115]), "+f"(d[116]), "+f"(d[117]), "+f"(d[118]), "+f"(d[119]),
          "+f"(d[120]), "+f"(d[121]), "+f"(d[122]), "+f"(d[123]), "+f"(d[124]), "+f"(d[125]), "+f"(d[126]), "+f"(d[127])
        : "l"(da), "l"(db));
}
__device__ __forceinline__ void wgmma_ss_n256_tb_init(float (&d)[128], uint64_t da, uint64_t db) {
    asm volatile("wgmma.mma_async.sync.aligned.m64n256k16.f32.bf16.bf16 {"
        "%0, %1, %2, %3, %4, %5, %6, %7, %8, %9, %10, %11, %12, %13, %14, %15, %16, %17, %18, %19, %20, %21, %22, %23, %24, %25, %26, %27, %28, %29, %30, %31, "
        "%32, %33, %34, %35, %36, %37, %38, %39, %40, %41, %42, %43, %44, %45, %46, %47, %48, %49, %50, %51, %52, %53, %54, %55, %56, %57, %58, %59, %60, %61, %62, %63, "
        "%64, %65, %66, %67, %68, %69, %70, %71, %72, %73, %74, %75, %76, %77, %78, %79, %80, %81, %82, %83, %84, %85, %86, %87, %88, %89, %90, %91, %92, %93, %94, %95, "
        "%96, %97, %98, %99, %100, %101, %102, %103, %104, %105, %106, %107, %108, %109, %110, %111, %112, %113, %114, %115, %116, %117, %118, %119, %120, %121, %122, %123, %124, %125, %126, %127}, %128, %129, 0, 1, 1, 0, 1;\n"
        : "=f"(d[0]), "=f"(d[1]), "=f"(d[2]), "=f"(d[3]), "=f"(d[4]), "=f"(d[5]), "=f"(d[6]), "=f"(d[7]),
          "=f"(d[8]), "=f"(d[9]), "=f"(d[10]), "=f"(d[11]), "=f"(d[12]), "=f"(d[13]), "=f"(d[14]), "=f"(d[15]),
          "=f"(d[16]), "=f"(d[17]), "=f"(d[18]), "=f"(d[19]), "=f"(d[20]), "=f"(d[21]), "=f"(d[22]), "=f"(d[23]),
          "=f"(d[24]), "=f"(d[25]), "=f"(d[26]), "=f"(d[27]), "=f"(d[28]), "=f"(d[29]), "=f"(d[30]), "=f"(d[31]),
          "=f"(d[32]), "=f"(d[33]), "=f"(d[34]), "=f"(d[35]), "=f"(d[36]), "=f"(d[37]), "=f"(d[38]), "=f"(d[39]),
          "=f"(d[40]), "=f"(d[41]), "=f"(d[42]), "=f"(d[43]), "=f"(d[44]), "=f"(d[45]), "=f"(d[46]), "=f"(d[47]),
          "=f"(d[48]), "=f"(d[49]), "=f"(d[50]), "=f"(d[51]), "=f"(d[52]), "=f"(d[53]), "=f"(d[54]), "=f"(d[55]),
          "=f"(d[56]), "=f"(d[57]), "=f"(d[58]), "=f"(d[59]), "=f"(d[60]), "=f"(d[61]), "=f"(d[62]), "=f"(d[63]),
          "=f"(d[64]), "=f"(d[65]), "=f"(d[66]), "=f"(d[67]), "=f"(d[68]), "=f"(d[69]), "=f"(d[70]), "=f"(d[71]),
          "=f"(d[72]), "=f"(d[73]), "=f"(d[74]), "=f"(d[75]), "=f"(d[76]), "=f"(d[77]), "=f"(d[78]), "=f"(d[79]),
          "=f"(d[80]), "=f"(d[81]), "=f"(d[82]), "=f"(d[83]), "=f"(d[84]), "=f"(d[85]), "=f"(d[86]), "=f"(d[87]),
          "=f"(d[88]), "=f"(d[89]), "=f"(d[90]), "=f"(d[91]), "=f"(d[92]), "=f"(d[93]), "=f"(d[94]), "=f"(d[95]),
          "=f"(d[96]), "=f"(d[97]), "=f"(d[98]), "=f"(d[99]), "=f"(d[100]), "=f"(d[101]), "=f"(d[102]), "=f"(d[103]),
          "=f"(d[104]), "=f"(d[105]), "=f"(d[106]), "=f"(d[107]), "=f"(d[108]), "=f"(d[109]), "=f"(d[110]), "=f"(d[111]),
          "=f"(d[112]), "=f"(d[113]), "=f"(d[114]), "=f"(d[115]), "=f"(d[116]), "=f"(d[117]), "=f"(d[118]), "=f"(d[119]),
          "=f"(d[120]), "=f"(d[121]), "=f"(d[122]), "=f"(d[123]), "=f"(d[124]), "=f"(d[125]), "=f"(d[126]), "=f"(d[127])
        : "l"(da), "l"(db));
}
__device__ __forceinline__ void wgmma_ss_n256_tb_pred(float (&d)[128], uint64_t da, uint64_t db, int acc) {
    asm volatile("{\n.reg .pred p;\nsetp.ne.s32 p, %130, 0;\nwgmma.mma_async.sync.aligned.m64n256k16.f32.bf16.bf16 {"
        "%0, %1, %2, %3, %4, %5, %6, %7, %8, %9, %10, %11, %12, %13, %14, %15, %16, %17, %18, %19, %20, %21, %22, %23, %24, %25, %26, %27, %28, %29, %30, %31, "
        "%32, %33, %34, %35, %36, %37, %38, %39, %40, %41, %42, %43, %44, %45, %46, %47, %48, %49, %50, %51, %52, %53, %54, %55, %56, %57, %58, %59, %60, %61, %62, %63, "
        "%64, %65, %66, %67, %68, %69, %70, %71, %72, %73, %74, %75, %76, %77, %78, %79, %80, %81, %82, %83, %84, %85, %86, %87, %88, %89, %90, %91, %92, %93, %94, %95, "
        "%96, %97, %98, %99, %100, %101, %102, %103, %104, %105, %106, %107, %108, %109, %110, %111, %112, %113, %114, %115, %116, %117, %118, %119, %120, %121, %122, %123, %124, %125, %126, %127}, %128, %129, p, 1, 1, 0, 1;\n}\n"
        : "+f"(d[0]), "+f"(d[1]), "+f"(d[2]), "+f"(d[3]), "+f"(d[4]), "+f"(d[5]), "+f"(d[6]), "+f"(d[7]),
          "+f"(d[8]), "+f"(d[9]), "+f"(d[10]), "+f"(d[11]), "+f"(d[12]), "+f"(d[13]), "+f"(d[14]), "+f"(d[15]),
          "+f"(d[16]), "+f"(d[17]), "+f"(d[18]), "+f"(d[19]), "+f"(d[20]), "+f"(d[21]), "+f"(d[22]), "+f"(d[23]),
          "+f"(d[24]), "+f"(d[25]), "+f"(d[26]), "+f"(d[27]), "+f"(d[28]), "+f"(d[29]), "+f"(d[30]), "+f"(d[31]),
          "+f"(d[32]), "+f"(d[33]), "+f"(d[34]), "+f"(d[35]), "+f"(d[36]), "+f"(d[37]), "+f"(d[38]), "+f"(d[39]),
          "+f"(d[40]), "+f"(d[41]), "+f"(d[42]), "+f"(d[43]), "+f"(d[44]), "+f"(d[45]), "+f"(d[46]), "+f"(d[47]),
          "+f"(d[48]), "+f"(d[49]), "+f"(d[50]), "+f"(d[51]), "+f"(d[52]), "+f"(d[53]), "+f"(d[54]), "+f"(d[55]),
          "+f"(d[56]), "+f"(d[57]), "+f"(d[58]), "+f"(d[59]), "+f"(d[60]), "+f"(d[61]), "+f"(d[62]), "+f"(d[63]),
          "+f"(d[64]), "+f"(d[65]), "+f"(d[66]), "+f"(d[67]), "+f"(d[68]), "+f"(d[69]), "+f"(d[70]), "+f"(d[71]),
          "+f"(d[72]), "+f"(d[73]), "+f"(d[74]), "+f"(d[75]), "+f"(d[76]), "+f"(d[77]), "+f"(d[78]), "+f"(d[79]),
          "+f"(d[80]), "+f"(d[81]), "+f"(d[82]), "+f"(d[83]), "+f"(d[84]), "+f"(d[85]), "+f"(d[86]), "+f"(d[87]),
          "+f"(d[88]), "+f"(d[89]), "+f"(d[90]), "+f"(d[91]), "+f"(d[92]), "+f"(d[93]), "+f"(d[94]), "+f"(d[95]),
          "+f"(d[96]), "+f"(d[97]), "+f"(d[98]), "+f"(d[99]), "+f"(d[100]), "+f"(d[101]), "+f"(d[102]), "+f"(d[103]),
          "+f"(d[104]), "+f"(d[105]), "+f"(d[106]), "+f"(d[107]), "+f"(d[108]), "+f"(d[109]), "+f"(d[110]), "+f"(d[111]),
          "+f"(d[112]), "+f"(d[113]), "+f"(d[114]), "+f"(d[115]), "+f"(d[116]), "+f"(d[117]), "+f"(d[118]), "+f"(d[119]),
          "+f"(d[120]), "+f"(d[121]), "+f"(d[122]), "+f"(d[123]), "+f"(d[124]), "+f"(d[125]), "+f"(d[126]), "+f"(d[127])
        : "l"(da), "l"(db), "r"(acc));
}
__device__ __forceinline__ void wgmma_rs_n64_tb(float (&d)[32], uint32_t a0, uint32_t a1, uint32_t a2, uint32_t a3, uint64_t db) {
    asm volatile("wgmma.mma_async.sync.aligned.m64n64k16.f32.bf16.bf16 {"
        "%0, %1, %2, %3, %4, %5, %6, %7, %8, %9, %10, %11, %12, %13, %14, %15, %16, %17, %18, %19, %20, %21, %22, %23, %24, %25, %26, %27, %28, %29, %30, %31}, {%32, %33, %34, %35}, %36, 1, 1, 1, 1;\n"
        : "+f"(d[0]), "+f"(d[1]), "+f"(d[2]), "+f"(d[3]), "+f"(d[4]), "+f"(d[5]), "+f"(d[6]), "+f"(d[7]),
          "+f"(d[8]), "+f"(d[9]), "+f"(d[10]), "+f"(d[11]), "+f"(d[12]), "+f"(d[13]), "+f"(d[14]), "+f"(d[15]),
          "+f"(d[16]), "+f"(d[17]), "+f"(d[18]), "+f"(d[19]), "+f"(d[20]), "+f"(d[21]), "+f"(d[22]), "+f"(d[23]),
          "+f"(d[24]), "+f"(d[25]), "+f"(d[26]), "+f"(d[27]), "+f"(d[28]), "+f"(d[29]), "+f"(d[30]), "+f"(d[31])
        : "r"(a0), "r"(a1), "r"(a2), "r"(a3), "l"(db));
}
__device__ __forceinline__ void wgmma_rs_n64_tb_init(float (&d)[32], uint32_t a0, uint32_t a1, uint32_t a2, uint32_t a3, uint64_t db) {
    asm volatile("wgmma.mma_async.sync.aligned.m64n64k16.f32.bf16.bf16 {"
        "%0, %1, %2, %3, %4, %5, %6, %7, %8, %9, %10, %11, %12, %13, %14, %15, %16, %17, %18, %19, %20, %21, %22, %23, %24, %25, %26, %27, %28, %29, %30, %31}, {%32, %33, %34, %35}, %36, 0, 1, 1, 1;\n"
        : "=f"(d[0]), "=f"(d[1]), "=f"(d[2]), "=f"(d[3]), "=f"(d[4]), "=f"(d[5]), "=f"(d[6]), "=f"(d[7]),
          "=f"(d[8]), "=f"(d[9]), "=f"(d[10]), "=f"(d[11]), "=f"(d[12]), "=f"(d[13]), "=f"(d[14]), "=f"(d[15]),
          "=f"(d[16]), "=f"(d[17]), "=f"(d[18]), "=f"(d[19]), "=f"(d[20]), "=f"(d[21]), "=f"(d[22]), "=f"(d[23]),
          "=f"(d[24]), "=f"(d[25]), "=f"(d[26]), "=f"(d[27]), "=f"(d[28]), "=f"(d[29]), "=f"(d[30]), "=f"(d[31])
        : "r"(a0), "r"(a1), "r"(a2), "r"(a3), "l"(db));
}

__device__ __forceinline__ void wg_fence() { asm volatile("wgmma.fence.sync.aligned;\n" ::: "memory"); }
__device__ __forceinline__ void wg_commit() { asm volatile("wgmma.commit_group.sync.aligned;\n" ::: "memory"); }
template <int N> __device__ __forceinline__ void wg_wait() { asm volatile("wgmma.wait_group.sync.aligned %0;\n" ::"n"(N) : "memory"); }
template <int N> __device__ __forceinline__ void fence_regs(float (&a)[N]) {
#pragma unroll
    for (int i = 0; i < N; i++) asm volatile("" : "+f"(a[i])::"memory");
}
template <int N> __device__ __forceinline__ void fence_regs(uint32_t (&a)[N]) {
#pragma unroll
    for (int i = 0; i < N; i++) asm volatile("" : "+r"(a[i])::"memory");
}
__device__ __forceinline__ void mbar_init(uint32_t bar, uint32_t cnt) {
    asm volatile("mbarrier.init.shared::cta.b64 [%0], %1;\n" ::"r"(bar), "r"(cnt) : "memory");
}
__device__ __forceinline__ void mbar_expect_tx(uint32_t bar, uint32_t bytes) {
    asm volatile("mbarrier.arrive.expect_tx.shared::cta.b64 _, [%0], %1;\n" ::"r"(bar), "r"(bytes) : "memory");
}
__device__ __forceinline__ void mbar_wait(uint32_t bar, uint32_t parity) {
    asm volatile("{\n.reg .pred p;\nLW:\nmbarrier.try_wait.parity.shared::cta.b64 p, [%0], %1;\n@!p pmevent 0;\n@!p bra LW;\n}\n" ::"r"(bar), "r"(parity) : "memory");
}
__device__ __forceinline__ void mbar_wait_sleep(uint32_t bar, uint32_t parity) {
    asm volatile("{\n.reg .pred p;\nLW:\nmbarrier.try_wait.parity.shared::cta.b64 p, [%0], %1, 20000;\n@!p pmevent 0;\n@!p bra LW;\n}\n" ::"r"(bar), "r"(parity) : "memory");
}
__device__ __forceinline__ void mbar_wait_bounded(uint32_t bar, uint32_t parity) {
    asm volatile("{\n.reg .pred p;\n.reg .u32 c;\nmov.u32 c, 0;\nLW:\nmbarrier.try_wait.parity.shared::cta.b64 p, [%0], %1, 20000;\n@p bra LD;\n"
                 "add.u32 c, c, 1;\nsetp.ge.u32 p, c, 262144;\n@p trap;\nbra LW;\nLD:\n}\n" ::"r"(bar), "r"(parity) : "memory");
}
__device__ __forceinline__ void flag_wait(const int* p, int v) {
    asm volatile("{\n.reg .pred p;\n.reg .s32 f;\nLW:\nld.acquire.gpu.global.s32 f, [%0];\nsub.s32 f, f, %1;\nsetp.lt.s32 p, f, 0;\n@p bra LW;\n}\n" ::"l"(p), "r"(v) : "memory");
}
__device__ __forceinline__ void flag_wait_bounded(const int* p, int v) {
    asm volatile("{\n.reg .pred p;\n.reg .u32 c;\n.reg .s32 f;\nmov.u32 c, 0;\nLW:\nld.acquire.gpu.global.s32 f, [%0];\nsub.s32 f, f, %1;\nsetp.ge.s32 p, f, 0;\n@p bra LD;\n"
                 "nanosleep.u32 500;\nadd.u32 c, c, 1;\nsetp.ge.u32 p, c, 4194304;\n@p trap;\nbra LW;\nLD:\n}\n" ::"l"(p), "r"(v) : "memory");
}
__device__ __forceinline__ bool elect() {
    uint32_t p; asm volatile("{\n.reg .pred p;\nelect.sync _|p, -1;\nselp.u32 %0, 1, 0, p;\n}\n" : "=r"(p)); return p;
}
__device__ __forceinline__ void bulk_g2s(uint32_t dst, const void* src, uint32_t bytes, uint32_t bar) {
    asm volatile("cp.async.bulk.shared::cluster.global.mbarrier::complete_tx::bytes [%0], [%1], %2, [%3];\n"
                 ::"r"(dst), "l"(src), "r"(bytes), "r"(bar) : "memory");
}
__device__ __forceinline__ void bulk_g2s_mc(uint32_t dst, const void* src, uint32_t bytes, uint32_t bar, uint16_t mask) {
    asm volatile("cp.async.bulk.shared::cluster.global.mbarrier::complete_tx::bytes.multicast::cluster [%0], [%1], %2, [%3], %4;\n"
                 ::"r"(dst), "l"(src), "r"(bytes), "r"(bar), "h"(mask) : "memory");
}
__device__ __forceinline__ void tma_g2s(uint32_t dst, const CUtensorMap* tm, int rowgroup, uint32_t bar) {
    asm volatile("cp.async.bulk.tensor.4d.shared::cluster.global.tile.mbarrier::complete_tx::bytes [%0], [%1, {0, 0, 0, %2}], [%3];\n"
                 ::"r"(dst), "l"(tm), "r"(rowgroup), "r"(bar) : "memory");
}
__device__ __forceinline__ void bar_sync(int id, int n) { asm volatile("bar.sync %0, %1;\n" ::"r"(id), "r"(n) : "memory"); }
__device__ __forceinline__ void bar_arrive(int id, int n) { asm volatile("bar.arrive %0, %1;\n" ::"r"(id), "r"(n) : "memory"); }
__device__ __forceinline__ float quad_last(float v) {
    float r; asm volatile("shfl.sync.idx.b32 %0, %1, 3, 0x1c1f, -1;\n" : "=f"(r) : "f"(v)); return r;
}
__device__ __forceinline__ float ex2(float x) { float y; asm("ex2.approx.ftz.f32 %0, %1;\n" : "=f"(y) : "f"(x)); return y; }
__device__ __forceinline__ float rcp(float x) { float y; asm("rcp.approx.ftz.f32 %0, %1;\n" : "=f"(y) : "f"(x)); return y; }
__device__ __forceinline__ uint32_t pack_bf16(float lo, float hi) {
    uint32_t r; asm("cvt.rn.bf16x2.f32 %0, %1, %2;\n" : "=r"(r) : "f"(hi), "f"(lo)); return r;
}
__device__ __forceinline__ uint32_t pack_f16(float lo, float hi) {
    uint32_t r; asm("cvt.rn.f16x2.f32 %0, %1, %2;\n" : "=r"(r) : "f"(hi), "f"(lo)); return r;
}
__device__ __forceinline__ uint32_t pack_f16_sat(float lo, float hi) {
    uint32_t r; asm("cvt.rn.satfinite.f16x2.f32 %0, %1, %2;\n" : "=r"(r) : "f"(hi), "f"(lo)); return r;
}
__device__ __forceinline__ float f16_lo(uint32_t v) { float r; asm("cvt.f32.f16 %0, %1;\n" : "=f"(r) : "h"((unsigned short)v)); return r; }
__device__ __forceinline__ float f16_hi(uint32_t v) { return f16_lo(v >> 16); }
__device__ __forceinline__ float bf_lo(uint32_t v) { return __uint_as_float(v << 16); }
__device__ __forceinline__ float bf_hi(uint32_t v) { return __uint_as_float(v & 0xFFFF0000u); }
__device__ __forceinline__ float bf_round(float x) { return __uint_as_float(pack_bf16(0.f, x)); }
__device__ __forceinline__ void st_release(int* p, int v) {
    asm volatile("st.release.gpu.global.s32 [%0], %1;\n" ::"l"(p), "r"(v) : "memory");
}
__device__ __forceinline__ uint4 ldg_pinned(const uint4* p) {
    uint4 v; asm volatile("ld.global.nc.v4.u32 {%0, %1, %2, %3}, [%4];\n" : "=r"(v.x), "=r"(v.y), "=r"(v.z), "=r"(v.w) : "l"(p) : "memory"); return v;
}
__device__ __forceinline__ void stmatrix_x4(uint32_t addr, uint32_t r0, uint32_t r1, uint32_t r2, uint32_t r3) {
    asm volatile("stmatrix.sync.aligned.m8n8.x4.shared.b16 [%0], {%1, %2, %3, %4};\n" ::"r"(addr), "r"(r0), "r"(r1), "r"(r2), "r"(r3) : "memory");
}

__device__ __forceinline__ uint32_t tile_off(int r, int ch) {
    return (uint32_t)((r >> 3) * 4096 + (ch >> 3) * 1024 + (r & 7) * 128 + (((ch ^ r) & 7) << 4));
}
__device__ __forceinline__ int h_unit(int qt, int u) { return qt < 78 ? u * 78 + qt : 624; }
__device__ __forceinline__ int row_off(int r) { return 4096 + h_unit(r >> 7, (r >> 4) & 7) * 8192 + (r & 8) * 512 + (r & 7) * 144; }

__device__ __forceinline__ float4 lds128f(uint32_t a) {
    float4 v; asm volatile("ld.shared.v4.f32 {%0, %1, %2, %3}, [%4];\n" : "=f"(v.x), "=f"(v.y), "=f"(v.z), "=f"(v.w) : "r"(a) : "memory"); return v;
}
__device__ __forceinline__ uint64_t lds64(uint32_t a) { uint64_t v; asm volatile("ld.shared.u64 %0, [%1];\n" : "=l"(v) : "r"(a) : "memory"); return v; }
__device__ __forceinline__ uint4 lds128(uint32_t a) {
    uint4 v; asm volatile("ld.shared.v4.u32 {%0, %1, %2, %3}, [%4];\n" : "=r"(v.x), "=r"(v.y), "=r"(v.z), "=r"(v.w) : "r"(a) : "memory"); return v;
}
__device__ __forceinline__ void sts128(uint32_t a, uint32_t x, uint32_t y, uint32_t z, uint32_t w) {
    asm volatile("st.shared.v4.u32 [%0], {%1, %2, %3, %4};\n" ::"r"(a), "r"(x), "r"(y), "r"(z), "r"(w) : "memory");
}
__device__ __forceinline__ void mbar_arrive(uint32_t bar) {
    asm volatile("mbarrier.arrive.shared::cta.b64 _, [%0];\n" ::"r"(bar) : "memory");
}
__device__ __forceinline__ uint64_t mkaddr(uint32_t lo, uint32_t hi) { uint64_t a; asm("mov.b64 %0, {%1, %2};\n" : "=l"(a) : "r"(lo), "r"(hi)); return a; }
__device__ __forceinline__ void red_add(int* p) { asm volatile("red.relaxed.gpu.global.add.s32 [%0], 1;\n" ::"l"(p) : "memory"); }
__device__ __forceinline__ void red_release(int* p) {
    asm volatile("fence.proxy.async.global;\nfence.acq_rel.gpu;\nred.relaxed.gpu.global.add.s32 [%0], 1;\n" ::"l"(p) : "memory");
}
__device__ __forceinline__ void fence_async_global() { asm volatile("fence.proxy.async.global;\n" ::: "memory"); }
__device__ __forceinline__ void fence_async_smem() { asm volatile("fence.proxy.async.shared::cta;\n" ::: "memory"); }
__device__ __forceinline__ void bulk_s2g(void* dst, uint32_t src, uint32_t bytes) {
    asm volatile("cp.async.bulk.global.shared::cta.bulk_group [%0], [%1], %2;\ncp.async.bulk.commit_group;\n" ::"l"(dst), "r"(src), "r"(bytes) : "memory");
}
__device__ __forceinline__ void mma16816(float (&c)[4], uint32_t a0, uint32_t a1, uint32_t a2, uint32_t a3, uint32_t b0, uint32_t b1) {
    asm("mma.sync.aligned.m16n8k16.row.col.f32.bf16.bf16.f32 {%0, %1, %2, %3}, {%4, %5, %6, %7}, {%8, %9}, {%0, %1, %2, %3};\n"
        : "+f"(c[0]), "+f"(c[1]), "+f"(c[2]), "+f"(c[3]) : "r"(a0), "r"(a1), "r"(a2), "r"(a3), "r"(b0), "r"(b1));
}
__device__ __forceinline__ void mma1688(float (&c)[4], uint32_t a0, uint32_t a1, uint32_t b0) {
    asm("mma.sync.aligned.m16n8k8.row.col.f32.bf16.bf16.f32 {%0, %1, %2, %3}, {%4, %5}, {%6}, {%0, %1, %2, %3};\n"
        : "+f"(c[0]), "+f"(c[1]), "+f"(c[2]), "+f"(c[3]) : "r"(a0), "r"(a1), "r"(b0));
}
__device__ __forceinline__ uint32_t hadd2_f16(uint32_t a, uint32_t b) { uint32_t r; asm("add.rn.f16x2 %0, %1, %2;\n" : "=r"(r) : "r"(a), "r"(b)); return r; }
__device__ __forceinline__ uint32_t hadd2(uint32_t a, uint32_t b) { uint32_t r; asm("add.rn.bf16x2 %0, %1, %2;\n" : "=r"(r) : "r"(a), "r"(b)); return r; }
__device__ __forceinline__ uint32_t hmul2(uint32_t a, uint32_t b) { uint32_t r; asm("mul.rn.bf16x2 %0, %1, %2;\n" : "=r"(r) : "r"(a), "r"(b)); return r; }
__device__ __forceinline__ uint32_t hfma2(uint32_t a, uint32_t b, uint32_t c) { uint32_t r; asm("fma.rn.bf16x2 %0, %1, %2, %3;\n" : "=r"(r) : "r"(a), "r"(b), "r"(c)); return r; }

constexpr int SM_Q = 0;
constexpr int SM_KV = 65536;
constexpr int SM_ML = SM_KV + STAGES * KV_BYTES;
constexpr int SM_BAR = SM_ML + 1024;
constexpr int SM_TOTAL = SM_BAR + 256;
constexpr float SCALE_LOG2 = 1.4426950408889634f / 16.0f;
constexpr float KV_SCALE = 0.75f;
constexpr float KV_OFF = 6.f;
constexpr uint32_t KV_OFF2 = 0x46004600u;
constexpr uint32_t KV_NEG4 = 0xCE00CE00u;
constexpr uint32_t P_LIMIT = 0x78007800u;
constexpr float REF_UP = REFUP;
__device__ __forceinline__ uint32_t kvf(uint32_t a) {
    uint32_t r; asm("fma.rn.f16x2 %0, %1, %2, %3;\n" : "=r"(r) : "r"(a), "r"(pack_f16(KV_SCALE, KV_SCALE)), "r"(KV_OFF2)); return r;
}
enum { BAR_PP0 = 1, BAR_PP1 = 2, BAR_WG0 = 3, BAR_WG1 = 4, BAR_H0 = 5, BAR_H1 = 6, BAR_AUX = 7, BAR_BF = 8, BAR_H2 = 9, BAR_X = 10, BAR_GO = 11, BAR_WG2 = 12, BAR_ST = 13 };

struct Hot {
    const __nv_bfloat16 *wk, *wq, *x;
    Scratch* s;
};
struct Params {
    const __nv_bfloat16* deg_inv;
    const int *src, *dst;
    __nv_bfloat16* out;
    uint32_t dhi;
    int E;
    CUtensorMap tm_out;
    CUtensorMap tm_outc;
    CUtensorMap tm_w[3];
};
static_assert(offsetof(Params, tm_outc) == offsetof(Params, tm_out) + 128, "layout");
#define SC_PAIR (blockIdx.x < 104)
#define SC_TAIL (blockIdx.x >= NCTA - 2)
#define SC_LAST (blockIdx.x == NCTA - 1)
#define SC_HELP (SC_PAIR && rank)
#define SC_OWNER (!SC_HELP && !SC_LAST)
#define SC_QT1 (26 + (int)(blockIdx.x >> 1))
#define SC_QT0 (SC_PAIR ? (rank ? (int)(blockIdx.x >> 2) : SC_QT1) : SC_TAIL ? 78 : (int)blockIdx.x - 104)
#define SC_NKV (SC_LAST ? 50 : 75)
#define SC_NMC (SC_PAIR ? 25 : SC_TAIL ? 0 : 75)
#define SC_CLS (SC_PAIR ? (rank ? 0x120 ^ (blockIdx.x & 2) * 0x80 : 0x430) | (blockIdx.x & 2) >> 1 : SC_LAST ? 0x10 : 0x432)
#define SC_NW (SC_PAIR ? 8 : SC_LAST ? 0 : 4)
#define SC_ZB (2 * SC_QT1 + 1 - (int)rank)
#define SC_TZB(k) (rank && !(k) ? 156 : 2 * (k) - (int)rank)

__global__ void __cluster_dims__(2, 1, 1) __launch_bounds__(384, 1) k_main(const __grid_constant__ Hot H, const __grid_constant__ Params P) {
    extern __shared__ __align__(1024) uint8_t smem[];
    const uint32_t sb = (uint32_t)__cvta_generic_to_shared(smem);
    const int tid = threadIdx.x, wg = __shfl_sync(~0u, tid >> 7, 0);
    const int lane = tid & 31, g = lane >> 2, q = lane & 3;
    const uint32_t rank = blockIdx.x & 1;
    const uint32_t bar_full = sb + SM_BAR, bar_q = bar_full + 32, bar_go = bar_full + 48;
    const uint32_t bar_pin = bar_full + 56;
    const uint32_t bar_qfree = bar_full + 72, bar_pdone = bar_full + 88, bar_zst = bar_full + 104, bar_rfree = bar_full + 120;
    const uint32_t bar_empty = bar_full + 128, bar_end = bar_full + 160, s_tm = bar_full + 184, bar_x = bar_full + 192;
    const uint32_t bar_a = sb + SM_ML;

    const int t = tid & 127, warp = __shfl_sync(~0u, t >> 5, 0);
    int ep = 0;
    if (wg & 2) {
        unsigned done;
        {
            uint4 ra[2], rb[2], rk[5][2];
            if (blockIdx.x < 128) {
                const int e = (blockIdx.x >> 4) * 32 + (g >> 1) * 8 + (blockIdx.x & 8) / 2 + (g & 1);
                const uint4* pq = (const uint4*)(H.wq + e * 256) + warp * 8 + q;
                const uint4* pk = (const uint4*)(H.wk + ((blockIdx.x & 7) * 32 + g) * 256) + warp * 8 + q;
                const uint4* pz = (const uint4*)(H.wk + 255 * 256) + warp * 8 + q;
#pragma unroll
                for (int s = 0; s < 2; s++) {
                    ra[s] = ldg_pinned(pq + 4 * s);
                    rb[s] = ldg_pinned(pq + 4 * s + 64);
#pragma unroll
                    for (int n = 0; n < 4; n++) rk[n][s] = ldg_pinned(pk + 4 * s + n * 256);
                    rk[4][s] = ldg_pinned(pz + 4 * s);
                }
            }
            asm volatile("{\n.reg .pred p;\nsetp.eq.s32 p, %2, 0;\nmov.u32 %0, 0;\n@p ld.global.cg.u32 %0, [%1];\n}\n" : "=r"(done) : "l"(&g_sync[SY_DONE * 32]), "r"(lane) : "memory");
            bar_arrive(BAR_X, 384);
            if (warp == 0 && elect()) {
#pragma unroll
                for (int i = 0; i < 21; i++) mbar_init(bar_full + 8 * i, i < 9 ? 1 : i < 16 ? 4 : i == 20 ? 11 : SC_TAIL ? 8 : 16);
#pragma unroll
                for (int i = 0; i < 4; i++) mbar_init(bar_a + 8 * i, 1);
                mbar_expect_tx(bar_pin, QB_BYTES / 2 + 512); mbar_expect_tx(bar_pin + 8, QB_BYTES / 2);
                asm volatile("fence.mbarrier_init.release.cluster;\n" ::: "memory");
            }
            __syncwarp();
            asm volatile("barrier.cluster.arrive.relaxed.aligned;\n" ::: "memory");
            if (blockIdx.x < 128) {
                float c[5][4] = {};
#pragma unroll
                for (int s = 0; s < 2; s++) {
#pragma unroll
                    for (int n = 0; n < 5; n++) mma16816(c[n], ra[s].x, rb[s].x, ra[s].y, rb[s].y, rk[n][s].x, rk[n][s].y);
#pragma unroll
                    for (int n = 0; n < 5; n++) mma16816(c[n], ra[s].z, rb[s].z, ra[s].w, rb[s].w, rk[n][s].z, rk[n][s].w);
                }
#pragma unroll
                for (int i = 0; i < 4; i++) {
                    const int r = i & 2, n = (i & 1) * 2;
                    sts128(sb + SM_KV + 3 * KV_BYTES + QB_BYTES + i * 2048 + t * 16, __float_as_uint(c[n][r] - c[4][r]), __float_as_uint(c[n][r + 1] - c[4][r]),
                           __float_as_uint(c[n + 1][r] - c[4][r]), __float_as_uint(c[n + 1][r + 1] - c[4][r]));
                }
            }
        }
        asm volatile("setmaxnreg.dec.sync.aligned.u32 %0;\n" ::"n"(REG_P));
        if (blockIdx.x < 128) {
            bar_sync(BAR_WG2, 128);
            float4 v[4];
#pragma unroll
            for (int i = 0; i < 4; i++) v[i] = lds128f(sb + SM_KV + 3 * KV_BYTES + QB_BYTES + (warp & 2) * 2048 + (lane & 1) * 2048 + i * 512 + ((warp & 1) * 16 + (lane >> 1)) * 16);
            constexpr float SC = SCALE_LOG2 / KV_SCALE;
            const int r = (warp & 1) * 4 + (lane >> 3);
            *(uint2*)(g_w + tile_off((blockIdx.x >> 3) * 16 + (warp & 2) * 4 + r, (blockIdx.x & 7) * 4 + ((lane >> 1) & 3)) + (lane & 1) * 8) =
                make_uint2(pack_f16_sat(((v[0].x + v[1].x) + (v[2].x + v[3].x)) * SC, ((v[0].y + v[1].y) + (v[2].y + v[3].y)) * SC) | 1,
                           pack_f16_sat(((v[0].z + v[1].z) + (v[2].z + v[3].z)) * SC, ((v[0].w + v[1].w) + (v[2].w + v[3].w)) * SC) | 1);
            if (warp != 1) {
                bar_arrive(BAR_AUX, 128);
            } else {
                bar_sync(BAR_AUX, 128);
                if (elect()) { red_add(&g_sync[SY_DONE * 32 + 4 + (blockIdx.x >> 5)]); }
                __syncwarp();
            }
        }
        else bar_sync(BAR_WG2, 128);
        if (warp == 1) bar_arrive(BAR_GO, 160);
        auto load_a = [&](int j) {
            if (elect()) {
                mbar_expect_tx(bar_a + 8 * j, QB_BYTES);
                bulk_g2s(sb + SM_KV + j * KV_BYTES, g_w + j * QB_BYTES, QB_BYTES, bar_a + 8 * j);
            }
            __syncwarp();
        };
        if (warp == 0) {
            auto poll = [&]() { int c; asm volatile("ld.relaxed.gpu.global.s32 %0, [%1];\n" : "=r"(c) : "l"(&g_sync[SY_DONE * 32 + 4 + (lane & 3)]) : "memory"); return c; };
#pragma unroll 1
            for (int j = 0; j < 4;) {
#pragma unroll 1
                for (const uint32_t mk = __ballot_sync(~0u, poll() >= 32) & 15; (mk >> j) & 1; j++) load_a(j);
            }
        } else if (warp & 1) {
#pragma unroll 1
            for (int j = 0, n = 0; j < 4;) {
                mbar_wait_bounded(bar_a + 8 * j, n & 1);
                uint32_t ok = 1;
#pragma unroll
                for (int i = 0; i < 16; i++) {
                    uint32_t v;
                    asm volatile("ld.shared.u32 %0, [%1];\n" : "=r"(v) : "r"(sb + SM_KV + j * KV_BYTES + (warp & 2) * 8192 + i * 1024 + lane * 32 + g * 4) : "memory");
                    ok &= v;
                }
                asm volatile("{\n.reg .pred p;\nsetp.ne.u32 p, %0, 0;\nbar.red.and.pred p, %1, 64, p;\nselp.u32 %0, 1, 0, p;\n}\n" : "+r"(ok) : "n"((int)BAR_WG2) : "memory");
                if (__any_sync(~0u, ok)) {
                    if (warp == 1 && elect()) asm volatile("mbarrier.arrive.shared::cta.b64 _, [%0];\nmbarrier.inval.shared::cta.b64 [%1];\n" ::"r"(bar_full + 8 * j), "r"(bar_a + 8 * j) : "memory");
                    __syncwarp();
                    j++; n = 0;
                } else {
                    asm volatile("{\n.reg .pred p;\nsetp.gt.s32 p, %0, 1000000;\n@p trap;\n}\n" ::"r"(++n) : "memory");
                    fence_async_smem();
                    if (warp == 1) load_a(j);
                }
            }
        }
        done = __shfl_sync(~0u, done, 0);
        ep = (int)(done / NCTA) + 1;
        asm volatile("barrier.cluster.wait.acquire.aligned;\n" ::: "memory");
        if (warp == 0) {
            asm volatile("st.shared.u64 [%0], %1;\n" ::"r"(s_tm), "l"(&P.tm_outc) : "memory");
            __syncwarp();
            if (elect()) {
                const uint8_t* base = (const uint8_t*)H.s;
                uint32_t cls = SC_CLS, bytes = KV_BYTES, moff = SC_NMC ? rank * (KV_BYTES / 2) : 0, step = 5 * KV_BYTES;
                const uint8_t* src = base;
                int next = 0;
                const int nit = SC_NKV + SC_NW;
#pragma unroll 1
                for (int j = 0; j < nit; j++) {
                    const uint32_t slot = sb + SM_KV + (j & 3) * KV_BYTES, fb = bar_full + 8 * (j & 3);
                    if (j == next) {
                        const int k = j - SC_NKV;
                        const int sw = SC_HELP ? j - 25 : -1;
                        next = j + 1;
                        if (j >= 3 && (unsigned)sw >= 5) next = k >= 0 ? next : j < 25 ? 25 : j < GO0 ? GO0 : j < 49 ? 49 : j < 50 ? 50 : 75;
                        if (j == SC_NMC) moff = 0;
                        if (j == 0 || j == 25 || j == 50) { src = base + (4096 + (cls & 15) * KV_BYTES + moff); cls >>= 4; }
                        if (SC_TAIL ? j == nit - 1 : j == GO0) mbar_arrive(bar_go);
                        int fo = -1, fv = 1;
                        if (j < 3) { fo = (SY_H0 + 5 * j + (SC_CLS & 15)) * 32; fv = 5; }
                        if (j == 3) { fo = SY_H1 * 32; fv = 79; }
                        if (sw == 1) fo = 25 * 32 + SC_QT1;
                        if (k == 0) fo = SY_B * 32;
                        if (k == 1 && !SC_PAIR) { fo = SY_AUX0 * 32; fv = NAUX; }
                        if (k == 2 && SC_PAIR) { fo = SY_AUX * 32; fv = NAUX / 3; }
                        if (fo >= 0) {
                            flag_wait(g_sync + fo, fv * ep);
                            fence_async_global();
                        }
                        if (sw == 2 || (k == 2 && !SC_TAIL)) {
                            uint32_t qs = sw == 2 ? offsetof(Scratch, q) + (2 * SC_QT1 + 1) * QB_BYTES : SC_PAIR ? offsetof(Scratch, agg) + SC_ZB * QB_BYTES : offsetof(Scratch, part) + SC_QT0 * (4 * PART_BYTES);
#pragma unroll 1
                            for (int w = 0; w < (k == 2 && SC_PAIR ? 1 : 2); w++) {
                                mbar_wait_sleep(bar_qfree + 8 * w, k == 2 && SC_HELP);
                                mbar_expect_tx(bar_q + 8 * w, SC_PAIR ? QB_BYTES : PART_BYTES);
                                if (!SC_PAIR) bulk_g2s(sb + SM_ML + w * 512, base + (qs + (w ? -512 : QB_BYTES)), 512, bar_q + 8 * w);
                                bulk_g2s(sb + SM_Q + w * QB_BYTES, base + qs, QB_BYTES, bar_q + 8 * w);
                                qs += sw == 2 ? -QB_BYTES : PART_BYTES + 512;
                            }
                        }
                        if ((sw | 1) == 3) {
                            mbar_wait_sleep(bar_pdone + 8 * (sw - 2), 0);
                            bulk_s2g(g_part + (blockIdx.x - 3 + sw) * PART_BYTES, slot, PART_BYTES);
                            asm volatile("cp.async.bulk.wait_group.read 0;\n" ::: "memory");
                        }
                        if (sw == 5) {
                            asm volatile("cp.async.bulk.wait_group 0;\n" ::: "memory");
                            red_release(&g_sync[SY_PART * 32]);
                        }
                        if (k == 0) {
                            asm volatile("prefetch.tensormap [%0];\n" ::"l"(&P.tm_outc) : "memory");
                            src = g_w + (12 - SC_NW) * QB_BYTES; bytes = step = QB_BYTES;
                        }
                        if (k == 2) next = SC_TAIL ? nit - 1 : nit;
                    }
                    mbar_wait_sleep(fb + (bar_empty - bar_full), (j >> 2) & 1);
                    mbar_expect_tx(fb, bytes);
                    if (j < SC_NMC) bulk_g2s_mc(slot + moff, src, KV_BYTES / 2, fb, 3);
                    else bulk_g2s(slot, src, bytes, fb);
                    src += step;
                }
            }
        } else {
            if (warp == 2 && SC_OWNER) {
                uint8_t* dst = g_hz + 4096 + h_unit(SC_QT0, 0) * 8192;
                auto send = [&](int u0, int u1) {
#pragma unroll
                    for (int u = u0; u < u1; u++) {
                        bulk_s2g(dst + u * (78 * 8192), sb + SM_Q + u * 8192, 8192);
                        asm volatile("cp.async.bulk.wait_group 0;\n" ::: "memory");
                    }
                };
                int* f0 = &g_sync[(SY_H0 + SC_QT0 / 5) * 32];
                bar_sync(BAR_H0, 64);
                if (elect()) {
                    send(0, 1);
                    if (SC_QT0 < 65) red_release(f0);
                }
                bar_sync(BAR_H1, 160);
                if (elect()) {
                    if (!SC_TAIL) send(1, 4);
                    mbar_arrive(bar_q);
                }
                bar_sync(BAR_H2, 160);
                if (elect()) {
                    if (!SC_TAIL) { send(4, 8); mbar_arrive(bar_q + 8); }
                    red_release(&g_sync[SY_H1 * 32]);
                }
                __syncwarp();
            }
        }
    } else {
        const uint32_t sq = sb + SM_Q + wg * QB_BYTES;
        const uint32_t qbar = bar_q + 8 * wg;
        const uint32_t dq0 = __shfl_sync(~0u, ((sq & 0x3FFFF) >> 4) | (64u << 16), 0);
        const uint32_t dk0 = __shfl_sync(~0u, (((sb + SM_KV) & 0x3FFFF) >> 4) | (64u << 16), 0);
        float o[128];
        int it = 4;
        const uint32_t dhi = P.dhi;
        uint32_t rel_addr;
        auto rel_target = [&](uint32_t r) {
            asm("mapa.shared::cluster.u32 %0, %1, %2;\n" : "=r"(rel_addr) : "r"(bar_empty), "r"(r));
            if (lane >= 2) rel_addr = 0;
            asm volatile("" : "+r"(rel_addr));
        };
        rel_target(SC_NMC ? rank ^ (lane & 1) : rank);
        auto release = [&](int st) {
            asm volatile("{\n.reg .pred p;\nsetp.ne.u32 p, %1, 0;\n@p mbarrier.arrive.shared::cluster.b64 _, [%0];\n}\n"
                         ::"r"(rel_addr + 8 * st), "r"(rel_addr) : "memory");
        };
        const bool active = !(SC_TAIL && wg == 1);
        auto pp_sync = [&]() { if (!SC_TAIL) bar_sync(BAR_PP0 + wg, 256); };
        auto pp_arrive = [&]() { if (!SC_TAIL) bar_arrive(BAR_PP1 - wg, 256); };
        auto warp_arrive = [&](uint32_t bar) {
            __syncwarp();
            asm volatile("{\n.reg .pred p;\nelect.sync _|p, -1;\n@p mbarrier.arrive.shared::cta.b64 _, [%0];\n}\n" ::"r"(bar + 8 * wg) : "memory");
        };
        auto peer_arrive = [&]() {
            asm volatile("{\n.reg .pred p;\n.reg .b32 a;\nelect.sync _|p, -1;\nmapa.shared::cluster.u32 a, %0, %1;\n"
                         "@p mbarrier.arrive.shared::cluster.b64 _, [a];\n}\n" ::"r"(bar_rfree), "r"(rank ^ 1) : "memory");
        };
        auto stage_q = [&]() {
            auto pk = [&](int i) { return QRND(pack_f16_sat(o[i], o[i + 1])); };
#pragma unroll
            for (int i = 0; i < 16; i++)
                stmatrix_x4(sq + warp * 8192 + tile_off(lane & 15, 2 * i + (lane >> 4)), pk(8 * i), pk(8 * i + 2), pk(8 * i + 4), pk(8 * i + 6));
        };
        float s[40];
        auto issue_qk = [&](int st) {
            const uint64_t kb = mkaddr(dk0 + st * (KV_BYTES >> 4), dhi);
            const uint64_t qd = mkaddr(dq0 + ((uint32_t)it >> 24), dhi);
            wgmma_ss_n80_init(s, qd + 198, kb + 198);
#pragma unroll
            for (int kk = 0; kk < 15; kk++) wgmma_ss_n80(s, qd + ((kk >> 2) * 64 + (kk & 3) * 2), kb + ((kk >> 2) * 64 + (kk & 3) * 2));
            wg_commit();
        };

        {
            const int rb = (2 * SC_QT0 + wg) * 64 + warp * 16;
            const uint32_t xbar = bar_x + 32 * wg + 8 * warp;
            if (elect()) {
                mbar_init(xbar, 1);
                asm volatile("fence.mbarrier_init.release.cluster;\nfence.proxy.async.shared::cta;\n" ::: "memory");
                mbar_expect_tx(xbar, rb < NN ? 8192 : 0);
            }
            asm volatile("barrier.cluster.arrive.relaxed.aligned;\n" ::: "memory");
            if (wg == 1) pp_arrive();
            bar_sync(BAR_X, 384);
            if (wg == 1) bar_sync(BAR_GO, 160);
            if (rb < NN && elect()) bulk_g2s(sq + warp * 8192, H.x + (size_t)rb * 256, 8192, xbar);
            if (rb >= NN) {
#pragma unroll 1
                for (int i = 0; i < 16; i++) sts128(sq + warp * 8192 + i * 512 + lane * 16, 0, 0, 0, 0);
            }
            __syncwarp();
            mbar_wait(xbar, 0);
            uint4 xa[8], xb[8];
#pragma unroll
            for (int s = 0; s < 8; s++) {
                xa[s] = lds128(sq + (warp * 16 + g) * 512 + (4 * s + q) * 16);
                xb[s] = lds128(sq + (warp * 16 + g + 8) * 512 + (4 * s + q) * 16);
            }
            float sm[2][4], sq2[2][4][4];
#pragma unroll
            for (int i = 0; i < 4; i++) {
                sm[0][i] = sm[1][i] = 0.f;
#pragma unroll
                for (int k = 0; k < 4; k++) sq2[0][k][i] = sq2[1][k][i] = 0.f;
            }
#pragma unroll
            for (int s = 0; s < 8; s++) {
#pragma unroll
                for (int hh = 0; hh < 2; hh++) {
                    const uint4 v = hh ? xb[s] : xa[s];
                    mma16816(sm[hh], v.x, v.y, v.z, v.w, 0x3F803F80u, 0x3F803F80u);
                    mma1688(sq2[hh][0], v.x, v.y, v.x); mma1688(sq2[hh][1], v.x, v.y, v.y);
                    mma1688(sq2[hh][2], v.z, v.w, v.z); mma1688(sq2[hh][3], v.z, v.w, v.w);
                }
            }
            float inv[2], off[2];
#pragma unroll
            for (int hh = 0; hh < 2; hh++) {
                const float mean = (sm[hh][0] + sm[hh][2]) * (1.f / 256.f);
                const float d0 = (sq2[hh][0][0] + sq2[hh][2][0]) + (sq2[hh][1][2] + sq2[hh][3][2]);
                const float d1 = (sq2[hh][0][1] + sq2[hh][2][1]) + (sq2[hh][1][3] + sq2[hh][3][3]);
                const float ss = __shfl_sync(~0u, (g & 1) ? d1 : d0, g * 4 + (g >> 1));
                const float var = fmaxf(ss * (1.f / 256.f) - mean * mean, 0.f);
                float sd;
                asm("sqrt.approx.ftz.f32 %0, %1;\n" : "=f"(sd) : "f"(bf_round(bf_round(var) + 1e-5f)));
                asm("rcp.approx.ftz.f32 %0, %1;\n" : "=f"(inv[hh]) : "f"(bf_round(sd)));
                off[hh] = -mean * inv[hh];
            }
            uint32_t a[64];
#pragma unroll
            for (int s = 0; s < 8; s++) {
                a[8 * s] = xa[s].x; a[8 * s + 1] = xb[s].x; a[8 * s + 2] = xa[s].y; a[8 * s + 3] = xb[s].y;
                a[8 * s + 4] = xa[s].z; a[8 * s + 5] = xb[s].z; a[8 * s + 6] = xa[s].w; a[8 * s + 7] = xb[s].w;
            }
            fence_regs(a);
            if (wg == 1 && __any_sync(~0u, inv[0] + inv[1] != -1.f)) bar_arrive(BAR_ST, 256);
            asm volatile("setmaxnreg.inc.sync.aligned.u32 %0;\n" ::"n"(REG_C));
            fence_regs(a);
#pragma unroll
            for (int i = 0; i < 64; i++)
                a[i] = pack_f16(fmaf(bf_lo(a[i]), inv[i & 1], off[i & 1]), fmaf(bf_hi(a[i]), inv[i & 1], off[i & 1]));
            if (SC_OWNER) {
#pragma unroll
                for (int i = 0; i < 16; i++) {
                    const uint32_t mk = (i == 15 && q == 3) ? 0xFFFFu : ~0u;
                    stmatrix_x4(sq + warp * 8192 + tile_off(lane & 15, 2 * i + (lane >> 4)), kvf(a[4 * i]), kvf(a[4 * i + 1]),
                                kvf(a[4 * i + 2] & mk), kvf(a[4 * i + 3] & mk));
                }
                fence_async_smem();
                if (tid < 32) bar_arrive(BAR_H0, 64);
                bar_arrive(wg ? BAR_H2 : BAR_H1, 160);
            }
            asm volatile("barrier.cluster.wait.acquire.aligned;\n" ::: "memory");
            if (wg == 0) bar_sync(BAR_ST, 256);
            if (active) {
                fence_regs(a);
#pragma unroll
                for (int c = 0; c < 4; c++) {
                    if (c == 1) {
                        if (wg == 1) {
                            wg_wait<0>();
                            release(0);
                        }
                        pp_sync();
                    }
                    mbar_wait(bar_full + 8 * c, 0);
                    const uint64_t wb = mkaddr(dk0 + c * (KV_BYTES >> 4), dhi);
                    wg_fence();
#pragma unroll
                    for (int kk = 0; kk < 4; kk++) {
                        if (c | kk) wgmma_rs_n256_tb(o, a[16 * c + 4 * kk], a[16 * c + 4 * kk + 1], a[16 * c + 4 * kk + 2], a[16 * c + 4 * kk + 3], wb + kk * 512);
                        else wgmma_rs_n256_tb_init(o, a[0], a[1], a[2], a[3], wb);
                    }
                    wg_commit();
                    if (c > 0) { wg_wait<1>(); if (c > 1 || wg == 0) release(c - 1); }
                }
                if (wg == 0) pp_arrive();
                wg_wait<0>();
                fence_regs(o);
                release(3);
                if (SC_OWNER) mbar_wait(qbar, 0);
                stage_q();
                fence_async_smem();
                bar_sync(BAR_WG0 + wg, 128);
                mbar_wait(bar_full, 1);
                wg_fence();
                issue_qk(0);
                if (wg == 1) pp_arrive();
            } else {
                peer_arrive();
            }
        }

        uint32_t p[20];
        float m0 = 0.f, m1 = 0.f, e0, e1, l0, l1;
        uint32_t plim;
        uint32_t qphase = (SC_OWNER && active) ? 1 : 0;
        auto issue_pv = [&](int st, int acc) {
            const uint64_t vb = mkaddr(dk0 + st * (KV_BYTES >> 4), dhi);
            wgmma_rs_n256_tb_pred(o, p[0], p[1], p[2], p[3], vb, acc);
#pragma unroll
            for (int kk = 1; kk < 5; kk++)
                wgmma_rs_n256_tb(o, p[4 * kk], p[4 * kk + 1], p[4 * kk + 2], p[4 * kk + 3], vb + kk * 512);
            wg_commit();
        };
        const uint32_t mq_addr = sq + tile_off(warp * 16 + g, 31) + 14;
        auto exceeds = [&](const uint32_t (&p)[20]) {
            uint32_t a = __vimax3_s16x2(P_LIMIT, p[0], p[1]), b = __vimax3_s16x2(p[2], p[3], p[4]);
#pragma unroll
            for (int i = 5; i < 17; i += 4) { a = __vimax3_s16x2(a, p[i], p[i + 1]); b = __vimax3_s16x2(b, p[i + 2], p[i + 3]); }
            a = __vimax3_s16x2(a, p[17], p[18]);
            return __any_sync(~0u, __vimax3_s16x2(a, b, p[19]) != plim);
        };
        auto remax = [&](float& a, float& b, bool store) {
            float a1 = fmaxf(s[0], s[1]), b1 = fmaxf(s[2], s[3]), a2 = fmaxf(s[4], s[5]), b2 = fmaxf(s[6], s[7]);
#pragma unroll
            for (int i = 2; i < 10; i++) {
                a1 = fmaxf(a1, s[4 * i]); a2 = fmaxf(a2, s[4 * i + 1]);
                b1 = fmaxf(b1, s[4 * i + 2]); b2 = fmaxf(b2, s[4 * i + 3]);
            }
            a1 = fmaxf(a1, a2); b1 = fmaxf(b1, b2);
            a1 = fmaxf(a1, __shfl_xor_sync(~0u, a1, 1)); b1 = fmaxf(b1, __shfl_xor_sync(~0u, b1, 1));
            a1 = fmaxf(a1, __shfl_xor_sync(~0u, a1, 2)); b1 = fmaxf(b1, __shfl_xor_sync(~0u, b1, 2));
            a = fmaxf(a, a1 - e0 + REF_UP); b = fmaxf(b, b1 - e1 + REF_UP);
            const uint32_t u = pack_f16_sat((m0 + a) * (-1.f / KV_OFF), (m1 + b) * (-1.f / KV_OFF));
            const float g0 = (m0 + a) + KV_OFF * f16_lo(u), g1 = (m1 + b) + KV_OFF * f16_hi(u);
            const bool x0 = fabsf(g0) <= 1.f, x1 = fabsf(g1) <= 1.f;
            if (x0) a -= g0;
            if (x1) b -= g1;
            const float da = a + e0, db = b + e1;
            m0 += a; m1 += b;
            e0 = x0 ? 0.f : g0; e1 = x1 ? 0.f : g1;
            plim = (x0 && x1) ? P_LIMIT : 0u;
            asm volatile("{\n.reg .pred p;\nsetp.ne.s32 p, %3, 0;\n@p st.shared.u16 [%0], %1;\n@p st.shared.u16 [%0 + 4096], %2;\n}\n"
                         ::"r"(mq_addr), "h"((unsigned short)u), "h"((unsigned short)(u >> 16)), "r"((int)(store && q == 0)) : "memory");
#pragma unroll
            for (int i = 0; i < 10; i++) {
                p[2 * i] = pack_f16(ex2(s[4 * i] - da), ex2(s[4 * i + 1] - da));
                p[2 * i + 1] = pack_f16(ex2(s[4 * i + 2] - db), ex2(s[4 * i + 3] - db));
            }
            fence_regs(p);
            fence_async_smem();
            __syncwarp();
        };

        auto row_sums = [&](float& z0, float& z1) {
            z0 = quad_last(o[125]); z1 = quad_last(o[127]);
            l0 = z0 * (KV_SCALE / KV_OFF); l1 = z1 * (KV_SCALE / KV_OFF);
        };
        auto cut = [&]() { asm volatile("{\n.reg .pred p;\nsetp.lt.s32 p, %0, 0;\nL:\n@p pmevent 0;\n@p bra L;\n}\n" ::"r"(it) : "memory"); };
        auto stats = [&]() { return (q & 2) ? ((q & 1) ? l1 : m1) : ((q & 1) ? l0 : m0); };
        const int nseg = SC_HELP ? 2 : 1;
        if (active) {
#pragma unroll 1
        for (int seg = 0;; seg++) {
            wg_wait<0>();
            fence_regs(s);
            e0 = e1 = 0.f;
            const int it0 = it, itl = __shfl_sync(~0u, seg + 1 < nseg ? 3 + 25 : 3 + SC_NKV, 0);
            const int itx = (wg == 1 && seg + 1 == nseg) ? itl : -1;
            bool redo = true, have = !seg;
#pragma unroll 1
            for (;;) {
                if (!have) {
#pragma unroll
                    for (int i = 0; i < 20; i++) p[i] = pack_f16(ex2(s[2 * i]), ex2(s[2 * i + 1]));
                    redo = exceeds(p);
                }
                if (redo) {
                    float d0 = it != it0 ? 0.f : -INFINITY, d1 = d0;
                    remax(d0, d1, it != itl);
                    if (it != it0) {
                        const float a0 = ex2(-d0), a1 = ex2(-d1);
#pragma unroll
                        for (int i = 0; i < 32; i++) { o[4 * i] *= a0; o[4 * i + 1] *= a0; o[4 * i + 2] *= a1; o[4 * i + 3] *= a1; }
                    }
                }
                if (it == it0 && (seg || SC_OWNER)) {
                    fence_async_smem();
                    warp_arrive(bar_pdone);
                }
                if (it == itl) break;
                const int stp = it & 3;
                it++;
                mbar_wait(bar_full + 8 * (it & 3), (it >> 2) & 1);
                pp_sync();
                fence_regs(o); fence_regs(p);
                wg_fence();
                issue_qk(it & 3);
                if (it == itx) {
                    wg_wait<0>();
                    if (SC_PAIR) peer_arrive(); else warp_arrive(bar_qfree);
                    bar_sync(BAR_ST, 256);
                }
                wg_fence();
                issue_pv(stp, it - 1 - it0);
                pp_arrive();
                if (it == itl && itx < 0) {
                    wg_wait<1>();
                    warp_arrive(bar_qfree);
                }
                have = SC_TAIL || it == itx;
                if (have) {
                    uint32_t p2[20];
                    wg_wait<1>();
                    fence_regs(s);
#pragma unroll
                    for (int i = 0; i < 20; i++) p2[i] = pack_f16(ex2(s[2 * i]), ex2(s[2 * i + 1]));
                    redo = exceeds(p2);
                    if (redo) asm volatile("wgmma.wait_group.sync.aligned 0;\nnanosleep.u32 0;\n" ::: "memory");
                    else wg_wait<0>();
                    fence_regs(o); fence_regs(p);
#pragma unroll
                    for (int i = 0; i < 20; i++) p[i] = p2[i];
                } else {
                    wg_wait<0>();
                    fence_regs(s); fence_regs(o); fence_regs(p);
                }
                release(stp);
                if (it == SC_NMC) rel_target(rank);
            }
            if (seg + 1 < nseg) pp_sync();
            fence_regs(o); fence_regs(p);
            wg_fence();
            issue_pv(it & 3, 1);
            asm volatile("{\n.reg .pred p;\nsetp.ne.s32 p, %0, 0;\n@p bar.arrive %1, 256;\n}\n" ::"r"((int)(seg + 1 == nseg && (wg ? SC_PAIR : !SC_TAIL))), "r"(BAR_ST + wg) : "memory");
            it++;
            if (seg + 1 == nseg) break;
            const int is = it - 2 + wg;
            uint32_t dst = sb + SM_KV + (is & 3) * KV_BYTES + wg * 512 + warp * 8192 + lane * 16;
            uint32_t dml = sb + SM_KV + (is & 3) * KV_BYTES + (wg ? 0 : QB_BYTES) + t * 4;
            asm volatile("" : "+r"(dst), "+r"(dml));
            mbar_wait(qbar, qphase); qphase ^= 1;
            unsigned short u0, u1;
            asm volatile("ld.shared.u16 %0, [%2];\nld.shared.u16 %1, [%2 + 4096];\n" : "=h"(u0), "=h"(u1) : "r"(mq_addr) : "memory");
            mbar_wait(bar_full + 8 * (it & 3), (it >> 2) & 1);
            wg_wait<0>();
            fence_regs(o);
            float z0, z1;
            row_sums(z0, z1);
            release((it - 1) & 3);
            wg_fence();
            issue_qk(it & 3);
            pp_arrive();
#pragma unroll
            for (int i = 0; i < 128; i++) o[i] -= (i & 2) ? z1 : z0;
            fence_regs(o);
            mbar_wait(bar_empty + 8 * (is & 3), (is >> 2) & 1);
            asm volatile("st.shared.f32 [%0], %1;\n" ::"r"(dml), "f"(stats()) : "memory");
            m0 = -KV_OFF * f16_lo(u0); m1 = -KV_OFF * f16_lo(u1);
            plim = fmaxf(fabsf(m0), fabsf(m1)) <= 3072.f ? P_LIMIT : 0u;
            uint32_t v[2][8] = {};
#pragma unroll
            for (int i = 0; i < 8; i++) {
                uint32_t *w = v[i & 1], *u = v[(i & 1) ^ 1];
#pragma unroll
                for (int j = 0; j < 8; j++) w[j] = pack_bf16(o[16 * i + 2 * j], o[16 * i + 2 * j + 1]);
                sts128(dst + i * 1024, w[0], w[1], w[2], w[3]);
                sts128(dst + i * 1024 + 512, w[4], w[5], w[6], w[7]);
                if (i) asm volatile("{\n.reg .pred p;\nsetp.lt.s32 p, %9, 0;\nL:\n@p st.shared.v4.u32 [%0], {%1, %2, %3, %4};\n@p st.shared.v4.u32 [%0 + 16], {%5, %6, %7, %8};\n@p bra L;\n}\n"
                             ::"r"(dst), "r"(u[0]), "r"(u[1]), "r"(u[2]), "r"(u[3]), "r"(u[4]), "r"(u[5]), "r"(u[6]), "r"(u[7]), "r"(it) : "memory");
            }
        }
        constexpr int IW = 4 + 75;
        uint32_t a[64];
        if (wg == 0 && (SC_PAIR || SC_LAST)) {
            uint32_t rq, rml, rbar;
            asm volatile("mapa.shared::cluster.u32 %0, %3, %6;\nmapa.shared::cluster.u32 %1, %4, %6;\nmapa.shared::cluster.u32 %2, %5, %6;\n"
                         : "=r"(rq), "=r"(rml), "=r"(rbar) : "r"(sb + SM_Q + QB_BYTES + warp * 8192 + lane * 16), "r"(sb + SM_ML + 512 + t * 4),
                         "r"(bar_pin), "r"(rank ^ 1));
            auto send = [&](int i) {
                asm volatile("st.async.weak.shared::cluster.mbarrier::complete_tx::bytes.v4.b32 [%0], {%1, %2, %3, %4}, [%5];\n"
                             ::"r"(rq + i * 512), "r"(a[4 * i]), "r"(a[4 * i + 1]), "r"(a[4 * i + 2]), "r"(a[4 * i + 3]), "r"(rbar + (i & 8)) : "memory");
            };
            mbar_wait(bar_rfree, 0);
            wg_wait<0>();
            fence_regs(o);
            release((it - 1) & 3);
            float z0, z1;
            row_sums(z0, z1);
            asm volatile("st.async.weak.shared::cluster.mbarrier::complete_tx::bytes.f32 [%0], %1, [%2];\n" ::"r"(rml), "f"(stats()), "r"(rbar) : "memory");
#pragma unroll
            for (int i = 0; i < 16; i++) {
                a[4 * i] = pack_bf16(o[8 * i] - z0, o[8 * i + 1] - z0); a[4 * i + 1] = pack_bf16(o[8 * i + 2] - z1, o[8 * i + 3] - z1);
                a[4 * i + 2] = pack_bf16(o[8 * i + 4] - z0, o[8 * i + 5] - z0); a[4 * i + 3] = pack_bf16(o[8 * i + 6] - z1, o[8 * i + 7] - z1);
                if (i * SND0 / 16 != (i + 1) * SND0 / 16) send(i * SND0 / 16);
                if (i % CUT2 == CUT2 - 1) cut();
            }
            if (SC_PAIR) {
                float z[128];
                const uint32_t dkz = dk0 + ((uint32_t)it >> 24), dqz = dq0 + ((uint32_t)it >> 24);
                auto gemm = [&](int c) {
                    mbar_wait(bar_full + 8 * ((IW + c) & 3), ((IW + c) >> 2) & 1);
                    const uint64_t wb = mkaddr(dkz + ((IW + c) & 3) * (KV_BYTES >> 4), dhi), ab = mkaddr(dqz + c * 64, dhi);
                    wg_fence();
#pragma unroll
                    for (int kk = 0; kk < 4; kk++) {
                        if (c | kk) wgmma_ss_n256_tb(z, ab + kk * 2, wb + kk * 512);
                        else wgmma_ss_n256_tb_init(z, ab, wb);
                    }
                    wg_commit();
                };
                auto release2 = [&](int c) {
                    asm volatile("{\n.reg .pred p;\nsetp.ne.u32 p, %1, 0;\n@p mbarrier.arrive.shared::cluster.b64 _, [%0], 2;\n}\n"
                                 ::"r"(rel_addr + 8 * ((IW + c) & 3)), "r"(rel_addr) : "memory");
                };
                mbar_wait(qbar, qphase);
                bar_sync(BAR_ST + 1, 256);
                gemm(0);
#pragma unroll
                for (int i = SND0; i < 16; i++) send(i);
#pragma unroll
                for (int c = 1; c < 4; c++) { gemm(c); if (c == 3) pp_arrive(); wg_wait<1>(); release2(c - 1); }
                wg_wait<0>();
                fence_regs(z);
                release2(3);
#pragma unroll
                for (int i = 0; i < 16; i++) {
                    sts128(sq + warp * 8192 + lane * 16 + i * 512, pack_bf16(z[8 * i], z[8 * i + 1]), pack_bf16(z[8 * i + 2], z[8 * i + 3]),
                           pack_bf16(z[8 * i + 4], z[8 * i + 5]), pack_bf16(z[8 * i + 6], z[8 * i + 7]));
                    if (i == 3 || i == 15) bar_arrive(i == 3 ? BAR_BF : BAR_H0, 256);
                    if (i == 3) cut();
                }
            } else {
#pragma unroll
                for (int i = SND0; i < 16; i++) send(i);
            }
        } else {
            const int pair = SC_PAIR;
            const bool glob = !(pair || SC_TAIL);
            const uint32_t ml = sb + SM_ML + (t & ~3) * 4, src = (glob ? sq : sb + SM_Q + QB_BYTES) + warp * 8192 + lane * 16;
            const uint64_t tm = lds64(s_tm);
            wg_wait<0>();
            fence_regs(o);
            release((IW - 1) & 3);
            float c0, c1;
            row_sums(c0, c1);
            mbar_wait(glob ? qbar : bar_pin, glob ? qphase : 0);
            const float4 ps = lds128f(ml + (glob ? wg * 512 : 512));
            auto load = [&](int i) {
                asm volatile("ld.shared.v4.u32 {%0, %1, %2, %3}, [%4];\n" : "=r"(a[4 * i]), "=r"(a[4 * i + 1]), "=r"(a[4 * i + 2]), "=r"(a[4 * i + 3]) : "r"(src + i * 512) : "memory");
            };
#pragma unroll
            for (int i = 0; i < 8; i++) load(i);
            const float n0 = fmaxf(m0, ps.x), n1 = fmaxf(m1, ps.z);
            const float a0 = ex2(m0 - n0), a1 = ex2(m1 - n1), b0 = ex2(ps.x - n0), b1 = ex2(ps.z - n1);
            const float i0 = rcp(l0 * a0 + ps.y * b0), i1 = rcp(l1 * a1 + ps.w * b1);
            const float r0 = a0 * i0, r1 = a1 * i1;
            c0 *= -r0; c1 *= -r1;
            const uint32_t u0 = pack_bf16(b0 * i0, b0 * i0), u1 = pack_bf16(b1 * i1, b1 * i1);
#pragma unroll
            for (int i = 0; i < 32; i++) {
                if (i == 16) {
                    if (!glob) mbar_wait(bar_pin + 8, 0);
#pragma unroll
                    for (int j = 8; j < 16; j++) load(j);
                }
                a[2 * i] = hfma2(a[2 * i], u0, pack_bf16(fmaf(o[4 * i], r0, c0), fmaf(o[4 * i + 1], r0, c0)));
                a[2 * i + 1] = hfma2(a[2 * i + 1], u1, pack_bf16(fmaf(o[4 * i + 2], r1, c1), fmaf(o[4 * i + 3], r1, c1)));
            }
            float y[2][32];
            auto gemm = [&](int c, int kh) {
                if (!kh) mbar_wait(bar_full + 8 * ((IW + c) & 3), (((IW + c) >> 2) & 1) ^ pair);
                const uint64_t wb = mkaddr(dk0 + ((IW + c) & 3) * (KV_BYTES >> 4), dhi - 192);
                wg_fence();
#pragma unroll
                for (int kk = 8 * kh; kk < 8 * kh + 8; kk++) {
                    if (kk) wgmma_rs_n64_tb(y[c & 1], a[4 * kk], a[4 * kk + 1], a[4 * kk + 2], a[4 * kk + 3], wb + kk * 128);
                    else wgmma_rs_n64_tb_init(y[c & 1], a[0], a[1], a[2], a[3], wb);
                }
                wg_commit();
            };
            const uint32_t stg = sq + warp * 8192 + (lane & 15) * 128 + (((lane >> 4) ^ lane) & 7) * 16;
            uint4 z[4] = {};
            auto load_z = [&](int cb) {
                if (cb < 2) asm volatile("{\n.reg .pred p;\nsetp.ne.s32 p, %0, 0;\n@p bar.sync %1, 256;\n}\n" ::"r"(pair), "r"(cb ? BAR_H0 : BAR_BF) : "memory");
#pragma unroll
                for (int i = 0; i < 4; i++)
                    asm volatile("{\n.reg .pred p;\nsetp.ne.u32 p, %4, 0;\n@p ld.shared.v4.u32 {%0, %1, %2, %3}, [%5];\n}\n"
                                 : "+r"(z[i].x), "+r"(z[i].y), "+r"(z[i].z), "+r"(z[i].w) : "r"(pair), "r"(src - QB_BYTES + (4 * cb + i) * 512) : "memory");
            };
            pp_sync();
            gemm(0, 0);
            gemm(0, 1);
#pragma unroll
            for (int c = 0; c < 4; c++) {
                if (c) load_z(c);
                if (c < 3) gemm(c + 1, 0);
                if (!c) load_z(0);
                if (c < 3) wg_wait<1>(); else wg_wait<0>();
                fence_regs(y[c & 1]);
                const float* x = y[c & 1];
#pragma unroll
                for (int i = 0; i < 4; i++)
                    stmatrix_x4((stg ^ (32 * i)) + c * 2048, hadd2(pack_bf16(x[8 * i], x[8 * i + 1]), z[i].x), hadd2(pack_bf16(x[8 * i + 2], x[8 * i + 3]), z[i].y),
                                hadd2(pack_bf16(x[8 * i + 4], x[8 * i + 5]), z[i].z), hadd2(pack_bf16(x[8 * i + 6], x[8 * i + 7]), z[i].w));
                if (c < 3) gemm(c + 1, 1);
                fence_async_smem();
                __syncwarp();
                asm volatile("{\n.reg .pred p;\nelect.sync _|p, -1;\n"
                             "@p cp.reduce.async.bulk.tensor.4d.global.shared::cta.add.tile.bulk_group [%0, {0, 0, %1, %2}], [%3];\n}\n"
                             ::"l"(tm), "r"(c), "r"((pair ? SC_ZB : 2 * SC_QT0 + wg) * 8 + warp * 2), "r"(sq + warp * 8192 + c * 2048) : "memory");
                if (c == 2 && glob) pp_arrive();
            }
            asm volatile("cp.async.bulk.commit_group;\ncp.async.bulk.wait_group.read 0;\n" ::: "memory");
        }
        } else {
            wg_wait<0>();
        }
        if (SC_TAIL) {
        float o[128];
        auto emit = [&](uint32_t base, int lane, int row0, uint8_t* wdst, int turn) {
#pragma unroll
            for (int hh = 0; hh < 2; hh++) {
                if (turn > 0) mbar_wait(bar_zst + 8 * hh, (turn - 1) & 1);
#pragma unroll
                for (int i = 0; i < 8; i++)
                    stmatrix_x4(base + tile_off(8 * hh + (lane & 7), 4 * i + (lane >> 3)),
                                pack_bf16(o[16 * i + 2 * hh], o[16 * i + 2 * hh + 1]), pack_bf16(o[16 * i + 4 + 2 * hh], o[16 * i + 5 + 2 * hh]),
                                pack_bf16(o[16 * i + 8 + 2 * hh], o[16 * i + 9 + 2 * hh]), pack_bf16(o[16 * i + 12 + 2 * hh], o[16 * i + 13 + 2 * hh]));
                fence_async_smem();
                __syncwarp();
                if (wdst) {
                    if (lane < 4)
                        asm volatile("cp.async.bulk.global.shared::cta.bulk_group [%0], [%1], 1024;\n"
                                     ::"l"(wdst + ((turn & 1) ? hh * 4096 + lane * 1024 : hh * 1024 + lane * QB_BYTES)), "r"(base + hh * 4096 + lane * 1024) : "memory");
                    asm volatile("cp.async.bulk.commit_group;\n" ::: "memory");
                } else {
                    asm volatile("{\n.reg .pred p;\nsetp.eq.s32 p, %3, 0;\n"
                                 "@p cp.reduce.async.bulk.tensor.4d.global.shared::cta.add.tile.bulk_group [%0, {0, 0, 0, %1}], [%2];\n"
                                 "cp.async.bulk.commit_group;\n}\n"
                                 ::"l"(&P.tm_out), "r"((row0 >> 3) + hh), "r"(base + hh * 4096), "r"(lane) : "memory");
                }
            }
            asm volatile("cp.async.bulk.wait_group.read 1;\n" ::: "memory");
            warp_arrive(bar_zst - 8 * wg);
        };
        auto emit_done = [&](bool pending) {
            asm volatile("cp.async.bulk.wait_group.read 0;\n" ::: "memory");
            __syncwarp();
            asm volatile("{\n.reg .pred p;\nsetp.eq.s32 p, %1, 0;\n@p mbarrier.arrive.shared::cta.b64 _, [%0];\n}\n"
                         ::"r"(bar_zst + 8), "r"(pending ? lane : 1) : "memory");
        };
        if (!(rank | wg)) { release(0); release(1); release(2); release(3); }
        bar_sync(BAR_BF, 256);
        warp_arrive(bar_qfree);
        const int nf = rank ? 8 : 0;
        const int nz = nf + 26 + rank;
        const int itz = 4 + SC_NKV + SC_NW;
        bool pend = false;
#pragma unroll 1
        for (int k = wg; k < nz; k += 2) {
            const int iz = itz + (k < nf ? 0 : nf >> 1);
            mbar_wait(qbar, qphase); qphase ^= 1;
#pragma unroll 1
            for (int c = 0; c < 4; c++) {
                mbar_wait(bar_full + 8 * ((iz + c) & 3), ((iz + c) >> 2) & 1);
                const uint64_t wb = mkaddr(dk0 + ((iz + c) & 3) * (KV_BYTES >> 4), dhi), ab = mkaddr(dq0 + c * 64, dhi);
                wg_fence();
                wgmma_ss_n256_tb_pred(o, ab, wb, c);
#pragma unroll
                for (int kk = 1; kk < 4; kk++) wgmma_ss_n256_tb(o, ab + kk * 2, wb + kk * 512);
                wg_commit();
                emit_done(pend);
                pend = false;
            }
            wg_wait<0>();
            fence_regs(o);
            warp_arrive(bar_qfree);
            const int fb = ((k >> 1) + 3) & 3;
            if (k < nf) {
                float2* r255 = (float2*)H.s->r255 + wg * 128 + q;
                if (k < 2) {
                    if (t >= 124) {
#pragma unroll
                        for (int i = 0; i < 32; i++) r255[4 * i] = make_float2(o[4 * i + 2], o[4 * i + 3]);
                    }
                    bar_sync(BAR_WG0 + wg, 128);
                }
#pragma unroll
                for (int i = 0; i < 32; i++) {
                    const float2 v = __ldcg(r255 + 4 * i);
                    o[4 * i] -= v.x; o[4 * i + 1] -= v.y; o[4 * i + 2] -= v.x; o[4 * i + 3] -= v.y;
                }
            }
            int ln = lane;
            asm volatile("" : "+r"(ln));
            emit(sb + SM_KV + QB_BYTES + warp * KV_BYTES, ln, SC_TZB(k - nf) * 64 + warp * 16,
                 k >= nf ? nullptr : (k & 1) ? g_w + (4 + fb) * QB_BYTES + warp * 8192 : g_w + 8 * QB_BYTES + fb * 8192 + warp * 2048, k);
            pend = k + 2 < nz && (k | 1) != nf - 1;
            if (!pend) emit_done(true);
            if ((k | 1) == nf - 1) {
                asm volatile("cp.async.bulk.wait_group 0;\nfence.proxy.async.global;\nfence.acq_rel.gpu;\n" ::: "memory");
                bar_sync(BAR_BF, 256);
                if (tid == 0) red_release(&g_sync[SY_B * 32]);
                if (wg == 0) { release(0); release(1); release(2); release(3); }
            }
        }
        }
        if (wg == 0) pp_sync();
        warp_arrive(bar_end - 8 * wg);
        asm volatile("barrier.cluster.arrive.relaxed.aligned;\n" ::: "memory");
        if (P.E >= 0) return;
        asm volatile("setmaxnreg.dec.sync.aligned.u32 %0;\n" ::"n"(REG_P));
    }
    {
        if (warp != 0) {
            if (warp == 3 && SC_OWNER && SC_PAIR && elect()) {
                flag_wait_bounded(&g_sync[SY_H1 * 32], 79 * ep);
                mbar_wait_sleep(bar_pdone, 0);
                mbar_wait_sleep(bar_pdone + 8, 0);
#pragma unroll 1
                for (int u = 0; u < 16; u++) {
                    bulk_s2g(g_q + SC_QT0 * (2 * QB_BYTES) + u * 4096, sb + SM_Q + u * 4096, 4096);
                    asm volatile("cp.async.bulk.wait_group 0;\n" ::: "memory");
                }
                fence_async_global();
                st_release(&g_qflag[SC_QT0], ep);
            }
            __syncwarp();
            if (SC_TAIL) {
                bar_sync(BAR_AUX, 96);
                if (warp == 1 && elect()) red_release(&g_sync[SY_CSR * 32]);
                __syncwarp();
            }
            mbar_wait_bounded(bar_go, 0);
            if (SC_TAIL) {
                if (warp == 1 && elect()) red_add(&g_sync[SY_DONE * 32]);
                if (warp == 3 && elect()) {
                    int it = 4 + SC_NKV + SC_NW;
                    asm volatile("prefetch.tensormap [%0];\n" ::"l"(&P.tm_out) : "memory");
                    if (rank) {
#pragma unroll 1
                        for (int j = 0; j < 4; j++, it++) {
                            mbar_wait_sleep(bar_empty + 8 * (it & 3), ((it >> 2) & 1) ^ 1);
                            mbar_expect_tx(bar_full + 8 * (it & 3), QB_BYTES);
                            tma_g2s(sb + SM_KV + (it & 3) * KV_BYTES, &P.tm_w[2], 8 * j, bar_full + 8 * (it & 3));
                        }
#pragma unroll 1
                        for (int k = 0; k < 8; k++) {
                            mbar_wait_sleep(bar_qfree + 8 * (k & 1), ((k >> 1) ^ (k & 1) ^ 1) & 1);
                            mbar_expect_tx(bar_q + 8 * (k & 1), QB_BYTES);
#pragma unroll 1
                            for (int hf = 0; hf < 2; hf++)
                                asm volatile("cp.async.bulk.tensor.5d.shared::cluster.global.tile.mbarrier::complete_tx::bytes [%0], [%1, {0, 0, %2, 0, 0}], [%3];\n"
                                             ::"r"(sb + SM_Q + (k & 1) * QB_BYTES + hf * 16384), "l"(&P.tm_w[k & 1]),
                                             "r"(8 * (((k >> 1) + 3) & 3) + 4 * hf), "r"(bar_q + 8 * (k & 1)) : "memory");
                        }
                        flag_wait_bounded(&g_sync[SY_B * 32], ep);
                        fence_async_global();
                    }
#pragma unroll 1
                    for (int j = 0; j < 4; j++, it++) {
                        mbar_wait_sleep(bar_empty + 8 * (it & 3), ((it >> 2) & 1) ^ 1);
                        mbar_expect_tx(bar_full + 8 * (it & 3), QB_BYTES);
                        bulk_g2s(sb + SM_KV + (it & 3) * KV_BYTES, g_w + (4 + j) * QB_BYTES, QB_BYTES, bar_full + 8 * (it & 3));
                    }
#pragma unroll 1
                    for (int k = 0; k < 26 + rank; k++) {
                        if (k == 0 || k == ((GF0 + 1) * NAUX - 16) / 128) { flag_wait_bounded(&g_sync[(k ? SY_AUX1 : SY_AUX0) * 32], NAUX * ep); fence_async_global(); }
                        mbar_wait_sleep(bar_qfree + 8 * (k & 1), ((k >> 1) ^ (k & 1) ^ 1) & 1);
                        mbar_expect_tx(bar_q + 8 * (k & 1), QB_BYTES);
                        bulk_g2s(sb + SM_Q + (k & 1) * QB_BYTES, g_agg + SC_TZB(k) * QB_BYTES, QB_BYTES, bar_q + 8 * (k & 1));
                    }
                }
            } else {
            const int par = ep & 1;
            if (blockIdx.x == 0 && t == 32) g_ovf_n[par ^ 1] = 0;
            if (blockIdx.x == 0 && warp == 1) *(uint4*)(g_hz + (lane >> 3) * 1024 + (lane & 7) * 16) = make_uint4(KV_OFF2, KV_OFF2, KV_OFF2, KV_OFF2);
            const uint32_t wlo = (uint32_t)(uintptr_t)H.s, whi = (uint32_t)((uintptr_t)H.s >> 32);
            const uint32_t blo = wlo + (uint32_t)offsetof(Scratch, bucket);
            {
                const int* pd = P.dst + blockIdx.x * 96 + (t - 32);
                const int* ps = P.src + blockIdx.x * 96 + (t - 32);
#pragma unroll 1
                for (int e = P.E - (blockIdx.x * 96 + (t - 32)); e > 0; e -= CSRU * NAUX * 32, pd += CSRU * NAUX * 32, ps += CSRU * NAUX * 32) {
                    int d[CSRU], sr[CSRU], sl[CSRU];
#pragma unroll
                    for (int i = 0; i < CSRU; i++) {
                        d[i] = e > i * NAUX * 32 ? __ldg(pd + i * NAUX * 32) : NN;
                        sr[i] = e > i * NAUX * 32 ? __ldg(ps + i * NAUX * 32) : 0;
                    }
#pragma unroll
                    for (int i = 0; i < CSRU; i++) {
                        sl[i] = 0;
                        asm volatile("{\n.reg .pred p;\nsetp.lt.s32 p, %2, %3;\n@p atom.relaxed.gpu.global.add.s32 %0, [%1], 1;\n}\n"
                                     : "+r"(sl[i]) : "l"(mkaddr(wlo + (uint32_t)offsetof(Scratch, cnt) + d[i] * 4, whi)), "r"(d[i]), "n"(NN) : "memory");
                    }
                    uint32_t ov = 0;
#pragma unroll
                    for (int i = 0; i < CSRU; i++) {
                        asm volatile("{\n.reg .pred p;\nsetp.lt.s32 p, %3, %4;\n@p st.global.s32 [%1], %2;\n@!p or.b32 %0, %0, %5;\n}\n"
                                     : "+r"(ov) : "l"(mkaddr(blo + (d[i] * CAP + sl[i]) * 4, whi)), "r"(sr[i]), "r"(sl[i]), "n"(CAP), "r"(1 << i) : "memory");
                    }
#pragma unroll 1
                    for (; ov; ov &= ov - 1) {
                        const int i = (__ffs(ov) - 1) * (NAUX * 32);
                        int at;
                        asm volatile("atom.relaxed.gpu.global.add.s32 %0, [%1], 1;\n" : "=r"(at) : "l"(&g_ovf_n[par]) : "memory");
                        g_ovf[at] = make_int2(__ldg(pd + i), __ldg(ps + i));
                    }
                }
            }
            bar_sync(BAR_AUX, 96);
            if (warp == 1 && elect()) { red_release(&g_sync[SY_CSR * 32]); }
            __syncwarp();
            {
                const int r0 = blockIdx.x * 3 + warp - 1;
                const uint4* xp = (const uint4*)(H.x + r0 * 256) + lane;
                uint4* op = (uint4*)(P.out + r0 * 256) + lane;
#pragma unroll 1
                for (int r = r0; r < NN; r += CPYU * NAUX, xp += CPYU * NAUX * 32, op += CPYU * NAUX * 32) {
                    uint4 v[CPYU];
#pragma unroll
                    for (int i = 0; i < CPYU; i++) if (r + i * NAUX < NN) v[i] = ldg_pinned(xp + i * NAUX * 32);
#pragma unroll
                    for (int i = 0; i < CPYU; i++) if (r + i * NAUX < NN) op[i * NAUX * 32] = v[i];
                }
            }
            if (const int un = (3 - warp) * (NAUX / 3) + (NAUX / 3 - 1) - blockIdx.x; un < 208) {
                flag_wait_bounded(&g_sync[SY_PART * 32], 52 * ep);
                uint8_t* pp = g_part + (un >> 3) * (4 * PART_BYTES);
                float* ml = (float*)(pp + QB_BYTES) + (un & 7) * 32;
                const float4 sa = __ldcg((const float4*)ml + g), sc = __ldcg((const float4*)ml + g + 2 * PART_BYTES / 16);
                const float n0 = fmaxf(sa.x, sc.x), n1 = fmaxf(sa.z, sc.z);
                const uint32_t a0 = pack_bf16(ex2(sa.x - n0), ex2(sa.x - n0)), a1 = pack_bf16(ex2(sa.z - n1), ex2(sa.z - n1));
                const uint32_t b0 = pack_bf16(ex2(sc.x - n0), ex2(sc.x - n0)), b1 = pack_bf16(ex2(sc.z - n1), ex2(sc.z - n1));
                __syncwarp();
                if (q == 0) ((float4*)ml)[g] = make_float4(n0, sa.y * bf_hi(a0) + sc.y * bf_hi(b0), n1, sa.w * bf_hi(a1) + sc.w * bf_hi(b1));
                uint4* d = (uint4*)(pp + (un & 4) * 256 + (un & 7) * 8192) + lane;
#pragma unroll 1
                for (int i = 0; i < 4; i++, d += 128) {
                    uint4 u[4], v[4];
#pragma unroll
                    for (int j = 0; j < 4; j++) { u[j] = __ldcg(d + j * 32); v[j] = __ldcg(d + j * 32 + 2 * PART_BYTES / 16); }
#pragma unroll
                    for (int j = 0; j < 4; j++)
                        d[j * 32] = make_uint4(hfma2(v[j].x, b0, hmul2(u[j].x, a0)), hfma2(v[j].y, b1, hmul2(u[j].y, a1)),
                                               hfma2(v[j].z, b0, hmul2(u[j].z, a0)), hfma2(v[j].w, b1, hmul2(u[j].w, a1)));
                }
            }
            flag_wait_bounded(&g_sync[SY_CSR * 32], NCTA * ep);
            if (warp == 2 && blockIdx.x < 129) {
                uint4* z = blockIdx.x < 128 ? (uint4*)(g_w + blockIdx.x * 1024) + lane : (uint4*)&g_sync[SY_DONE * 32 + 4];
                z[0] = make_uint4(0, 0, 0, 0);
                if (blockIdx.x < 128) z[32] = make_uint4(0, 0, 0, 0);
            }
            {
                const uint32_t lc = (lane >> 3) * 1024 + (lane & 7) * 16;
                const uint32_t alo = wlo ^ lc;
                const int node0 = blockIdx.x * 3 + warp - 17;
                auto node = [&](int i) { const int nd = node0 + i * NAUX; return (int)min((unsigned)nd, (unsigned)(nd + NN)); };
                const int num = (NN - 17 - node0) / NAUX + 1;
                uint32_t mine = 0;
                if (lane < num) {
                    mine = min(__ldcg(&g_cnt[node(lane)]), CAP + 1) | (uint32_t)__ldg((const unsigned short*)P.deg_inv + node(lane)) << 16;
                    g_cnt[node(lane)] = 0;
                }
                auto row = [&](int off) {
                    uint4 v;
                    asm volatile("ld.global.v4.u32 {%0, %1, %2, %3}, [%4];\n"
                                 : "=r"(v.x), "=r"(v.y), "=r"(v.z), "=r"(v.w) : "l"(mkaddr(alo ^ off, whi)));
                    return v;
                };
                auto ents = [&](int i) {
                    int e;
                    asm volatile("ld.global.cg.s32 %0, [%1];\n" : "=r"(e) : "l"(mkaddr(blo + (min(node(i), NN - 1) * CAP + lane) * 4, whi)));
                    return e;
                };
                auto store = [&](int i, const float (&a)[8]) {
                    const float di = bf_hi(__shfl_sync(~0u, mine, i)) * (1.f / KV_SCALE);
                    const int nd = node(i);
                    *(uint4*)(g_agg + (uint32_t)(((nd >> 3) * 4096 + (nd & 7) * 144) ^ lc)) =
                        make_uint4(pack_bf16(a[0] * di, a[1] * di), pack_bf16(a[2] * di, a[3] * di), pack_bf16(a[4] * di, a[5] * di), pack_bf16(a[6] * di, a[7] * di));
                };
#pragma unroll 1
                for (uint32_t big = __ballot_sync(~0u, (mine & 0xFFFF) > CAP); big; big &= big - 1) {
                    const int i = __ffs(big) - 1, no = __ldcg(&g_ovf_n[par]);
                    float a[8] = {};
#pragma unroll 1
                    for (int k = -32; k < no; k += 32) {
                        const int2 pr = k < 0 ? make_int2(node(i), ents(i)) : k + lane < no ? __ldcg(&g_ovf[k + lane]) : make_int2(-1, 0);
#pragma unroll 1
                        for (uint32_t mk = __ballot_sync(~0u, pr.x == node(i)); mk; mk &= mk - 1) {
                            const uint4 v = row(row_off(__shfl_sync(~0u, pr.y, __ffs(mk) - 1)));
                            a[0] += f16_lo(v.x) - KV_OFF; a[1] += f16_hi(v.x) - KV_OFF; a[2] += f16_lo(v.y) - KV_OFF; a[3] += f16_hi(v.y) - KV_OFF;
                            a[4] += f16_lo(v.z) - KV_OFF; a[5] += f16_hi(v.z) - KV_OFF; a[6] += f16_lo(v.w) - KV_OFF; a[7] += f16_hi(v.w) - KV_OFF;
                        }
                    }
                    store(i, a);
                }
                auto add4 = [&](const uint4& a, const uint4& b) { return make_uint4(hadd2_f16(a.x, b.x), hadd2_f16(a.y, b.y), hadd2_f16(a.z, b.z), hadd2_f16(a.w, b.w)); };
                int ni = -1, left = 0, pos = 0, ec = 0, en = ents(0);
                uint4 acc = make_uint4(0, 0, 0, 0);
                auto step = [&](uint4 (&v)[4], int& tag) {
                    if (left <= 0) {
                        ni++;
                        left = __shfl_sync(~0u, mine, ni) & 0xFFFF;
                        if (left > CAP) left = 0;
                        ec = lane < left ? row_off(en) : 0;
                        en = ents(ni + 1);
                        pos = 0;
                    }
                    int of[4];
#pragma unroll
                    for (int j = 0; j < 4; j++) asm volatile("shfl.sync.idx.b32 %0, %1, %2, 31, -1;\n" : "=r"(of[j]) : "r"(ec), "r"(pos + j));
                    acc = add4(acc, add4(add4(add4(v[0], v[1]), make_uint4(KV_NEG4, KV_NEG4, KV_NEG4, KV_NEG4)), add4(v[2], v[3])));
                    asm volatile("" : "+r"(acc.x), "+r"(acc.y), "+r"(acc.z), "+r"(acc.w));
                    asm volatile("{\n.reg .pred p;\nsetp.lt.s32 p, %0, 0;\nL:\n@p pmevent 0;\n@p bra L;\n}\n" ::"r"(ni) : "memory");
#pragma unroll
                    for (int j = 0; j < 4; j++) v[j] = row(of[j]);
                    pos += 4; left -= 4;
                    const int i = tag;
                    tag = left <= 0 ? ni : -1;
                    if (i >= 0) {
                        const float a[8] = {f16_lo(acc.x), f16_hi(acc.x), f16_lo(acc.y), f16_hi(acc.y), f16_lo(acc.z), f16_hi(acc.z), f16_lo(acc.w), f16_hi(acc.w)};
                        if ((__shfl_sync(~0u, mine, i) & 0xFFFF) <= CAP) store(i, a);
                        acc = make_uint4(0, 0, 0, 0);
                        if (i == GF0 || i == 8) {
                            __syncwarp();
                            if (elect()) red_release(&g_sync[(i == 8 ? SY_AUX1 : SY_AUX0) * 32]);
                            __syncwarp();
                        }
                    }
                    return i == num - 1;
                };
                uint4 va[4], vb[4];
#pragma unroll
                for (int j = 0; j < 4; j++) va[j] = vb[j] = make_uint4(KV_OFF2, KV_OFF2, KV_OFF2, KV_OFF2);
                int ta = -1, tb = -1;
#pragma unroll 1
                while (!step(va, ta) && !step(vb, tb)) {}
            }
            bar_sync(BAR_AUX, 96);
            if (warp == 1 && elect()) {
                red_release(&g_sync[SY_AUX * 32]);
                red_add(&g_sync[SY_DONE * 32]);
            }
            }
        }
        __syncwarp();
        asm volatile("barrier.cluster.arrive.relaxed.aligned;\n" ::: "memory");
        if (warp == 1) mbar_wait_bounded(bar_end, 0);
        else if (elect()) mbar_arrive(bar_end);
        __syncwarp();
        asm volatile("barrier.cluster.wait.acquire.aligned;\n" ::: "memory");
    }
}

}

extern "C" void kernel_launch(void* const* d_in, const int* in_sizes, int n_in, void* d_out, int out_size) {
    Hot H;
    Params P;
    H.x = (const __nv_bfloat16*)d_in[0];
    P.src = (const int*)d_in[1];
    P.dst = (const int*)d_in[2];
    P.deg_inv = (const __nv_bfloat16*)d_in[3];
    H.wq = (const __nv_bfloat16*)d_in[5];
    H.wk = (const __nv_bfloat16*)d_in[6];
    P.out = (__nv_bfloat16*)d_out;
    typedef CUresult (*EncodeFn)(CUtensorMap*, CUtensorMapDataType, cuuint32_t, void*, const cuuint64_t*, const cuuint64_t*, const cuuint32_t*,
                                 const cuuint32_t*, CUtensorMapInterleave, CUtensorMapSwizzle, CUtensorMapL2promotion, CUtensorMapFloatOOBfill);
    void* fn = nullptr;
    cudaDriverEntryPointQueryResult qr;
    cudaGetDriverEntryPoint("cuTensorMapEncodeTiled", &fn, cudaEnableDefault, &qr);
    auto encode = [&](CUtensorMap* tm, const void* ptr, int rows, int box_rows, int box_cb = 4) {
        const cuuint64_t dims[4] = {64, 8, 4, (cuuint64_t)rows / 8};
        const cuuint64_t strides[3] = {512, 128, 4096};
        const cuuint32_t box[4] = {64, 8, (cuuint32_t)box_cb, (cuuint32_t)box_rows / 8}, es[4] = {1, 1, 1, 1};
        ((EncodeFn)fn)(tm, CU_TENSOR_MAP_DATA_TYPE_BFLOAT16, 4, (void*)ptr, dims, strides, box, es, CU_TENSOR_MAP_INTERLEAVE_NONE,
                       CU_TENSOR_MAP_SWIZZLE_128B, CU_TENSOR_MAP_L2_PROMOTION_NONE, CU_TENSOR_MAP_FLOAT_OOB_FILL_NONE);
    };
    encode(&P.tm_out, d_out, NN, 8);
    encode(&P.tm_outc, d_out, NN, 16, 1);
    for (int i = 0; i < 2; i++) {
        const cuuint64_t dims[5] = {64, 2, 32, 4, 4};
        const cuuint64_t strides[4] = {512, 4096, 128, 1024};
        const cuuint32_t box[5] = {64, 2, 4, 4, 4}, es[5] = {1, 1, 1, 1, 1};
        ((EncodeFn)fn)(&P.tm_w[i], CU_TENSOR_MAP_DATA_TYPE_BFLOAT16, 5, d_in[i ? 4 : 7], dims, strides, box, es, CU_TENSOR_MAP_INTERLEAVE_NONE,
                       CU_TENSOR_MAP_SWIZZLE_128B, CU_TENSOR_MAP_L2_PROMOTION_NONE, CU_TENSOR_MAP_FLOAT_OOB_FILL_NONE);
    }
    encode(&P.tm_w[2], d_in[8], 256, 64);
    void* raw = nullptr;
    cudaGetSymbolAddress(&raw, g_raw);
    H.s = (Scratch*)(((uintptr_t)raw + ((8 << 20) - 1)) & ~(uintptr_t)((8 << 20) - 1));
    P.dhi = 0x40000100u;
    P.E = in_sizes[1] < MAXE ? in_sizes[1] : MAXE;
    cudaFuncSetAttribute(k_main, cudaFuncAttributeMaxDynamicSharedMemorySize, SM_TOTAL);
    k_main<<<NCTA, 384, SM_TOTAL>>>(H, P);
}
```

```cpp
#include <cuda_runtime.h>
#include <cuda.h>
#include <cuda_bf16.h>
#include <stdint.h>
#include <stddef.h>

namespace {

constexpr int NN = 10000;
constexpr int BN = 80;
constexpr int NKV = NN / BN;
constexpr int NQB = 158;
constexpr int NCTA = 132;
constexpr int NAUX = 3 * (NCTA - 2);
constexpr int STAGES = 4;
constexpr int KV_BYTES = BN * 512;
constexpr int QB_BYTES = 64 * 512;
constexpr int PART_BYTES = QB_BYTES + 512;
constexpr int CAP = 64;
constexpr int MAXE = 160000;

#define QRND(v) (((v) + 0x00040004u) & 0xFFF8FFF8u)
#define GO0 30
#define GF0 2
#define CSRU 3
#define CPYU 9
#define REFUP 2.f
#define SND0 10
#define CUT2 2
#define REG_C 224
#define REG_P 56

enum { SY_PART = 4, SY_H1 = 5, SY_CSR = 6, SY_AUX = 7, SY_DONE = 8, SY_AUX0 = 9, SY_B = 10, SY_AUX1 = 11, SY_H0 = 12 };
struct Scratch {
    uint8_t hz[4096 + NN * 512];
    uint8_t w[12 * QB_BYTES];
    int sync[25 * 32];
    int qflag[96];
    int ovf_n[32];
    float r255[512];
    int cnt[NN + 16];
    int bucket[(NN + 1) * 32];
    int2 ovf[MAXE];
    uint8_t q[NQB * QB_BYTES];
    uint8_t agg[NQB * QB_BYTES];
    uint8_t part[52 * 2 * PART_BYTES];
};
static_assert(offsetof(Scratch, ovf) <= (8 << 20), "window");
static_assert(offsetof(Scratch, qflag) == offsetof(Scratch, sync) + 25 * 128, "flags");
static_assert(offsetof(Scratch, w) % 1024 == 0 && offsetof(Scratch, sync) % 128 == 0 &&
              offsetof(Scratch, bucket) % 128 == 0 && offsetof(Scratch, q) % 128 == 0, "alignment");
__device__ uint8_t g_raw[(8 << 20) + sizeof(Scratch)];
#define g_hz (H.s->hz)
#define g_w (H.s->w)
#define g_sync (H.s->sync)
#define g_qflag (H.s->qflag)
#define g_ovf_n (H.s->ovf_n)
#define g_cnt (H.s->cnt)
#define g_bucket (H.s->bucket)
#define g_ovf (H.s->ovf)
#define g_q (H.s->q)
#define g_agg (H.s->agg)
#define g_part (H.s->part)

__device__ __forceinline__ void wgmma_ss_n80(float (&d)[40], uint64_t da, uint64_t db) {
    asm volatile("wgmma.mma_async.sync.aligned.m64n80k16.f32.f16.f16 {"
        "%0, %1, %2, %3, %4, %5, %6, %7, %8, %9, %10, %11, %12, %13, %14, %15, %16, %17, %18, %19, %20, %21, %22, %23, %24, %25, %26, %27, %28, %29, %30, %31, "
        "%32, %33, %34, %35, %36, %37, %38, %39}, %40, %41, 1, 1, 1, 0, 0;\n"
        : "+f"(d[0]), "+f"(d[1]), "+f"(d[2]), "+f"(d[3]), "+f"(d[4]), "+f"(d[5]), "+f"(d[6]), "+f"(d[7]),
          "+f"(d[8]), "+f"(d[9]), "+f"(d[10]), "+f"(d[11]), "+f"(d[12]), "+f"(d[13]), "+f"(d[14]), "+f"(d[15]),
          "+f"(d[16]), "+f"(d[17]), "+f"(d[18]), "+f"(d[19]), "+f"(d[20]), "+f"(d[21]), "+f"(d[22]), "+f"(d[23]),
          "+f"(d[24]), "+f"(d[25]), "+f"(d[26]), "+f"(d[27]), "+f"(d[28]), "+f"(d[29]), "+f"(d[30]), "+f"(d[31]),
          "+f"(d[32]), "+f"(d[33]), "+f"(d[34]), "+f"(d[35]), "+f"(d[36]), "+f"(d[37]), "+f"(d[38]), "+f"(d[39])
        : "l"(da), "l"(db));
}
__device__ __forceinline__ void wgmma_ss_n80_init(float (&d)[40], uint64_t da, uint64_t db) {
    asm volatile("wgmma.mma_async.sync.aligned.m64n80k16.f32.f16.f16 {"
        "%0, %1, %2, %3, %4, %5, %6, %7, %8, %9, %10, %11, %12, %13, %14, %15, %16, %17, %18, %19, %20, %21, %22, %23, %24, %25, %26, %27, %28, %29, %30, %31, "
        "%32, %33, %34, %35, %36, %37, %38, %39}, %40, %41, 0, 1, 1, 0, 0;\n"
        : "=f"(d[0]), "=f"(d[1]), "=f"(d[2]), "=f"(d[3]), "=f"(d[4]), "=f"(d[5]), "=f"(d[6]), "=f"(d[7]),
          "=f"(d[8]), "=f"(d[9]), "=f"(d[10]), "=f"(d[11]), "=f"(d[12]), "=f"(d[13]), "=f"(d[14]), "=f"(d[15]),
          "=f"(d[16]), "=f"(d[17]), "=f"(d[18]), "=f"(d[19]), "=f"(d[20]), "=f"(d[21]), "=f"(d[22]), "=f"(d[23]),
          "=f"(d[24]), "=f"(d[25]), "=f"(d[26]), "=f"(d[27]), "=f"(d[28]), "=f"(d[29]), "=f"(d[30]), "=f"(d[31]),
          "=f"(d[32]), "=f"(d[33]), "=f"(d[34]), "=f"(d[35]), "=f"(d[36]), "=f"(d[37]), "=f"(d[38]), "=f"(d[39])
        : "l"(da), "l"(db));
}
__device__ __forceinline__ void wgmma_rs_n256_tb(float (&d)[128], uint32_t a0, uint32_t a1, uint32_t a2, uint32_t a3, uint64_t db) {
    asm volatile("wgmma.mma_async.sync.aligned.m64n256k16.f32.f16.f16 {"
        "%0, %1, %2, %3, %4, %5, %6, %7, %8, %9, %10, %11, %12, %13, %14, %15, %16, %17, %18, %19, %20, %21, %22, %23, %24, %25, %26, %27, %28, %29, %30, %31, "
        "%32, %33, %34, %35, %36, %37, %38, %39, %40, %41, %42, %43, %44, %45, %46, %47, %48, %49, %50, %51, %52, %53, %54, %55, %56, %57, %58, %59, %60, %61, %62, %63, "
        "%64, %65, %66, %67, %68, %69, %70, %71, %72, %73, %74, %75, %76, %77, %78, %79, %80, %81, %82, %83, %84, %85, %86, %87, %88, %89, %90, %91, %92, %93, %94, %95, "
        "%96, %97, %98, %99, %100, %101, %102, %103, %104, %105, %106, %107, %108, %109, %110, %111, %112, %113, %114, %115, %116, %117, %118, %119, %120, %121, %122, %123, %124, %125, %126, %127}, {%128, %129, %130, %131}, %132, 1, 1, 1, 1;\n"
        : "+f"(d[0]), "+f"(d[1]), "+f"(d[2]), "+f"(d[3]), "+f"(d[4]), "+f"(d[5]), "+f"(d[6]), "+f"(d[7]),
          "+f"(d[8]), "+f"(d[9]), "+f"(d[10]), "+f"(d[11]), "+f"(d[12]), "+f"(d[13]), "+f"(d[14]), "+f"(d[15]),
          "+f"(d[16]), "+f"(d[17]), "+f"(d[18]), "+f"(d[19]), "+f"(d[20]), "+f"(d[21]), "+f"(d[22]), "+f"(d[23]),
          "+f"(d[24]), "+f"(d[25]), "+f"(d[26]), "+f"(d[27]), "+f"(d[28]), "+f"(d[29]), "+f"(d[30]), "+f"(d[31]),
          "+f"(d[32]), "+f"(d[33]), "+f"(d[34]), "+f"(d[35]), "+f"(d[36]), "+f"(d[37]), "+f"(d[38]), "+f"(d[39]),
          "+f"(d[40]), "+f"(d[41]), "+f"(d[42]), "+f"(d[43]), "+f"(d[44]), "+f"(d[45]), "+f"(d[46]), "+f"(d[47]),
          "+f"(d[48]), "+f"(d[49]), "+f"(d[50]), "+f"(d[51]), "+f"(d[52]), "+f"(d[53]), "+f"(d[54]), "+f"(d[55]),
          "+f"(d[56]), "+f"(d[57]), "+f"(d[58]), "+f"(d[59]), "+f"(d[60]), "+f"(d[61]), "+f"(d[62]), "+f"(d[63]),
          "+f"(d[64]), "+f"(d[65]), "+f"(d[66]), "+f"(d[67]), "+f"(d[68]), "+f"(d[69]), "+f"(d[70]), "+f"(d[71]),
          "+f"(d[72]), "+f"(d[73]), "+f"(d[74]), "+f"(d[75]), "+f"(d[76]), "+f"(d[77]), "+f"(d[78]), "+f"(d[79]),
          "+f"(d[80]), "+f"(d[81]), "+f"(d[82]), "+f"(d[83]), "+f"(d[84]), "+f"(d[85]), "+f"(d[86]), "+f"(d[87]),
          "+f"(d[88]), "+f"(d[89]), "+f"(d[90]), "+f"(d[91]), "+f"(d[92]), "+f"(d[93]), "+f"(d[94]), "+f"(d[95]),
          "+f"(d[96]), "+f"(d[97]), "+f"(d[98]), "+f"(d[99]), "+f"(d[100]), "+f"(d[101]), "+f"(d[102]), "+f"(d[103]),
          "+f"(d[104]), "+f"(d[105]), "+f"(d[106]), "+f"(d[107]), "+f"(d[108]), "+f"(d[109]), "+f"(d[110]), "+f"(d[111]),
          "+f"(d[112]), "+f"(d[113]), "+f"(d[114]), "+f"(d[115]), "+f"(d[116]), "+f"(d[117]), "+f"(d[118]), "+f"(d[119]),
          "+f"(d[120]), "+f"(d[121]), "+f"(d[122]), "+f"(d[123]), "+f"(d[124]), "+f"(d[125]), "+f"(d[126]), "+f"(d[127])
        : "r"(a0), "r"(a1), "r"(a2), "r"(a3), "l"(db));
}
__device__ __forceinline__ void wgmma_rs_n256_tb_init(float (&d)[128], uint32_t a0, uint32_t a1, uint32_t a2, uint32_t a3, uint64_t db) {
    asm volatile("wgmma.mma_async.sync.aligned.m64n256k16.f32.f16.f16 {"
        "%0, %1, %2, %3, %4, %5, %6, %7, %8, %9, %10, %11, %12, %13, %14, %15, %16, %17, %18, %19, %20, %21, %22, %23, %24, %25, %26, %27, %28, %29, %30, %31, "
        "%32, %33, %34, %35, %36, %37, %38, %39, %40, %41, %42, %43, %44, %45, %46, %47, %48, %49, %50, %51, %52, %53, %54, %55, %56, %57, %58, %59, %60, %61, %62, %63, "
        "%64, %65, %66, %67, %68, %69, %70, %71, %72, %73, %74, %75, %76, %77, %78, %79, %80, %81, %82, %83, %84, %85, %86, %87, %88, %89, %90, %91, %92, %93, %94, %95, "
        "%96, %97, %98, %99, %100, %101, %102, %103, %104, %105, %106, %107, %108, %109, %110, %111, %112, %113, %114, %115, %116, %117, %118, %119, %120, %121, %122, %123, %124, %125, %126, %127}, {%128, %129, %130, %131}, %132, 0, 1, 1, 1;\n"
        : "=f"(d[0]), "=f"(d[1]), "=f"(d[2]), "=f"(d[3]), "=f"(d[4]), "=f"(d[5]), "=f"(d[6]), "=f"(d[7]),
          "=f"(d[8]), "=f"(d[9]), "=f"(d[10]), "=f"(d[11]), "=f"(d[12]), "=f"(d[13]), "=f"(d[14]), "=f"(d[15]),
          "=f"(d[16]), "=f"(d[17]), "=f"(d[18]), "=f"(d[19]), "=f"(d[20]), "=f"(d[21]), "=f"(d[22]), "=f"(d[23]),
          "=f"(d[24]), "=f"(d[25]), "=f"(d[26]), "=f"(d[27]), "=f"(d[28]), "=f"(d[29]), "=f"(d[30]), "=f"(d[31]),
          "=f"(d[32]), "=f"(d[33]), "=f"(d[34]), "=f"(d[35]), "=f"(d[36]), "=f"(d[37]), "=f"(d[38]), "=f"(d[39]),
          "=f"(d[40]), "=f"(d[41]), "=f"(d[42]), "=f"(d[43]), "=f"(d[44]), "=f"(d[45]), "=f"(d[46]), "=f"(d[47]),
          "=f"(d[48]), "=f"(d[49]), "=f"(d[50]), "=f"(d[51]), "=f"(d[52]), "=f"(d[53]), "=f"(d[54]), "=f"(d[55]),
          "=f"(d[56]), "=f"(d[57]), "=f"(d[58]), "=f"(d[59]), "=f"(d[60]), "=f"(d[61]), "=f"(d[62]), "=f"(d[63]),
          "=f"(d[64]), "=f"(d[65]), "=f"(d[66]), "=f"(d[67]), "=f"(d[68]), "=f"(d[69]), "=f"(d[70]), "=f"(d[71]),
          "=f"(d[72]), "=f"(d[73]), "=f"(d[74]), "=f"(d[75]), "=f"(d[76]), "=f"(d[77]), "=f"(d[78]), "=f"(d[79]),
          "=f"(d[80]), "=f"(d[81]), "=f"(d[82]), "=f"(d[83]), "=f"(d[84]), "=f"(d[85]), "=f"(d[86]), "=f"(d[87]),
          "=f"(d[88]), "=f"(d[89]), "=f"(d[90]), "=f"(d[91]), "=f"(d[92]), "=f"(d[93]), "=f"(d[94]), "=f"(d[95]),
          "=f"(d[96]), "=f"(d[97]), "=f"(d[98]), "=f"(d[99]), "=f"(d[100]), "=f"(d[101]), "=f"(d[102]), "=f"(d[103]),
          "=f"(d[104]), "=f"(d[105]), "=f"(d[106]), "=f"(d[107]), "=f"(d[108]), "=f"(d[109]), "=f"(d[110]), "=f"(d[111]),
          "=f"(d[112]), "=f"(d[113]), "=f"(d[114]), "=f"(d[115]), "=f"(d[116]), "=f"(d[117]), "=f"(d[118]), "=f"(d[119]),
          "=f"(d[120]), "=f"(d[121]), "=f"(d[122]), "=f"(d[123]), "=f"(d[124]), "=f"(d[125]), "=f"(d[126]), "=f"(d[127])
        : "r"(a0), "r"(a1), "r"(a2), "r"(a3), "l"(db));
}
__device__ __forceinline__ void wgmma_rs_n256_tb_pred(float (&d)[128], uint32_t a0, uint32_t a1, uint32_t a2, uint32_t a3, uint64_t db, int acc) {
    asm volatile("{\n.reg .pred p;\nsetp.ne.s32 p, %133, 0;\nwgmma.mma_async.sync.aligned.m64n256k16.f32.f16.f16 {"
        "%0, %1, %2, %3, %4, %5, %6, %7, %8, %9, %10, %11, %12, %13, %14, %15, %16, %17, %18, %19, %20, %21, %22, %23, %24, %25, %26, %27, %28, %29, %30, %31, "
        "%32, %33, %34, %35, %36, %37, %38, %39, %40, %41, %42, %43, %44, %45, %46, %47, %48, %49, %50, %51, %52, %53, %54, %55, %56, %57, %58, %59, %60, %61, %62, %63, "
        "%64, %65, %66, %67, %68, %69, %70, %71, %72, %73, %74, %75, %76, %77, %78, %79, %80, %81, %82, %83, %84, %85, %86, %87, %88, %89, %90, %91, %92, %93, %94, %95, "
        "%96, %97, %98, %99, %100, %101, %102, %103, %104, %105, %106, %107, %108, %109, %110, %111, %112, %113, %114, %115, %116, %117, %118, %119, %120, %121, %122, %123, %124, %125, %126, %127}, {%128, %129, %130, %131}, %132, p, 1, 1, 1;\n}\n"
        : "+f"(d[0]), "+f"(d[1]), "+f"(d[2]), "+f"(d[3]), "+f"(d[4]), "+f"(d[5]), "+f"(d[6]), "+f"(d[7]),
          "+f"(d[8]), "+f"(d[9]), "+f"(d[10]), "+f"(d[11]), "+f"(d[12]), "+f"(d[13]), "+f"(d[14]), "+f"(d[15]),
          "+f"(d[16]), "+f"(d[17]), "+f"(d[18]), "+f"(d[19]), "+f"(d[20]), "+f"(d[21]), "+f"(d[22]), "+f"(d[23]),
          "+f"(d[24]), "+f"(d[25]), "+f"(d[26]), "+f"(d[27]), "+f"(d[28]), "+f"(d[29]), "+f"(d[30]), "+f"(d[31]),
          "+f"(d[32]), "+f"(d[33]), "+f"(d[34]), "+f"(d[35]), "+f"(d[36]), "+f"(d[37]), "+f"(d[38]), "+f"(d[39]),
          "+f"(d[40]), "+f"(d[41]), "+f"(d[42]), "+f"(d[43]), "+f"(d[44]), "+f"(d[45]), "+f"(d[46]), "+f"(d[47]),
          "+f"(d[48]), "+f"(d[49]), "+f"(d[50]), "+f"(d[51]), "+f"(d[52]), "+f"(d[53]), "+f"(d[54]), "+f"(d[55]),
          "+f"(d[56]), "+f"(d[57]), "+f"(d[58]), "+f"(d[59]), "+f"(d[60]), "+f"(d[61]), "+f"(d[62]), "+f"(d[63]),
          "+f"(d[64]), "+f"(d[65]), "+f"(d[66]), "+f"(d[67]), "+f"(d[68]), "+f"(d[69]), "+f"(d[70]), "+f"(d[71]),
          "+f"(d[72]), "+f"(d[73]), "+f"(d[74]), "+f"(d[75]), "+f"(d[76]), "+f"(d[77]), "+f"(d[78]), "+f"(d[79]),
          "+f"(d[80]), "+f"(d[81]), "+f"(d[82]), "+f"(d[83]), "+f"(d[84]), "+f"(d[85]), "+f"(d[86]), "+f"(d[87]),
          "+f"(d[88]), "+f"(d[89]), "+f"(d[90]), "+f"(d[91]), "+f"(d[92]), "+f"(d[93]), "+f"(d[94]), "+f"(d[95]),
          "+f"(d[96]), "+f"(d[97]), "+f"(d[98]), "+f"(d[99]), "+f"(d[100]), "+f"(d[101]), "+f"(d[102]), "+f"(d[103]),
          "+f"(d[104]), "+f"(d[105]), "+f"(d[106]), "+f"(d[107]), "+f"(d[108]), "+f"(d[109]), "+f"(d[110]), "+f"(d[111]),
          "+f"(d[112]), "+f"(d[113]), "+f"(d[114]), "+f"(d[115]), "+f"(d[116]), "+f"(d[117]), "+f"(d[118]), "+f"(d[119]),
          "+f"(d[120]), "+f"(d[121]), "+f"(d[122]), "+f"(d[123]), "+f"(d[124]), "+f"(d[125]), "+f"(d[126]), "+f"(d[127])
        : "r"(a0), "r"(a1), "r"(a2), "r"(a3), "l"(db), "r"(acc));
}
__device__ __forceinline__ void wgmma_ss_n256_tb(float (&d)[128], uint64_t da, uint64_t db) {
    asm volatile("wgmma.mma_async.sync.aligned.m64n256k16.f32.bf16.bf16 {"
        "%0, %1, %2, %3, %4, %5, %6, %7, %8, %9, %10, %11, %12, %13, %14, %15, %16, %17, %18, %19, %20, %21, %22, %23, %24, %25, %26, %27, %28, %29, %30, %31, "
        "%32, %33, %34, %35, %36, %37, %38, %39, %40, %41, %42, %43, %44, %45, %46, %47, %48, %49, %50, %51, %52, %53, %54, %55, %56, %57, %58, %59, %60, %61, %62, %63, "
        "%64, %65, %66, %67, %68, %69, %70, %71, %72, %73, %74, %75, %76, %77, %78, %79, %80, %81, %82, %83, %84, %85, %86, %87, %88, %89, %90, %91, %92, %93, %94, %95, "
        "%96, %97, %98, %99, %100, %101, %102, %103, %104, %105, %106, %107, %108, %109, %110, %111, %112, %113, %114, %115, %116, %117, %118, %119, %120, %121, %122, %123, %124, %125, %126, %127}, %128, %129, 1, 1, 1, 0, 1;\n"
        : "+f"(d[0]), "+f"(d[1]), "+f"(d[2]), "+f"(d[3]), "+f"(d[4]), "+f"(d[5]), "+f"(d[6]), "+f"(d[7]),
          "+f"(d[8]), "+f"(d[9]), "+f"(d[10]), "+f"(d[11]), "+f"(d[12]), "+f"(d[13]), "+f"(d[14]), "+f"(d[15]),
          "+f"(d[16]), "+f"(d[17]), "+f"(d[18]), "+f"(d[19]), "+f"(d[20]), "+f"(d[21]), "+f"(d[22]), "+f"(d[23]),
          "+f"(d[24]), "+f"(d[25]), "+f"(d[26]), "+f"(d[27]), "+f"(d[28]), "+f"(d[29]), "+f"(d[30]), "+f"(d[31]),
          "+f"(d[32]), "+f"(d[33]), "+f"(d[34]), "+f"(d[35]), "+f"(d[36]), "+f"(d[37]), "+f"(d[38]), "+f"(d[39]),
          "+f"(d[40]), "+f"(d[41]), "+f"(d[42]), "+f"(d[43]), "+f"(d[44]), "+f"(d[45]), "+f"(d[46]), "+f"(d[47]),
          "+f"(d[48]), "+f"(d[49]), "+f"(d[50]), "+f"(d[51]), "+f"(d[52]), "+f"(d[53]), "+f"(d[54]), "+f"(d[55]),
          "+f"(d[56]), "+f"(d[57]), "+f"(d[58]), "+f"(d[59]), "+f"(d[60]), "+f"(d[61]), "+f"(d[62]), "+f"(d[63]),
          "+f"(d[64]), "+f"(d[65]), "+f"(d[66]), "+f"(d[67]), "+f"(d[68]), "+f"(d[69]), "+f"(d[70]), "+f"(d[71]),
          "+f"(d[72]), "+f"(d[73]), "+f"(d[74]), "+f"(d[75]), "+f"(d[76]), "+f"(d[77]), "+f"(d[78]), "+f"(d[79]),
          "+f"(d[80]), "+f"(d[81]), "+f"(d[82]), "+f"(d[83]), "+f"(d[84]), "+f"(d[85]), "+f"(d[86]), "+f"(d[87]),
          "+f"(d[88]), "+f"(d[89]), "+f"(d[90]), "+f"(d[91]), "+f"(d[92]), "+f"(d[93]), "+f"(d[94]), "+f"(d[95]),
          "+f"(d[96]), "+f"(d[97]), "+f"(d[98]), "+f"(d[99]), "+f"(d[100]), "+f"(d[101]), "+f"(d[102]), "+f"(d[103]),
          "+f"(d[104]), "+f"(d[105]), "+f"(d[106]), "+f"(d[107]), "+f"(d[108]), "+f"(d[109]), "+f"(d[110]), "+f"(d[111]),
          "+f"(d[112]), "+f"(d[113]), "+f"(d[114]), "+f"(d[115]), "+f"(d[116]), "+f"(d[117]), "+f"(d[118]), "+f"(d[119]),
          "+f"(d[120]), "+f"(d[121]), "+f"(d[122]), "+f"(d[123]), "+f"(d[124]), "+f"(d[125]), "+f"(d[126]), "+f"(d[127])
        : "l"(da), "l"(db));
}
__device__ __forceinline__ void wgmma_ss_n256_tb_init(float (&d)[128], uint64_t da, uint64_t db) {
    asm volatile("wgmma.mma_async.sync.aligned.m64n256k16.f32.bf16.bf16 {"
        "%0, %1, %2, %3, %4, %5, %6, %7, %8, %9, %10, %11, %12, %13, %14, %15, %16, %17, %18, %19, %20, %21, %22, %23, %24, %25, %26, %27, %28, %29, %30, %31, "
        "%32, %33, %34, %35, %36, %37, %38, %39, %40, %41, %42, %43, %44, %45, %46, %47, %48, %49, %50, %51, %52, %53, %54, %55, %56, %57, %58, %59, %60, %61, %62, %63, "
        "%64, %65, %66, %67, %68, %69, %70, %71, %72, %73, %74, %75, %76, %77, %78, %79, %80, %81, %82, %83, %84, %85, %86, %87, %88, %89, %90, %91, %92, %93, %94, %95, "
        "%96, %97, %98, %99, %100, %101, %102, %103, %104, %105, %106, %107, %108, %109, %110, %111, %112, %113, %114, %115, %116, %117, %118, %119, %120, %121, %122, %123, %124, %125, %126, %127}, %128, %129, 0, 1, 1, 0, 1;\n"
        : "=f"(d[0]), "=f"(d[1]), "=f"(d[2]), "=f"(d[3]), "=f"(d[4]), "=f"(d[5]), "=f"(d[6]), "=f"(d[7]),
          "=f"(d[8]), "=f"(d[9]), "=f"(d[10]), "=f"(d[11]), "=f"(d[12]), "=f"(d[13]), "=f"(d[14]), "=f"(d[15]),
          "=f"(d[16]), "=f"(d[17]), "=f"(d[18]), "=f"(d[19]), "=f"(d[20]), "=f"(d[21]), "=f"(d[22]), "=f"(d[23]),
          "=f"(d[24]), "=f"(d[25]), "=f"(d[26]), "=f"(d[27]), "=f"(d[28]), "=f"(d[29]), "=f"(d[30]), "=f"(d[31]),
          "=f"(d[32]), "=f"(d[33]), "=f"(d[34]), "=f"(d[35]), "=f"(d[36]), "=f"(d[37]), "=f"(d[38]), "=f"(d[39]),
          "=f"(d[40]), "=f"(d[41]), "=f"(d[42]), "=f"(d[43]), "=f"(d[44]), "=f"(d[45]), "=f"(d[46]), "=f"(d[47]),
          "=f"(d[48]), "=f"(d[49]), "=f"(d[50]), "=f"(d[51]), "=f"(d[52]), "=f"(d[53]), "=f"(d[54]), "=f"(d[55]),
          "=f"(d[56]), "=f"(d[57]), "=f"(d[58]), "=f"(d[59]), "=f"(d[60]), "=f"(d[61]), "=f"(d[62]), "=f"(d[63]),
          "=f"(d[64]), "=f"(d[65]), "=f"(d[66]), "=f"(d[67]), "=f"(d[68]), "=f"(d[69]), "=f"(d[70]), "=f"(d[71]),
          "=f"(d[72]), "=f"(d[73]), "=f"(d[74]), "=f"(d[75]), "=f"(d[76]), "=f"(d[77]), "=f"(d[78]), "=f"(d[79]),
          "=f"(d[80]), "=f"(d[81]), "=f"(d[82]), "=f"(d[83]), "=f"(d[84]), "=f"(d[85]), "=f"(d[86]), "=f"(d[87]),
          "=f"(d[88]), "=f"(d[89]), "=f"(d[90]), "=f"(d[91]), "=f"(d[92]), "=f"(d[93]), "=f"(d[94]), "=f"(d[95]),
          "=f"(d[96]), "=f"(d[97]), "=f"(d[98]), "=f"(d[99]), "=f"(d[100]), "=f"(d[101]), "=f"(d[102]), "=f"(d[103]),
          "=f"(d[104]), "=f"(d[105]), "=f"(d[106]), "=f"(d[107]), "=f"(d[108]), "=f"(d[109]), "=f"(d[110]), "=f"(d[111]),
          "=f"(d[112]), "=f"(d[113]), "=f"(d[114]), "=f"(d[115]), "=f"(d[116]), "=f"(d[117]), "=f"(d[118]), "=f"(d[119]),
          "=f"(d[120]), "=f"(d[121]), "=f"(d[122]), "=f"(d[123]), "=f"(d[124]), "=f"(d[125]), "=f"(d[126]), "=f"(d[127])
        : "l"(da), "l"(db));
}
__device__ __forceinline__ void wgmma_ss_n256_tb_pred(float (&d)[128], uint64_t da, uint64_t db, int acc) {
    asm volatile("{\n.reg .pred p;\nsetp.ne.s32 p, %130, 0;\nwgmma.mma_async.sync.aligned.m64n256k16.f32.bf16.bf16 {"
        "%0, %1, %2, %3, %4, %5, %6, %7, %8, %9, %10, %11, %12, %13, %14, %15, %16, %17, %18, %19, %20, %21, %22, %23, %24, %25, %26, %27, %28, %29, %30, %31, "
        "%32, %33, %34, %35, %36, %37, %38, %39, %40, %41, %42, %43, %44, %45, %46, %47, %48, %49, %50, %51, %52, %53, %54, %55, %56, %57, %58, %59, %60, %61, %62, %63, "
        "%64, %65, %66, %67, %68, %69, %70, %71, %72, %73, %74, %75, %76, %77, %78, %79, %80, %81, %82, %83, %84, %85, %86, %87, %88, %89, %90, %91, %92, %93, %94, %95, "
        "%96, %97, %98, %99, %100, %101, %102, %103, %104, %105, %106, %107, %108, %109, %110, %111, %112, %113, %114, %115, %116, %117, %118, %119, %120, %121, %122, %123, %124, %125, %126, %127}, %128, %129, p, 1, 1, 0, 1;\n}\n"
        : "+f"(d[0]), "+f"(d[1]), "+f"(d[2]), "+f"(d[3]), "+f"(d[4]), "+f"(d[5]), "+f"(d[6]), "+f"(d[7]),
          "+f"(d[8]), "+f"(d[9]), "+f"(d[10]), "+f"(d[11]), "+f"(d[12]), "+f"(d[13]), "+f"(d[14]), "+f"(d[15]),
          "+f"(d[16]), "+f"(d[17]), "+f"(d[18]), "+f"(d[19]), "+f"(d[20]), "+f"(d[21]), "+f"(d[22]), "+f"(d[23]),
          "+f"(d[24]), "+f"(d[25]), "+f"(d[26]), "+f"(d[27]), "+f"(d[28]), "+f"(d[29]), "+f"(d[30]), "+f"(d[31]),
          "+f"(d[32]), "+f"(d[33]), "+f"(d[34]), "+f"(d[35]), "+f"(d[36]), "+f"(d[37]), "+f"(d[38]), "+f"(d[39]),
          "+f"(d[40]), "+f"(d[41]), "+f"(d[42]), "+f"(d[43]), "+f"(d[44]), "+f"(d[45]), "+f"(d[46]), "+f"(d[47]),
          "+f"(d[48]), "+f"(d[49]), "+f"(d[50]), "+f"(d[51]), "+f"(d[52]), "+f"(d[53]), "+f"(d[54]), "+f"(d[55]),
          "+f"(d[56]), "+f"(d[57]), "+f"(d[58]), "+f"(d[59]), "+f"(d[60]), "+f"(d[61]), "+f"(d[62]), "+f"(d[63]),
          "+f"(d[64]), "+f"(d[65]), "+f"(d[66]), "+f"(d[67]), "+f"(d[68]), "+f"(d[69]), "+f"(d[70]), "+f"(d[71]),
          "+f"(d[72]), "+f"(d[73]), "+f"(d[74]), "+f"(d[75]), "+f"(d[76]), "+f"(d[77]), "+f"(d[78]), "+f"(d[79]),
          "+f"(d[80]), "+f"(d[81]), "+f"(d[82]), "+f"(d[83]), "+f"(d[84]), "+f"(d[85]), "+f"(d[86]), "+f"(d[87]),
          "+f"(d[88]), "+f"(d[89]), "+f"(d[90]), "+f"(d[91]), "+f"(d[92]), "+f"(d[93]), "+f"(d[94]), "+f"(d[95]),
          "+f"(d[96]), "+f"(d[97]), "+f"(d[98]), "+f"(d[99]), "+f"(d[100]), "+f"(d[101]), "+f"(d[102]), "+f"(d[103]),
          "+f"(d[104]), "+f"(d[105]), "+f"(d[106]), "+f"(d[107]), "+f"(d[108]), "+f"(d[109]), "+f"(d[110]), "+f"(d[111]),
          "+f"(d[112]), "+f"(d[113]), "+f"(d[114]), "+f"(d[115]), "+f"(d[116]), "+f"(d[117]), "+f"(d[118]), "+f"(d[119]),
          "+f"(d[120]), "+f"(d[121]), "+f"(d[122]), "+f"(d[123]), "+f"(d[124]), "+f"(d[125]), "+f"(d[126]), "+f"(d[127])
        : "l"(da), "l"(db), "r"(acc));
}
__device__ __forceinline__ void wgmma_rs_n64_tb(float (&d)[32], uint32_t a0, uint32_t a1, uint32_t a2, uint32_t a3, uint64_t db) {
    asm volatile("wgmma.mma_async.sync.aligned.m64n64k16.f32.bf16.bf16 {"
        "%0, %1, %2, %3, %4, %5, %6, %7, %8, %9, %10, %11, %12, %13, %14, %15, %16, %17, %18, %19, %20, %21, %22, %23, %24, %25, %26, %27, %28, %29, %30, %31}, {%32, %33, %34, %35}, %36, 1, 1, 1, 1;\n"
        : "+f"(d[0]), "+f"(d[1]), "+f"(d[2]), "+f"(d[3]), "+f"(d[4]), "+f"(d[5]), "+f"(d[6]), "+f"(d[7]),
          "+f"(d[8]), "+f"(d[9]), "+f"(d[10]), "+f"(d[11]), "+f"(d[12]), "+f"(d[13]), "+f"(d[14]), "+f"(d[15]),
          "+f"(d[16]), "+f"(d[17]), "+f"(d[18]), "+f"(d[19]), "+f"(d[20]), "+f"(d[21]), "+f"(d[22]), "+f"(d[23]),
          "+f"(d[24]), "+f"(d[25]), "+f"(d[26]), "+f"(d[27]), "+f"(d[28]), "+f"(d[29]), "+f"(d[30]), "+f"(d[31])
        : "r"(a0), "r"(a1), "r"(a2), "r"(a3), "l"(db));
}
__device__ __forceinline__ void wgmma_rs_n64_tb_init(float (&d)[32], uint32_t a0, uint32_t a1, uint32_t a2, uint32_t a3, uint64_t db) {
    asm volatile("wgmma.mma_async.sync.aligned.m64n64k16.f32.bf16.bf16 {"
        "%0, %1, %2, %3, %4, %5, %6, %7, %8, %9, %10, %11, %12, %13, %14, %15, %16, %17, %18, %19, %20, %21, %22, %23, %24, %25, %26, %27, %28, %29, %30, %31}, {%32, %33, %34, %35}, %36, 0, 1, 1, 1;\n"
        : "=f"(d[0]), "=f"(d[1]), "=f"(d[2]), "=f"(d[3]), "=f"(d[4]), "=f"(d[5]), "=f"(d[6]), "=f"(d[7]),
          "=f"(d[8]), "=f"(d[9]), "=f"(d[10]), "=f"(d[11]), "=f"(d[12]), "=f"(d[13]), "=f"(d[14]), "=f"(d[15]),
          "=f"(d[16]), "=f"(d[17]), "=f"(d[18]), "=f"(d[19]), "=f"(d[20]), "=f"(d[21]), "=f"(d[22]), "=f"(d[23]),
          "=f"(d[24]), "=f"(d[25]), "=f"(d[26]), "=f"(d[27]), "=f"(d[28]), "=f"(d[29]), "=f"(d[30]), "=f"(d[31])
        : "r"(a0), "r"(a1), "r"(a2), "r"(a3), "l"(db));
}

__device__ __forceinline__ void wg_fence() { asm volatile("wgmma.fence.sync.aligned;\n" ::: "memory"); }
__device__ __forceinline__ void wg_commit() { asm volatile("wgmma.commit_group.sync.aligned;\n" ::: "memory"); }
template <int N> __device__ __forceinline__ void wg_wait() { asm volatile("wgmma.wait_group.sync.aligned %0;\n" ::"n"(N) : "memory"); }
template <int N> __device__ __forceinline__ void fence_regs(float (&a)[N]) {
#pragma unroll
    for (int i = 0; i < N; i++) asm volatile("" : "+f"(a[i])::"memory");
}
template <int N> __device__ __forceinline__ void fence_regs(uint32_t (&a)[N]) {
#pragma unroll
    for (int i = 0; i < N; i++) asm volatile("" : "+r"(a[i])::"memory");
}
__device__ __forceinline__ void mbar_init(uint32_t bar, uint32_t cnt) {
    asm volatile("mbarrier.init.shared::cta.b64 [%0], %1;\n" ::"r"(bar), "r"(cnt) : "memory");
}
__device__ __forceinline__ void mbar_expect_tx(uint32_t bar, uint32_t bytes) {
    asm volatile("mbarrier.arrive.expect_tx.shared::cta.b64 _, [%0], %1;\n" ::"r"(bar), "r"(bytes) : "memory");
}
__device__ __forceinline__ void mbar_wait(uint32_t bar, uint32_t parity) {
    asm volatile("{\n.reg .pred p;\nLW:\nmbarrier.try_wait.parity.shared::cta.b64 p, [%0], %1;\n@!p pmevent 0;\n@!p bra LW;\n}\n" ::"r"(bar), "r"(parity) : "memory");
}
__device__ __forceinline__ void mbar_wait_sleep(uint32_t bar, uint32_t parity) {
    asm volatile("{\n.reg .pred p;\nLW:\nmbarrier.try_wait.parity.shared::cta.b64 p, [%0], %1, 20000;\n@!p pmevent 0;\n@!p bra LW;\n}\n" ::"r"(bar), "r"(parity) : "memory");
}
__device__ __forceinline__ void mbar_wait_bounded(uint32_t bar, uint32_t parity) {
    asm volatile("{\n.reg .pred p;\n.reg .u32 c;\nmov.u32 c, 0;\nLW:\nmbarrier.try_wait.parity.shared::cta.b64 p, [%0], %1, 20000;\n@p bra LD;\n"
                 "add.u32 c, c, 1;\nsetp.ge.u32 p, c, 262144;\n@p trap;\nbra LW;\nLD:\n}\n" ::"r"(bar), "r"(parity) : "memory");
}
__device__ __forceinline__ void flag_wait(const int* p, int v) {
    asm volatile("{\n.reg .pred p;\n.reg .s32 f;\nLW:\nld.acquire.gpu.global.s32 f, [%0];\nsub.s32 f, f, %1;\nsetp.lt.s32 p, f, 0;\n@p bra LW;\n}\n" ::"l"(p), "r"(v) : "memory");
}
__device__ __forceinline__ void flag_wait_bounded(const int* p, int v) {
    asm volatile("{\n.reg .pred p;\n.reg .u32 c;\n.reg .s32 f;\nmov.u32 c, 0;\nLW:\nld.acquire.gpu.global.s32 f, [%0];\nsub.s32 f, f, %1;\nsetp.ge.s32 p, f, 0;\n@p bra LD;\n"
                 "nanosleep.u32 500;\nadd.u32 c, c, 1;\nsetp.ge.u32 p, c, 4194304;\n@p trap;\nbra LW;\nLD:\n}\n" ::"l"(p), "r"(v) : "memory");
}
__device__ __forceinline__ bool elect() {
    uint32_t p; asm volatile("{\n.reg .pred p;\nelect.sync _|p, -1;\nselp.u32 %0, 1, 0, p;\n}\n" : "=r"(p)); return p;
}
__device__ __forceinline__ void bulk_g2s(uint32_t dst, const void* src, uint32_t bytes, uint32_t bar) {
    asm volatile("cp.async.bulk.shared::cluster.global.mbarrier::complete_tx::bytes [%0], [%1], %2, [%3];\n"
                 ::"r"(dst), "l"(src), "r"(bytes), "r"(bar) : "memory");
}
__device__ __forceinline__ void bulk_g2s_mc(uint32_t dst, const void* src, uint32_t bytes, uint32_t bar, uint16_t mask) {
    asm volatile("cp.async.bulk.shared::cluster.global.mbarrier::complete_tx::bytes.multicast::cluster [%0], [%1], %2, [%3], %4;\n"
                 ::"r"(dst), "l"(src), "r"(bytes), "r"(bar), "h"(mask) : "memory");
}
__device__ __forceinline__ void tma_g2s(uint32_t dst, const CUtensorMap* tm, int rowgroup, uint32_t bar) {
    asm volatile("cp.async.bulk.tensor.4d.shared::cluster.global.tile.mbarrier::complete_tx::bytes [%0], [%1, {0, 0, 0, %2}], [%3];\n"
                 ::"r"(dst), "l"(tm), "r"(rowgroup), "r"(bar) : "memory");
}
__device__ __forceinline__ void bar_sync(int id, int n) { asm volatile("bar.sync %0, %1;\n" ::"r"(id), "r"(n) : "memory"); }
__device__ __forceinline__ void bar_arrive(int id, int n) { asm volatile("bar.arrive %0, %1;\n" ::"r"(id), "r"(n) : "memory"); }
__device__ __forceinline__ float quad_last(float v) {
    float r; asm volatile("shfl.sync.idx.b32 %0, %1, 3, 0x1c1f, -1;\n" : "=f"(r) : "f"(v)); return r;
}
__device__ __forceinline__ float ex2(float x) { float y; asm("ex2.approx.ftz.f32 %0, %1;\n" : "=f"(y) : "f"(x)); return y; }
__device__ __forceinline__ float rcp(float x) { float y; asm("rcp.approx.ftz.f32 %0, %1;\n" : "=f"(y) : "f"(x)); return y; }
__device__ __forceinline__ uint32_t pack_bf16(float lo, float hi) {
    uint32_t r; asm("cvt.rn.bf16x2.f32 %0, %1, %2;\n" : "=r"(r) : "f"(hi), "f"(lo)); return r;
}
__device__ __forceinline__ uint32_t pack_f16(float lo, float hi) {
    uint32_t r; asm("cvt.rn.f16x2.f32 %0, %1, %2;\n" : "=r"(r) : "f"(hi), "f"(lo)); return r;
}
__device__ __forceinline__ uint32_t pack_f16_sat(float lo, float hi) {
    uint32_t r; asm("cvt.rn.satfinite.f16x2.f32 %0, %1, %2;\n" : "=r"(r) : "f"(hi), "f"(lo)); return r;
}
__device__ __forceinline__ float f16_lo(uint32_t v) { float r; asm("cvt.f32.f16 %0, %1;\n" : "=f"(r) : "h"((unsigned short)v)); return r; }
__device__ __forceinline__ float f16_hi(uint32_t v) { return f16_lo(v >> 16); }
__device__ __forceinline__ float bf_lo(uint32_t v) { return __uint_as_float(v << 16); }
__device__ __forceinline__ float bf_hi(uint32_t v) { return __uint_as_float(v & 0xFFFF0000u); }
__device__ __forceinline__ float bf_round(float x) { return __uint_as_float(pack_bf16(0.f, x)); }
__device__ __forceinline__ void st_release(int* p, int v) {
    asm volatile("st.release.gpu.global.s32 [%0], %1;\n" ::"l"(p), "r"(v) : "memory");
}
__device__ __forceinline__ uint4 ldg_pinned(const uint4* p) {
    uint4 v; asm volatile("ld.global.nc.v4.u32 {%0, %1, %2, %3}, [%4];\n" : "=r"(v.x), "=r"(v.y), "=r"(v.z), "=r"(v.w) : "l"(p) : "memory"); return v;
}
__device__ __forceinline__ void stmatrix_x4(uint32_t addr, uint32_t r0, uint32_t r1, uint32_t r2, uint32_t r3) {
    asm volatile("stmatrix.sync.aligned.m8n8.x4.shared.b16 [%0], {%1, %2, %3, %4};\n" ::"r"(addr), "r"(r0), "r"(r1), "r"(r2), "r"(r3) : "memory");
}

__device__ __forceinline__ uint32_t tile_off(int r, int ch) {
    return (uint32_t)((r >> 3) * 4096 + (ch >> 3) * 1024 + (r & 7) * 128 + (((ch ^ r) & 7) << 4));
}
__device__ __forceinline__ int h_unit(int qt, int u) { return qt < 78 ? u * 78 + qt : 624; }
__device__ __forceinline__ int row_off(int r) { return 4096 + h_unit(r >> 7, (r >> 4) & 7) * 8192 + (r & 8) * 512 + (r & 7) * 144; }

__device__ __forceinline__ float4 lds128f(uint32_t a) {
    float4 v; asm volatile("ld.shared.v4.f32 {%0, %1, %2, %3}, [%4];\n" : "=f"(v.x), "=f"(v.y), "=f"(v.z), "=f"(v.w) : "r"(a) : "memory"); return v;
}
__device__ __forceinline__ uint64_t lds64(uint32_t a) { uint64_t v; asm volatile("ld.shared.u64 %0, [%1];\n" : "=l"(v) : "r"(a) : "memory"); return v; }
__device__ __forceinline__ uint4 lds128(uint32_t a) {
    uint4 v; asm volatile("ld.shared.v4.u32 {%0, %1, %2, %3}, [%4];\n" : "=r"(v.x), "=r"(v.y), "=r"(v.z), "=r"(v.w) : "r"(a) : "memory"); return v;
}
__device__ __forceinline__ void sts128(uint32_t a, uint32_t x, uint32_t y, uint32_t z, uint32_t w) {
    asm volatile("st.shared.v4.u32 [%0], {%1, %2, %3, %4};\n" ::"r"(a), "r"(x), "r"(y), "r"(z), "r"(w) : "memory");
}
__device__ __forceinline__ void mbar_arrive(uint32_t bar) {
    asm volatile("mbarrier.arrive.shared::cta.b64 _, [%0];\n" ::"r"(bar) : "memory");
}
__device__ __forceinline__ uint64_t mkaddr(uint32_t lo, uint32_t hi) { uint64_t a; asm("mov.b64 %0, {%1, %2};\n" : "=l"(a) : "r"(lo), "r"(hi)); return a; }
__device__ __forceinline__ void red_add(int* p) { asm volatile("red.relaxed.gpu.global.add.s32 [%0], 1;\n" ::"l"(p) : "memory"); }
__device__ __forceinline__ void red_release(int* p) {
    asm volatile("fence.proxy.async.global;\nfence.acq_rel.gpu;\nred.relaxed.gpu.global.add.s32 [%0], 1;\n" ::"l"(p) : "memory");
}
__device__ __forceinline__ void fence_async_global() { asm volatile("fence.proxy.async.global;\n" ::: "memory"); }
__device__ __forceinline__ void fence_async_smem() { asm volatile("fence.proxy.async.shared::cta;\n" ::: "memory"); }
__device__ __forceinline__ void bulk_s2g(void* dst, uint32_t src, uint32_t bytes) {
    asm volatile("cp.async.bulk.global.shared::cta.bulk_group [%0], [%1], %2;\ncp.async.bulk.commit_group;\n" ::"l"(dst), "r"(src), "r"(bytes) : "memory");
}
__device__ __forceinline__ void mma16816(float (&c)[4], uint32_t a0, uint32_t a1, uint32_t a2, uint32_t a3, uint32_t b0, uint32_t b1) {
    asm("mma.sync.aligned.m16n8k16.row.col.f32.bf16.bf16.f32 {%0, %1, %2, %3}, {%4, %5, %6, %7}, {%8, %9}, {%0, %1, %2, %3};\n"
        : "+f"(c[0]), "+f"(c[1]), "+f"(c[2]), "+f"(c[3]) : "r"(a0), "r"(a1), "r"(a2), "r"(a3), "r"(b0), "r"(b1));
}
__device__ __forceinline__ void mma1688(float (&c)[4], uint32_t a0, uint32_t a1, uint32_t b0) {
    asm("mma.sync.aligned.m16n8k8.row.col.f32.bf16.bf16.f32 {%0, %1, %2, %3}, {%4, %5}, {%6}, {%0, %1, %2, %3};\n"
        : "+f"(c[0]), "+f"(c[1]), "+f"(c[2]), "+f"(c[3]) : "r"(a0), "r"(a1), "r"(b0));
}
__device__ __forceinline__ uint32_t hadd2_f16(uint32_t a, uint32_t b) { uint32_t r; asm("add.rn.f16x2 %0, %1, %2;\n" : "=r"(r) : "r"(a), "r"(b)); return r; }
__device__ __forceinline__ uint32_t hadd2(uint32_t a, uint32_t b) { uint32_t r; asm("add.rn.bf16x2 %0, %1, %2;\n" : "=r"(r) : "r"(a), "r"(b)); return r; }
__device__ __forceinline__ uint32_t hmul2(uint32_t a, uint32_t b) { uint32_t r; asm("mul.rn.bf16x2 %0, %1, %2;\n" : "=r"(r) : "r"(a), "r"(b)); return r; }
__device__ __forceinline__ uint32_t hfma2(uint32_t a, uint32_t b, uint32_t c) { uint32_t r; asm("fma.rn.bf16x2 %0, %1, %2, %3;\n" : "=r"(r) : "r"(a), "r"(b), "r"(c)); return r; }

constexpr int SM_Q = 0;
constexpr int SM_KV = 65536;
constexpr int SM_ML = SM_KV + STAGES * KV_BYTES;
constexpr int SM_BAR = SM_ML + 1024;
constexpr int SM_TOTAL = SM_BAR + 256;
constexpr float SCALE_LOG2 = 1.4426950408889634f / 16.0f;
constexpr float KV_SCALE = 0.75f;
constexpr float KV_OFF = 6.f;
constexpr uint32_t KV_OFF2 = 0x46004600u;
constexpr uint32_t KV_NEG4 = 0xCE00CE00u;
constexpr uint32_t P_LIMIT = 0x78007800u;
constexpr float REF_UP = REFUP;
__device__ __forceinline__ uint32_t kvf(uint32_t a) {
    uint32_t r; asm("fma.rn.f16x2 %0, %1, %2, %3;\n" : "=r"(r) : "r"(a), "r"(pack_f16(KV_SCALE, KV_SCALE)), "r"(KV_OFF2)); return r;
}
enum { BAR_PP0 = 1, BAR_PP1 = 2, BAR_WG0 = 3, BAR_WG1 = 4, BAR_H0 = 5, BAR_H1 = 6, BAR_AUX = 7, BAR_BF = 8, BAR_H2 = 9, BAR_X = 10, BAR_GO = 11, BAR_WG2 = 12, BAR_ST = 13 };

struct Hot {
    const __nv_bfloat16 *wk, *wq, *x;
    Scratch* s;
};
struct Params {
    const __nv_bfloat16* deg_inv;
    const int *src, *dst;
    __nv_bfloat16* out;
    uint32_t dhi;
    int E;
    CUtensorMap tm_out;
    CUtensorMap tm_outc;
    CUtensorMap tm_w[3];
};
static_assert(offsetof(Params, tm_outc) == offsetof(Params, tm_out) + 128, "layout");
#define SC_PAIR (blockIdx.x < 104)
#define SC_TAIL (blockIdx.x >= NCTA - 2)
#define SC_LAST (blockIdx.x == NCTA - 1)
#define SC_HELP (SC_PAIR && rank)
#define SC_OWNER (!SC_HELP && !SC_LAST)
#define SC_QT1 (26 + (int)(blockIdx.x >> 1))
#define SC_QT0 (SC_PAIR ? (rank ? (int)(blockIdx.x >> 2) : SC_QT1) : SC_TAIL ? 78 : (int)blockIdx.x - 104)
#define SC_NKV (SC_LAST ? 50 : 75)
#define SC_NMC (SC_PAIR ? 25 : SC_TAIL ? 0 : 75)
#define SC_CLS (SC_PAIR ? (rank ? 0x120 ^ (blockIdx.x & 2) * 0x80 : 0x430) | (blockIdx.x & 2) >> 1 : SC_LAST ? 0x10 : 0x432)
#define SC_NW (SC_PAIR ? 8 : SC_LAST ? 0 : 4)
#define SC_ZB (2 * SC_QT1 + 1 - (int)rank)
#define SC_TZB(k) (rank && !(k) ? 156 : 2 * (k) - (int)rank)

__global__ void __cluster_dims__(2, 1, 1) __launch_bounds__(384, 1) k_main(const __grid_constant__ Hot H, const __grid_constant__ Params P) {
    extern __shared__ __align__(1024) uint8_t smem[];
    const uint32_t sb = (uint32_t)__cvta_generic_to_shared(smem);
    const int tid = threadIdx.x, wg = __shfl_sync(~0u, tid >> 7, 0);
    const int lane = tid & 31, g = lane >> 2, q = lane & 3;
    const uint32_t rank = blockIdx.x & 1;
    const uint32_t bar_full = sb + SM_BAR, bar_q = bar_full + 32, bar_go = bar_full + 48;
    const uint32_t bar_pin = bar_full + 56;
    const uint32_t bar_qfree = bar_full + 72, bar_pdone = bar_full + 88, bar_zst = bar_full + 104, bar_rfree = bar_full + 120;
    const uint32_t bar_empty = bar_full + 128, bar_end = bar_full + 160, s_tm = bar_full + 184, bar_x = bar_full + 192;
    const uint32_t bar_a = sb + SM_ML;

    const int t = tid & 127, warp = __shfl_sync(~0u, t >> 5, 0);
    int ep = 0;
    if (wg & 2) {
        unsigned done;
        {
            uint4 ra[2], rb[2], rk[5][2];
            if (blockIdx.x < 128) {
                const int e = (blockIdx.x >> 4) * 32 + (g >> 1) * 8 + (blockIdx.x & 8) / 2 + (g & 1);
                const uint4* pq = (const uint4*)(H.wq + e * 256) + warp * 8 + q;
                const uint4* pk = (const uint4*)(H.wk + ((blockIdx.x & 7) * 32 + g) * 256) + warp * 8 + q;
                const uint4* pz = (const uint4*)(H.wk + 255 * 256) + warp * 8 + q;
#pragma unroll
                for (int s = 0; s < 2; s++) {
                    ra[s] = ldg_pinned(pq + 4 * s);
                    rb[s] = ldg_pinned(pq + 4 * s + 64);
#pragma unroll
                    for (int n = 0; n < 4; n++) rk[n][s] = ldg_pinned(pk + 4 * s + n * 256);
                    rk[4][s] = ldg_pinned(pz + 4 * s);
                }
            }
            asm volatile("{\n.reg .pred p;\nsetp.eq.s32 p, %2, 0;\nmov.u32 %0, 0;\n@p ld.global.cg.u32 %0, [%1];\n}\n" : "=r"(done) : "l"(&g_sync[SY_DONE * 32]), "r"(lane) : "memory");
            bar_arrive(BAR_X, 384);
            if (warp == 0 && elect()) {
#pragma unroll
                for (int i = 0; i < 21; i++) mbar_init(bar_full + 8 * i, i < 9 ? 1 : i < 16 ? 4 : i == 20 ? 11 : SC_TAIL ? 8 : 16);
#pragma unroll
                for (int i = 0; i < 4; i++) mbar_init(bar_a + 8 * i, 1);
                mbar_expect_tx(bar_pin, QB_BYTES / 2 + 512); mbar_expect_tx(bar_pin + 8, QB_BYTES / 2);
                asm volatile("fence.mbarrier_init.release.cluster;\n" ::: "memory");
            }
            __syncwarp();
            asm volatile("barrier.cluster.arrive.relaxed.aligned;\n" ::: "memory");
            if (blockIdx.x < 128) {
                float c[5][4] = {};
#pragma unroll
                for (int s = 0; s < 2; s++) {
#pragma unroll
                    for (int n = 0; n < 5; n++) mma16816(c[n], ra[s].x, rb[s].x, ra[s].y, rb[s].y, rk[n][s].x, rk[n][s].y);
#pragma unroll
                    for (int n = 0; n < 5; n++) mma16816(c[n], ra[s].z, rb[s].z, ra[s].w, rb[s].w, rk[n][s].z, rk[n][s].w);
                }
#pragma unroll
                for (int i = 0; i < 4; i++) {
                    const int r = i & 2, n = (i & 1) * 2;
                    sts128(sb + SM_KV + 3 * KV_BYTES + QB_BYTES + i * 2048 + t * 16, __float_as_uint(c[n][r] - c[4][r]), __float_as_uint(c[n][r + 1] - c[4][r]),
                           __float_as_uint(c[n + 1][r] - c[4][r]), __float_as_uint(c[n + 1][r + 1] - c[4][r]));
                }
            }
        }
        asm volatile("setmaxnreg.dec.sync.aligned.u32 %0;\n" ::"n"(REG_P));
        if (blockIdx.x < 128) {
            bar_sync(BAR_WG2, 128);
            float4 v[4];
#pragma unroll
            for (int i = 0; i < 4; i++) v[i] = lds128f(sb + SM_KV + 3 * KV_BYTES + QB_BYTES + (warp & 2) * 2048 + (lane & 1) * 2048 + i * 512 + ((warp & 1) * 16 + (lane >> 1)) * 16);
            constexpr float SC = SCALE_LOG2 / KV_SCALE;
            const int r = (warp & 1) * 4 + (lane >> 3);
            *(uint2*)(g_w + tile_off((blockIdx.x >> 3) * 16 + (warp & 2) * 4 + r, (blockIdx.x & 7) * 4 + ((lane >> 1) & 3)) + (lane & 1) * 8) =
                make_uint2(pack_f16_sat(((v[0].x + v[1].x) + (v[2].x + v[3].x)) * SC, ((v[0].y + v[1].y) + (v[2].y + v[3].y)) * SC) | 1,
                           pack_f16_sat(((v[0].z + v[1].z) + (v[2].z + v[3].z)) * SC, ((v[0].w + v[1].w) + (v[2].w + v[3].w)) * SC) | 1);
            if (warp != 1) {
                bar_arrive(BAR_AUX, 128);
            } else {
                bar_sync(BAR_AUX, 128);
                if (elect()) { red_add(&g_sync[SY_DONE * 32 + 4 + (blockIdx.x >> 5)]); }
                __syncwarp();
            }
        }
        else bar_sync(BAR_WG2, 128);
        if (warp == 1) bar_arrive(BAR_GO, 160);
        auto load_a = [&](int j) {
            if (elect()) {
                mbar_expect_tx(bar_a + 8 * j, QB_BYTES);
                bulk_g2s(sb + SM_KV + j * KV_BYTES, g_w + j * QB_BYTES, QB_BYTES, bar_a + 8 * j);
            }
            __syncwarp();
        };
        if (warp == 0) {
            auto poll = [&]() { int c; asm volatile("ld.relaxed.gpu.global.s32 %0, [%1];\n" : "=r"(c) : "l"(&g_sync[SY_DONE * 32 + 4 + (lane & 3)]) : "memory"); return c; };
#pragma unroll 1
            for (int j = 0; j < 4;) {
#pragma unroll 1
                for (const uint32_t mk = __ballot_sync(~0u, poll() >= 32) & 15; (mk >> j) & 1; j++) load_a(j);
            }
        } else if (warp & 1) {
#pragma unroll 1
            for (int j = 0, n = 0; j < 4;) {
                mbar_wait_bounded(bar_a + 8 * j, n & 1);
                uint32_t ok = 1;
#pragma unroll
                for (int i = 0; i < 16; i++) {
                    uint32_t v;
                    asm volatile("ld.shared.u32 %0, [%1];\n" : "=r"(v) : "r"(sb + SM_KV + j * KV_BYTES + (warp & 2) * 8192 + i * 1024 + lane * 32 + g * 4) : "memory");
                    ok &= v;
                }
                asm volatile("{\n.reg .pred p;\nsetp.ne.u32 p, %0, 0;\nbar.red.and.pred p, %1, 64, p;\nselp.u32 %0, 1, 0, p;\n}\n" : "+r"(ok) : "n"((int)BAR_WG2) : "memory");
                if (__any_sync(~0u, ok)) {
                    if (warp == 1 && elect()) asm volatile("mbarrier.arrive.shared::cta.b64 _, [%0];\nmbarrier.inval.shared::cta.b64 [%1];\n" ::"r"(bar_full + 8 * j), "r"(bar_a + 8 * j) : "memory");
                    __syncwarp();
                    j++; n = 0;
                } else {
                    asm volatile("{\n.reg .pred p;\nsetp.gt.s32 p, %0, 1000000;\n@p trap;\n}\n" ::"r"(++n) : "memory");
                    fence_async_smem();
                    if (warp == 1) load_a(j);
                }
            }
        }
        done = __shfl_sync(~0u, done, 0);
        ep = (int)(done / NCTA) + 1;
        asm volatile("barrier.cluster.wait.acquire.aligned;\n" ::: "memory");
        if (warp == 0) {
            asm volatile("st.shared.u64 [%0], %1;\n" ::"r"(s_tm), "l"(&P.tm_outc) : "memory");
            __syncwarp();
            if (elect()) {
                const uint8_t* base = (const uint8_t*)H.s;
                uint32_t cls = SC_CLS, bytes = KV_BYTES, moff = SC_NMC ? rank * (KV_BYTES / 2) : 0, step = 5 * KV_BYTES;
                const uint8_t* src = base;
                int next = 0;
                const int nit = SC_NKV + SC_NW;
#pragma unroll 1
                for (int j = 0; j < nit; j++) {
                    const uint32_t slot = sb + SM_KV + (j & 3) * KV_BYTES, fb = bar_full + 8 * (j & 3);
                    if (j == next) {
                        const int k = j - SC_NKV;
                        const int sw = SC_HELP ? j - 25 : -1;
                        next = j + 1;
                        if (j >= 3 && (unsigned)sw >= 5) next = k >= 0 ? next : j < 25 ? 25 : j < GO0 ? GO0 : j < 49 ? 49 : j < 50 ? 50 : 75;
                        if (j == SC_NMC) moff = 0;
                        if (j == 0 || j == 25 || j == 50) { src = base + (4096 + (cls & 15) * KV_BYTES + moff); cls >>= 4; }
                        if (SC_TAIL ? j == nit - 1 : j == GO0) mbar_arrive(bar_go);
                        int fo = -1, fv = 1;
                        if (j < 3) { fo = (SY_H0 + 5 * j + (SC_CLS & 15)) * 32; fv = 5; }
                        if (j == 3) { fo = SY_H1 * 32; fv = 79; }
                        if (sw == 1) fo = 25 * 32 + SC_QT1;
                        if (k == 0) fo = SY_B * 32;
                        if (k == 1 && !SC_PAIR) { fo = SY_AUX0 * 32; fv = NAUX; }
                        if (k == 2 && SC_PAIR) { fo = SY_AUX * 32; fv = NAUX / 3; }
                        if (fo >= 0) {
                            flag_wait(g_sync + fo, fv * ep);
                            fence_async_global();
                        }
                        if (sw == 2 || (k == 2 && !SC_TAIL)) {
                            uint32_t qs = sw == 2 ? offsetof(Scratch, q) + (2 * SC_QT1 + 1) * QB_BYTES : SC_PAIR ? offsetof(Scratch, agg) + SC_ZB * QB_BYTES : offsetof(Scratch, part) + SC_QT0 * (4 * PART_BYTES);
#pragma unroll 1
                            for (int w = 0; w < (k == 2 && SC_PAIR ? 1 : 2); w++) {
                                mbar_wait_sleep(bar_qfree + 8 * w, k == 2 && SC_HELP);
                                mbar_expect_tx(bar_q + 8 * w, SC_PAIR ? QB_BYTES : PART_BYTES);
                                if (!SC_PAIR) bulk_g2s(sb + SM_ML + w * 512, base + (qs + (w ? -512 : QB_BYTES)), 512, bar_q + 8 * w);
                                bulk_g2s(sb + SM_Q + w * QB_BYTES, base + qs, QB_BYTES, bar_q + 8 * w);
                                qs += sw == 2 ? -QB_BYTES : PART_BYTES + 512;
                            }
                        }
                        if ((sw | 1) == 3) {
                            mbar_wait_sleep(bar_pdone + 8 * (sw - 2), 0);
                            bulk_s2g(g_part + (blockIdx.x - 3 + sw) * PART_BYTES, slot, PART_BYTES);
                            asm volatile("cp.async.bulk.wait_group.read 0;\n" ::: "memory");
                        }
                        if (sw == 5) {
                            asm volatile("cp.async.bulk.wait_group 0;\n" ::: "memory");
                            red_release(&g_sync[SY_PART * 32]);
                        }
                        if (k == 0) {
                            asm volatile("prefetch.tensormap [%0];\n" ::"l"(&P.tm_outc) : "memory");
                            src = g_w + (12 - SC_NW) * QB_BYTES; bytes = step = QB_BYTES;
                        }
                        if (k == 2) next = SC_TAIL ? nit - 1 : nit;
                    }
                    mbar_wait_sleep(fb + (bar_empty - bar_full), (j >> 2) & 1);
                    mbar_expect_tx(fb, bytes);
                    if (j < SC_NMC) bulk_g2s_mc(slot + moff, src, KV_BYTES / 2, fb, 3);
                    else bulk_g2s(slot, src, bytes, fb);
                    src += step;
                }
            }
        } else {
            if (warp == 2 && SC_OWNER) {
                uint8_t* dst = g_hz + 4096 + h_unit(SC_QT0, 0) * 8192;
                auto send = [&](int u0, int u1) {
#pragma unroll
                    for (int u = u0; u < u1; u++) {
                        bulk_s2g(dst + u * (78 * 8192), sb + SM_Q + u * 8192, 8192);
                        asm volatile("cp.async.bulk.wait_group 0;\n" ::: "memory");
                    }
                };
                int* f0 = &g_sync[(SY_H0 + SC_QT0 / 5) * 32];
                bar_sync(BAR_H0, 64);
                if (elect()) {
                    send(0, 1);
                    if (SC_QT0 < 65) red_release(f0);
                }
                bar_sync(BAR_H1, 160);
                if (elect()) {
                    if (!SC_TAIL) send(1, 4);
                    mbar_arrive(bar_q);
                }
                bar_sync(BAR_H2, 160);
                if (elect()) {
                    if (!SC_TAIL) { send(4, 8); mbar_arrive(bar_q + 8); }
                    red_release(&g_sync[SY_H1 * 32]);
                }
                __syncwarp();
            }
        }
    } else {
        const uint32_t sq = sb + SM_Q + wg * QB_BYTES;
        const uint32_t qbar = bar_q + 8 * wg;
        const uint32_t dq0 = __shfl_sync(~0u, ((sq & 0x3FFFF) >> 4) | (64u << 16), 0);
        const uint32_t dk0 = __shfl_sync(~0u, (((sb + SM_KV) & 0x3FFFF) >> 4) | (64u << 16), 0);
        float o[128];
        int it = 4;
        const uint32_t dhi = P.dhi;
        uint32_t rel_addr;
        auto rel_target = [&](uint32_t r) {
            asm("mapa.shared::cluster.u32 %0, %1, %2;\n" : "=r"(rel_addr) : "r"(bar_empty), "r"(r));
            if (lane >= 2) rel_addr = 0;
            asm volatile("" : "+r"(rel_addr));
        };
        rel_target(SC_NMC ? rank ^ (lane & 1) : rank);
        auto release = [&](int st) {
            asm volatile("{\n.reg .pred p;\nsetp.ne.u32 p, %1, 0;\n@p mbarrier.arrive.shared::cluster.b64 _, [%0];\n}\n"
                         ::"r"(rel_addr + 8 * st), "r"(rel_addr) : "memory");
        };
        const bool active = !(SC_TAIL && wg == 1);
        auto pp_sync = [&]() { if (!SC_TAIL) bar_sync(BAR_PP0 + wg, 256); };
        auto pp_arrive = [&]() { if (!SC_TAIL) bar_arrive(BAR_PP1 - wg, 256); };
        auto warp_arrive = [&](uint32_t bar) {
            __syncwarp();
            asm volatile("{\n.reg .pred p;\nelect.sync _|p, -1;\n@p mbarrier.arrive.shared::cta.b64 _, [%0];\n}\n" ::"r"(bar + 8 * wg) : "memory");
        };
        auto peer_arrive = [&]() {
            asm volatile("{\n.reg .pred p;\n.reg .b32 a;\nelect.sync _|p, -1;\nmapa.shared::cluster.u32 a, %0, %1;\n"
                         "@p mbarrier.arrive.shared::cluster.b64 _, [a];\n}\n" ::"r"(bar_rfree), "r"(rank ^ 1) : "memory");
        };
        auto stage_q = [&]() {
            auto pk = [&](int i) { return QRND(pack_f16_sat(o[i], o[i + 1])); };
#pragma unroll
            for (int i = 0; i < 16; i++)
                stmatrix_x4(sq + warp * 8192 + tile_off(lane & 15, 2 * i + (lane >> 4)), pk(8 * i), pk(8 * i + 2), pk(8 * i + 4), pk(8 * i + 6));
        };
        float s[40];
        auto issue_qk = [&](int st) {
            const uint64_t kb = mkaddr(dk0 + st * (KV_BYTES >> 4), dhi);
            const uint64_t qd = mkaddr(dq0 + ((uint32_t)it >> 24), dhi);
            wgmma_ss_n80_init(s, qd + 198, kb + 198);
#pragma unroll
            for (int kk = 0; kk < 15; kk++) wgmma_ss_n80(s, qd + ((kk >> 2) * 64 + (kk & 3) * 2), kb + ((kk >> 2) * 64 + (kk & 3) * 2));
            wg_commit();
        };

        {
            const int rb = (2 * SC_QT0 + wg) * 64 + warp * 16;
            const uint32_t xbar = bar_x + 32 * wg + 8 * warp;
            if (elect()) {
                mbar_init(xbar, 1);
                asm volatile("fence.mbarrier_init.release.cluster;\nfence.proxy.async.shared::cta;\n" ::: "memory");
                mbar_expect_tx(xbar, rb < NN ? 8192 : 0);
            }
            asm volatile("barrier.cluster.arrive.relaxed.aligned;\n" ::: "memory");
            if (wg == 1) pp_arrive();
            bar_sync(BAR_X, 384);
            if (wg == 1) bar_sync(BAR_GO, 160);
            if (rb < NN && elect()) bulk_g2s(sq + warp * 8192, H.x + (size_t)rb * 256, 8192, xbar);
            if (rb >= NN) {
#pragma unroll 1
                for (int i = 0; i < 16; i++) sts128(sq + warp * 8192 + i * 512 + lane * 16, 0, 0, 0, 0);
            }
            __syncwarp();
            mbar_wait(xbar, 0);
            uint4 xa[8], xb[8];
#pragma unroll
            for (int s = 0; s < 8; s++) {
                xa[s] = lds128(sq + (warp * 16 + g) * 512 + (4 * s + q) * 16);
                xb[s] = lds128(sq + (warp * 16 + g + 8) * 512 + (4 * s + q) * 16);
            }
            float sm[2][4], sq2[2][4][4];
#pragma unroll
            for (int i = 0; i < 4; i++) {
                sm[0][i] = sm[1][i] = 0.f;
#pragma unroll
                for (int k = 0; k < 4; k++) sq2[0][k][i] = sq2[1][k][i] = 0.f;
            }
#pragma unroll
            for (int s = 0; s < 8; s++) {
#pragma unroll
                for (int hh = 0; hh < 2; hh++) {
                    const uint4 v = hh ? xb[s] : xa[s];
                    mma16816(sm[hh], v.x, v.y, v.z, v.w, 0x3F803F80u, 0x3F803F80u);
                    mma1688(sq2[hh][0], v.x, v.y, v.x); mma1688(sq2[hh][1], v.x, v.y, v.y);
                    mma1688(sq2[hh][2], v.z, v.w, v.z); mma1688(sq2[hh][3], v.z, v.w, v.w);
                }
            }
            float inv[2], off[2];
#pragma unroll
            for (int hh = 0; hh < 2; hh++) {
                const float mean = (sm[hh][0] + sm[hh][2]) * (1.f / 256.f);
                const float d0 = (sq2[hh][0][0] + sq2[hh][2][0]) + (sq2[hh][1][2] + sq2[hh][3][2]);
                const float d1 = (sq2[hh][0][1] + sq2[hh][2][1]) + (sq2[hh][1][3] + sq2[hh][3][3]);
                const float ss = __shfl_sync(~0u, (g & 1) ? d1 : d0, g * 4 + (g >> 1));
                const float var = fmaxf(ss * (1.f / 256.f) - mean * mean, 0.f);
                float sd;
                asm("sqrt.approx.ftz.f32 %0, %1;\n" : "=f"(sd) : "f"(bf_round(bf_round(var) + 1e-5f)));
                asm("rcp.approx.ftz.f32 %0, %1;\n" : "=f"(inv[hh]) : "f"(bf_round(sd)));
                off[hh] = -mean * inv[hh];
            }
            uint32_t a[64];
#pragma unroll
            for (int s = 0; s < 8; s++) {
                a[8 * s] = xa[s].x; a[8 * s + 1] = xb[s].x; a[8 * s + 2] = xa[s].y; a[8 * s + 3] = xb[s].y;
                a[8 * s + 4] = xa[s].z; a[8 * s + 5] = xb[s].z; a[8 * s + 6] = xa[s].w; a[8 * s + 7] = xb[s].w;
            }
            fence_regs(a);
            if (wg == 1 && __any_sync(~0u, inv[0] + inv[1] != -1.f)) bar_arrive(BAR_ST, 256);
            asm volatile("setmaxnreg.inc.sync.aligned.u32 %0;\n" ::"n"(REG_C));
            fence_regs(a);
#pragma unroll
            for (int i = 0; i < 64; i++)
                a[i] = pack_f16(fmaf(bf_lo(a[i]), inv[i & 1], off[i & 1]), fmaf(bf_hi(a[i]), inv[i & 1], off[i & 1]));
            if (SC_OWNER) {
#pragma unroll
                for (int i = 0; i < 16; i++) {
                    const uint32_t mk = (i == 15 && q == 3) ? 0xFFFFu : ~0u;
                    stmatrix_x4(sq + warp * 8192 + tile_off(lane & 15, 2 * i + (lane >> 4)), kvf(a[4 * i]), kvf(a[4 * i + 1]),
                                kvf(a[4 * i + 2] & mk), kvf(a[4 * i + 3] & mk));
                }
                fence_async_smem();
                if (tid < 32) bar_arrive(BAR_H0, 64);
                bar_arrive(wg ? BAR_H2 : BAR_H1, 160);
            }
            asm volatile("barrier.cluster.wait.acquire.aligned;\n" ::: "memory");
            if (wg == 0) bar_sync(BAR_ST, 256);
            if (active) {
                fence_regs(a);
#pragma unroll
                for (int c = 0; c < 4; c++) {
                    if (c == 1) {
                        if (wg == 1) {
                            wg_wait<0>();
                            release(0);
                        }
                        pp_sync();
                    }
                    mbar_wait(bar_full + 8 * c, 0);
                    const uint64_t wb = mkaddr(dk0 + c * (KV_BYTES >> 4), dhi);
                    wg_fence();
#pragma unroll
                    for (int kk = 0; kk < 4; kk++) {
                        if (c | kk) wgmma_rs_n256_tb(o, a[16 * c + 4 * kk], a[16 * c + 4 * kk + 1], a[16 * c + 4 * kk + 2], a[16 * c + 4 * kk + 3], wb + kk * 512);
                        else wgmma_rs_n256_tb_init(o, a[0], a[1], a[2], a[3], wb);
                    }
                    wg_commit();
                    if (c > 0) { wg_wait<1>(); if (c > 1 || wg == 0) release(c - 1); }
                }
                if (wg == 0) pp_arrive();
                wg_wait<0>();
                fence_regs(o);
                release(3);
                if (SC_OWNER) mbar_wait(qbar, 0);
                stage_q();
                fence_async_smem();
                bar_sync(BAR_WG0 + wg, 128);
                mbar_wait(bar_full, 1);
                wg_fence();
                issue_qk(0);
                if (wg == 1) pp_arrive();
            } else {
                peer_arrive();
            }
        }

        uint32_t p[20];
        float m0 = 0.f, m1 = 0.f, e0, e1, l0, l1;
        uint32_t plim;
        uint32_t qphase = (SC_OWNER && active) ? 1 : 0;
        auto issue_pv = [&](int st, int acc) {
            const uint64_t vb = mkaddr(dk0 + st * (KV_BYTES >> 4), dhi);
            wgmma_rs_n256_tb_pred(o, p[0], p[1], p[2], p[3], vb, acc);
#pragma unroll
            for (int kk = 1; kk < 5; kk++)
                wgmma_rs_n256_tb(o, p[4 * kk], p[4 * kk + 1], p[4 * kk + 2], p[4 * kk + 3], vb + kk * 512);
            wg_commit();
        };
        const uint32_t mq_addr = sq + tile_off(warp * 16 + g, 31) + 14;
        auto exceeds = [&](const uint32_t (&p)[20]) {
            uint32_t a = __vimax3_s16x2(P_LIMIT, p[0], p[1]), b = __vimax3_s16x2(p[2], p[3], p[4]);
#pragma unroll
            for (int i = 5; i < 17; i += 4) { a = __vimax3_s16x2(a, p[i], p[i + 1]); b = __vimax3_s16x2(b, p[i + 2], p[i + 3]); }
            a = __vimax3_s16x2(a, p[17], p[18]);
            return __any_sync(~0u, __vimax3_s16x2(a, b, p[19]) != plim);
        };
        auto remax = [&](float& a, float& b, bool store) {
            float a1 = fmaxf(s[0], s[1]), b1 = fmaxf(s[2], s[3]), a2 = fmaxf(s[4], s[5]), b2 = fmaxf(s[6], s[7]);
#pragma unroll
            for (int i = 2; i < 10; i++) {
                a1 = fmaxf(a1, s[4 * i]); a2 = fmaxf(a2, s[4 * i + 1]);
                b1 = fmaxf(b1, s[4 * i + 2]); b2 = fmaxf(b2, s[4 * i + 3]);
            }
            a1 = fmaxf(a1, a2); b1 = fmaxf(b1, b2);
            a1 = fmaxf(a1, __shfl_xor_sync(~0u, a1, 1)); b1 = fmaxf(b1, __shfl_xor_sync(~0u, b1, 1));
            a1 = fmaxf(a1, __shfl_xor_sync(~0u, a1, 2)); b1 = fmaxf(b1, __shfl_xor_sync(~0u, b1, 2));
            a = fmaxf(a, a1 - e0 + REF_UP); b = fmaxf(b, b1 - e1 + REF_UP);
            const uint32_t u = pack_f16_sat((m0 + a) * (-1.f / KV_OFF), (m1 + b) * (-1.f / KV_OFF));
            const float g0 = (m0 + a) + KV_OFF * f16_lo(u), g1 = (m1 + b) + KV_OFF * f16_hi(u);
            const bool x0 = fabsf(g0) <= 1.f, x1 = fabsf(g1) <= 1.f;
            if (x0) a -= g0;
            if (x1) b -= g1;
            const float da = a + e0, db = b + e1;
            m0 += a; m1 += b;
            e0 = x0 ? 0.f : g0; e1 = x1 ? 0.f : g1;
            plim = (x0 && x1) ? P_LIMIT : 0u;
            asm volatile("{\n.reg .pred p;\nsetp.ne.s32 p, %3, 0;\n@p st.shared.u16 [%0], %1;\n@p st.shared.u16 [%0 + 4096], %2;\n}\n"
                         ::"r"(mq_addr), "h"((unsigned short)u), "h"((unsigned short)(u >> 16)), "r"((int)(store && q == 0)) : "memory");
#pragma unroll
            for (int i = 0; i < 10; i++) {
                p[2 * i] = pack_f16(ex2(s[4 * i] - da), ex2(s[4 * i + 1] - da));
                p[2 * i + 1] = pack_f16(ex2(s[4 * i + 2] - db), ex2(s[4 * i + 3] - db));
            }
            fence_regs(p);
            fence_async_smem();
            __syncwarp();
        };

        auto row_sums = [&](float& z0, float& z1) {
            z0 = quad_last(o[125]); z1 = quad_last(o[127]);
            l0 = z0 * (KV_SCALE / KV_OFF); l1 = z1 * (KV_SCALE / KV_OFF);
        };
        auto cut = [&]() { asm volatile("{\n.reg .pred p;\nsetp.lt.s32 p, %0, 0;\nL:\n@p pmevent 0;\n@p bra L;\n}\n" ::"r"(it) : "memory"); };
        auto stats = [&]() { return (q & 2) ? ((q & 1) ? l1 : m1) : ((q & 1) ? l0 : m0); };
        const int nseg = SC_HELP ? 2 : 1;
        if (active) {
#pragma unroll 1
        for (int seg = 0;; seg++) {
            wg_wait<0>();
            fence_regs(s);
            e0 = e1 = 0.f;
            const int it0 = it, itl = __shfl_sync(~0u, seg + 1 < nseg ? 3 + 25 : 3 + SC_NKV, 0);
            const int itx = (wg == 1 && seg + 1 == nseg) ? itl : -1;
            bool redo = true, have = !seg;
#pragma unroll 1
            for (;;) {
                if (!have) {
#pragma unroll
                    for (int i = 0; i < 20; i++) p[i] = pack_f16(ex2(s[2 * i]), ex2(s[2 * i + 1]));
                    redo = exceeds(p);
                }
                if (redo) {
                    float d0 = it != it0 ? 0.f : -INFINITY, d1 = d0;
                    remax(d0, d1, it != itl);
                    if (it != it0) {
                        const float a0 = ex2(-d0), a1 = ex2(-d1);
#pragma unroll
                        for (int i = 0; i < 32; i++) { o[4 * i] *= a0; o[4 * i + 1] *= a0; o[4 * i + 2] *= a1; o[4 * i + 3] *= a1; }
                    }
                }
                if (it == it0 && (seg || SC_OWNER)) {
                    fence_async_smem();
                    warp_arrive(bar_pdone);
                }
                if (it == itl) break;
                const int stp = it & 3;
                it++;
                mbar_wait(bar_full + 8 * (it & 3), (it >> 2) & 1);
                pp_sync();
                fence_regs(o); fence_regs(p);
                wg_fence();
                issue_qk(it & 3);
                if (it == itx) {
                    wg_wait<0>();
                    if (SC_PAIR) peer_arrive(); else warp_arrive(bar_qfree);
                    bar_sync(BAR_ST, 256);
                }
                wg_fence();
                issue_pv(stp, it - 1 - it0);
                pp_arrive();
                if (it == itl && itx < 0) {
                    wg_wait<1>();
                    warp_arrive(bar_qfree);
                }
                have = SC_TAIL || it == itx;
                if (have) {
                    uint32_t p2[20];
                    wg_wait<1>();
                    fence_regs(s);
#pragma unroll
                    for (int i = 0; i < 20; i++) p2[i] = pack_f16(ex2(s[2 * i]), ex2(s[2 * i + 1]));
                    redo = exceeds(p2);
                    if (redo) asm volatile("wgmma.wait_group.sync.aligned 0;\nnanosleep.u32 0;\n" ::: "memory");
                    else wg_wait<0>();
                    fence_regs(o); fence_regs(p);
#pragma unroll
                    for (int i = 0; i < 20; i++) p[i] = p2[i];
                } else {
                    wg_wait<0>();
                    fence_regs(s); fence_regs(o); fence_regs(p);
                }
                release(stp);
                if (it == SC_NMC) rel_target(rank);
            }
            if (seg + 1 < nseg) pp_sync();
            fence_regs(o); fence_regs(p);
            wg_fence();
            issue_pv(it & 3, 1);
            asm volatile("{\n.reg .pred p;\nsetp.ne.s32 p, %0, 0;\n@p bar.arrive %1, 256;\n}\n" ::"r"((int)(seg + 1 == nseg && (wg ? SC_PAIR : !SC_TAIL))), "r"(BAR_ST + wg) : "memory");
            it++;
            if (seg + 1 == nseg) break;
            const int is = it - 2 + wg;
            uint32_t dst = sb + SM_KV + (is & 3) * KV_BYTES + wg * 512 + warp * 8192 + lane * 16;
            uint32_t dml = sb + SM_KV + (is & 3) * KV_BYTES + (wg ? 0 : QB_BYTES) + t * 4;
            asm volatile("" : "+r"(dst), "+r"(dml));
            mbar_wait(qbar, qphase); qphase ^= 1;
            unsigned short u0, u1;
            asm volatile("ld.shared.u16 %0, [%2];\nld.shared.u16 %1, [%2 + 4096];\n" : "=h"(u0), "=h"(u1) : "r"(mq_addr) : "memory");
            mbar_wait(bar_full + 8 * (it & 3), (it >> 2) & 1);
            wg_wait<0>();
            fence_regs(o);
            float z0, z1;
            row_sums(z0, z1);
            release((it - 1) & 3);
            wg_fence();
            issue_qk(it & 3);
            pp_arrive();
#pragma unroll
            for (int i = 0; i < 128; i++) o[i] -= (i & 2) ? z1 : z0;
            fence_regs(o);
            mbar_wait(bar_empty + 8 * (is & 3), (is >> 2) & 1);
            asm volatile("st.shared.f32 [%0], %1;\n" ::"r"(dml), "f"(stats()) : "memory");
            m0 = -KV_OFF * f16_lo(u0); m1 = -KV_OFF * f16_lo(u1);
            plim = fmaxf(fabsf(m0), fabsf(m1)) <= 3072.f ? P_LIMIT : 0u;
            uint32_t v[2][8] = {};
#pragma unroll
            for (int i = 0; i < 8; i++) {
                uint32_t *w = v[i & 1], *u = v[(i & 1) ^ 1];
#pragma unroll
                for (int j = 0; j < 8; j++) w[j] = pack_bf16(o[16 * i + 2 * j], o[16 * i + 2 * j + 1]);
                sts128(dst + i * 1024, w[0], w[1], w[2], w[3]);
                sts128(dst + i * 1024 + 512, w[4], w[5], w[6], w[7]);
                if (i) asm volatile("{\n.reg .pred p;\nsetp.lt.s32 p, %9, 0;\nL:\n@p st.shared.v4.u32 [%0], {%1, %2, %3, %4};\n@p st.shared.v4.u32 [%0 + 16], {%5, %6, %7, %8};\n@p bra L;\n}\n"
                             ::"r"(dst), "r"(u[0]), "r"(u[1]), "r"(u[2]), "r"(u[3]), "r"(u[4]), "r"(u[5]), "r"(u[6]), "r"(u[7]), "r"(it) : "memory");
            }
        }
        constexpr int IW = 4 + 75;
        uint32_t a[64];
        if (wg == 0 && (SC_PAIR || SC_LAST)) {
            uint32_t rq, rml, rbar;
            asm volatile("mapa.shared::cluster.u32 %0, %3, %6;\nmapa.shared::cluster.u32 %1, %4, %6;\nmapa.shared::cluster.u32 %2, %5, %6;\n"
                         : "=r"(rq), "=r"(rml), "=r"(rbar) : "r"(sb + SM_Q + QB_BYTES + warp * 8192 + lane * 16), "r"(sb + SM_ML + 512 + t * 4),
                         "r"(bar_pin), "r"(rank ^ 1));
            auto send = [&](int i) {
                asm volatile("st.async.weak.shared::cluster.mbarrier::complete_tx::bytes.v4.b32 [%0], {%1, %2, %3, %4}, [%5];\n"
                             ::"r"(rq + i * 512), "r"(a[4 * i]), "r"(a[4 * i + 1]), "r"(a[4 * i + 2]), "r"(a[4 * i + 3]), "r"(rbar + (i & 8)) : "memory");
            };
            mbar_wait(bar_rfree, 0);
            wg_wait<0>();
            fence_regs(o);
            release((it - 1) & 3);
            float z0, z1;
            row_sums(z0, z1);
            asm volatile("st.async.weak.shared::cluster.mbarrier::complete_tx::bytes.f32 [%0], %1, [%2];\n" ::"r"(rml), "f"(stats()), "r"(rbar) : "memory");
#pragma unroll
            for (int i = 0; i < 16; i++) {
                a[4 * i] = pack_bf16(o[8 * i] - z0, o[8 * i + 1] - z0); a[4 * i + 1] = pack_bf16(o[8 * i + 2] - z1, o[8 * i + 3] - z1);
                a[4 * i + 2] = pack_bf16(o[8 * i + 4] - z0, o[8 * i + 5] - z0); a[4 * i + 3] = pack_bf16(o[8 * i + 6] - z1, o[8 * i + 7] - z1);
                if (i * SND0 / 16 != (i + 1) * SND0 / 16) send(i * SND0 / 16);
                if (i % CUT2 == CUT2 - 1) cut();
            }
            if (SC_PAIR) {
                float z[128];
                const uint32_t dkz = dk0 + ((uint32_t)it >> 24), dqz = dq0 + ((uint32_t)it >> 24);
                auto gemm = [&](int c) {
                    mbar_wait(bar_full + 8 * ((IW + c) & 3), ((IW + c) >> 2) & 1);
                    const uint64_t wb = mkaddr(dkz + ((IW + c) & 3) * (KV_BYTES >> 4), dhi), ab = mkaddr(dqz + c * 64, dhi);
                    wg_fence();
#pragma unroll
                    for (int kk = 0; kk < 4; kk++) {
                        if (c | kk) wgmma_ss_n256_tb(z, ab + kk * 2, wb + kk * 512);
                        else wgmma_ss_n256_tb_init(z, ab, wb);
                    }
                    wg_commit();
                };
                auto release2 = [&](int c) {
                    asm volatile("{\n.reg .pred p;\nsetp.ne.u32 p, %1, 0;\n@p mbarrier.arrive.shared::cluster.b64 _, [%0], 2;\n}\n"
                                 ::"r"(rel_addr + 8 * ((IW + c) & 3)), "r"(rel_addr) : "memory");
                };
                mbar_wait(qbar, qphase);
                bar_sync(BAR_ST + 1, 256);
                gemm(0);
#pragma unroll
                for (int i = SND0; i < 16; i++) send(i);
#pragma unroll
                for (int c = 1; c < 4; c++) { gemm(c); if (c == 3) pp_arrive(); wg_wait<1>(); release2(c - 1); }
                wg_wait<0>();
                fence_regs(z);
                release2(3);
#pragma unroll
                for (int i = 0; i < 16; i++) {
                    sts128(sq + warp * 8192 + lane * 16 + i * 512, pack_bf16(z[8 * i], z[8 * i + 1]), pack_bf16(z[8 * i + 2], z[8 * i + 3]),
                           pack_bf16(z[8 * i + 4], z[8 * i + 5]), pack_bf16(z[8 * i + 6], z[8 * i + 7]));
                    if (i == 3 || i == 15) bar_arrive(i == 3 ? BAR_BF : BAR_H0, 256);
                    if (i == 3) cut();
                }
            } else {
#pragma unroll
                for (int i = SND0; i < 16; i++) send(i);
            }
        } else {
            const int pair = SC_PAIR;
            const bool glob = !(pair || SC_TAIL);
            const uint32_t ml = sb + SM_ML + (t & ~3) * 4, src = (glob ? sq : sb + SM_Q + QB_BYTES) + warp * 8192 + lane * 16;
            const uint64_t tm = lds64(s_tm);
            wg_wait<0>();
            fence_regs(o);
            release((IW - 1) & 3);
            float c0, c1;
            row_sums(c0, c1);
            mbar_wait(glob ? qbar : bar_pin, glob ? qphase : 0);
            const float4 ps = lds128f(ml + (glob ? wg * 512 : 512));
            auto load = [&](int i) {
                asm volatile("ld.shared.v4.u32 {%0, %1, %2, %3}, [%4];\n" : "=r"(a[4 * i]), "=r"(a[4 * i + 1]), "=r"(a[4 * i + 2]), "=r"(a[4 * i + 3]) : "r"(src + i * 512) : "memory");
            };
#pragma unroll
            for (int i = 0; i < 8; i++) load(i);
            const float n0 = fmaxf(m0, ps.x), n1 = fmaxf(m1, ps.z);
            const float a0 = ex2(m0 - n0), a1 = ex2(m1 - n1), b0 = ex2(ps.x - n0), b1 = ex2(ps.z - n1);
            const float i0 = rcp(l0 * a0 + ps.y * b0), i1 = rcp(l1 * a1 + ps.w * b1);
            const float r0 = a0 * i0, r1 = a1 * i1;
            c0 *= -r0; c1 *= -r1;
            const uint32_t u0 = pack_bf16(b0 * i0, b0 * i0), u1 = pack_bf16(b1 * i1, b1 * i1);
#pragma unroll
            for (int i = 0; i < 32; i++) {
                if (i == 16) {
                    if (!glob) mbar_wait(bar_pin + 8, 0);
#pragma unroll
                    for (int j = 8; j < 16; j++) load(j);
                }
                a[2 * i] = hfma2(a[2 * i], u0, pack_bf16(fmaf(o[4 * i], r0, c0), fmaf(o[4 * i + 1], r0, c0)));
                a[2 * i + 1] = hfma2(a[2 * i + 1], u1, pack_bf16(fmaf(o[4 * i + 2], r1, c1), fmaf(o[4 * i + 3], r1, c1)));
            }
            float y[2][32];
            auto gemm = [&](int c, int kh) {
                if (!kh) mbar_wait(bar_full + 8 * ((IW + c) & 3), (((IW + c) >> 2) & 1) ^ pair);
                const uint64_t wb = mkaddr(dk0 + ((IW + c) & 3) * (KV_BYTES >> 4), dhi - 192);
                wg_fence();
#pragma unroll
                for (int kk = 8 * kh; kk < 8 * kh + 8; kk++) {
                    if (kk) wgmma_rs_n64_tb(y[c & 1], a[4 * kk], a[4 * kk + 1], a[4 * kk + 2], a[4 * kk + 3], wb + kk * 128);
                    else wgmma_rs_n64_tb_init(y[c & 1], a[0], a[1], a[2], a[3], wb);
                }
                wg_commit();
            };
            const uint32_t stg = sq + warp * 8192 + (lane & 15) * 128 + (((lane >> 4) ^ lane) & 7) * 16;
            uint4 z[4] = {};
            auto load_z = [&](int cb) {
                if (cb < 2) asm volatile("{\n.reg .pred p;\nsetp.ne.s32 p, %0, 0;\n@p bar.sync %1, 256;\n}\n" ::"r"(pair), "r"(cb ? BAR_H0 : BAR_BF) : "memory");
#pragma unroll
                for (int i = 0; i < 4; i++)
                    asm volatile("{\n.reg .pred p;\nsetp.ne.u32 p, %4, 0;\n@p ld.shared.v4.u32 {%0, %1, %2, %3}, [%5];\n}\n"
                                 : "+r"(z[i].x), "+r"(z[i].y), "+r"(z[i].z), "+r"(z[i].w) : "r"(pair), "r"(src - QB_BYTES + (4 * cb + i) * 512) : "memory");
            };
            pp_sync();
            gemm(0, 0);
            gemm(0, 1);
#pragma unroll
            for (int c = 0; c < 4; c++) {
                if (c) load_z(c);
                if (c < 3) gemm(c + 1, 0);
                if (!c) load_z(0);
                if (c < 3) wg_wait<1>(); else wg_wait<0>();
                fence_regs(y[c & 1]);
                const float* x = y[c & 1];
#pragma unroll
                for (int i = 0; i < 4; i++)
                    stmatrix_x4((stg ^ (32 * i)) + c * 2048, hadd2(pack_bf16(x[8 * i], x[8 * i + 1]), z[i].x), hadd2(pack_bf16(x[8 * i + 2], x[8 * i + 3]), z[i].y),
                                hadd2(pack_bf16(x[8 * i + 4], x[8 * i + 5]), z[i].z), hadd2(pack_bf16(x[8 * i + 6], x[8 * i + 7]), z[i].w));
                if (c < 3) gemm(c + 1, 1);
                fence_async_smem();
                __syncwarp();
                asm volatile("{\n.reg .pred p;\nelect.sync _|p, -1;\n"
                             "@p cp.reduce.async.bulk.tensor.4d.global.shared::cta.add.tile.bulk_group [%0, {0, 0, %1, %2}], [%3];\n}\n"
                             ::"l"(tm), "r"(c), "r"((pair ? SC_ZB : 2 * SC_QT0 + wg) * 8 + warp * 2), "r"(sq + warp * 8192 + c * 2048) : "memory");
                if (c == 2 && glob) pp_arrive();
            }
            asm volatile("cp.async.bulk.commit_group;\ncp.async.bulk.wait_group.read 0;\n" ::: "memory");
        }
        } else {
            wg_wait<0>();
        }
        if (SC_TAIL) {
        float o[128];
        auto emit = [&](uint32_t base, int lane, int row0, uint8_t* wdst, int turn) {
#pragma unroll
            for (int hh = 0; hh < 2; hh++) {
                if (turn > 0) mbar_wait(bar_zst + 8 * hh, (turn - 1) & 1);
#pragma unroll
                for (int i = 0; i < 8; i++)
                    stmatrix_x4(base + tile_off(8 * hh + (lane & 7), 4 * i + (lane >> 3)),
                                pack_bf16(o[16 * i + 2 * hh], o[16 * i + 2 * hh + 1]), pack_bf16(o[16 * i + 4 + 2 * hh], o[16 * i + 5 + 2 * hh]),
                                pack_bf16(o[16 * i + 8 + 2 * hh], o[16 * i + 9 + 2 * hh]), pack_bf16(o[16 * i + 12 + 2 * hh], o[16 * i + 13 + 2 * hh]));
                fence_async_smem();
                __syncwarp();
                if (wdst) {
                    if (lane < 4)
                        asm volatile("cp.async.bulk.global.shared::cta.bulk_group [%0], [%1], 1024;\n"
                                     ::"l"(wdst + ((turn & 1) ? hh * 4096 + lane * 1024 : hh * 1024 + lane * QB_BYTES)), "r"(base + hh * 4096 + lane * 1024) : "memory");
                    asm volatile("cp.async.bulk.commit_group;\n" ::: "memory");
                } else {
                    asm volatile("{\n.reg .pred p;\nsetp.eq.s32 p, %3, 0;\n"
                                 "@p cp.reduce.async.bulk.tensor.4d.global.shared::cta.add.tile.bulk_group [%0, {0, 0, 0, %1}], [%2];\n"
                                 "cp.async.bulk.commit_group;\n}\n"
                                 ::"l"(&P.tm_out), "r"((row0 >> 3) + hh), "r"(base + hh * 4096), "r"(lane) : "memory");
                }
            }
            asm volatile("cp.async.bulk.wait_group.read 1;\n" ::: "memory");
            warp_arrive(bar_zst - 8 * wg);
        };
        auto emit_done = [&](bool pending) {
            asm volatile("cp.async.bulk.wait_group.read 0;\n" ::: "memory");
            __syncwarp();
            asm volatile("{\n.reg .pred p;\nsetp.eq.s32 p, %1, 0;\n@p mbarrier.arrive.shared::cta.b64 _, [%0];\n}\n"
                         ::"r"(bar_zst + 8), "r"(pending ? lane : 1) : "memory");
        };
        if (!(rank | wg)) { release(0); release(1); release(2); release(3); }
        bar_sync(BAR_BF, 256);
        warp_arrive(bar_qfree);
        const int nf = rank ? 8 : 0;
        const int nz = nf + 26 + rank;
        const int itz = 4 + SC_NKV + SC_NW;
        bool pend = false;
#pragma unroll 1
        for (int k = wg; k < nz; k += 2) {
            const int iz = itz + (k < nf ? 0 : nf >> 1);
            mbar_wait(qbar, qphase); qphase ^= 1;
#pragma unroll 1
            for (int c = 0; c < 4; c++) {
                mbar_wait(bar_full + 8 * ((iz + c) & 3), ((iz + c) >> 2) & 1);
                const uint64_t wb = mkaddr(dk0 + ((iz + c) & 3) * (KV_BYTES >> 4), dhi), ab = mkaddr(dq0 + c * 64, dhi);
                wg_fence();
                wgmma_ss_n256_tb_pred(o, ab, wb, c);
#pragma unroll
                for (int kk = 1; kk < 4; kk++) wgmma_ss_n256_tb(o, ab + kk * 2, wb + kk * 512);
                wg_commit();
                emit_done(pend);
                pend = false;
            }
            wg_wait<0>();
            fence_regs(o);
            warp_arrive(bar_qfree);
            const int fb = ((k >> 1) + 3) & 3;
            if (k < nf) {
                float2* r255 = (float2*)H.s->r255 + wg * 128 + q;
                if (k < 2) {
                    if (t >= 124) {
#pragma unroll
                        for (int i = 0; i < 32; i++) r255[4 * i] = make_float2(o[4 * i + 2], o[4 * i + 3]);
                    }
                    bar_sync(BAR_WG0 + wg, 128);
                }
#pragma unroll
                for (int i = 0; i < 32; i++) {
                    const float2 v = __ldcg(r255 + 4 * i);
                    o[4 * i] -= v.x; o[4 * i + 1] -= v.y; o[4 * i + 2] -= v.x; o[4 * i + 3] -= v.y;
                }
            }
            int ln = lane;
            asm volatile("" : "+r"(ln));
            emit(sb + SM_KV + QB_BYTES + warp * KV_BYTES, ln, SC_TZB(k - nf) * 64 + warp * 16,
                 k >= nf ? nullptr : (k & 1) ? g_w + (4 + fb) * QB_BYTES + warp * 8192 : g_w + 8 * QB_BYTES + fb * 8192 + warp * 2048, k);
            pend = k + 2 < nz && (k | 1) != nf - 1;
            if (!pend) emit_done(true);
            if ((k | 1) == nf - 1) {
                asm volatile("cp.async.bulk.wait_group 0;\nfence.proxy.async.global;\nfence.acq_rel.gpu;\n" ::: "memory");
                bar_sync(BAR_BF, 256);
                if (tid == 0) red_release(&g_sync[SY_B * 32]);
                if (wg == 0) { release(0); release(1); release(2); release(3); }
            }
        }
        }
        if (wg == 0) pp_sync();
        warp_arrive(bar_end - 8 * wg);
        asm volatile("barrier.cluster.arrive.relaxed.aligned;\n" ::: "memory");
        if (P.E >= 0) return;
        asm volatile("setmaxnreg.dec.sync.aligned.u32 %0;\n" ::"n"(REG_P));
    }
    {
        if (warp != 0) {
            if (warp == 3 && SC_OWNER && SC_PAIR && elect()) {
                flag_wait_bounded(&g_sync[SY_H1 * 32], 79 * ep);
                mbar_wait_sleep(bar_pdone, 0);
                mbar_wait_sleep(bar_pdone + 8, 0);
#pragma unroll 1
                for (int u = 0; u < 16; u++) {
                    bulk_s2g(g_q + SC_QT0 * (2 * QB_BYTES) + u * 4096, sb + SM_Q + u * 4096, 4096);
                    asm volatile("cp.async.bulk.wait_group 0;\n" ::: "memory");
                }
                fence_async_global();
                st_release(&g_qflag[SC_QT0], ep);
            }
            __syncwarp();
            if (SC_TAIL) {
                bar_sync(BAR_AUX, 96);
                if (warp == 1 && elect()) red_release(&g_sync[SY_CSR * 32]);
                __syncwarp();
            }
            mbar_wait_bounded(bar_go, 0);
            if (SC_TAIL) {
                if (warp == 1 && elect()) red_add(&g_sync[SY_DONE * 32]);
                if (warp == 3 && elect()) {
                    int it = 4 + SC_NKV + SC_NW;
                    asm volatile("prefetch.tensormap [%0];\n" ::"l"(&P.tm_out) : "memory");
                    if (rank) {
#pragma unroll 1
                        for (int j = 0; j < 4; j++, it++) {
                            mbar_wait_sleep(bar_empty + 8 * (it & 3), ((it >> 2) & 1) ^ 1);
                            mbar_expect_tx(bar_full + 8 * (it & 3), QB_BYTES);
                            tma_g2s(sb + SM_KV + (it & 3) * KV_BYTES, &P.tm_w[2], 8 * j, bar_full + 8 * (it & 3));
                        }
#pragma unroll 1
                        for (int k = 0; k < 8; k++) {
                            mbar_wait_sleep(bar_qfree + 8 * (k & 1), ((k >> 1) ^ (k & 1) ^ 1) & 1);
                            mbar_expect_tx(bar_q + 8 * (k & 1), QB_BYTES);
#pragma unroll 1
                            for (int hf = 0; hf < 2; hf++)
                                asm volatile("cp.async.bulk.tensor.5d.shared::cluster.global.tile.mbarrier::complete_tx::bytes [%0], [%1, {0, 0, %2, 0, 0}], [%3];\n"
                                             ::"r"(sb + SM_Q + (k & 1) * QB_BYTES + hf * 16384), "l"(&P.tm_w[k & 1]),
                                             "r"(8 * (((k >> 1) + 3) & 3) + 4 * hf), "r"(bar_q + 8 * (k & 1)) : "memory");
                        }
                        flag_wait_bounded(&g_sync[SY_B * 32], ep);
                        fence_async_global();
                    }
#pragma unroll 1
                    for (int j = 0; j < 4; j++, it++) {
                        mbar_wait_sleep(bar_empty + 8 * (it & 3), ((it >> 2) & 1) ^ 1);
                        mbar_expect_tx(bar_full + 8 * (it & 3), QB_BYTES);
                        bulk_g2s(sb + SM_KV + (it & 3) * KV_BYTES, g_w + (4 + j) * QB_BYTES, QB_BYTES, bar_full + 8 * (it & 3));
                    }
#pragma unroll 1
                    for (int k = 0; k < 26 + rank; k++) {
                        if (k == 0 || k == ((GF0 + 1) * NAUX - 16) / 128) { flag_wait_bounded(&g_sync[(k ? SY_AUX1 : SY_AUX0) * 32], NAUX * ep); fence_async_global(); }
                        mbar_wait_sleep(bar_qfree + 8 * (k & 1), ((k >> 1) ^ (k & 1) ^ 1) & 1);
                        mbar_expect_tx(bar_q + 8 * (k & 1), QB_BYTES);
                        bulk_g2s(sb + SM_Q + (k & 1) * QB_BYTES, g_agg + SC_TZB(k) * QB_BYTES, QB_BYTES, bar_q + 8 * (k & 1));
                    }
                }
            } else {
            const int par = ep & 1;
            if (blockIdx.x == 0 && t == 32) g_ovf_n[par ^ 1] = 0;
            if (blockIdx.x == 0 && warp == 1) *(uint4*)(g_hz + (lane >> 3) * 1024 + (lane & 7) * 16) = make_uint4(KV_OFF2, KV_OFF2, KV_OFF2, KV_OFF2);
            const uint32_t wlo = (uint32_t)(uintptr_t)H.s, whi = (uint32_t)((uintptr_t)H.s >> 32);
            const uint32_t blo = wlo + (uint32_t)offsetof(Scratch, bucket);
            {
                const int* pd = P.dst + blockIdx.x * 96 + (t - 32);
                const int* ps = P.src + blockIdx.x * 96 + (t - 32);
#pragma unroll 1
                for (int e = P.E - (blockIdx.x * 96 + (t - 32)); e > 0; e -= CSRU * NAUX * 32, pd += CSRU * NAUX * 32, ps += CSRU * NAUX * 32) {
                    int d[CSRU], sr[CSRU], sl[CSRU];
#pragma unroll
                    for (int i = 0; i < CSRU; i++) {
                        d[i] = e > i * NAUX * 32 ? __ldg(pd + i * NAUX * 32) : NN;
                        sr[i] = e > i * NAUX * 32 ? __ldg(ps + i * NAUX * 32) : 0;
                    }
#pragma unroll
                    for (int i = 0; i < CSRU; i++) {
                        sl[i] = 0;
                        asm volatile("{\n.reg .pred p;\nsetp.lt.s32 p, %2, %3;\n@p atom.relaxed.gpu.global.add.s32 %0, [%1], 1;\n}\n"
                                     : "+r"(sl[i]) : "l"(mkaddr(wlo + (uint32_t)offsetof(Scratch, cnt) + d[i] * 4, whi)), "r"(d[i]), "n"(NN) : "memory");
                    }
                    uint32_t ov = 0;
#pragma unroll
                    for (int i = 0; i < CSRU; i++) {
                        asm volatile("{\n.reg .pred p;\nsetp.lt.s32 p, %3, %4;\n@p st.global.u16 [%1], %2;\n@!p or.b32 %0, %0, %5;\n}\n"
                                     : "+r"(ov) : "l"(mkaddr(blo + d[i] * 128 + (sl[i] & 31) * 4 + (sl[i] >> 5) * 2, whi)), "h"((unsigned short)sr[i]), "r"(sl[i]), "n"(CAP), "r"(1 << i) : "memory");
                    }
#pragma unroll 1
                    for (; ov; ov &= ov - 1) {
                        const int i = (__ffs(ov) - 1) * (NAUX * 32);
                        int at;
                        asm volatile("atom.relaxed.gpu.global.add.s32 %0, [%1], 1;\n" : "=r"(at) : "l"(&g_ovf_n[par]) : "memory");
                        g_ovf[at] = make_int2(__ldg(pd + i), __ldg(ps + i));
                    }
                }
            }
            bar_sync(BAR_AUX, 96);
            if (warp == 1 && elect()) { red_release(&g_sync[SY_CSR * 32]); }
            __syncwarp();
            {
                const int r0 = blockIdx.x * 3 + warp - 1;
                const uint4* xp = (const uint4*)(H.x + r0 * 256) + lane;
                uint4* op = (uint4*)(P.out + r0 * 256) + lane;
#pragma unroll 1
                for (int r = r0; r < NN; r += CPYU * NAUX, xp += CPYU * NAUX * 32, op += CPYU * NAUX * 32) {
                    uint4 v[CPYU];
#pragma unroll
                    for (int i = 0; i < CPYU; i++) if (r + i * NAUX < NN) v[i] = ldg_pinned(xp + i * NAUX * 32);
#pragma unroll
                    for (int i = 0; i < CPYU; i++) if (r + i * NAUX < NN) op[i * NAUX * 32] = v[i];
                }
            }
            if (const int un = (3 - warp) * (NAUX / 3) + (NAUX / 3 - 1) - blockIdx.x; un < 208) {
                flag_wait_bounded(&g_sync[SY_PART * 32], 52 * ep);
                uint8_t* pp = g_part + (un >> 3) * (4 * PART_BYTES);
                float* ml = (float*)(pp + QB_BYTES) + (un & 7) * 32;
                const float4 sa = __ldcg((const float4*)ml + g), sc = __ldcg((const float4*)ml + g + 2 * PART_BYTES / 16);
                const float n0 = fmaxf(sa.x, sc.x), n1 = fmaxf(sa.z, sc.z);
                const uint32_t a0 = pack_bf16(ex2(sa.x - n0), ex2(sa.x - n0)), a1 = pack_bf16(ex2(sa.z - n1), ex2(sa.z - n1));
                const uint32_t b0 = pack_bf16(ex2(sc.x - n0), ex2(sc.x - n0)), b1 = pack_bf16(ex2(sc.z - n1), ex2(sc.z - n1));
                __syncwarp();
                if (q == 0) ((float4*)ml)[g] = make_float4(n0, sa.y * bf_hi(a0) + sc.y * bf_hi(b0), n1, sa.w * bf_hi(a1) + sc.w * bf_hi(b1));
                uint4* d = (uint4*)(pp + (un & 4) * 256 + (un & 7) * 8192) + lane;
#pragma unroll 1
                for (int i = 0; i < 4; i++, d += 128) {
                    uint4 u[4], v[4];
#pragma unroll
                    for (int j = 0; j < 4; j++) { u[j] = __ldcg(d + j * 32); v[j] = __ldcg(d + j * 32 + 2 * PART_BYTES / 16); }
#pragma unroll
                    for (int j = 0; j < 4; j++)
                        d[j * 32] = make_uint4(hfma2(v[j].x, b0, hmul2(u[j].x, a0)), hfma2(v[j].y, b1, hmul2(u[j].y, a1)),
                                               hfma2(v[j].z, b0, hmul2(u[j].z, a0)), hfma2(v[j].w, b1, hmul2(u[j].w, a1)));
                }
            }
            flag_wait_bounded(&g_sync[SY_CSR * 32], NCTA * ep);
            if (warp == 2 && blockIdx.x < 129) {
                uint4* z = blockIdx.x < 128 ? (uint4*)(g_w + blockIdx.x * 1024) + lane : (uint4*)&g_sync[SY_DONE * 32 + 4];
                z[0] = make_uint4(0, 0, 0, 0);
                if (blockIdx.x < 128) z[32] = make_uint4(0, 0, 0, 0);
            }
            {
                const uint32_t lc = (lane >> 3) * 1024 + (lane & 7) * 16;
                const uint32_t alo = wlo ^ lc;
                const int node0 = blockIdx.x * 3 + warp - 17;
                auto node = [&](int i) { const int nd = node0 + i * NAUX; return (int)min((unsigned)nd, (unsigned)(nd + NN)); };
                const int num = (NN - 17 - node0) / NAUX + 1;
                uint32_t mine = 0;
                if (lane < num) {
                    mine = min(__ldcg(&g_cnt[node(lane)]), CAP + 1) | (uint32_t)__ldg((const unsigned short*)P.deg_inv + node(lane)) << 16;
                    g_cnt[node(lane)] = 0;
                }
                auto row = [&](int off) {
                    uint4 v;
                    asm volatile("ld.global.v4.u32 {%0, %1, %2, %3}, [%4];\n"
                                 : "=r"(v.x), "=r"(v.y), "=r"(v.z), "=r"(v.w) : "l"(mkaddr(alo ^ off, whi)));
                    return v;
                };
                auto ents = [&](int i) {
                    uint32_t e;
                    asm volatile("ld.global.cg.u32 %0, [%1];\n" : "=r"(e) : "l"(mkaddr(blo + (min(node(i), NN - 1) * 32 + lane) * 4, whi)));
                    return e;
                };
                auto store = [&](int i, const float (&a)[8]) {
                    const float di = bf_hi(__shfl_sync(~0u, mine, i)) * (1.f / KV_SCALE);
                    const int nd = node(i);
                    *(uint4*)(g_agg + (uint32_t)(((nd >> 3) * 4096 + (nd & 7) * 144) ^ lc)) =
                        make_uint4(pack_bf16(a[0] * di, a[1] * di), pack_bf16(a[2] * di, a[3] * di), pack_bf16(a[4] * di, a[5] * di), pack_bf16(a[6] * di, a[7] * di));
                };
#pragma unroll 1
                for (uint32_t big = __ballot_sync(~0u, (mine & 0xFFFF) > CAP); big; big &= big - 1) {
                    const int i = __ffs(big) - 1, no = __ldcg(&g_ovf_n[par]);
                    float a[8] = {};
#pragma unroll 1
                    for (int k = -64; k < no; k += 32) {
                        const int2 pr = k < 0 ? make_int2(node(i), (ents(i) >> (k & 32) / 2) & 0xFFFF) : k + lane < no ? __ldcg(&g_ovf[k + lane]) : make_int2(-1, 0);
#pragma unroll 1
                        for (uint32_t mk = __ballot_sync(~0u, pr.x == node(i)); mk; mk &= mk - 1) {
                            const uint4 v = row(row_off(__shfl_sync(~0u, pr.y, __ffs(mk) - 1)));
                            a[0] += f16_lo(v.x) - KV_OFF; a[1] += f16_hi(v.x) - KV_OFF; a[2] += f16_lo(v.y) - KV_OFF; a[3] += f16_hi(v.y) - KV_OFF;
                            a[4] += f16_lo(v.z) - KV_OFF; a[5] += f16_hi(v.z) - KV_OFF; a[6] += f16_lo(v.w) - KV_OFF; a[7] += f16_hi(v.w) - KV_OFF;
                        }
                    }
                    store(i, a);
                }
                auto add4 = [&](const uint4& a, const uint4& b) { return make_uint4(hadd2_f16(a.x, b.x), hadd2_f16(a.y, b.y), hadd2_f16(a.z, b.z), hadd2_f16(a.w, b.w)); };
                int ni = -1, left = 0, pos = 0, ec = 0;
                uint32_t en = ents(0);
                uint4 acc = make_uint4(0, 0, 0, 0);
                auto step = [&](uint4 (&v)[4], int& tag) {
                    if (left <= 0 || pos == 32) {
                        if (left > 0) {
                            en = ents(ni) >> 16;
                        } else {
                            ni++;
                            left = __shfl_sync(~0u, mine, ni) & 0xFFFF;
                            if (left > CAP) left = 0;
                        }
                        ec = lane < left ? row_off(en & 0xFFFF) : 0;
                        en = ents(ni + 1);
                        pos = 0;
                    }
                    int of[4];
#pragma unroll
                    for (int j = 0; j < 4; j++) asm volatile("shfl.sync.idx.b32 %0, %1, %2, 31, -1;\n" : "=r"(of[j]) : "r"(ec), "r"(pos + j));
                    acc = add4(acc, add4(add4(add4(v[0], v[1]), make_uint4(KV_NEG4, KV_NEG4, KV_NEG4, KV_NEG4)), add4(v[2], v[3])));
                    asm volatile("" : "+r"(acc.x), "+r"(acc.y), "+r"(acc.z), "+r"(acc.w));
                    asm volatile("{\n.reg .pred p;\nsetp.lt.s32 p, %0, 0;\nL:\n@p pmevent 0;\n@p bra L;\n}\n" ::"r"(ni) : "memory");
#pragma unroll
                    for (int j = 0; j < 4; j++) v[j] = row(of[j]);
                    pos += 4; left -= 4;
                    const int i = tag;
                    tag = left <= 0 ? ni : -1;
                    if (i >= 0) {
                        const float a[8] = {f16_lo(acc.x), f16_hi(acc.x), f16_lo(acc.y), f16_hi(acc.y), f16_lo(acc.z), f16_hi(acc.z), f16_lo(acc.w), f16_hi(acc.w)};
                        if ((__shfl_sync(~0u, mine, i) & 0xFFFF) <= CAP) store(i, a);
                        acc = make_uint4(0, 0, 0, 0);
                        if (i == GF0 || i == 8) {
                            __syncwarp();
                            if (elect()) red_release(&g_sync[(i == 8 ? SY_AUX1 : SY_AUX0) * 32]);
                            __syncwarp();
                        }
                    }
                    return i == num - 1;
                };
                uint4 va[4], vb[4];
#pragma unroll
                for (int j = 0; j < 4; j++) va[j] = vb[j] = make_uint4(KV_OFF2, KV_OFF2, KV_OFF2, KV_OFF2);
                int ta = -1, tb = -1;
#pragma unroll 1
                while (!step(va, ta) && !step(vb, tb)) {}
            }
            bar_sync(BAR_AUX, 96);
            if (warp == 1 && elect()) {
                red_release(&g_sync[SY_AUX * 32]);
                red_add(&g_sync[SY_DONE * 32]);
            }
            }
        }
        __syncwarp();
        asm volatile("barrier.cluster.arrive.relaxed.aligned;\n" ::: "memory");
        if (warp == 1) mbar_wait_bounded(bar_end, 0);
        else if (elect()) mbar_arrive(bar_end);
        __syncwarp();
        asm volatile("barrier.cluster.wait.acquire.aligned;\n" ::: "memory");
    }
}

}

extern "C" void kernel_launch(void* const* d_in, const int* in_sizes, int n_in, void* d_out, int out_size) {
    Hot H;
    Params P;
    H.x = (const __nv_bfloat16*)d_in[0];
    P.src = (const int*)d_in[1];
    P.dst = (const int*)d_in[2];
    P.deg_inv = (const __nv_bfloat16*)d_in[3];
    H.wq = (const __nv_bfloat16*)d_in[5];
    H.wk = (const __nv_bfloat16*)d_in[6];
    P.out = (__nv_bfloat16*)d_out;
    typedef CUresult (*EncodeFn)(CUtensorMap*, CUtensorMapDataType, cuuint32_t, void*, const cuuint64_t*, const cuuint64_t*, const cuuint32_t*,
                                 const cuuint32_t*, CUtensorMapInterleave, CUtensorMapSwizzle, CUtensorMapL2promotion, CUtensorMapFloatOOBfill);
    void* fn = nullptr;
    cudaDriverEntryPointQueryResult qr;
    cudaGetDriverEntryPoint("cuTensorMapEncodeTiled", &fn, cudaEnableDefault, &qr);
    auto encode = [&](CUtensorMap* tm, const void* ptr, int rows, int box_rows, int box_cb = 4) {
        const cuuint64_t dims[4] = {64, 8, 4, (cuuint64_t)rows / 8};
        const cuuint64_t strides[3] = {512, 128, 4096};
        const cuuint32_t box[4] = {64, 8, (cuuint32_t)box_cb, (cuuint32_t)box_rows / 8}, es[4] = {1, 1, 1, 1};
        ((EncodeFn)fn)(tm, CU_TENSOR_MAP_DATA_TYPE_BFLOAT16, 4, (void*)ptr, dims, strides, box, es, CU_TENSOR_MAP_INTERLEAVE_NONE,
                       CU_TENSOR_MAP_SWIZZLE_128B, CU_TENSOR_MAP_L2_PROMOTION_NONE, CU_TENSOR_MAP_FLOAT_OOB_FILL_NONE);
    };
    encode(&P.tm_out, d_out, NN, 8);
    encode(&P.tm_outc, d_out, NN, 16, 1);
    for (int i = 0; i < 2; i++) {
        const cuuint64_t dims[5] = {64, 2, 32, 4, 4};
        const cuuint64_t strides[4] = {512, 4096, 128, 1024};
        const cuuint32_t box[5] = {64, 2, 4, 4, 4}, es[5] = {1, 1, 1, 1, 1};
        ((EncodeFn)fn)(&P.tm_w[i], CU_TENSOR_MAP_DATA_TYPE_BFLOAT16, 5, d_in[i ? 4 : 7], dims, strides, box, es, CU_TENSOR_MAP_INTERLEAVE_NONE,
                       CU_TENSOR_MAP_SWIZZLE_128B, CU_TENSOR_MAP_L2_PROMOTION_NONE, CU_TENSOR_MAP_FLOAT_OOB_FILL_NONE);
    }
    encode(&P.tm_w[2], d_in[8], 256, 64);
    void* raw = nullptr;
    cudaGetSymbolAddress(&raw, g_raw);
    H.s = (Scratch*)(((uintptr_t)raw + ((8 << 20) - 1)) & ~(uintptr_t)((8 << 20) - 1));
    P.dhi = 0x40000100u;
    P.E = in_sizes[1] < MAXE ? in_sizes[1] : MAXE;
    cudaFuncSetAttribute(k_main, cudaFuncAttributeMaxDynamicSharedMemorySize, SM_TOTAL);
    k_main<<<NCTA, 384, SM_TOTAL>>>(H, P);
}
```

```cpp
#include <cuda_runtime.h>
#include <cuda.h>
#include <cuda_bf16.h>
#include <stdint.h>
#include <stddef.h>

namespace {

constexpr int NN = 10000;
constexpr int BN = 80;
constexpr int NKV = NN / BN;
constexpr int NQB = 158;
constexpr int NCTA = 132;
constexpr int NAUX = 3 * (NCTA - 2);
constexpr int STAGES = 4;
constexpr int KV_BYTES = BN * 512;
constexpr int QB_BYTES = 64 * 512;
constexpr int PART_BYTES = QB_BYTES + 512;
constexpr int CAP = 64;
constexpr int MAXE = 160000;

#define QRND(v) (((v) + 0x00040004u) & 0xFFF8FFF8u)
#define GO0 5
#define GO1 37
#define GF0 2
#define CSRU 3
#define CPYU 9
#define REFUP 2.f
#define SND0 10
#define CUT2 2
#define REG_C 224
#define REG_P 56

enum { SY_PART = 4, SY_H1 = 5, SY_CSR = 6, SY_AUX = 7, SY_DONE = 8, SY_AUX0 = 9, SY_B = 10, SY_AUX1 = 11, SY_H0 = 12 };
struct Scratch {
    uint8_t hz[4096 + NN * 512];
    uint8_t w[12 * QB_BYTES];
    int sync[25 * 32];
    int qflag[96];
    int ovf_n[32];
    float r255[512];
    int cnt[NN + 16];
    int bucket[(NN + 1) * 32];
    int2 ovf[MAXE];
    uint8_t q[NQB * QB_BYTES];
    uint8_t agg[NQB * QB_BYTES];
    uint8_t part[52 * 2 * PART_BYTES];
};
static_assert(offsetof(Scratch, ovf) <= (8 << 20), "window");
static_assert(offsetof(Scratch, qflag) == offsetof(Scratch, sync) + 25 * 128, "flags");
static_assert(offsetof(Scratch, w) % 1024 == 0 && offsetof(Scratch, sync) % 128 == 0 &&
              offsetof(Scratch, bucket) % 128 == 0 && offsetof(Scratch, q) % 128 == 0, "alignment");
__device__ uint8_t g_raw[(8 << 20) + sizeof(Scratch)];
#define g_hz (H.s->hz)
#define g_w (H.s->w)
#define g_sync (H.s->sync)
#define g_qflag (H.s->qflag)
#define g_ovf_n (H.s->ovf_n)
#define g_cnt (H.s->cnt)
#define g_bucket (H.s->bucket)
#define g_ovf (H.s->ovf)
#define g_q (H.s->q)
#define g_agg (H.s->agg)
#define g_part (H.s->part)

__device__ __forceinline__ void wgmma_ss_n80(float (&d)[40], uint64_t da, uint64_t db) {
    asm volatile("wgmma.mma_async.sync.aligned.m64n80k16.f32.f16.f16 {"
        "%0, %1, %2, %3, %4, %5, %6, %7, %8, %9, %10, %11, %12, %13, %14, %15, %16, %17, %18, %19, %20, %21, %22, %23, %24, %25, %26, %27, %28, %29, %30, %31, "
        "%32, %33, %34, %35, %36, %37, %38, %39}, %40, %41, 1, 1, 1, 0, 0;\n"
        : "+f"(d[0]), "+f"(d[1]), "+f"(d[2]), "+f"(d[3]), "+f"(d[4]), "+f"(d[5]), "+f"(d[6]), "+f"(d[7]),
          "+f"(d[8]), "+f"(d[9]), "+f"(d[10]), "+f"(d[11]), "+f"(d[12]), "+f"(d[13]), "+f"(d[14]), "+f"(d[15]),
          "+f"(d[16]), "+f"(d[17]), "+f"(d[18]), "+f"(d[19]), "+f"(d[20]), "+f"(d[21]), "+f"(d[22]), "+f"(d[23]),
          "+f"(d[24]), "+f"(d[25]), "+f"(d[26]), "+f"(d[27]), "+f"(d[28]), "+f"(d[29]), "+f"(d[30]), "+f"(d[31]),
          "+f"(d[32]), "+f"(d[33]), "+f"(d[34]), "+f"(d[35]), "+f"(d[36]), "+f"(d[37]), "+f"(d[38]), "+f"(d[39])
        : "l"(da), "l"(db));
}
__device__ __forceinline__ void wgmma_ss_n80_init(float (&d)[40], uint64_t da, uint64_t db) {
    asm volatile("wgmma.mma_async.sync.aligned.m64n80k16.f32.f16.f16 {"
        "%0, %1, %2, %3, %4, %5, %6, %7, %8, %9, %10, %11, %12, %13, %14, %15, %16, %17, %18, %19, %20, %21, %22, %23, %24, %25, %26, %27, %28, %29, %30, %31, "
        "%32, %33, %34, %35, %36, %37, %38, %39}, %40, %41, 0, 1, 1, 0, 0;\n"
        : "=f"(d[0]), "=f"(d[1]), "=f"(d[2]), "=f"(d[3]), "=f"(d[4]), "=f"(d[5]), "=f"(d[6]), "=f"(d[7]),
          "=f"(d[8]), "=f"(d[9]), "=f"(d[10]), "=f"(d[11]), "=f"(d[12]), "=f"(d[13]), "=f"(d[14]), "=f"(d[15]),
          "=f"(d[16]), "=f"(d[17]), "=f"(d[18]), "=f"(d[19]), "=f"(d[20]), "=f"(d[21]), "=f"(d[22]), "=f"(d[23]),
          "=f"(d[24]), "=f"(d[25]), "=f"(d[26]), "=f"(d[27]), "=f"(d[28]), "=f"(d[29]), "=f"(d[30]), "=f"(d[31]),
          "=f"(d[32]), "=f"(d[33]), "=f"(d[34]), "=f"(d[35]), "=f"(d[36]), "=f"(d[37]), "=f"(d[38]), "=f"(d[39])
        : "l"(da), "l"(db));
}
__device__ __forceinline__ void wgmma_rs_n256_tb(float (&d)[128], uint32_t a0, uint32_t a1, uint32_t a2, uint32_t a3, uint64_t db) {
    asm volatile("wgmma.mma_async.sync.aligned.m64n256k16.f32.f16.f16 {"
        "%0, %1, %2, %3, %4, %5, %6, %7, %8, %9, %10, %11, %12, %13, %14, %15, %16, %17, %18, %19, %20, %21, %22, %23, %24, %25, %26, %27, %28, %29, %30, %31, "
        "%32, %33, %34, %35, %36, %37, %38, %39, %40, %41, %42, %43, %44, %45, %46, %47, %48, %49, %50, %51, %52, %53, %54, %55, %56, %57, %58, %59, %60, %61, %62, %63, "
        "%64, %65, %66, %67, %68, %69, %70, %71, %72, %73, %74, %75, %76, %77, %78, %79, %80, %81, %82, %83, %84, %85, %86, %87, %88, %89, %90, %91, %92, %93, %94, %95, "
        "%96, %97, %98, %99, %100, %101, %102, %103, %104, %105, %106, %107, %108, %109, %110, %111, %112, %113, %114, %115, %116, %117, %118, %119, %120, %121, %122, %123, %124, %125, %126, %127}, {%128, %129, %130, %131}, %132, 1, 1, 1, 1;\n"
        : "+f"(d[0]), "+f"(d[1]), "+f"(d[2]), "+f"(d[3]), "+f"(d[4]), "+f"(d[5]), "+f"(d[6]), "+f"(d[7]),
          "+f"(d[8]), "+f"(d[9]), "+f"(d[10]), "+f"(d[11]), "+f"(d[12]), "+f"(d[13]), "+f"(d[14]), "+f"(d[15]),
          "+f"(d[16]), "+f"(d[17]), "+f"(d[18]), "+f"(d[19]), "+f"(d[20]), "+f"(d[21]), "+f"(d[22]), "+f"(d[23]),
          "+f"(d[24]), "+f"(d[25]), "+f"(d[26]), "+f"(d[27]), "+f"(d[28]), "+f"(d[29]), "+f"(d[30]), "+f"(d[31]),
          "+f"(d[32]), "+f"(d[33]), "+f"(d[34]), "+f"(d[35]), "+f"(d[36]), "+f"(d[37]), "+f"(d[38]), "+f"(d[39]),
          "+f"(d[40]), "+f"(d[41]), "+f"(d[42]), "+f"(d[43]), "+f"(d[44]), "+f"(d[45]), "+f"(d[46]), "+f"(d[47]),
          "+f"(d[48]), "+f"(d[49]), "+f"(d[50]), "+f"(d[51]), "+f"(d[52]), "+f"(d[53]), "+f"(d[54]), "+f"(d[55]),
          "+f"(d[56]), "+f"(d[57]), "+f"(d[58]), "+f"(d[59]), "+f"(d[60]), "+f"(d[61]), "+f"(d[62]), "+f"(d[63]),
          "+f"(d[64]), "+f"(d[65]), "+f"(d[66]), "+f"(d[67]), "+f"(d[68]), "+f"(d[69]), "+f"(d[70]), "+f"(d[71]),
          "+f"(d[72]), "+f"(d[73]), "+f"(d[74]), "+f"(d[75]), "+f"(d[76]), "+f"(d[77]), "+f"(d[78]), "+f"(d[79]),
          "+f"(d[80]), "+f"(d[81]), "+f"(d[82]), "+f"(d[83]), "+f"(d[84]), "+f"(d[85]), "+f"(d[86]), "+f"(d[87]),
          "+f"(d[88]), "+f"(d[89]), "+f"(d[90]), "+f"(d[91]), "+f"(d[92]), "+f"(d[93]), "+f"(d[94]), "+f"(d[95]),
          "+f"(d[96]), "+f"(d[97]), "+f"(d[98]), "+f"(d[99]), "+f"(d[100]), "+f"(d[101]), "+f"(d[102]), "+f"(d[103]),
          "+f"(d[104]), "+f"(d[105]), "+f"(d[106]), "+f"(d[107]), "+f"(d[108]), "+f"(d[109]), "+f"(d[110]), "+f"(d[111]),
          "+f"(d[112]), "+f"(d[113]), "+f"(d[114]), "+f"(d[115]), "+f"(d[116]), "+f"(d[117]), "+f"(d[118]), "+f"(d[119]),
          "+f"(d[120]), "+f"(d[121]), "+f"(d[122]), "+f"(d[123]), "+f"(d[124]), "+f"(d[125]), "+f"(d[126]), "+f"(d[127])
        : "r"(a0), "r"(a1), "r"(a2), "r"(a3), "l"(db));
}
__device__ __forceinline__ void wgmma_rs_n256_tb_init(float (&d)[128], uint32_t a0, uint32_t a1, uint32_t a2, uint32_t a3, uint64_t db) {
    asm volatile("wgmma.mma_async.sync.aligned.m64n256k16.f32.f16.f16 {"
        "%0, %1, %2, %3, %4, %5, %6, %7, %8, %9, %10, %11, %12, %13, %14, %15, %16, %17, %18, %19, %20, %21, %22, %23, %24, %25, %26, %27, %28, %29, %30, %31, "
        "%32, %33, %34, %35, %36, %37, %38, %39, %40, %41, %42, %43, %44, %45, %46, %47, %48, %49, %50, %51, %52, %53, %54, %55, %56, %57, %58, %59, %60, %61, %62, %63, "
        "%64, %65, %66, %67, %68, %69, %70, %71, %72, %73, %74, %75, %76, %77, %78, %79, %80, %81, %82, %83, %84, %85, %86, %87, %88, %89, %90, %91, %92, %93, %94, %95, "
        "%96, %97, %98, %99, %100, %101, %102, %103, %104, %105, %106, %107, %108, %109, %110, %111, %112, %113, %114, %115, %116, %117, %118, %119, %120, %121, %122, %123, %124, %125, %126, %127}, {%128, %129, %130, %131}, %132, 0, 1, 1, 1;\n"
        : "=f"(d[0]), "=f"(d[1]), "=f"(d[2]), "=f"(d[3]), "=f"(d[4]), "=f"(d[5]), "=f"(d[6]), "=f"(d[7]),
          "=f"(d[8]), "=f"(d[9]), "=f"(d[10]), "=f"(d[11]), "=f"(d[12]), "=f"(d[13]), "=f"(d[14]), "=f"(d[15]),
          "=f"(d[16]), "=f"(d[17]), "=f"(d[18]), "=f"(d[19]), "=f"(d[20]), "=f"(d[21]), "=f"(d[22]), "=f"(d[23]),
          "=f"(d[24]), "=f"(d[25]), "=f"(d[26]), "=f"(d[27]), "=f"(d[28]), "=f"(d[29]), "=f"(d[30]), "=f"(d[31]),
          "=f"(d[32]), "=f"(d[33]), "=f"(d[34]), "=f"(d[35]), "=f"(d[36]), "=f"(d[37]), "=f"(d[38]), "=f"(d[39]),
          "=f"(d[40]), "=f"(d[41]), "=f"(d[42]), "=f"(d[43]), "=f"(d[44]), "=f"(d[45]), "=f"(d[46]), "=f"(d[47]),
          "=f"(d[48]), "=f"(d[49]), "=f"(d[50]), "=f"(d[51]), "=f"(d[52]), "=f"(d[53]), "=f"(d[54]), "=f"(d[55]),
          "=f"(d[56]), "=f"(d[57]), "=f"(d[58]), "=f"(d[59]), "=f"(d[60]), "=f"(d[61]), "=f"(d[62]), "=f"(d[63]),
          "=f"(d[64]), "=f"(d[65]), "=f"(d[66]), "=f"(d[67]), "=f"(d[68]), "=f"(d[69]), "=f"(d[70]), "=f"(d[71]),
          "=f"(d[72]), "=f"(d[73]), "=f"(d[74]), "=f"(d[75]), "=f"(d[76]), "=f"(d[77]), "=f"(d[78]), "=f"(d[79]),
          "=f"(d[80]), "=f"(d[81]), "=f"(d[82]), "=f"(d[83]), "=f"(d[84]), "=f"(d[85]), "=f"(d[86]), "=f"(d[87]),
          "=f"(d[88]), "=f"(d[89]), "=f"(d[90]), "=f"(d[91]), "=f"(d[92]), "=f"(d[93]), "=f"(d[94]), "=f"(d[95]),
          "=f"(d[96]), "=f"(d[97]), "=f"(d[98]), "=f"(d[99]), "=f"(d[100]), "=f"(d[101]), "=f"(d[102]), "=f"(d[103]),
          "=f"(d[104]), "=f"(d[105]), "=f"(d[106]), "=f"(d[107]), "=f"(d[108]), "=f"(d[109]), "=f"(d[110]), "=f"(d[111]),
          "=f"(d[112]), "=f"(d[113]), "=f"(d[114]), "=f"(d[115]), "=f"(d[116]), "=f"(d[117]), "=f"(d[118]), "=f"(d[119]),
          "=f"(d[120]), "=f"(d[121]), "=f"(d[122]), "=f"(d[123]), "=f"(d[124]), "=f"(d[125]), "=f"(d[126]), "=f"(d[127])
        : "r"(a0), "r"(a1), "r"(a2), "r"(a3), "l"(db));
}
__device__ __forceinline__ void wgmma_rs_n256_tb_pred(float (&d)[128], uint32_t a0, uint32_t a1, uint32_t a2, uint32_t a3, uint64_t db, int acc) {
    asm volatile("{\n.reg .pred p;\nsetp.ne.s32 p, %133, 0;\nwgmma.mma_async.sync.aligned.m64n256k16.f32.f16.f16 {"
        "%0, %1, %2, %3, %4, %5, %6, %7, %8, %9, %10, %11, %12, %13, %14, %15, %16, %17, %18, %19, %20, %21, %22, %23, %24, %25, %26, %27, %28, %29, %30, %31, "
        "%32, %33, %34, %35, %36, %37, %38, %39, %40, %41, %42, %43, %44, %45, %46, %47, %48, %49, %50, %51, %52, %53, %54, %55, %56, %57, %58, %59, %60, %61, %62, %63, "
        "%64, %65, %66, %67, %68, %69, %70, %71, %72, %73, %74, %75, %76, %77, %78, %79, %80, %81, %82, %83, %84, %85, %86, %87, %88, %89, %90, %91, %92, %93, %94, %95, "
        "%96, %97, %98, %99, %100, %101, %102, %103, %104, %105, %106, %107, %108, %109, %110, %111, %112, %113, %114, %115, %116, %117, %118, %119, %120, %121, %122, %123, %124, %125, %126, %127}, {%128, %129, %130, %131}, %132, p, 1, 1, 1;\n}\n"
        : "+f"(d[0]), "+f"(d[1]), "+f"(d[2]), "+f"(d[3]), "+f"(d[4]), "+f"(d[5]), "+f"(d[6]), "+f"(d[7]),
          "+f"(d[8]), "+f"(d[9]), "+f"(d[10]), "+f"(d[11]), "+f"(d[12]), "+f"(d[13]), "+f"(d[14]), "+f"(d[15]),
          "+f"(d[16]), "+f"(d[17]), "+f"(d[18]), "+f"(d[19]), "+f"(d[20]), "+f"(d[21]), "+f"(d[22]), "+f"(d[23]),
          "+f"(d[24]), "+f"(d[25]), "+f"(d[26]), "+f"(d[27]), "+f"(d[28]), "+f"(d[29]), "+f"(d[30]), "+f"(d[31]),
          "+f"(d[32]), "+f"(d[33]), "+f"(d[34]), "+f"(d[35]), "+f"(d[36]), "+f"(d[37]), "+f"(d[38]), "+f"(d[39]),
          "+f"(d[40]), "+f"(d[41]), "+f"(d[42]), "+f"(d[43]), "+f"(d[44]), "+f"(d[45]), "+f"(d[46]), "+f"(d[47]),
          "+f"(d[48]), "+f"(d[49]), "+f"(d[50]), "+f"(d[51]), "+f"(d[52]), "+f"(d[53]), "+f"(d[54]), "+f"(d[55]),
          "+f"(d[56]), "+f"(d[57]), "+f"(d[58]), "+f"(d[59]), "+f"(d[60]), "+f"(d[61]), "+f"(d[62]), "+f"(d[63]),
          "+f"(d[64]), "+f"(d[65]), "+f"(d[66]), "+f"(d[67]), "+f"(d[68]), "+f"(d[69]), "+f"(d[70]), "+f"(d[71]),
          "+f"(d[72]), "+f"(d[73]), "+f"(d[74]), "+f"(d[75]), "+f"(d[76]), "+f"(d[77]), "+f"(d[78]), "+f"(d[79]),
          "+f"(d[80]), "+f"(d[81]), "+f"(d[82]), "+f"(d[83]), "+f"(d[84]), "+f"(d[85]), "+f"(d[86]), "+f"(d[87]),
          "+f"(d[88]), "+f"(d[89]), "+f"(d[90]), "+f"(d[91]), "+f"(d[92]), "+f"(d[93]), "+f"(d[94]), "+f"(d[95]),
          "+f"(d[96]), "+f"(d[97]), "+f"(d[98]), "+f"(d[99]), "+f"(d[100]), "+f"(d[101]), "+f"(d[102]), "+f"(d[103]),
          "+f"(d[104]), "+f"(d[105]), "+f"(d[106]), "+f"(d[107]), "+f"(d[108]), "+f"(d[109]), "+f"(d[110]), "+f"(d[111]),
          "+f"(d[112]), "+f"(d[113]), "+f"(d[114]), "+f"(d[115]), "+f"(d[116]), "+f"(d[117]), "+f"(d[118]), "+f"(d[119]),
          "+f"(d[120]), "+f"(d[121]), "+f"(d[122]), "+f"(d[123]), "+f"(d[124]), "+f"(d[125]), "+f"(d[126]), "+f"(d[127])
        : "r"(a0), "r"(a1), "r"(a2), "r"(a3), "l"(db), "r"(acc));
}
__device__ __forceinline__ void wgmma_ss_n256_tb(float (&d)[128], uint64_t da, uint64_t db) {
    asm volatile("wgmma.mma_async.sync.aligned.m64n256k16.f32.bf16.bf16 {"
        "%0, %1, %2, %3, %4, %5, %6, %7, %8, %9, %10, %11, %12, %13, %14, %15, %16, %17, %18, %19, %20, %21, %22, %23, %24, %25, %26, %27, %28, %29, %30, %31, "
        "%32, %33, %34, %35, %36, %37, %38, %39, %40, %41, %42, %43, %44, %45, %46, %47, %48, %49, %50, %51, %52, %53, %54, %55, %56, %57, %58, %59, %60, %61, %62, %63, "
        "%64, %65, %66, %67, %68, %69, %70, %71, %72, %73, %74, %75, %76, %77, %78, %79, %80, %81, %82, %83, %84, %85, %86, %87, %88, %89, %90, %91, %92, %93, %94, %95, "
        "%96, %97, %98, %99, %100, %101, %102, %103, %104, %105, %106, %107, %108, %109, %110, %111, %112, %113, %114, %115, %116, %117, %118, %119, %120, %121, %122, %123, %124, %125, %126, %127}, %128, %129, 1, 1, 1, 0, 1;\n"
        : "+f"(d[0]), "+f"(d[1]), "+f"(d[2]), "+f"(d[3]), "+f"(d[4]), "+f"(d[5]), "+f"(d[6]), "+f"(d[7]),
          "+f"(d[8]), "+f"(d[9]), "+f"(d[10]), "+f"(d[11]), "+f"(d[12]), "+f"(d[13]), "+f"(d[14]), "+f"(d[15]),
          "+f"(d[16]), "+f"(d[17]), "+f"(d[18]), "+f"(d[19]), "+f"(d[20]), "+f"(d[21]), "+f"(d[22]), "+f"(d[23]),
          "+f"(d[24]), "+f"(d[25]), "+f"(d[26]), "+f"(d[27]), "+f"(d[28]), "+f"(d[29]), "+f"(d[30]), "+f"(d[31]),
          "+f"(d[32]), "+f"(d[33]), "+f"(d[34]), "+f"(d[35]), "+f"(d[36]), "+f"(d[37]), "+f"(d[38]), "+f"(d[39]),
          "+f"(d[40]), "+f"(d[41]), "+f"(d[42]), "+f"(d[43]), "+f"(d[44]), "+f"(d[45]), "+f"(d[46]), "+f"(d[47]),
          "+f"(d[48]), "+f"(d[49]), "+f"(d[50]), "+f"(d[51]), "+f"(d[52]), "+f"(d[53]), "+f"(d[54]), "+f"(d[55]),
          "+f"(d[56]), "+f"(d[57]), "+f"(d[58]), "+f"(d[59]), "+f"(d[60]), "+f"(d[61]), "+f"(d[62]), "+f"(d[63]),
          "+f"(d[64]), "+f"(d[65]), "+f"(d[66]), "+f"(d[67]), "+f"(d[68]), "+f"(d[69]), "+f"(d[70]), "+f"(d[71]),
          "+f"(d[72]), "+f"(d[73]), "+f"(d[74]), "+f"(d[75]), "+f"(d[76]), "+f"(d[77]), "+f"(d[78]), "+f"(d[79]),
          "+f"(d[80]), "+f"(d[81]), "+f"(d[82]), "+f"(d[83]), "+f"(d[84]), "+f"(d[85]), "+f"(d[86]), "+f"(d[87]),
          "+f"(d[88]), "+f"(d[89]), "+f"(d[90]), "+f"(d[91]), "+f"(d[92]), "+f"(d[93]), "+f"(d[94]), "+f"(d[95]),
          "+f"(d[96]), "+f"(d[97]), "+f"(d[98]), "+f"(d[99]), "+f"(d[100]), "+f"(d[101]), "+f"(d[102]), "+f"(d[103]),
          "+f"(d[104]), "+f"(d[105]), "+f"(d[106]), "+f"(d[107]), "+f"(d[108]), "+f"(d[109]), "+f"(d[110]), "+f"(d[111]),
          "+f"(d[112]), "+f"(d[113]), "+f"(d[114]), "+f"(d[115]), "+f"(d[116]), "+f"(d[117]), "+f"(d[118]), "+f"(d[119]),
          "+f"(d[120]), "+f"(d[121]), "+f"(d[122]), "+f"(d[123]), "+f"(d[124]), "+f"(d[125]), "+f"(d[126]), "+f"(d[127])
        : "l"(da), "l"(db));
}
__device__ __forceinline__ void wgmma_ss_n256_tb_init(float (&d)[128], uint64_t da, uint64_t db) {
    asm volatile("wgmma.mma_async.sync.aligned.m64n256k16.f32.bf16.bf16 {"
        "%0, %1, %2, %3, %4, %5, %6, %7, %8, %9, %10, %11, %12, %13, %14, %15, %16, %17, %18, %19, %20, %21, %22, %23, %24, %25, %26, %27, %28, %29, %30, %31, "
        "%32, %33, %34, %35, %36, %37, %38, %39, %40, %41, %42, %43, %44, %45, %46, %47, %48, %49, %50, %51, %52, %53, %54, %55, %56, %57, %58, %59, %60, %61, %62, %63, "
        "%64, %65, %66, %67, %68, %69, %70, %71, %72, %73, %74, %75, %76, %77, %78, %79, %80, %81, %82, %83, %84, %85, %86, %87, %88, %89, %90, %91, %92, %93, %94, %95, "
        "%96, %97, %98, %99, %100, %101, %102, %103, %104, %105, %106, %107, %108, %109, %110, %111, %112, %113, %114, %115, %116, %117, %118, %119, %120, %121, %122, %123, %124, %125, %126, %127}, %128, %129, 0, 1, 1, 0, 1;\n"
        : "=f"(d[0]), "=f"(d[1]), "=f"(d[2]), "=f"(d[3]), "=f"(d[4]), "=f"(d[5]), "=f"(d[6]), "=f"(d[7]),
          "=f"(d[8]), "=f"(d[9]), "=f"(d[10]), "=f"(d[11]), "=f"(d[12]), "=f"(d[13]), "=f"(d[14]), "=f"(d[15]),
          "=f"(d[16]), "=f"(d[17]), "=f"(d[18]), "=f"(d[19]), "=f"(d[20]), "=f"(d[21]), "=f"(d[22]), "=f"(d[23]),
          "=f"(d[24]), "=f"(d[25]), "=f"(d[26]), "=f"(d[27]), "=f"(d[28]), "=f"(d[29]), "=f"(d[30]), "=f"(d[31]),
          "=f"(d[32]), "=f"(d[33]), "=f"(d[34]), "=f"(d[35]), "=f"(d[36]), "=f"(d[37]), "=f"(d[38]), "=f"(d[39]),
          "=f"(d[40]), "=f"(d[41]), "=f"(d[42]), "=f"(d[43]), "=f"(d[44]), "=f"(d[45]), "=f"(d[46]), "=f"(d[47]),
          "=f"(d[48]), "=f"(d[49]), "=f"(d[50]), "=f"(d[51]), "=f"(d[52]), "=f"(d[53]), "=f"(d[54]), "=f"(d[55]),
          "=f"(d[56]), "=f"(d[57]), "=f"(d[58]), "=f"(d[59]), "=f"(d[60]), "=f"(d[61]), "=f"(d[62]), "=f"(d[63]),
          "=f"(d[64]), "=f"(d[65]), "=f"(d[66]), "=f"(d[67]), "=f"(d[68]), "=f"(d[69]), "=f"(d[70]), "=f"(d[71]),
          "=f"(d[72]), "=f"(d[73]), "=f"(d[74]), "=f"(d[75]), "=f"(d[76]), "=f"(d[77]), "=f"(d[78]), "=f"(d[79]),
          "=f"(d[80]), "=f"(d[81]), "=f"(d[82]), "=f"(d[83]), "=f"(d[84]), "=f"(d[85]), "=f"(d[86]), "=f"(d[87]),
          "=f"(d[88]), "=f"(d[89]), "=f"(d[90]), "=f"(d[91]), "=f"(d[92]), "=f"(d[93]), "=f"(d[94]), "=f"(d[95]),
          "=f"(d[96]), "=f"(d[97]), "=f"(d[98]), "=f"(d[99]), "=f"(d[100]), "=f"(d[101]), "=f"(d[102]), "=f"(d[103]),
          "=f"(d[104]), "=f"(d[105]), "=f"(d[106]), "=f"(d[107]), "=f"(d[108]), "=f"(d[109]), "=f"(d[110]), "=f"(d[111]),
          "=f"(d[112]), "=f"(d[113]), "=f"(d[114]), "=f"(d[115]), "=f"(d[116]), "=f"(d[117]), "=f"(d[118]), "=f"(d[119]),
          "=f"(d[120]), "=f"(d[121]), "=f"(d[122]), "=f"(d[123]), "=f"(d[124]), "=f"(d[125]), "=f"(d[126]), "=f"(d[127])
        : "l"(da), "l"(db));
}
__device__ __forceinline__ void wgmma_ss_n256_tb_pred(float (&d)[128], uint64_t da, uint64_t db, int acc) {
    asm volatile("{\n.reg .pred p;\nsetp.ne.s32 p, %130, 0;\nwgmma.mma_async.sync.aligned.m64n256k16.f32.bf16.bf16 {"
        "%0, %1, %2, %3, %4, %5, %6, %7, %8, %9, %10, %11, %12, %13, %14, %15, %16, %17, %18, %19, %20, %21, %22, %23, %24, %25, %26, %27, %28, %29, %30, %31, "
        "%32, %33, %34, %35, %36, %37, %38, %39, %40, %41, %42, %43, %44, %45, %46, %47, %48, %49, %50, %51, %52, %53, %54, %55, %56, %57, %58, %59, %60, %61, %62, %63, "
        "%64, %65, %66, %67, %68, %69, %70, %71, %72, %73, %74, %75, %76, %77, %78, %79, %80, %81, %82, %83, %84, %85, %86, %87, %88, %89, %90, %91, %92, %93, %94, %95, "
        "%96, %97, %98, %99, %100, %101, %102, %103, %104, %105, %106, %107, %108, %109, %110, %111, %112, %113, %114, %115, %116, %117, %118, %119, %120, %121, %122, %123, %124, %125, %126, %127}, %128, %129, p, 1, 1, 0, 1;\n}\n"
        : "+f"(d[0]), "+f"(d[1]), "+f"(d[2]), "+f"(d[3]), "+f"(d[4]), "+f"(d[5]), "+f"(d[6]), "+f"(d[7]),
          "+f"(d[8]), "+f"(d[9]), "+f"(d[10]), "+f"(d[11]), "+f"(d[12]), "+f"(d[13]), "+f"(d[14]), "+f"(d[15]),
          "+f"(d[16]), "+f"(d[17]), "+f"(d[18]), "+f"(d[19]), "+f"(d[20]), "+f"(d[21]), "+f"(d[22]), "+f"(d[23]),
          "+f"(d[24]), "+f"(d[25]), "+f"(d[26]), "+f"(d[27]), "+f"(d[28]), "+f"(d[29]), "+f"(d[30]), "+f"(d[31]),
          "+f"(d[32]), "+f"(d[33]), "+f"(d[34]), "+f"(d[35]), "+f"(d[36]), "+f"(d[37]), "+f"(d[38]), "+f"(d[39]),
          "+f"(d[40]), "+f"(d[41]), "+f"(d[42]), "+f"(d[43]), "+f"(d[44]), "+f"(d[45]), "+f"(d[46]), "+f"(d[47]),
          "+f"(d[48]), "+f"(d[49]), "+f"(d[50]), "+f"(d[51]), "+f"(d[52]), "+f"(d[53]), "+f"(d[54]), "+f"(d[55]),
          "+f"(d[56]), "+f"(d[57]), "+f"(d[58]), "+f"(d[59]), "+f"(d[60]), "+f"(d[61]), "+f"(d[62]), "+f"(d[63]),
          "+f"(d[64]), "+f"(d[65]), "+f"(d[66]), "+f"(d[67]), "+f"(d[68]), "+f"(d[69]), "+f"(d[70]), "+f"(d[71]),
          "+f"(d[72]), "+f"(d[73]), "+f"(d[74]), "+f"(d[75]), "+f"(d[76]), "+f"(d[77]), "+f"(d[78]), "+f"(d[79]),
          "+f"(d[80]), "+f"(d[81]), "+f"(d[82]), "+f"(d[83]), "+f"(d[84]), "+f"(d[85]), "+f"(d[86]), "+f"(d[87]),
          "+f"(d[88]), "+f"(d[89]), "+f"(d[90]), "+f"(d[91]), "+f"(d[92]), "+f"(d[93]), "+f"(d[94]), "+f"(d[95]),
          "+f"(d[96]), "+f"(d[97]), "+f"(d[98]), "+f"(d[99]), "+f"(d[100]), "+f"(d[101]), "+f"(d[102]), "+f"(d[103]),
          "+f"(d[104]), "+f"(d[105]), "+f"(d[106]), "+f"(d[107]), "+f"(d[108]), "+f"(d[109]), "+f"(d[110]), "+f"(d[111]),
          "+f"(d[112]), "+f"(d[113]), "+f"(d[114]), "+f"(d[115]), "+f"(d[116]), "+f"(d[117]), "+f"(d[118]), "+f"(d[119]),
          "+f"(d[120]), "+f"(d[121]), "+f"(d[122]), "+f"(d[123]), "+f"(d[124]), "+f"(d[125]), "+f"(d[126]), "+f"(d[127])
        : "l"(da), "l"(db), "r"(acc));
}
__device__ __forceinline__ void wgmma_rs_n64_tb(float (&d)[32], uint32_t a0, uint32_t a1, uint32_t a2, uint32_t a3, uint64_t db) {
    asm volatile("wgmma.mma_async.sync.aligned.m64n64k16.f32.bf16.bf16 {"
        "%0, %1, %2, %3, %4, %5, %6, %7, %8, %9, %10, %11, %12, %13, %14, %15, %16, %17, %18, %19, %20, %21, %22, %23, %24, %25, %26, %27, %28, %29, %30, %31}, {%32, %33, %34, %35}, %36, 1, 1, 1, 1;\n"
        : "+f"(d[0]), "+f"(d[1]), "+f"(d[2]), "+f"(d[3]), "+f"(d[4]), "+f"(d[5]), "+f"(d[6]), "+f"(d[7]),
          "+f"(d[8]), "+f"(d[9]), "+f"(d[10]), "+f"(d[11]), "+f"(d[12]), "+f"(d[13]), "+f"(d[14]), "+f"(d[15]),
          "+f"(d[16]), "+f"(d[17]), "+f"(d[18]), "+f"(d[19]), "+f"(d[20]), "+f"(d[21]), "+f"(d[22]), "+f"(d[23]),
          "+f"(d[24]), "+f"(d[25]), "+f"(d[26]), "+f"(d[27]), "+f"(d[28]), "+f"(d[29]), "+f"(d[30]), "+f"(d[31])
        : "r"(a0), "r"(a1), "r"(a2), "r"(a3), "l"(db));
}
__device__ __forceinline__ void wgmma_rs_n64_tb_init(float (&d)[32], uint32_t a0, uint32_t a1, uint32_t a2, uint32_t a3, uint64_t db) {
    asm volatile("wgmma.mma_async.sync.aligned.m64n64k16.f32.bf16.bf16 {"
        "%0, %1, %2, %3, %4, %5, %6, %7, %8, %9, %10, %11, %12, %13, %14, %15, %16, %17, %18, %19, %20, %21, %22, %23, %24, %25, %26, %27, %28, %29, %30, %31}, {%32, %33, %34, %35}, %36, 0, 1, 1, 1;\n"
        : "=f"(d[0]), "=f"(d[1]), "=f"(d[2]), "=f"(d[3]), "=f"(d[4]), "=f"(d[5]), "=f"(d[6]), "=f"(d[7]),
          "=f"(d[8]), "=f"(d[9]), "=f"(d[10]), "=f"(d[11]), "=f"(d[12]), "=f"(d[13]), "=f"(d[14]), "=f"(d[15]),
          "=f"(d[16]), "=f"(d[17]), "=f"(d[18]), "=f"(d[19]), "=f"(d[20]), "=f"(d[21]), "=f"(d[22]), "=f"(d[23]),
          "=f"(d[24]), "=f"(d[25]), "=f"(d[26]), "=f"(d[27]), "=f"(d[28]), "=f"(d[29]), "=f"(d[30]), "=f"(d[31])
        : "r"(a0), "r"(a1), "r"(a2), "r"(a3), "l"(db));
}

__device__ __forceinline__ void wg_fence() { asm volatile("wgmma.fence.sync.aligned;\n" ::: "memory"); }
__device__ __forceinline__ void wg_commit() { asm volatile("wgmma.commit_group.sync.aligned;\n" ::: "memory"); }
template <int N> __device__ __forceinline__ void wg_wait() { asm volatile("wgmma.wait_group.sync.aligned %0;\n" ::"n"(N) : "memory"); }
template <int N> __device__ __forceinline__ void fence_regs(float (&a)[N]) {
#pragma unroll
    for (int i = 0; i < N; i++) asm volatile("" : "+f"(a[i])::"memory");
}
template <int N> __device__ __forceinline__ void fence_regs(uint32_t (&a)[N]) {
#pragma unroll
    for (int i = 0; i < N; i++) asm volatile("" : "+r"(a[i])::"memory");
}
__device__ __forceinline__ void mbar_init(uint32_t bar, uint32_t cnt) {
    asm volatile("mbarrier.init.shared::cta.b64 [%0], %1;\n" ::"r"(bar), "r"(cnt) : "memory");
}
__device__ __forceinline__ void mbar_expect_tx(uint32_t bar, uint32_t bytes) {
    asm volatile("mbarrier.arrive.expect_tx.shared::cta.b64 _, [%0], %1;\n" ::"r"(bar), "r"(bytes) : "memory");
}
__device__ __forceinline__ void mbar_wait(uint32_t bar, uint32_t parity) {
    asm volatile("{\n.reg .pred p;\nLW:\nmbarrier.try_wait.parity.shared::cta.b64 p, [%0], %1;\n@!p pmevent 0;\n@!p bra LW;\n}\n" ::"r"(bar), "r"(parity) : "memory");
}
__device__ __forceinline__ void mbar_wait_sleep(uint32_t bar, uint32_t parity) {
    asm volatile("{\n.reg .pred p;\nLW:\nmbarrier.try_wait.parity.shared::cta.b64 p, [%0], %1, 20000;\n@!p pmevent 0;\n@!p bra LW;\n}\n" ::"r"(bar), "r"(parity) : "memory");
}
__device__ __forceinline__ void mbar_wait_bounded(uint32_t bar, uint32_t parity) {
    asm volatile("{\n.reg .pred p;\n.reg .u32 c;\nmov.u32 c, 0;\nLW:\nmbarrier.try_wait.parity.shared::cta.b64 p, [%0], %1, 20000;\n@p bra LD;\n"
                 "add.u32 c, c, 1;\nsetp.ge.u32 p, c, 262144;\n@p trap;\nbra LW;\nLD:\n}\n" ::"r"(bar), "r"(parity) : "memory");
}
__device__ __forceinline__ void flag_wait(const int* p, int v) {
    asm volatile("{\n.reg .pred p;\n.reg .s32 f;\nLW:\nld.acquire.gpu.global.s32 f, [%0];\nsub.s32 f, f, %1;\nsetp.lt.s32 p, f, 0;\n@p bra LW;\n}\n" ::"l"(p), "r"(v) : "memory");
}
__device__ __forceinline__ void flag_wait_bounded(const int* p, int v) {
    asm volatile("{\n.reg .pred p;\n.reg .u32 c;\n.reg .s32 f;\nmov.u32 c, 0;\nLW:\nld.acquire.gpu.global.s32 f, [%0];\nsub.s32 f, f, %1;\nsetp.ge.s32 p, f, 0;\n@p bra LD;\n"
                 "nanosleep.u32 500;\nadd.u32 c, c, 1;\nsetp.ge.u32 p, c, 4194304;\n@p trap;\nbra LW;\nLD:\n}\n" ::"l"(p), "r"(v) : "memory");
}
__device__ __forceinline__ bool elect() {
    uint32_t p; asm volatile("{\n.reg .pred p;\nelect.sync _|p, -1;\nselp.u32 %0, 1, 0, p;\n}\n" : "=r"(p)); return p;
}
__device__ __forceinline__ void bulk_g2s(uint32_t dst, const void* src, uint32_t bytes, uint32_t bar) {
    asm volatile("cp.async.bulk.shared::cluster.global.mbarrier::complete_tx::bytes [%0], [%1], %2, [%3];\n"
                 ::"r"(dst), "l"(src), "r"(bytes), "r"(bar) : "memory");
}
__device__ __forceinline__ void bulk_g2s_mc(uint32_t dst, const void* src, uint32_t bytes, uint32_t bar, uint16_t mask) {
    asm volatile("cp.async.bulk.shared::cluster.global.mbarrier::complete_tx::bytes.multicast::cluster [%0], [%1], %2, [%3], %4;\n"
                 ::"r"(dst), "l"(src), "r"(bytes), "r"(bar), "h"(mask) : "memory");
}
__device__ __forceinline__ void tma_g2s(uint32_t dst, const CUtensorMap* tm, int rowgroup, uint32_t bar) {
    asm volatile("cp.async.bulk.tensor.4d.shared::cluster.global.tile.mbarrier::complete_tx::bytes [%0], [%1, {0, 0, 0, %2}], [%3];\n"
                 ::"r"(dst), "l"(tm), "r"(rowgroup), "r"(bar) : "memory");
}
__device__ __forceinline__ void bar_sync(int id, int n) { asm volatile("bar.sync %0, %1;\n" ::"r"(id), "r"(n) : "memory"); }
__device__ __forceinline__ void bar_arrive(int id, int n) { asm volatile("bar.arrive %0, %1;\n" ::"r"(id), "r"(n) : "memory"); }
__device__ __forceinline__ float quad_last(float v) {
    float r; asm volatile("shfl.sync.idx.b32 %0, %1, 3, 0x1c1f, -1;\n" : "=f"(r) : "f"(v)); return r;
}
__device__ __forceinline__ float ex2(float x) { float y; asm("ex2.approx.ftz.f32 %0, %1;\n" : "=f"(y) : "f"(x)); return y; }
__device__ __forceinline__ float rcp(float x) { float y; asm("rcp.approx.ftz.f32 %0, %1;\n" : "=f"(y) : "f"(x)); return y; }
__device__ __forceinline__ uint32_t pack_bf16(float lo, float hi) {
    uint32_t r; asm("cvt.rn.bf16x2.f32 %0, %1, %2;\n" : "=r"(r) : "f"(hi), "f"(lo)); return r;
}
__device__ __forceinline__ uint32_t pack_f16(float lo, float hi) {
    uint32_t r; asm("cvt.rn.f16x2.f32 %0, %1, %2;\n" : "=r"(r) : "f"(hi), "f"(lo)); return r;
}
__device__ __forceinline__ uint32_t pack_f16_sat(float lo, float hi) {
    uint32_t r; asm("cvt.rn.satfinite.f16x2.f32 %0, %1, %2;\n" : "=r"(r) : "f"(hi), "f"(lo)); return r;
}
__device__ __forceinline__ float f16_lo(uint32_t v) { float r; asm("cvt.f32.f16 %0, %1;\n" : "=f"(r) : "h"((unsigned short)v)); return r; }
__device__ __forceinline__ float f16_hi(uint32_t v) { return f16_lo(v >> 16); }
__device__ __forceinline__ float bf_lo(uint32_t v) { return __uint_as_float(v << 16); }
__device__ __forceinline__ float bf_hi(uint32_t v) { return __uint_as_float(v & 0xFFFF0000u); }
__device__ __forceinline__ float bf_round(float x) { return __uint_as_float(pack_bf16(0.f, x)); }
__device__ __forceinline__ void st_release(int* p, int v) {
    asm volatile("st.release.gpu.global.s32 [%0], %1;\n" ::"l"(p), "r"(v) : "memory");
}
__device__ __forceinline__ uint4 ldg_pinned(const uint4* p) {
    uint4 v; asm volatile("ld.global.nc.v4.u32 {%0, %1, %2, %3}, [%4];\n" : "=r"(v.x), "=r"(v.y), "=r"(v.z), "=r"(v.w) : "l"(p) : "memory"); return v;
}
__device__ __forceinline__ void stmatrix_x4(uint32_t addr, uint32_t r0, uint32_t r1, uint32_t r2, uint32_t r3) {
    asm volatile("stmatrix.sync.aligned.m8n8.x4.shared.b16 [%0], {%1, %2, %3, %4};\n" ::"r"(addr), "r"(r0), "r"(r1), "r"(r2), "r"(r3) : "memory");
}

__device__ __forceinline__ uint32_t tile_off(int r, int ch) {
    return (uint32_t)((r >> 3) * 4096 + (ch >> 3) * 1024 + (r & 7) * 128 + (((ch ^ r) & 7) << 4));
}
__device__ __forceinline__ int h_unit(int qt, int u) { return qt < 78 ? u * 78 + qt : 624; }
__device__ __forceinline__ int row_off(int r) { return 4096 + h_unit(r >> 7, (r >> 4) & 7) * 8192 + (r & 8) * 512 + (r & 7) * 144; }

__device__ __forceinline__ float4 lds128f(uint32_t a) {
    float4 v; asm volatile("ld.shared.v4.f32 {%0, %1, %2, %3}, [%4];\n" : "=f"(v.x), "=f"(v.y), "=f"(v.z), "=f"(v.w) : "r"(a) : "memory"); return v;
}
__device__ __forceinline__ uint64_t lds64(uint32_t a) { uint64_t v; asm volatile("ld.shared.u64 %0, [%1];\n" : "=l"(v) : "r"(a) : "memory"); return v; }
__device__ __forceinline__ uint4 lds128(uint32_t a) {
    uint4 v; asm volatile("ld.shared.v4.u32 {%0, %1, %2, %3}, [%4];\n" : "=r"(v.x), "=r"(v.y), "=r"(v.z), "=r"(v.w) : "r"(a) : "memory"); return v;
}
__device__ __forceinline__ void sts128(uint32_t a, uint32_t x, uint32_t y, uint32_t z, uint32_t w) {
    asm volatile("st.shared.v4.u32 [%0], {%1, %2, %3, %4};\n" ::"r"(a), "r"(x), "r"(y), "r"(z), "r"(w) : "memory");
}
__device__ __forceinline__ void mbar_arrive(uint32_t bar) {
    asm volatile("mbarrier.arrive.shared::cta.b64 _, [%0];\n" ::"r"(bar) : "memory");
}
__device__ __forceinline__ uint64_t mkaddr(uint32_t lo, uint32_t hi) { uint64_t a; asm("mov.b64 %0, {%1, %2};\n" : "=l"(a) : "r"(lo), "r"(hi)); return a; }
__device__ __forceinline__ void red_add(int* p) { asm volatile("red.relaxed.gpu.global.add.s32 [%0], 1;\n" ::"l"(p) : "memory"); }
__device__ __forceinline__ void red_release(int* p) {
    asm volatile("fence.proxy.async.global;\nfence.acq_rel.gpu;\nred.relaxed.gpu.global.add.s32 [%0], 1;\n" ::"l"(p) : "memory");
}
__device__ __forceinline__ void fence_async_global() { asm volatile("fence.proxy.async.global;\n" ::: "memory"); }
__device__ __forceinline__ void fence_async_smem() { asm volatile("fence.proxy.async.shared::cta;\n" ::: "memory"); }
__device__ __forceinline__ void bulk_s2g(void* dst, uint32_t src, uint32_t bytes) {
    asm volatile("cp.async.bulk.global.shared::cta.bulk_group [%0], [%1], %2;\ncp.async.bulk.commit_group;\n" ::"l"(dst), "r"(src), "r"(bytes) : "memory");
}
__device__ __forceinline__ void mma16816(float (&c)[4], uint32_t a0, uint32_t a1, uint32_t a2, uint32_t a3, uint32_t b0, uint32_t b1) {
    asm("mma.sync.aligned.m16n8k16.row.col.f32.bf16.bf16.f32 {%0, %1, %2, %3}, {%4, %5, %6, %7}, {%8, %9}, {%0, %1, %2, %3};\n"
        : "+f"(c[0]), "+f"(c[1]), "+f"(c[2]), "+f"(c[3]) : "r"(a0), "r"(a1), "r"(a2), "r"(a3), "r"(b0), "r"(b1));
}
__device__ __forceinline__ void mma1688(float (&c)[4], uint32_t a0, uint32_t a1, uint32_t b0) {
    asm("mma.sync.aligned.m16n8k8.row.col.f32.bf16.bf16.f32 {%0, %1, %2, %3}, {%4, %5}, {%6}, {%0, %1, %2, %3};\n"
        : "+f"(c[0]), "+f"(c[1]), "+f"(c[2]), "+f"(c[3]) : "r"(a0), "r"(a1), "r"(b0));
}
__device__ __forceinline__ uint32_t hadd2_f16(uint32_t a, uint32_t b) { uint32_t r; asm("add.rn.f16x2 %0, %1, %2;\n" : "=r"(r) : "r"(a), "r"(b)); return r; }
__device__ __forceinline__ uint32_t hadd2(uint32_t a, uint32_t b) { uint32_t r; asm("add.rn.bf16x2 %0, %1, %2;\n" : "=r"(r) : "r"(a), "r"(b)); return r; }
__device__ __forceinline__ uint32_t hmul2(uint32_t a, uint32_t b) { uint32_t r; asm("mul.rn.bf16x2 %0, %1, %2;\n" : "=r"(r) : "r"(a), "r"(b)); return r; }
__device__ __forceinline__ uint32_t hfma2(uint32_t a, uint32_t b, uint32_t c) { uint32_t r; asm("fma.rn.bf16x2 %0, %1, %2, %3;\n" : "=r"(r) : "r"(a), "r"(b), "r"(c)); return r; }

constexpr int SM_Q = 0;
constexpr int SM_KV = 65536;
constexpr int SM_ML = SM_KV + STAGES * KV_BYTES;
constexpr int SM_BAR = SM_ML + 1024;
constexpr int SM_TOTAL = SM_BAR + 256;
constexpr float SCALE_LOG2 = 1.4426950408889634f / 16.0f;
constexpr float KV_SCALE = 0.75f;
constexpr float KV_OFF = 6.f;
constexpr uint32_t KV_OFF2 = 0x46004600u;
constexpr uint32_t KV_NEG4 = 0xCE00CE00u;
constexpr uint32_t P_LIMIT = 0x78007800u;
constexpr float REF_UP = REFUP;
__device__ __forceinline__ uint32_t kvf(uint32_t a) {
    uint32_t r; asm("fma.rn.f16x2 %0, %1, %2, %3;\n" : "=r"(r) : "r"(a), "r"(pack_f16(KV_SCALE, KV_SCALE)), "r"(KV_OFF2)); return r;
}
enum { BAR_PP0 = 1, BAR_PP1 = 2, BAR_WG0 = 3, BAR_WG1 = 4, BAR_H0 = 5, BAR_H1 = 6, BAR_AUX = 7, BAR_BF = 8, BAR_H2 = 9, BAR_X = 10, BAR_GO = 11, BAR_WG2 = 12, BAR_ST = 13 };

struct Hot {
    const __nv_bfloat16 *wk, *wq, *x;
    Scratch* s;
};
struct Params {
    const __nv_bfloat16* deg_inv;
    const int *src, *dst;
    __nv_bfloat16* out;
    uint32_t dhi;
    int E;
    CUtensorMap tm_out;
    CUtensorMap tm_outc;
    CUtensorMap tm_w[3];
};
static_assert(offsetof(Params, tm_outc) == offsetof(Params, tm_out) + 128, "layout");
#define SC_PAIR (blockIdx.x < 104)
#define SC_TAIL (blockIdx.x >= NCTA - 2)
#define SC_LAST (blockIdx.x == NCTA - 1)
#define SC_HELP (SC_PAIR && rank)
#define SC_OWNER (!SC_HELP && !SC_LAST)
#define SC_QT1 (26 + (int)(blockIdx.x >> 1))
#define SC_QT0 (SC_PAIR ? (rank ? (int)(blockIdx.x >> 2) : SC_QT1) : SC_TAIL ? 78 : (int)blockIdx.x - 104)
#define SC_NKV (SC_LAST ? 50 : 75)
#define SC_NMC (SC_PAIR ? 25 : SC_TAIL ? 0 : 75)
#define SC_CLS (SC_PAIR ? (rank ? 0x120 ^ (blockIdx.x & 2) * 0x80 : 0x430) | (blockIdx.x & 2) >> 1 : SC_LAST ? 0x10 : 0x432)
#define SC_NW (SC_PAIR ? 8 : SC_LAST ? 0 : 4)
#define SC_ZB (2 * SC_QT1 + 1 - (int)rank)
#define SC_TZB(k) (rank && !(k) ? 156 : 2 * (k) - (int)rank)

__global__ void __cluster_dims__(2, 1, 1) __launch_bounds__(384, 1) k_main(const __grid_constant__ Hot H, const __grid_constant__ Params P) {
    extern __shared__ __align__(1024) uint8_t smem[];
    const uint32_t sb = (uint32_t)__cvta_generic_to_shared(smem);
    const int tid = threadIdx.x, wg = __shfl_sync(~0u, tid >> 7, 0);
    const int lane = tid & 31, g = lane >> 2, q = lane & 3;
    const uint32_t rank = blockIdx.x & 1;
    const uint32_t bar_full = sb + SM_BAR, bar_q = bar_full + 32, bar_go = bar_full + 48;
    const uint32_t bar_pin = bar_full + 56;
    const uint32_t bar_qfree = bar_full + 72, bar_pdone = bar_full + 88, bar_zst = bar_full + 104, bar_rfree = bar_full + 120;
    const uint32_t bar_empty = bar_full + 128, bar_end = bar_full + 160, s_tm = bar_full + 184, bar_x = bar_full + 192;
    const uint32_t bar_a = sb + SM_ML;

    const int t = tid & 127, warp = __shfl_sync(~0u, t >> 5, 0);
    int ep = 0;
    if (wg & 2) {
        unsigned done;
        {
            uint4 ra[2], rb[2], rk[5][2];
            if (blockIdx.x < 128) {
                const int e = (blockIdx.x >> 4) * 32 + (g >> 1) * 8 + (blockIdx.x & 8) / 2 + (g & 1);
                const uint4* pq = (const uint4*)(H.wq + e * 256) + warp * 8 + q;
                const uint4* pk = (const uint4*)(H.wk + ((blockIdx.x & 7) * 32 + g) * 256) + warp * 8 + q;
                const uint4* pz = (const uint4*)(H.wk + 255 * 256) + warp * 8 + q;
#pragma unroll
                for (int s = 0; s < 2; s++) {
                    ra[s] = ldg_pinned(pq + 4 * s);
                    rb[s] = ldg_pinned(pq + 4 * s + 64);
#pragma unroll
                    for (int n = 0; n < 4; n++) rk[n][s] = ldg_pinned(pk + 4 * s + n * 256);
                    rk[4][s] = ldg_pinned(pz + 4 * s);
                }
            }
            asm volatile("{\n.reg .pred p;\nsetp.eq.s32 p, %2, 0;\nmov.u32 %0, 0;\n@p ld.global.cg.u32 %0, [%1];\n}\n" : "=r"(done) : "l"(&g_sync[SY_DONE * 32]), "r"(lane) : "memory");
            bar_arrive(BAR_X, 384);
            if (warp == 0 && elect()) {
#pragma unroll
                for (int i = 0; i < 21; i++) mbar_init(bar_full + 8 * i, i < 9 ? 1 : i < 16 ? 4 : i == 20 ? 11 : SC_TAIL ? 8 : 16);
#pragma unroll
                for (int i = 0; i < 4; i++) mbar_init(bar_a + 8 * i, 1);
                mbar_expect_tx(bar_pin, QB_BYTES / 2 + 512); mbar_expect_tx(bar_pin + 8, QB_BYTES / 2);
                asm volatile("fence.mbarrier_init.release.cluster;\n" ::: "memory");
            }
            __syncwarp();
            asm volatile("barrier.cluster.arrive.relaxed.aligned;\n" ::: "memory");
            if (blockIdx.x < 128) {
                float c[5][4] = {};
#pragma unroll
                for (int s = 0; s < 2; s++) {
#pragma unroll
                    for (int n = 0; n < 5; n++) mma16816(c[n], ra[s].x, rb[s].x, ra[s].y, rb[s].y, rk[n][s].x, rk[n][s].y);
#pragma unroll
                    for (int n = 0; n < 5; n++) mma16816(c[n], ra[s].z, rb[s].z, ra[s].w, rb[s].w, rk[n][s].z, rk[n][s].w);
                }
#pragma unroll
                for (int i = 0; i < 4; i++) {
                    const int r = i & 2, n = (i & 1) * 2;
                    sts128(sb + SM_KV + 3 * KV_BYTES + QB_BYTES + i * 2048 + t * 16, __float_as_uint(c[n][r] - c[4][r]), __float_as_uint(c[n][r + 1] - c[4][r]),
                           __float_as_uint(c[n + 1][r] - c[4][r]), __float_as_uint(c[n + 1][r + 1] - c[4][r]));
                }
            }
        }
        asm volatile("setmaxnreg.dec.sync.aligned.u32 %0;\n" ::"n"(REG_P));
        if (blockIdx.x < 128) {
            bar_sync(BAR_WG2, 128);
            float4 v[4];
#pragma unroll
            for (int i = 0; i < 4; i++) v[i] = lds128f(sb + SM_KV + 3 * KV_BYTES + QB_BYTES + (warp & 2) * 2048 + (lane & 1) * 2048 + i * 512 + ((warp & 1) * 16 + (lane >> 1)) * 16);
            constexpr float SC = SCALE_LOG2 / KV_SCALE;
            const int r = (warp & 1) * 4 + (lane >> 3);
            *(uint2*)(g_w + tile_off((blockIdx.x >> 3) * 16 + (warp & 2) * 4 + r, (blockIdx.x & 7) * 4 + ((lane >> 1) & 3)) + (lane & 1) * 8) =
                make_uint2(pack_f16_sat(((v[0].x + v[1].x) + (v[2].x + v[3].x)) * SC, ((v[0].y + v[1].y) + (v[2].y + v[3].y)) * SC) | 1,
                           pack_f16_sat(((v[0].z + v[1].z) + (v[2].z + v[3].z)) * SC, ((v[0].w + v[1].w) + (v[2].w + v[3].w)) * SC) | 1);
            if (warp != 1) {
                bar_arrive(BAR_AUX, 128);
            } else {
                bar_sync(BAR_AUX, 128);
                if (elect()) { red_add(&g_sync[SY_DONE * 32 + 4 + (blockIdx.x >> 5)]); }
                __syncwarp();
            }
        }
        else bar_sync(BAR_WG2, 128);
        if (warp == 1) bar_arrive(BAR_GO, 160);
        auto load_a = [&](int j) {
            if (elect()) {
                mbar_expect_tx(bar_a + 8 * j, QB_BYTES);
                bulk_g2s(sb + SM_KV + j * KV_BYTES, g_w + j * QB_BYTES, QB_BYTES, bar_a + 8 * j);
            }
            __syncwarp();
        };
        if (warp == 0) {
            auto poll = [&]() { int c; asm volatile("ld.relaxed.gpu.global.s32 %0, [%1];\n" : "=r"(c) : "l"(&g_sync[SY_DONE * 32 + 4 + (lane & 3)]) : "memory"); return c; };
#pragma unroll 1
            for (int j = 0; j < 4;) {
#pragma unroll 1
                for (const uint32_t mk = __ballot_sync(~0u, poll() >= 32) & 15; (mk >> j) & 1; j++) load_a(j);
            }
        } else if (warp & 1) {
#pragma unroll 1
            for (int j = 0, n = 0; j < 4;) {
                mbar_wait_bounded(bar_a + 8 * j, n & 1);
                uint32_t ok = 1;
#pragma unroll
                for (int i = 0; i < 16; i++) {
                    uint32_t v;
                    asm volatile("ld.shared.u32 %0, [%1];\n" : "=r"(v) : "r"(sb + SM_KV + j * KV_BYTES + (warp & 2) * 8192 + i * 1024 + lane * 32 + g * 4) : "memory");
                    ok &= v;
                }
                asm volatile("{\n.reg .pred p;\nsetp.ne.u32 p, %0, 0;\nbar.red.and.pred p, %1, 64, p;\nselp.u32 %0, 1, 0, p;\n}\n" : "+r"(ok) : "n"((int)BAR_WG2) : "memory");
                if (__any_sync(~0u, ok)) {
                    if (warp == 1 && elect()) asm volatile("mbarrier.arrive.shared::cta.b64 _, [%0];\nmbarrier.inval.shared::cta.b64 [%1];\n" ::"r"(bar_full + 8 * j), "r"(bar_a + 8 * j) : "memory");
                    __syncwarp();
                    j++; n = 0;
                } else {
                    asm volatile("{\n.reg .pred p;\nsetp.gt.s32 p, %0, 1000000;\n@p trap;\n}\n" ::"r"(++n) : "memory");
                    fence_async_smem();
                    if (warp == 1) load_a(j);
                }
            }
        }
        done = __shfl_sync(~0u, done, 0);
        ep = (int)(done / NCTA) + 1;
        asm volatile("barrier.cluster.wait.acquire.aligned;\n" ::: "memory");
        if (warp == 0) {
            asm volatile("st.shared.u64 [%0], %1;\n" ::"r"(s_tm), "l"(&P.tm_outc) : "memory");
            __syncwarp();
            if (elect()) {
                const uint8_t* base = (const uint8_t*)H.s;
                uint32_t cls = SC_CLS, bytes = KV_BYTES, moff = SC_NMC ? rank * (KV_BYTES / 2) : 0, step = 5 * KV_BYTES;
                const uint8_t* src = base;
                int next = 0;
                const int nit = SC_NKV + SC_NW;
#pragma unroll 1
                for (int j = 0; j < nit; j++) {
                    const uint32_t slot = sb + SM_KV + (j & 3) * KV_BYTES, fb = bar_full + 8 * (j & 3);
                    if (j == next) {
                        const int k = j - SC_NKV;
                        const int sw = SC_HELP ? j - 25 : -1;
                        next = j + 1;
                        if (j >= 3 && (unsigned)sw >= 5) next = k >= 0 ? next : j < GO0 ? GO0 : j < 25 ? 25 : j < GO1 ? GO1 : j < 49 ? 49 : j < 50 ? 50 : 75;
                        if (j == SC_NMC) moff = 0;
                        if (j == 0 || j == 25 || j == 50) { src = base + (4096 + (cls & 15) * KV_BYTES + moff); cls >>= 4; }
                        if (SC_TAIL ? j == nit - 1 : j == GO0 || j == GO1) mbar_arrive(bar_go);
                        int fo = -1, fv = 1;
                        if (j < 3) { fo = (SY_H0 + 5 * j + (SC_CLS & 15)) * 32; fv = 5; }
                        if (j == 3) { fo = SY_H1 * 32; fv = 79; }
                        if (sw == 1) fo = 25 * 32 + SC_QT1;
                        if (k == 0) fo = SY_B * 32;
                        if (k == 1 && !SC_PAIR) { fo = SY_AUX0 * 32; fv = NAUX; }
                        if (k == 2 && SC_PAIR) { fo = SY_AUX * 32; fv = NAUX / 3; }
                        if (fo >= 0) {
                            flag_wait(g_sync + fo, fv * ep);
                            fence_async_global();
                        }
                        if (sw == 2 || (k == 2 && !SC_TAIL)) {
                            uint32_t qs = sw == 2 ? offsetof(Scratch, q) + (2 * SC_QT1 + 1) * QB_BYTES : SC_PAIR ? offsetof(Scratch, agg) + SC_ZB * QB_BYTES : offsetof(Scratch, part) + SC_QT0 * (4 * PART_BYTES);
#pragma unroll 1
                            for (int w = 0; w < (k == 2 && SC_PAIR ? 1 : 2); w++) {
                                mbar_wait_sleep(bar_qfree + 8 * w, k == 2 && SC_HELP);
                                mbar_expect_tx(bar_q + 8 * w, SC_PAIR ? QB_BYTES : PART_BYTES);
                                if (!SC_PAIR) bulk_g2s(sb + SM_ML + w * 512, base + (qs + (w ? -512 : QB_BYTES)), 512, bar_q + 8 * w);
                                bulk_g2s(sb + SM_Q + w * QB_BYTES, base + qs, QB_BYTES, bar_q + 8 * w);
                                qs += sw == 2 ? -QB_BYTES : PART_BYTES + 512;
                            }
                        }
                        if ((sw | 1) == 3) {
                            mbar_wait_sleep(bar_pdone + 8 * (sw - 2), 0);
                            bulk_s2g(g_part + (blockIdx.x - 3 + sw) * PART_BYTES, slot, PART_BYTES);
                            asm volatile("cp.async.bulk.wait_group.read 0;\n" ::: "memory");
                        }
                        if (sw == 5) {
                            asm volatile("cp.async.bulk.wait_group 0;\n" ::: "memory");
                            red_release(&g_sync[SY_PART * 32]);
                        }
                        if (k == 0) {
                            asm volatile("prefetch.tensormap [%0];\n" ::"l"(&P.tm_outc) : "memory");
                            src = g_w + (12 - SC_NW) * QB_BYTES; bytes = step = QB_BYTES;
                        }
                        if (k == 2) next = SC_TAIL ? nit - 1 : nit;
                    }
                    mbar_wait_sleep(fb + (bar_empty - bar_full), (j >> 2) & 1);
                    mbar_expect_tx(fb, bytes);
                    if (j < SC_NMC) bulk_g2s_mc(slot + moff, src, KV_BYTES / 2, fb, 3);
                    else bulk_g2s(slot, src, bytes, fb);
                    src += step;
                }
            }
        } else {
            if (warp == 2 && SC_OWNER) {
                uint8_t* dst = g_hz + 4096 + h_unit(SC_QT0, 0) * 8192;
                auto send = [&](int u0, int u1) {
#pragma unroll
                    for (int u = u0; u < u1; u++) {
                        bulk_s2g(dst + u * (78 * 8192), sb + SM_Q + u * 8192, 8192);
                        asm volatile("cp.async.bulk.wait_group 0;\n" ::: "memory");
                    }
                };
                int* f0 = &g_sync[(SY_H0 + SC_QT0 / 5) * 32];
                bar_sync(BAR_H0, 64);
                if (elect()) {
                    send(0, 1);
                    if (SC_QT0 < 65) red_release(f0);
                }
                bar_sync(BAR_H1, 160);
                if (elect()) {
                    if (!SC_TAIL) send(1, 4);
                    mbar_arrive(bar_q);
                }
                bar_sync(BAR_H2, 160);
                if (elect()) {
                    if (!SC_TAIL) { send(4, 8); mbar_arrive(bar_q + 8); }
                    red_release(&g_sync[SY_H1 * 32]);
                }
                __syncwarp();
            }
        }
    } else {
        const uint32_t sq = sb + SM_Q + wg * QB_BYTES;
        const uint32_t qbar = bar_q + 8 * wg;
        const uint32_t dq0 = __shfl_sync(~0u, ((sq & 0x3FFFF) >> 4) | (64u << 16), 0);
        const uint32_t dk0 = __shfl_sync(~0u, (((sb + SM_KV) & 0x3FFFF) >> 4) | (64u << 16), 0);
        float o[128];
        int it = 4;
        const uint32_t dhi = P.dhi;
        uint32_t rel_addr;
        auto rel_target = [&](uint32_t r) {
            asm("mapa.shared::cluster.u32 %0, %1, %2;\n" : "=r"(rel_addr) : "r"(bar_empty), "r"(r));
            if (lane >= 2) rel_addr = 0;
            asm volatile("" : "+r"(rel_addr));
        };
        rel_target(SC_NMC ? rank ^ (lane & 1) : rank);
        auto release = [&](int st) {
            asm volatile("{\n.reg .pred p;\nsetp.ne.u32 p, %1, 0;\n@p mbarrier.arrive.shared::cluster.b64 _, [%0];\n}\n"
                         ::"r"(rel_addr + 8 * st), "r"(rel_addr) : "memory");
        };
        const bool active = !(SC_TAIL && wg == 1);
        auto pp_sync = [&]() { if (!SC_TAIL) bar_sync(BAR_PP0 + wg, 256); };
        auto pp_arrive = [&]() { if (!SC_TAIL) bar_arrive(BAR_PP1 - wg, 256); };
        auto warp_arrive = [&](uint32_t bar) {
            __syncwarp();
            asm volatile("{\n.reg .pred p;\nelect.sync _|p, -1;\n@p mbarrier.arrive.shared::cta.b64 _, [%0];\n}\n" ::"r"(bar + 8 * wg) : "memory");
        };
        auto peer_arrive = [&]() {
            asm volatile("{\n.reg .pred p;\n.reg .b32 a;\nelect.sync _|p, -1;\nmapa.shared::cluster.u32 a, %0, %1;\n"
                         "@p mbarrier.arrive.shared::cluster.b64 _, [a];\n}\n" ::"r"(bar_rfree), "r"(rank ^ 1) : "memory");
        };
        auto stage_q = [&]() {
            auto pk = [&](int i) { return QRND(pack_f16_sat(o[i], o[i + 1])); };
#pragma unroll
            for (int i = 0; i < 16; i++)
                stmatrix_x4(sq + warp * 8192 + tile_off(lane & 15, 2 * i + (lane >> 4)), pk(8 * i), pk(8 * i + 2), pk(8 * i + 4), pk(8 * i + 6));
        };
        float s[40];
        auto issue_qk = [&](int st) {
            const uint64_t kb = mkaddr(dk0 + st * (KV_BYTES >> 4), dhi);
            const uint64_t qd = mkaddr(dq0 + ((uint32_t)it >> 24), dhi);
            wgmma_ss_n80_init(s, qd + 198, kb + 198);
#pragma unroll
            for (int kk = 0; kk < 15; kk++) wgmma_ss_n80(s, qd + ((kk >> 2) * 64 + (kk & 3) * 2), kb + ((kk >> 2) * 64 + (kk & 3) * 2));
            wg_commit();
        };

        {
            const int rb = (2 * SC_QT0 + wg) * 64 + warp * 16;
            const uint32_t xbar = bar_x + 32 * wg + 8 * warp;
            if (elect()) {
                mbar_init(xbar, 1);
                asm volatile("fence.mbarrier_init.release.cluster;\nfence.proxy.async.shared::cta;\n" ::: "memory");
                mbar_expect_tx(xbar, rb < NN ? 8192 : 0);
            }
            asm volatile("barrier.cluster.arrive.relaxed.aligned;\n" ::: "memory");
            if (wg == 1) pp_arrive();
            bar_sync(BAR_X, 384);
            if (wg == 1) bar_sync(BAR_GO, 160);
            if (rb < NN && elect()) bulk_g2s(sq + warp * 8192, H.x + (size_t)rb * 256, 8192, xbar);
            if (rb >= NN) {
#pragma unroll 1
                for (int i = 0; i < 16; i++) sts128(sq + warp * 8192 + i * 512 + lane * 16, 0, 0, 0, 0);
            }
            __syncwarp();
            mbar_wait(xbar, 0);
            uint4 xa[8], xb[8];
#pragma unroll
            for (int s = 0; s < 8; s++) {
                xa[s] = lds128(sq + (warp * 16 + g) * 512 + (4 * s + q) * 16);
                xb[s] = lds128(sq + (warp * 16 + g + 8) * 512 + (4 * s + q) * 16);
            }
            float sm[2][4], sq2[2][4][4];
#pragma unroll
            for (int i = 0; i < 4; i++) {
                sm[0][i] = sm[1][i] = 0.f;
#pragma unroll
                for (int k = 0; k < 4; k++) sq2[0][k][i] = sq2[1][k][i] = 0.f;
            }
#pragma unroll
            for (int s = 0; s < 8; s++) {
#pragma unroll
                for (int hh = 0; hh < 2; hh++) {
                    const uint4 v = hh ? xb[s] : xa[s];
                    mma16816(sm[hh], v.x, v.y, v.z, v.w, 0x3F803F80u, 0x3F803F80u);
                    mma1688(sq2[hh][0], v.x, v.y, v.x); mma1688(sq2[hh][1], v.x, v.y, v.y);
                    mma1688(sq2[hh][2], v.z, v.w, v.z); mma1688(sq2[hh][3], v.z, v.w, v.w);
                }
            }
            float inv[2], off[2];
#pragma unroll
            for (int hh = 0; hh < 2; hh++) {
                const float mean = (sm[hh][0] + sm[hh][2]) * (1.f / 256.f);
                const float d0 = (sq2[hh][0][0] + sq2[hh][2][0]) + (sq2[hh][1][2] + sq2[hh][3][2]);
                const float d1 = (sq2[hh][0][1] + sq2[hh][2][1]) + (sq2[hh][1][3] + sq2[hh][3][3]);
                const float ss = __shfl_sync(~0u, (g & 1) ? d1 : d0, g * 4 + (g >> 1));
                const float var = fmaxf(ss * (1.f / 256.f) - mean * mean, 0.f);
                float sd;
                asm("sqrt.approx.ftz.f32 %0, %1;\n" : "=f"(sd) : "f"(bf_round(bf_round(var) + 1e-5f)));
                asm("rcp.approx.ftz.f32 %0, %1;\n" : "=f"(inv[hh]) : "f"(bf_round(sd)));
                off[hh] = -mean * inv[hh];
            }
            uint32_t a[64];
#pragma unroll
            for (int s = 0; s < 8; s++) {
                a[8 * s] = xa[s].x; a[8 * s + 1] = xb[s].x; a[8 * s + 2] = xa[s].y; a[8 * s + 3] = xb[s].y;
                a[8 * s + 4] = xa[s].z; a[8 * s + 5] = xb[s].z; a[8 * s + 6] = xa[s].w; a[8 * s + 7] = xb[s].w;
            }
            fence_regs(a);
            if (wg == 1 && __any_sync(~0u, inv[0] + inv[1] != -1.f)) bar_arrive(BAR_ST, 256);
            asm volatile("setmaxnreg.inc.sync.aligned.u32 %0;\n" ::"n"(REG_C));
            fence_regs(a);
#pragma unroll
            for (int i = 0; i < 64; i++)
                a[i] = pack_f16(fmaf(bf_lo(a[i]), inv[i & 1], off[i & 1]), fmaf(bf_hi(a[i]), inv[i & 1], off[i & 1]));
            if (SC_OWNER) {
#pragma unroll
                for (int i = 0; i < 16; i++) {
                    const uint32_t mk = (i == 15 && q == 3) ? 0xFFFFu : ~0u;
                    stmatrix_x4(sq + warp * 8192 + tile_off(lane & 15, 2 * i + (lane >> 4)), kvf(a[4 * i]), kvf(a[4 * i + 1]),
                                kvf(a[4 * i + 2] & mk), kvf(a[4 * i + 3] & mk));
                }
                fence_async_smem();
                if (tid < 32) bar_arrive(BAR_H0, 64);
                bar_arrive(wg ? BAR_H2 : BAR_H1, 160);
            }
            asm volatile("barrier.cluster.wait.acquire.aligned;\n" ::: "memory");
            if (wg == 0) bar_sync(BAR_ST, 256);
            if (active) {
                fence_regs(a);
#pragma unroll
                for (int c = 0; c < 4; c++) {
                    if (c == 1) {
                        if (wg == 1) {
                            wg_wait<0>();
                            release(0);
                        }
                        pp_sync();
                    }
                    mbar_wait(bar_full + 8 * c, 0);
                    const uint64_t wb = mkaddr(dk0 + c * (KV_BYTES >> 4), dhi);
                    wg_fence();
#pragma unroll
                    for (int kk = 0; kk < 4; kk++) {
                        if (c | kk) wgmma_rs_n256_tb(o, a[16 * c + 4 * kk], a[16 * c + 4 * kk + 1], a[16 * c + 4 * kk + 2], a[16 * c + 4 * kk + 3], wb + kk * 512);
                        else wgmma_rs_n256_tb_init(o, a[0], a[1], a[2], a[3], wb);
                    }
                    wg_commit();
                    if (c > 0) { wg_wait<1>(); if (c > 1 || wg == 0) release(c - 1); }
                }
                if (wg == 0) pp_arrive();
                wg_wait<0>();
                fence_regs(o);
                release(3);
                if (SC_OWNER) mbar_wait(qbar, 0);
                stage_q();
                fence_async_smem();
                bar_sync(BAR_WG0 + wg, 128);
                mbar_wait(bar_full, 1);
                wg_fence();
                issue_qk(0);
                if (wg == 1) pp_arrive();
            } else {
                peer_arrive();
            }
        }

        uint32_t p[20];
        float m0 = 0.f, m1 = 0.f, e0, e1, l0, l1;
        uint32_t plim;
        uint32_t qphase = (SC_OWNER && active) ? 1 : 0;
        auto issue_pv = [&](int st, int acc) {
            const uint64_t vb = mkaddr(dk0 + st * (KV_BYTES >> 4), dhi);
            wgmma_rs_n256_tb_pred(o, p[0], p[1], p[2], p[3], vb, acc);
#pragma unroll
            for (int kk = 1; kk < 5; kk++)
                wgmma_rs_n256_tb(o, p[4 * kk], p[4 * kk + 1], p[4 * kk + 2], p[4 * kk + 3], vb + kk * 512);
            wg_commit();
        };
        const uint32_t mq_addr = sq + tile_off(warp * 16 + g, 31) + 14;
        auto exceeds = [&](const uint32_t (&p)[20]) {
            uint32_t a = __vimax3_s16x2(P_LIMIT, p[0], p[1]), b = __vimax3_s16x2(p[2], p[3], p[4]);
#pragma unroll
            for (int i = 5; i < 17; i += 4) { a = __vimax3_s16x2(a, p[i], p[i + 1]); b = __vimax3_s16x2(b, p[i + 2], p[i + 3]); }
            a = __vimax3_s16x2(a, p[17], p[18]);
            return __any_sync(~0u, __vimax3_s16x2(a, b, p[19]) != plim);
        };
        auto remax = [&](float& a, float& b, bool store) {
            float a1 = fmaxf(s[0], s[1]), b1 = fmaxf(s[2], s[3]), a2 = fmaxf(s[4], s[5]), b2 = fmaxf(s[6], s[7]);
#pragma unroll
            for (int i = 2; i < 10; i++) {
                a1 = fmaxf(a1, s[4 * i]); a2 = fmaxf(a2, s[4 * i + 1]);
                b1 = fmaxf(b1, s[4 * i + 2]); b2 = fmaxf(b2, s[4 * i + 3]);
            }
            a1 = fmaxf(a1, a2); b1 = fmaxf(b1, b2);
            a1 = fmaxf(a1, __shfl_xor_sync(~0u, a1, 1)); b1 = fmaxf(b1, __shfl_xor_sync(~0u, b1, 1));
            a1 = fmaxf(a1, __shfl_xor_sync(~0u, a1, 2)); b1 = fmaxf(b1, __shfl_xor_sync(~0u, b1, 2));
            a = fmaxf(a, a1 - e0 + REF_UP); b = fmaxf(b, b1 - e1 + REF_UP);
            const uint32_t u = pack_f16_sat((m0 + a) * (-1.f / KV_OFF), (m1 + b) * (-1.f / KV_OFF));
            const float g0 = (m0 + a) + KV_OFF * f16_lo(u), g1 = (m1 + b) + KV_OFF * f16_hi(u);
            const bool x0 = fabsf(g0) <= 1.f, x1 = fabsf(g1) <= 1.f;
            if (x0) a -= g0;
            if (x1) b -= g1;
            const float da = a + e0, db = b + e1;
            m0 += a; m1 += b;
            e0 = x0 ? 0.f : g0; e1 = x1 ? 0.f : g1;
            plim = (x0 && x1) ? P_LIMIT : 0u;
            asm volatile("{\n.reg .pred p;\nsetp.ne.s32 p, %3, 0;\n@p st.shared.u16 [%0], %1;\n@p st.shared.u16 [%0 + 4096], %2;\n}\n"
                         ::"r"(mq_addr), "h"((unsigned short)u), "h"((unsigned short)(u >> 16)), "r"((int)(store && q == 0)) : "memory");
#pragma unroll
            for (int i = 0; i < 10; i++) {
                p[2 * i] = pack_f16(ex2(s[4 * i] - da), ex2(s[4 * i + 1] - da));
                p[2 * i + 1] = pack_f16(ex2(s[4 * i + 2] - db), ex2(s[4 * i + 3] - db));
            }
            fence_regs(p);
            fence_async_smem();
            __syncwarp();
        };

        auto row_sums = [&](float& z0, float& z1) {
            z0 = quad_last(o[125]); z1 = quad_last(o[127]);
            l0 = z0 * (KV_SCALE / KV_OFF); l1 = z1 * (KV_SCALE / KV_OFF);
        };
        auto cut = [&]() { asm volatile("{\n.reg .pred p;\nsetp.lt.s32 p, %0, 0;\nL:\n@p pmevent 0;\n@p bra L;\n}\n" ::"r"(it) : "memory"); };
        auto stats = [&]() { return (q & 2) ? ((q & 1) ? l1 : m1) : ((q & 1) ? l0 : m0); };
        const int nseg = SC_HELP ? 2 : 1;
        if (active) {
#pragma unroll 1
        for (int seg = 0;; seg++) {
            wg_wait<0>();
            fence_regs(s);
            e0 = e1 = 0.f;
            const int it0 = it, itl = __shfl_sync(~0u, seg + 1 < nseg ? 3 + 25 : 3 + SC_NKV, 0);
            const int itx = (wg == 1 && seg + 1 == nseg) ? itl : -1;
            bool redo = true, have = !seg;
#pragma unroll 1
            for (;;) {
                if (!have) {
#pragma unroll
                    for (int i = 0; i < 20; i++) p[i] = pack_f16(ex2(s[2 * i]), ex2(s[2 * i + 1]));
                    redo = exceeds(p);
                }
                if (redo) {
                    float d0 = it != it0 ? 0.f : -INFINITY, d1 = d0;
                    remax(d0, d1, it != itl);
                    if (it != it0) {
                        const float a0 = ex2(-d0), a1 = ex2(-d1);
#pragma unroll
                        for (int i = 0; i < 32; i++) { o[4 * i] *= a0; o[4 * i + 1] *= a0; o[4 * i + 2] *= a1; o[4 * i + 3] *= a1; }
                    }
                }
                if (it == it0 && (seg || SC_OWNER)) {
                    fence_async_smem();
                    warp_arrive(bar_pdone);
                }
                if (it == itl) break;
                const int stp = it & 3;
                it++;
                mbar_wait(bar_full + 8 * (it & 3), (it >> 2) & 1);
                pp_sync();
                fence_regs(o); fence_regs(p);
                wg_fence();
                issue_qk(it & 3);
                if (it == itx) {
                    wg_wait<0>();
                    if (SC_PAIR) peer_arrive(); else warp_arrive(bar_qfree);
                    bar_sync(BAR_ST, 256);
                }
                wg_fence();
                issue_pv(stp, it - 1 - it0);
                pp_arrive();
                if (it == itl && itx < 0) {
                    wg_wait<1>();
                    warp_arrive(bar_qfree);
                }
                have = SC_TAIL || it == itx;
                if (have) {
                    uint32_t p2[20];
                    wg_wait<1>();
                    fence_regs(s);
#pragma unroll
                    for (int i = 0; i < 20; i++) p2[i] = pack_f16(ex2(s[2 * i]), ex2(s[2 * i + 1]));
                    redo = exceeds(p2);
                    if (redo) asm volatile("wgmma.wait_group.sync.aligned 0;\nnanosleep.u32 0;\n" ::: "memory");
                    else wg_wait<0>();
                    fence_regs(o); fence_regs(p);
#pragma unroll
                    for (int i = 0; i < 20; i++) p[i] = p2[i];
                } else {
                    wg_wait<0>();
                    fence_regs(s); fence_regs(o); fence_regs(p);
                }
                release(stp);
                if (it == SC_NMC) rel_target(rank);
            }
            if (seg + 1 < nseg) pp_sync();
            fence_regs(o); fence_regs(p);
            wg_fence();
            issue_pv(it & 3, 1);
            asm volatile("{\n.reg .pred p;\nsetp.ne.s32 p, %0, 0;\n@p bar.arrive %1, 256;\n}\n" ::"r"((int)(seg + 1 == nseg && (wg ? SC_PAIR : !SC_TAIL))), "r"(BAR_ST + wg) : "memory");
            it++;
            if (seg + 1 == nseg) break;
            const int is = it - 2 + wg;
            uint32_t dst = sb + SM_KV + (is & 3) * KV_BYTES + wg * 512 + warp * 8192 + lane * 16;
            uint32_t dml = sb + SM_KV + (is & 3) * KV_BYTES + (wg ? 0 : QB_BYTES) + t * 4;
            asm volatile("" : "+r"(dst), "+r"(dml));
            mbar_wait(qbar, qphase); qphase ^= 1;
            unsigned short u0, u1;
            asm volatile("ld.shared.u16 %0, [%2];\nld.shared.u16 %1, [%2 + 4096];\n" : "=h"(u0), "=h"(u1) : "r"(mq_addr) : "memory");
            mbar_wait(bar_full + 8 * (it & 3), (it >> 2) & 1);
            wg_wait<0>();
            fence_regs(o);
            float z0, z1;
            row_sums(z0, z1);
            release((it - 1) & 3);
            wg_fence();
            issue_qk(it & 3);
            pp_arrive();
#pragma unroll
            for (int i = 0; i < 128; i++) o[i] -= (i & 2) ? z1 : z0;
            fence_regs(o);
            mbar_wait(bar_empty + 8 * (is & 3), (is >> 2) & 1);
            asm volatile("st.shared.f32 [%0], %1;\n" ::"r"(dml), "f"(stats()) : "memory");
            m0 = -KV_OFF * f16_lo(u0); m1 = -KV_OFF * f16_lo(u1);
            plim = fmaxf(fabsf(m0), fabsf(m1)) <= 3072.f ? P_LIMIT : 0u;
            uint32_t v[2][8] = {};
#pragma unroll
            for (int i = 0; i < 8; i++) {
                uint32_t *w = v[i & 1], *u = v[(i & 1) ^ 1];
#pragma unroll
                for (int j = 0; j < 8; j++) w[j] = pack_bf16(o[16 * i + 2 * j], o[16 * i + 2 * j + 1]);
                sts128(dst + i * 1024, w[0], w[1], w[2], w[3]);
                sts128(dst + i * 1024 + 512, w[4], w[5], w[6], w[7]);
                if (i) asm volatile("{\n.reg .pred p;\nsetp.lt.s32 p, %9, 0;\nL:\n@p st.shared.v4.u32 [%0], {%1, %2, %3, %4};\n@p st.shared.v4.u32 [%0 + 16], {%5, %6, %7, %8};\n@p bra L;\n}\n"
                             ::"r"(dst), "r"(u[0]), "r"(u[1]), "r"(u[2]), "r"(u[3]), "r"(u[4]), "r"(u[5]), "r"(u[6]), "r"(u[7]), "r"(it) : "memory");
            }
        }
        constexpr int IW = 4 + 75;
        uint32_t a[64];
        if (wg == 0 && (SC_PAIR || SC_LAST)) {
            uint32_t rq, rml, rbar;
            asm volatile("mapa.shared::cluster.u32 %0, %3, %6;\nmapa.shared::cluster.u32 %1, %4, %6;\nmapa.shared::cluster.u32 %2, %5, %6;\n"
                         : "=r"(rq), "=r"(rml), "=r"(rbar) : "r"(sb + SM_Q + QB_BYTES + warp * 8192 + lane * 16), "r"(sb + SM_ML + 512 + t * 4),
                         "r"(bar_pin), "r"(rank ^ 1));
            auto send = [&](int i) {
                asm volatile("st.async.weak.shared::cluster.mbarrier::complete_tx::bytes.v4.b32 [%0], {%1, %2, %3, %4}, [%5];\n"
                             ::"r"(rq + i * 512), "r"(a[4 * i]), "r"(a[4 * i + 1]), "r"(a[4 * i + 2]), "r"(a[4 * i + 3]), "r"(rbar + (i & 8)) : "memory");
            };
            mbar_wait(bar_rfree, 0);
            wg_wait<0>();
            fence_regs(o);
            release((it - 1) & 3);
            float z0, z1;
            row_sums(z0, z1);
            asm volatile("st.async.weak.shared::cluster.mbarrier::complete_tx::bytes.f32 [%0], %1, [%2];\n" ::"r"(rml), "f"(stats()), "r"(rbar) : "memory");
#pragma unroll
            for (int i = 0; i < 16; i++) {
                a[4 * i] = pack_bf16(o[8 * i] - z0, o[8 * i + 1] - z0); a[4 * i + 1] = pack_bf16(o[8 * i + 2] - z1, o[8 * i + 3] - z1);
                a[4 * i + 2] = pack_bf16(o[8 * i + 4] - z0, o[8 * i + 5] - z0); a[4 * i + 3] = pack_bf16(o[8 * i + 6] - z1, o[8 * i + 7] - z1);
                if (i * SND0 / 16 != (i + 1) * SND0 / 16) send(i * SND0 / 16);
                if (i % CUT2 == CUT2 - 1) cut();
            }
            if (SC_PAIR) {
                float z[128];
                const uint32_t dkz = dk0 + ((uint32_t)it >> 24), dqz = dq0 + ((uint32_t)it >> 24);
                auto gemm = [&](int c) {
                    mbar_wait(bar_full + 8 * ((IW + c) & 3), ((IW + c) >> 2) & 1);
                    const uint64_t wb = mkaddr(dkz + ((IW + c) & 3) * (KV_BYTES >> 4), dhi), ab = mkaddr(dqz + c * 64, dhi);
                    wg_fence();
#pragma unroll
                    for (int kk = 0; kk < 4; kk++) {
                        if (c | kk) wgmma_ss_n256_tb(z, ab + kk * 2, wb + kk * 512);
                        else wgmma_ss_n256_tb_init(z, ab, wb);
                    }
                    wg_commit();
                };
                auto release2 = [&](int c) {
                    asm volatile("{\n.reg .pred p;\nsetp.ne.u32 p, %1, 0;\n@p mbarrier.arrive.shared::cluster.b64 _, [%0], 2;\n}\n"
                                 ::"r"(rel_addr + 8 * ((IW + c) & 3)), "r"(rel_addr) : "memory");
                };
                mbar_wait(qbar, qphase);
                bar_sync(BAR_ST + 1, 256);
                gemm(0);
#pragma unroll
                for (int i = SND0; i < 16; i++) send(i);
#pragma unroll
                for (int c = 1; c < 4; c++) { gemm(c); if (c == 3) pp_arrive(); wg_wait<1>(); release2(c - 1); }
                wg_wait<0>();
                fence_regs(z);
                release2(3);
#pragma unroll
                for (int i = 0; i < 16; i++) {
                    sts128(sq + warp * 8192 + lane * 16 + i * 512, pack_bf16(z[8 * i], z[8 * i + 1]), pack_bf16(z[8 * i + 2], z[8 * i + 3]),
                           pack_bf16(z[8 * i + 4], z[8 * i + 5]), pack_bf16(z[8 * i + 6], z[8 * i + 7]));
                    if (i == 3 || i == 15) bar_arrive(i == 3 ? BAR_BF : BAR_H0, 256);
                    if (i == 3) cut();
                }
            } else {
#pragma unroll
                for (int i = SND0; i < 16; i++) send(i);
            }
        } else {
            const int pair = SC_PAIR;
            const bool glob = !(pair || SC_TAIL);
            const uint32_t ml = sb + SM_ML + (t & ~3) * 4, src = (glob ? sq : sb + SM_Q + QB_BYTES) + warp * 8192 + lane * 16;
            const uint64_t tm = lds64(s_tm);
            wg_wait<0>();
            fence_regs(o);
            release((IW - 1) & 3);
            float c0, c1;
            row_sums(c0, c1);
            mbar_wait(glob ? qbar : bar_pin, glob ? qphase : 0);
            const float4 ps = lds128f(ml + (glob ? wg * 512 : 512));
            auto load = [&](int i) {
                asm volatile("ld.shared.v4.u32 {%0, %1, %2, %3}, [%4];\n" : "=r"(a[4 * i]), "=r"(a[4 * i + 1]), "=r"(a[4 * i + 2]), "=r"(a[4 * i + 3]) : "r"(src + i * 512) : "memory");
            };
#pragma unroll
            for (int i = 0; i < 8; i++) load(i);
            const float n0 = fmaxf(m0, ps.x), n1 = fmaxf(m1, ps.z);
            const float a0 = ex2(m0 - n0), a1 = ex2(m1 - n1), b0 = ex2(ps.x - n0), b1 = ex2(ps.z - n1);
            const float i0 = rcp(l0 * a0 + ps.y * b0), i1 = rcp(l1 * a1 + ps.w * b1);
            const float r0 = a0 * i0, r1 = a1 * i1;
            c0 *= -r0; c1 *= -r1;
            const uint32_t u0 = pack_bf16(b0 * i0, b0 * i0), u1 = pack_bf16(b1 * i1, b1 * i1);
#pragma unroll
            for (int i = 0; i < 32; i++) {
                if (i == 16) {
                    if (!glob) mbar_wait(bar_pin + 8, 0);
#pragma unroll
                    for (int j = 8; j < 16; j++) load(j);
                }
                a[2 * i] = hfma2(a[2 * i], u0, pack_bf16(fmaf(o[4 * i], r0, c0), fmaf(o[4 * i + 1], r0, c0)));
                a[2 * i + 1] = hfma2(a[2 * i + 1], u1, pack_bf16(fmaf(o[4 * i + 2], r1, c1), fmaf(o[4 * i + 3], r1, c1)));
            }
            float y[2][32];
            auto gemm = [&](int c, int kh) {
                if (!kh) mbar_wait(bar_full + 8 * ((IW + c) & 3), (((IW + c) >> 2) & 1) ^ pair);
                const uint64_t wb = mkaddr(dk0 + ((IW + c) & 3) * (KV_BYTES >> 4), dhi - 192);
                wg_fence();
#pragma unroll
                for (int kk = 8 * kh; kk < 8 * kh + 8; kk++) {
                    if (kk) wgmma_rs_n64_tb(y[c & 1], a[4 * kk], a[4 * kk + 1], a[4 * kk + 2], a[4 * kk + 3], wb + kk * 128);
                    else wgmma_rs_n64_tb_init(y[c & 1], a[0], a[1], a[2], a[3], wb);
                }
                wg_commit();
            };
            const uint32_t stg = sq + warp * 8192 + (lane & 15) * 128 + (((lane >> 4) ^ lane) & 7) * 16;
            uint4 z[4] = {};
            auto load_z = [&](int cb) {
                if (cb < 2) asm volatile("{\n.reg .pred p;\nsetp.ne.s32 p, %0, 0;\n@p bar.sync %1, 256;\n}\n" ::"r"(pair), "r"(cb ? BAR_H0 : BAR_BF) : "memory");
#pragma unroll
                for (int i = 0; i < 4; i++)
                    asm volatile("{\n.reg .pred p;\nsetp.ne.u32 p, %4, 0;\n@p ld.shared.v4.u32 {%0, %1, %2, %3}, [%5];\n}\n"
                                 : "+r"(z[i].x), "+r"(z[i].y), "+r"(z[i].z), "+r"(z[i].w) : "r"(pair), "r"(src - QB_BYTES + (4 * cb + i) * 512) : "memory");
            };
            pp_sync();
            gemm(0, 0);
            gemm(0, 1);
#pragma unroll
            for (int c = 0; c < 4; c++) {
                if (c) load_z(c);
                if (c < 3) gemm(c + 1, 0);
                if (!c) load_z(0);
                if (c < 3) wg_wait<1>(); else wg_wait<0>();
                fence_regs(y[c & 1]);
                const float* x = y[c & 1];
#pragma unroll
                for (int i = 0; i < 4; i++)
                    stmatrix_x4((stg ^ (32 * i)) + c * 2048, hadd2(pack_bf16(x[8 * i], x[8 * i + 1]), z[i].x), hadd2(pack_bf16(x[8 * i + 2], x[8 * i + 3]), z[i].y),
                                hadd2(pack_bf16(x[8 * i + 4], x[8 * i + 5]), z[i].z), hadd2(pack_bf16(x[8 * i + 6], x[8 * i + 7]), z[i].w));
                if (c < 3) gemm(c + 1, 1);
                fence_async_smem();
                __syncwarp();
                asm volatile("{\n.reg .pred p;\nelect.sync _|p, -1;\n"
                             "@p cp.reduce.async.bulk.tensor.4d.global.shared::cta.add.tile.bulk_group [%0, {0, 0, %1, %2}], [%3];\n}\n"
                             ::"l"(tm), "r"(c), "r"((pair ? SC_ZB : 2 * SC_QT0 + wg) * 8 + warp * 2), "r"(sq + warp * 8192 + c * 2048) : "memory");
                if (c == 2 && glob) pp_arrive();
            }
            asm volatile("cp.async.bulk.commit_group;\ncp.async.bulk.wait_group.read 0;\n" ::: "memory");
        }
        } else {
            wg_wait<0>();
        }
        if (SC_TAIL) {
        float o[128];
        auto emit = [&](uint32_t base, int lane, int row0, uint8_t* wdst, int turn) {
#pragma unroll
            for (int hh = 0; hh < 2; hh++) {
                if (turn > 0) mbar_wait(bar_zst + 8 * hh, (turn - 1) & 1);
#pragma unroll
                for (int i = 0; i < 8; i++)
                    stmatrix_x4(base + tile_off(8 * hh + (lane & 7), 4 * i + (lane >> 3)),
                                pack_bf16(o[16 * i + 2 * hh], o[16 * i + 2 * hh + 1]), pack_bf16(o[16 * i + 4 + 2 * hh], o[16 * i + 5 + 2 * hh]),
                                pack_bf16(o[16 * i + 8 + 2 * hh], o[16 * i + 9 + 2 * hh]), pack_bf16(o[16 * i + 12 + 2 * hh], o[16 * i + 13 + 2 * hh]));
                fence_async_smem();
                __syncwarp();
                if (wdst) {
                    if (lane < 4)
                        asm volatile("cp.async.bulk.global.shared::cta.bulk_group [%0], [%1], 1024;\n"
                                     ::"l"(wdst + ((turn & 1) ? hh * 4096 + lane * 1024 : hh * 1024 + lane * QB_BYTES)), "r"(base + hh * 4096 + lane * 1024) : "memory");
                    asm volatile("cp.async.bulk.commit_group;\n" ::: "memory");
                } else {
                    asm volatile("{\n.reg .pred p;\nsetp.eq.s32 p, %3, 0;\n"
                                 "@p cp.reduce.async.bulk.tensor.4d.global.shared::cta.add.tile.bulk_group [%0, {0, 0, 0, %1}], [%2];\n"
                                 "cp.async.bulk.commit_group;\n}\n"
                                 ::"l"(&P.tm_out), "r"((row0 >> 3) + hh), "r"(base + hh * 4096), "r"(lane) : "memory");
                }
            }
            asm volatile("cp.async.bulk.wait_group.read 1;\n" ::: "memory");
            warp_arrive(bar_zst - 8 * wg);
        };
        auto emit_done = [&](bool pending) {
            asm volatile("cp.async.bulk.wait_group.read 0;\n" ::: "memory");
            __syncwarp();
            asm volatile("{\n.reg .pred p;\nsetp.eq.s32 p, %1, 0;\n@p mbarrier.arrive.shared::cta.b64 _, [%0];\n}\n"
                         ::"r"(bar_zst + 8), "r"(pending ? lane : 1) : "memory");
        };
        if (!(rank | wg)) { release(0); release(1); release(2); release(3); }
        bar_sync(BAR_BF, 256);
        warp_arrive(bar_qfree);
        const int nf = rank ? 8 : 0;
        const int nz = nf + 26 + rank;
        const int itz = 4 + SC_NKV + SC_NW;
        bool pend = false;
#pragma unroll 1
        for (int k = wg; k < nz; k += 2) {
            const int iz = itz + (k < nf ? 0 : nf >> 1);
            mbar_wait(qbar, qphase); qphase ^= 1;
#pragma unroll 1
            for (int c = 0; c < 4; c++) {
                mbar_wait(bar_full + 8 * ((iz + c) & 3), ((iz + c) >> 2) & 1);
                const uint64_t wb = mkaddr(dk0 + ((iz + c) & 3) * (KV_BYTES >> 4), dhi), ab = mkaddr(dq0 + c * 64, dhi);
                wg_fence();
                wgmma_ss_n256_tb_pred(o, ab, wb, c);
#pragma unroll
                for (int kk = 1; kk < 4; kk++) wgmma_ss_n256_tb(o, ab + kk * 2, wb + kk * 512);
                wg_commit();
                emit_done(pend);
                pend = false;
            }
            wg_wait<0>();
            fence_regs(o);
            warp_arrive(bar_qfree);
            const int fb = ((k >> 1) + 3) & 3;
            if (k < nf) {
                float2* r255 = (float2*)H.s->r255 + wg * 128 + q;
                if (k < 2) {
                    if (t >= 124) {
#pragma unroll
                        for (int i = 0; i < 32; i++) r255[4 * i] = make_float2(o[4 * i + 2], o[4 * i + 3]);
                    }
                    bar_sync(BAR_WG0 + wg, 128);
                }
#pragma unroll
                for (int i = 0; i < 32; i++) {
                    const float2 v = __ldcg(r255 + 4 * i);
                    o[4 * i] -= v.x; o[4 * i + 1] -= v.y; o[4 * i + 2] -= v.x; o[4 * i + 3] -= v.y;
                }
            }
            int ln = lane;
            asm volatile("" : "+r"(ln));
            emit(sb + SM_KV + QB_BYTES + warp * KV_BYTES, ln, SC_TZB(k - nf) * 64 + warp * 16,
                 k >= nf ? nullptr : (k & 1) ? g_w + (4 + fb) * QB_BYTES + warp * 8192 : g_w + 8 * QB_BYTES + fb * 8192 + warp * 2048, k);
            pend = k + 2 < nz && (k | 1) != nf - 1;
            if (!pend) emit_done(true);
            if ((k | 1) == nf - 1) {
                asm volatile("cp.async.bulk.wait_group 0;\nfence.proxy.async.global;\nfence.acq_rel.gpu;\n" ::: "memory");
                bar_sync(BAR_BF, 256);
                if (tid == 0) red_release(&g_sync[SY_B * 32]);
                if (wg == 0) { release(0); release(1); release(2); release(3); }
            }
        }
        }
        if (wg == 0) pp_sync();
        warp_arrive(bar_end - 8 * wg);
        asm volatile("barrier.cluster.arrive.relaxed.aligned;\n" ::: "memory");
        if (P.E >= 0) return;
        asm volatile("setmaxnreg.dec.sync.aligned.u32 %0;\n" ::"n"(REG_P));
    }
    {
        if (warp != 0) {
            if (warp == 3 && SC_OWNER && SC_PAIR && elect()) {
                flag_wait_bounded(&g_sync[SY_H1 * 32], 79 * ep);
                mbar_wait_sleep(bar_pdone, 0);
                mbar_wait_sleep(bar_pdone + 8, 0);
#pragma unroll 1
                for (int u = 0; u < 16; u++) {
                    bulk_s2g(g_q + SC_QT0 * (2 * QB_BYTES) + u * 4096, sb + SM_Q + u * 4096, 4096);
                    asm volatile("cp.async.bulk.wait_group 0;\n" ::: "memory");
                }
                fence_async_global();
                st_release(&g_qflag[SC_QT0], ep);
            }
            __syncwarp();
            if (SC_TAIL) {
                bar_sync(BAR_AUX, 96);
                if (warp == 1 && elect()) red_release(&g_sync[SY_CSR * 32]);
                __syncwarp();
            }
            mbar_wait_bounded(bar_go, 0);
            if (SC_TAIL) {
                if (warp == 1 && elect()) red_add(&g_sync[SY_DONE * 32]);
                if (warp == 3 && elect()) {
                    int it = 4 + SC_NKV + SC_NW;
                    asm volatile("prefetch.tensormap [%0];\n" ::"l"(&P.tm_out) : "memory");
                    if (rank) {
#pragma unroll 1
                        for (int j = 0; j < 4; j++, it++) {
                            mbar_wait_sleep(bar_empty + 8 * (it & 3), ((it >> 2) & 1) ^ 1);
                            mbar_expect_tx(bar_full + 8 * (it & 3), QB_BYTES);
                            tma_g2s(sb + SM_KV + (it & 3) * KV_BYTES, &P.tm_w[2], 8 * j, bar_full + 8 * (it & 3));
                        }
#pragma unroll 1
                        for (int k = 0; k < 8; k++) {
                            mbar_wait_sleep(bar_qfree + 8 * (k & 1), ((k >> 1) ^ (k & 1) ^ 1) & 1);
                            mbar_expect_tx(bar_q + 8 * (k & 1), QB_BYTES);
#pragma unroll 1
                            for (int hf = 0; hf < 2; hf++)
                                asm volatile("cp.async.bulk.tensor.5d.shared::cluster.global.tile.mbarrier::complete_tx::bytes [%0], [%1, {0, 0, %2, 0, 0}], [%3];\n"
                                             ::"r"(sb + SM_Q + (k & 1) * QB_BYTES + hf * 16384), "l"(&P.tm_w[k & 1]),
                                             "r"(8 * (((k >> 1) + 3) & 3) + 4 * hf), "r"(bar_q + 8 * (k & 1)) : "memory");
                        }
                        flag_wait_bounded(&g_sync[SY_B * 32], ep);
                        fence_async_global();
                    }
#pragma unroll 1
                    for (int j = 0; j < 4; j++, it++) {
                        mbar_wait_sleep(bar_empty + 8 * (it & 3), ((it >> 2) & 1) ^ 1);
                        mbar_expect_tx(bar_full + 8 * (it & 3), QB_BYTES);
                        bulk_g2s(sb + SM_KV + (it & 3) * KV_BYTES, g_w + (4 + j) * QB_BYTES, QB_BYTES, bar_full + 8 * (it & 3));
                    }
#pragma unroll 1
                    for (int k = 0; k < 26 + rank; k++) {
                        if (k == 0 || k == ((GF0 + 1) * NAUX - 16) / 128) { flag_wait_bounded(&g_sync[(k ? SY_AUX1 : SY_AUX0) * 32], NAUX * ep); fence_async_global(); }
                        mbar_wait_sleep(bar_qfree + 8 * (k & 1), ((k >> 1) ^ (k & 1) ^ 1) & 1);
                        mbar_expect_tx(bar_q + 8 * (k & 1), QB_BYTES);
                        bulk_g2s(sb + SM_Q + (k & 1) * QB_BYTES, g_agg + SC_TZB(k) * QB_BYTES, QB_BYTES, bar_q + 8 * (k & 1));
                    }
                }
            } else {
            const int par = ep & 1;
            if (blockIdx.x == 0 && t == 32) g_ovf_n[par ^ 1] = 0;
            if (blockIdx.x == 0 && warp == 1) *(uint4*)(g_hz + (lane >> 3) * 1024 + (lane & 7) * 16) = make_uint4(KV_OFF2, KV_OFF2, KV_OFF2, KV_OFF2);
            const uint32_t wlo = (uint32_t)(uintptr_t)H.s, whi = (uint32_t)((uintptr_t)H.s >> 32);
            const uint32_t blo = wlo + (uint32_t)offsetof(Scratch, bucket);
            {
                const int* pd = P.dst + blockIdx.x * 96 + (t - 32);
                const int* ps = P.src + blockIdx.x * 96 + (t - 32);
#pragma unroll 1
                for (int e = P.E - (blockIdx.x * 96 + (t - 32)); e > 0; e -= CSRU * NAUX * 32, pd += CSRU * NAUX * 32, ps += CSRU * NAUX * 32) {
                    int d[CSRU], sr[CSRU], sl[CSRU];
#pragma unroll
                    for (int i = 0; i < CSRU; i++) {
                        d[i] = e > i * NAUX * 32 ? __ldg(pd + i * NAUX * 32) : NN;
                        sr[i] = e > i * NAUX * 32 ? __ldg(ps + i * NAUX * 32) : 0;
                    }
#pragma unroll
                    for (int i = 0; i < CSRU; i++) {
                        sl[i] = 0;
                        asm volatile("{\n.reg .pred p;\nsetp.lt.s32 p, %2, %3;\n@p atom.relaxed.gpu.global.add.s32 %0, [%1], 1;\n}\n"
                                     : "+r"(sl[i]) : "l"(mkaddr(wlo + (uint32_t)offsetof(Scratch, cnt) + d[i] * 4, whi)), "r"(d[i]), "n"(NN) : "memory");
                    }
                    uint32_t ov = 0;
#pragma unroll
                    for (int i = 0; i < CSRU; i++) {
                        asm volatile("{\n.reg .pred p;\nsetp.lt.s32 p, %3, %4;\n@p st.global.u16 [%1], %2;\n@!p or.b32 %0, %0, %5;\n}\n"
                                     : "+r"(ov) : "l"(mkaddr(blo + d[i] * 128 + (sl[i] & 31) * 4 + (sl[i] >> 5) * 2, whi)), "h"((unsigned short)sr[i]), "r"(sl[i]), "n"(CAP), "r"(1 << i) : "memory");
                    }
#pragma unroll 1
                    for (; ov; ov &= ov - 1) {
                        const int i = (__ffs(ov) - 1) * (NAUX * 32);
                        int at;
                        asm volatile("atom.relaxed.gpu.global.add.s32 %0, [%1], 1;\n" : "=r"(at) : "l"(&g_ovf_n[par]) : "memory");
                        g_ovf[at] = make_int2(__ldg(pd + i), __ldg(ps + i));
                    }
                }
            }
            bar_sync(BAR_AUX, 96);
            if (warp == 1 && elect()) { red_release(&g_sync[SY_CSR * 32]); }
            __syncwarp();
            {
                const int r0 = blockIdx.x * 3 + warp - 1;
                const uint4* xp = (const uint4*)(H.x + r0 * 256) + lane;
                uint4* op = (uint4*)(P.out + r0 * 256) + lane;
#pragma unroll 1
                for (int r = r0; r < NN; r += CPYU * NAUX, xp += CPYU * NAUX * 32, op += CPYU * NAUX * 32) {
                    uint4 v[CPYU];
#pragma unroll
                    for (int i = 0; i < CPYU; i++) if (r + i * NAUX < NN) v[i] = ldg_pinned(xp + i * NAUX * 32);
#pragma unroll
                    for (int i = 0; i < CPYU; i++) if (r + i * NAUX < NN) op[i * NAUX * 32] = v[i];
                }
            }
            mbar_wait_bounded(bar_go, 1);
            if (const int un = (3 - warp) * (NAUX / 3) + (NAUX / 3 - 1) - blockIdx.x; un < 208) {
                flag_wait_bounded(&g_sync[SY_PART * 32], 52 * ep);
                uint8_t* pp = g_part + (un >> 3) * (4 * PART_BYTES);
                float* ml = (float*)(pp + QB_BYTES) + (un & 7) * 32;
                const float4 sa = __ldcg((const float4*)ml + g), sc = __ldcg((const float4*)ml + g + 2 * PART_BYTES / 16);
                const float n0 = fmaxf(sa.x, sc.x), n1 = fmaxf(sa.z, sc.z);
                const uint32_t a0 = pack_bf16(ex2(sa.x - n0), ex2(sa.x - n0)), a1 = pack_bf16(ex2(sa.z - n1), ex2(sa.z - n1));
                const uint32_t b0 = pack_bf16(ex2(sc.x - n0), ex2(sc.x - n0)), b1 = pack_bf16(ex2(sc.z - n1), ex2(sc.z - n1));
                __syncwarp();
                if (q == 0) ((float4*)ml)[g] = make_float4(n0, sa.y * bf_hi(a0) + sc.y * bf_hi(b0), n1, sa.w * bf_hi(a1) + sc.w * bf_hi(b1));
                uint4* d = (uint4*)(pp + (un & 4) * 256 + (un & 7) * 8192) + lane;
#pragma unroll 1
                for (int i = 0; i < 4; i++, d += 128) {
                    uint4 u[4], v[4];
#pragma unroll
                    for (int j = 0; j < 4; j++) { u[j] = __ldcg(d + j * 32); v[j] = __ldcg(d + j * 32 + 2 * PART_BYTES / 16); }
#pragma unroll
                    for (int j = 0; j < 4; j++)
                        d[j * 32] = make_uint4(hfma2(v[j].x, b0, hmul2(u[j].x, a0)), hfma2(v[j].y, b1, hmul2(u[j].y, a1)),
                                               hfma2(v[j].z, b0, hmul2(u[j].z, a0)), hfma2(v[j].w, b1, hmul2(u[j].w, a1)));
                }
            }
            flag_wait_bounded(&g_sync[SY_CSR * 32], NCTA * ep);
            if (warp == 2 && blockIdx.x < 129) {
                uint4* z = blockIdx.x < 128 ? (uint4*)(g_w + blockIdx.x * 1024) + lane : (uint4*)&g_sync[SY_DONE * 32 + 4];
                z[0] = make_uint4(0, 0, 0, 0);
                if (blockIdx.x < 128) z[32] = make_uint4(0, 0, 0, 0);
            }
            {
                const uint32_t lc = (lane >> 3) * 1024 + (lane & 7) * 16;
                const uint32_t alo = wlo ^ lc;
                const int node0 = blockIdx.x * 3 + warp - 17;
                auto node = [&](int i) { const int nd = node0 + i * NAUX; return (int)min((unsigned)nd, (unsigned)(nd + NN)); };
                const int num = (NN - 17 - node0) / NAUX + 1;
                uint32_t mine = 0;
                if (lane < num) {
                    mine = min(__ldcg(&g_cnt[node(lane)]), CAP + 1) | (uint32_t)__ldg((const unsigned short*)P.deg_inv + node(lane)) << 16;
                    g_cnt[node(lane)] = 0;
                }
                auto row = [&](int off) {
                    uint4 v;
                    asm volatile("ld.global.v4.u32 {%0, %1, %2, %3}, [%4];\n"
                                 : "=r"(v.x), "=r"(v.y), "=r"(v.z), "=r"(v.w) : "l"(mkaddr(alo ^ off, whi)));
                    return v;
                };
                auto ents = [&](int i) {
                    uint32_t e;
                    asm volatile("ld.global.cg.u32 %0, [%1];\n" : "=r"(e) : "l"(mkaddr(blo + (min(node(i), NN - 1) * 32 + lane) * 4, whi)));
                    return e;
                };
                auto store = [&](int i, const float (&a)[8]) {
                    const float di = bf_hi(__shfl_sync(~0u, mine, i)) * (1.f / KV_SCALE);
                    const int nd = node(i);
                    *(uint4*)(g_agg + (uint32_t)(((nd >> 3) * 4096 + (nd & 7) * 144) ^ lc)) =
                        make_uint4(pack_bf16(a[0] * di, a[1] * di), pack_bf16(a[2] * di, a[3] * di), pack_bf16(a[4] * di, a[5] * di), pack_bf16(a[6] * di, a[7] * di));
                };
#pragma unroll 1
                for (uint32_t big = __ballot_sync(~0u, (mine & 0xFFFF) > CAP); big; big &= big - 1) {
                    const int i = __ffs(big) - 1, no = __ldcg(&g_ovf_n[par]);
                    float a[8] = {};
#pragma unroll 1
                    for (int k = -64; k < no; k += 32) {
                        const int2 pr = k < 0 ? make_int2(node(i), (ents(i) >> (k & 32) / 2) & 0xFFFF) : k + lane < no ? __ldcg(&g_ovf[k + lane]) : make_int2(-1, 0);
#pragma unroll 1
                        for (uint32_t mk = __ballot_sync(~0u, pr.x == node(i)); mk; mk &= mk - 1) {
                            const uint4 v = row(row_off(__shfl_sync(~0u, pr.y, __ffs(mk) - 1)));
                            a[0] += f16_lo(v.x) - KV_OFF; a[1] += f16_hi(v.x) - KV_OFF; a[2] += f16_lo(v.y) - KV_OFF; a[3] += f16_hi(v.y) - KV_OFF;
                            a[4] += f16_lo(v.z) - KV_OFF; a[5] += f16_hi(v.z) - KV_OFF; a[6] += f16_lo(v.w) - KV_OFF; a[7] += f16_hi(v.w) - KV_OFF;
                        }
                    }
                    store(i, a);
                }
                auto add4 = [&](const uint4& a, const uint4& b) { return make_uint4(hadd2_f16(a.x, b.x), hadd2_f16(a.y, b.y), hadd2_f16(a.z, b.z), hadd2_f16(a.w, b.w)); };
                int ni = -1, left = 0, pos = 0, ec = 0;
                uint32_t en = ents(0);
                uint4 acc = make_uint4(0, 0, 0, 0);
                auto step = [&](uint4 (&v)[4], int& tag) {
                    if (left <= 0 || pos == 32) {
                        if (left > 0) {
                            en = ents(ni) >> 16;
                        } else {
                            ni++;
                            left = __shfl_sync(~0u, mine, ni) & 0xFFFF;
                            if (left > CAP) left = 0;
                        }
                        ec = lane < left ? row_off(en & 0xFFFF) : 0;
                        en = ents(ni + 1);
                        pos = 0;
                    }
                    int of[4];
#pragma unroll
                    for (int j = 0; j < 4; j++) asm volatile("shfl.sync.idx.b32 %0, %1, %2, 31, -1;\n" : "=r"(of[j]) : "r"(ec), "r"(pos + j));
                    acc = add4(acc, add4(add4(add4(v[0], v[1]), make_uint4(KV_NEG4, KV_NEG4, KV_NEG4, KV_NEG4)), add4(v[2], v[3])));
                    asm volatile("" : "+r"(acc.x), "+r"(acc.y), "+r"(acc.z), "+r"(acc.w));
                    asm volatile("{\n.reg .pred p;\nsetp.lt.s32 p, %0, 0;\nL:\n@p pmevent 0;\n@p bra L;\n}\n" ::"r"(ni) : "memory");
#pragma unroll
                    for (int j = 0; j < 4; j++) v[j] = row(of[j]);
                    pos += 4; left -= 4;
                    const int i = tag;
                    tag = left <= 0 ? ni : -1;
                    if (i >= 0) {
                        const float a[8] = {f16_lo(acc.x), f16_hi(acc.x), f16_lo(acc.y), f16_hi(acc.y), f16_lo(acc.z), f16_hi(acc.z), f16_lo(acc.w), f16_hi(acc.w)};
                        if ((__shfl_sync(~0u, mine, i) & 0xFFFF) <= CAP) store(i, a);
                        acc = make_uint4(0, 0, 0, 0);
                        if (i == GF0 || i == 8) {
                            __syncwarp();
                            if (elect()) red_release(&g_sync[(i == 8 ? SY_AUX1 : SY_AUX0) * 32]);
                            __syncwarp();
                        }
                    }
                    return i == num - 1;
                };
                uint4 va[4], vb[4];
#pragma unroll
                for (int j = 0; j < 4; j++) va[j] = vb[j] = make_uint4(KV_OFF2, KV_OFF2, KV_OFF2, KV_OFF2);
                int ta = -1, tb = -1;
#pragma unroll 1
                while (!step(va, ta) && !step(vb, tb)) {}
            }
            bar_sync(BAR_AUX, 96);
            if (warp == 1 && elect()) {
                red_release(&g_sync[SY_AUX * 32]);
                red_add(&g_sync[SY_DONE * 32]);
            }
            }
        }
        __syncwarp();
        asm volatile("barrier.cluster.arrive.relaxed.aligned;\n" ::: "memory");
        if (warp == 1) mbar_wait_bounded(bar_end, 0);
        else if (elect()) mbar_arrive(bar_end);
        __syncwarp();
        asm volatile("barrier.cluster.wait.acquire.aligned;\n" ::: "memory");
    }
}

}

extern "C" void kernel_launch(void* const* d_in, const int* in_sizes, int n_in, void* d_out, int out_size) {
    Hot H;
    Params P;
    H.x = (const __nv_bfloat16*)d_in[0];
    P.src = (const int*)d_in[1];
    P.dst = (const int*)d_in[2];
    P.deg_inv = (const __nv_bfloat16*)d_in[3];
    H.wq = (const __nv_bfloat16*)d_in[5];
    H.wk = (const __nv_bfloat16*)d_in[6];
    P.out = (__nv_bfloat16*)d_out;
    typedef CUresult (*EncodeFn)(CUtensorMap*, CUtensorMapDataType, cuuint32_t, void*, const cuuint64_t*, const cuuint64_t*, const cuuint32_t*,
                                 const cuuint32_t*, CUtensorMapInterleave, CUtensorMapSwizzle, CUtensorMapL2promotion, CUtensorMapFloatOOBfill);
    void* fn = nullptr;
    cudaDriverEntryPointQueryResult qr;
    cudaGetDriverEntryPoint("cuTensorMapEncodeTiled", &fn, cudaEnableDefault, &qr);
    auto encode = [&](CUtensorMap* tm, const void* ptr, int rows, int box_rows, int box_cb = 4) {
        const cuuint64_t dims[4] = {64, 8, 4, (cuuint64_t)rows / 8};
        const cuuint64_t strides[3] = {512, 128, 4096};
        const cuuint32_t box[4] = {64, 8, (cuuint32_t)box_cb, (cuuint32_t)box_rows / 8}, es[4] = {1, 1, 1, 1};
        ((EncodeFn)fn)(tm, CU_TENSOR_MAP_DATA_TYPE_BFLOAT16, 4, (void*)ptr, dims, strides, box, es, CU_TENSOR_MAP_INTERLEAVE_NONE,
                       CU_TENSOR_MAP_SWIZZLE_128B, CU_TENSOR_MAP_L2_PROMOTION_NONE, CU_TENSOR_MAP_FLOAT_OOB_FILL_NONE);
    };
    encode(&P.tm_out, d_out, NN, 8);
    encode(&P.tm_outc, d_out, NN, 16, 1);
    for (int i = 0; i < 2; i++) {
        const cuuint64_t dims[5] = {64, 2, 32, 4, 4};
        const cuuint64_t strides[4] = {512, 4096, 128, 1024};
        const cuuint32_t box[5] = {64, 2, 4, 4, 4}, es[5] = {1, 1, 1, 1, 1};
        ((EncodeFn)fn)(&P.tm_w[i], CU_TENSOR_MAP_DATA_TYPE_BFLOAT16, 5, d_in[i ? 4 : 7], dims, strides, box, es, CU_TENSOR_MAP_INTERLEAVE_NONE,
                       CU_TENSOR_MAP_SWIZZLE_128B, CU_TENSOR_MAP_L2_PROMOTION_NONE, CU_TENSOR_MAP_FLOAT_OOB_FILL_NONE);
    }
    encode(&P.tm_w[2], d_in[8], 256, 64);
    void* raw = nullptr;
    cudaGetSymbolAddress(&raw, g_raw);
    H.s = (Scratch*)(((uintptr_t)raw + ((8 << 20) - 1)) & ~(uintptr_t)((8 << 20) - 1));
    P.dhi = 0x40000100u;
    P.E = in_sizes[1] < MAXE ? in_sizes[1] : MAXE;
    cudaFuncSetAttribute(k_main, cudaFuncAttributeMaxDynamicSharedMemorySize, SM_TOTAL);
    k_main<<<NCTA, 384, SM_TOTAL>>>(H, P);
}
```

```cpp
#include <cuda_runtime.h>
#include <cuda.h>
#include <cuda_bf16.h>
#include <stdint.h>
#include <stddef.h>

namespace {

constexpr int NN = 10000;
constexpr int BN = 80;
constexpr int NKV = NN / BN;
constexpr int NQB = 158;
constexpr int NCTA = 132;
constexpr int NAUX = 3 * (NCTA - 2);
constexpr int STAGES = 4;
constexpr int KV_BYTES = BN * 512;
constexpr int QB_BYTES = 64 * 512;
constexpr int PART_BYTES = QB_BYTES + 512;
constexpr int CAP = 64;
constexpr int MAXE = 160000;

#define QRND(v) (((v) + 0x00040004u) & 0xFFF8FFF8u)
#define GO0 5
#define GO1 35
#define GF0 2
#define CSRU 3
#define CPYU 9
#define REFUP 2.f
#define SND0 10
#define CUT2 2
#define REG_C 224
#define REG_P 56

enum { SY_PART = 4, SY_H1 = 5, SY_CSR = 6, SY_AUX = 7, SY_DONE = 8, SY_AUX0 = 9, SY_B = 10, SY_AUX1 = 11, SY_H0 = 12 };
struct Scratch {
    uint8_t hz[4096 + NN * 512];
    uint8_t w[12 * QB_BYTES];
    int sync[25 * 32];
    int qflag[96];
    int ovf_n[32];
    float r255[512];
    int cnt[NN + 16];
    int bucket[(NN + 1) * 32];
    int2 ovf[MAXE];
    uint8_t q[NQB * QB_BYTES];
    uint8_t agg[NQB * QB_BYTES];
    uint8_t part[52 * 2 * PART_BYTES];
};
static_assert(offsetof(Scratch, ovf) <= (8 << 20), "window");
static_assert(offsetof(Scratch, qflag) == offsetof(Scratch, sync) + 25 * 128, "flags");
static_assert(offsetof(Scratch, w) % 1024 == 0 && offsetof(Scratch, sync) % 128 == 0 &&
              offsetof(Scratch, bucket) % 128 == 0 && offsetof(Scratch, q) % 128 == 0, "alignment");
__device__ uint8_t g_raw[(8 << 20) + sizeof(Scratch)];
#define g_hz (H.s->hz)
#define g_w (H.s->w)
#define g_sync (H.s->sync)
#define g_qflag (H.s->qflag)
#define g_ovf_n (H.s->ovf_n)
#define g_cnt (H.s->cnt)
#define g_bucket (H.s->bucket)
#define g_ovf (H.s->ovf)
#define g_q (H.s->q)
#define g_agg (H.s->agg)
#define g_part (H.s->part)

__device__ __forceinline__ void wgmma_ss_n80(float (&d)[40], uint64_t da, uint64_t db) {
    asm volatile("wgmma.mma_async.sync.aligned.m64n80k16.f32.f16.f16 {"
        "%0, %1, %2, %3, %4, %5, %6, %7, %8, %9, %10, %11, %12, %13, %14, %15, %16, %17, %18, %19, %20, %21, %22, %23, %24, %25, %26, %27, %28, %29, %30, %31, "
        "%32, %33, %34, %35, %36, %37, %38, %39}, %40, %41, 1, 1, 1, 0, 0;\n"
        : "+f"(d[0]), "+f"(d[1]), "+f"(d[2]), "+f"(d[3]), "+f"(d[4]), "+f"(d[5]), "+f"(d[6]), "+f"(d[7]),
          "+f"(d[8]), "+f"(d[9]), "+f"(d[10]), "+f"(d[11]), "+f"(d[12]), "+f"(d[13]), "+f"(d[14]), "+f"(d[15]),
          "+f"(d[16]), "+f"(d[17]), "+f"(d[18]), "+f"(d[19]), "+f"(d[20]), "+f"(d[21]), "+f"(d[22]), "+f"(d[23]),
          "+f"(d[24]), "+f"(d[25]), "+f"(d[26]), "+f"(d[27]), "+f"(d[28]), "+f"(d[29]), "+f"(d[30]), "+f"(d[31]),
          "+f"(d[32]), "+f"(d[33]), "+f"(d[34]), "+f"(d[35]), "+f"(d[36]), "+f"(d[37]), "+f"(d[38]), "+f"(d[39])
        : "l"(da), "l"(db));
}
__device__ __forceinline__ void wgmma_ss_n80_init(float (&d)[40], uint64_t da, uint64_t db) {
    asm volatile("wgmma.mma_async.sync.aligned.m64n80k16.f32.f16.f16 {"
        "%0, %1, %2, %3, %4, %5, %6, %7, %8, %9, %10, %11, %12, %13, %14, %15, %16, %17, %18, %19, %20, %21, %22, %23, %24, %25, %26, %27, %28, %29, %30, %31, "
        "%32, %33, %34, %35, %36, %37, %38, %39}, %40, %41, 0, 1, 1, 0, 0;\n"
        : "=f"(d[0]), "=f"(d[1]), "=f"(d[2]), "=f"(d[3]), "=f"(d[4]), "=f"(d[5]), "=f"(d[6]), "=f"(d[7]),
          "=f"(d[8]), "=f"(d[9]), "=f"(d[10]), "=f"(d[11]), "=f"(d[12]), "=f"(d[13]), "=f"(d[14]), "=f"(d[15]),
          "=f"(d[16]), "=f"(d[17]), "=f"(d[18]), "=f"(d[19]), "=f"(d[20]), "=f"(d[21]), "=f"(d[22]), "=f"(d[23]),
          "=f"(d[24]), "=f"(d[25]), "=f"(d[26]), "=f"(d[27]), "=f"(d[28]), "=f"(d[29]), "=f"(d[30]), "=f"(d[31]),
          "=f"(d[32]), "=f"(d[33]), "=f"(d[34]), "=f"(d[35]), "=f"(d[36]), "=f"(d[37]), "=f"(d[38]), "=f"(d[39])
        : "l"(da), "l"(db));
}
__device__ __forceinline__ void wgmma_rs_n256_tb(float (&d)[128], uint32_t a0, uint32_t a1, uint32_t a2, uint32_t a3, uint64_t db) {
    asm volatile("wgmma.mma_async.sync.aligned.m64n256k16.f32.f16.f16 {"
        "%0, %1, %2, %3, %4, %5, %6, %7, %8, %9, %10, %11, %12, %13, %14, %15, %16, %17, %18, %19, %20, %21, %22, %23, %24, %25, %26, %27, %28, %29, %30, %31, "
        "%32, %33, %34, %35, %36, %37, %38, %39, %40, %41, %42, %43, %44, %45, %46, %47, %48, %49, %50, %51, %52, %53, %54, %55, %56, %57, %58, %59, %60, %61, %62, %63, "
        "%64, %65, %66, %67, %68, %69, %70, %71, %72, %73, %74, %75, %76, %77, %78, %79, %80, %81, %82, %83, %84, %85, %86, %87, %88, %89, %90, %91, %92, %93, %94, %95, "
        "%96, %97, %98, %99, %100, %101, %102, %103, %104, %105, %106, %107, %108, %109, %110, %111, %112, %113, %114, %115, %116, %117, %118, %119, %120, %121, %122, %123, %124, %125, %126, %127}, {%128, %129, %130, %131}, %132, 1, 1, 1, 1;\n"
        : "+f"(d[0]), "+f"(d[1]), "+f"(d[2]), "+f"(d[3]), "+f"(d[4]), "+f"(d[5]), "+f"(d[6]), "+f"(d[7]),
          "+f"(d[8]), "+f"(d[9]), "+f"(d[10]), "+f"(d[11]), "+f"(d[12]), "+f"(d[13]), "+f"(d[14]), "+f"(d[15]),
          "+f"(d[16]), "+f"(d[17]), "+f"(d[18]), "+f"(d[19]), "+f"(d[20]), "+f"(d[21]), "+f"(d[22]), "+f"(d[23]),
          "+f"(d[24]), "+f"(d[25]), "+f"(d[26]), "+f"(d[27]), "+f"(d[28]), "+f"(d[29]), "+f"(d[30]), "+f"(d[31]),
          "+f"(d[32]), "+f"(d[33]), "+f"(d[34]), "+f"(d[35]), "+f"(d[36]), "+f"(d[37]), "+f"(d[38]), "+f"(d[39]),
          "+f"(d[40]), "+f"(d[41]), "+f"(d[42]), "+f"(d[43]), "+f"(d[44]), "+f"(d[45]), "+f"(d[46]), "+f"(d[47]),
          "+f"(d[48]), "+f"(d[49]), "+f"(d[50]), "+f"(d[51]), "+f"(d[52]), "+f"(d[53]), "+f"(d[54]), "+f"(d[55]),
          "+f"(d[56]), "+f"(d[57]), "+f"(d[58]), "+f"(d[59]), "+f"(d[60]), "+f"(d[61]), "+f"(d[62]), "+f"(d[63]),
          "+f"(d[64]), "+f"(d[65]), "+f"(d[66]), "+f"(d[67]), "+f"(d[68]), "+f"(d[69]), "+f"(d[70]), "+f"(d[71]),
          "+f"(d[72]), "+f"(d[73]), "+f"(d[74]), "+f"(d[75]), "+f"(d[76]), "+f"(d[77]), "+f"(d[78]), "+f"(d[79]),
          "+f"(d[80]), "+f"(d[81]), "+f"(d[82]), "+f"(d[83]), "+f"(d[84]), "+f"(d[85]), "+f"(d[86]), "+f"(d[87]),
          "+f"(d[88]), "+f"(d[89]), "+f"(d[90]), "+f"(d[91]), "+f"(d[92]), "+f"(d[93]), "+f"(d[94]), "+f"(d[95]),
          "+f"(d[96]), "+f"(d[97]), "+f"(d[98]), "+f"(d[99]), "+f"(d[100]), "+f"(d[101]), "+f"(d[102]), "+f"(d[103]),
          "+f"(d[104]), "+f"(d[105]), "+f"(d[106]), "+f"(d[107]), "+f"(d[108]), "+f"(d[109]), "+f"(d[110]), "+f"(d[111]),
          "+f"(d[112]), "+f"(d[113]), "+f"(d[114]), "+f"(d[115]), "+f"(d[116]), "+f"(d[117]), "+f"(d[118]), "+f"(d[119]),
          "+f"(d[120]), "+f"(d[121]), "+f"(d[122]), "+f"(d[123]), "+f"(d[124]), "+f"(d[125]), "+f"(d[126]), "+f"(d[127])
        : "r"(a0), "r"(a1), "r"(a2), "r"(a3), "l"(db));
}
__device__ __forceinline__ void wgmma_rs_n256_tb_init(float (&d)[128], uint32_t a0, uint32_t a1, uint32_t a2, uint32_t a3, uint64_t db) {
    asm volatile("wgmma.mma_async.sync.aligned.m64n256k16.f32.f16.f16 {"
        "%0, %1, %2, %3, %4, %5, %6, %7, %8, %9, %10, %11, %12, %13, %14, %15, %16, %17, %18, %19, %20, %21, %22, %23, %24, %25, %26, %27, %28, %29, %30, %31, "
        "%32, %33, %34, %35, %36, %37, %38, %39, %40, %41, %42, %43, %44, %45, %46, %47, %48, %49, %50, %51, %52, %53, %54, %55, %56, %57, %58, %59, %60, %61, %62, %63, "
        "%64, %65, %66, %67, %68, %69, %70, %71, %72, %73, %74, %75, %76, %77, %78, %79, %80, %81, %82, %83, %84, %85, %86, %87, %88, %89, %90, %91, %92, %93, %94, %95, "
        "%96, %97, %98, %99, %100, %101, %102, %103, %104, %105, %106, %107, %108, %109, %110, %111, %112, %113, %114, %115, %116, %117, %118, %119, %120, %121, %122, %123, %124, %125, %126, %127}, {%128, %129, %130, %131}, %132, 0, 1, 1, 1;\n"
        : "=f"(d[0]), "=f"(d[1]), "=f"(d[2]), "=f"(d[3]), "=f"(d[4]), "=f"(d[5]), "=f"(d[6]), "=f"(d[7]),
          "=f"(d[8]), "=f"(d[9]), "=f"(d[10]), "=f"(d[11]), "=f"(d[12]), "=f"(d[13]), "=f"(d[14]), "=f"(d[15]),
          "=f"(d[16]), "=f"(d[17]), "=f"(d[18]), "=f"(d[19]), "=f"(d[20]), "=f"(d[21]), "=f"(d[22]), "=f"(d[23]),
          "=f"(d[24]), "=f"(d[25]), "=f"(d[26]), "=f"(d[27]), "=f"(d[28]), "=f"(d[29]), "=f"(d[30]), "=f"(d[31]),
          "=f"(d[32]), "=f"(d[33]), "=f"(d[34]), "=f"(d[35]), "=f"(d[36]), "=f"(d[37]), "=f"(d[38]), "=f"(d[39]),
          "=f"(d[40]), "=f"(d[41]), "=f"(d[42]), "=f"(d[43]), "=f"(d[44]), "=f"(d[45]), "=f"(d[46]), "=f"(d[47]),
          "=f"(d[48]), "=f"(d[49]), "=f"(d[50]), "=f"(d[51]), "=f"(d[52]), "=f"(d[53]), "=f"(d[54]), "=f"(d[55]),
          "=f"(d[56]), "=f"(d[57]), "=f"(d[58]), "=f"(d[59]), "=f"(d[60]), "=f"(d[61]), "=f"(d[62]), "=f"(d[63]),
          "=f"(d[64]), "=f"(d[65]), "=f"(d[66]), "=f"(d[67]), "=f"(d[68]), "=f"(d[69]), "=f"(d[70]), "=f"(d[71]),
          "=f"(d[72]), "=f"(d[73]), "=f"(d[74]), "=f"(d[75]), "=f"(d[76]), "=f"(d[77]), "=f"(d[78]), "=f"(d[79]),
          "=f"(d[80]), "=f"(d[81]), "=f"(d[82]), "=f"(d[83]), "=f"(d[84]), "=f"(d[85]), "=f"(d[86]), "=f"(d[87]),
          "=f"(d[88]), "=f"(d[89]), "=f"(d[90]), "=f"(d[91]), "=f"(d[92]), "=f"(d[93]), "=f"(d[94]), "=f"(d[95]),
          "=f"(d[96]), "=f"(d[97]), "=f"(d[98]), "=f"(d[99]), "=f"(d[100]), "=f"(d[101]), "=f"(d[102]), "=f"(d[103]),
          "=f"(d[104]), "=f"(d[105]), "=f"(d[106]), "=f"(d[107]), "=f"(d[108]), "=f"(d[109]), "=f"(d[110]), "=f"(d[111]),
          "=f"(d[112]), "=f"(d[113]), "=f"(d[114]), "=f"(d[115]), "=f"(d[116]), "=f"(d[117]), "=f"(d[118]), "=f"(d[119]),
          "=f"(d[120]), "=f"(d[121]), "=f"(d[122]), "=f"(d[123]), "=f"(d[124]), "=f"(d[125]), "=f"(d[126]), "=f"(d[127])
        : "r"(a0), "r"(a1), "r"(a2), "r"(a3), "l"(db));
}
__device__ __forceinline__ void wgmma_rs_n256_tb_pred(float (&d)[128], uint32_t a0, uint32_t a1, uint32_t a2, uint32_t a3, uint64_t db, int acc) {
    asm volatile("{\n.reg .pred p;\nsetp.ne.s32 p, %133, 0;\nwgmma.mma_async.sync.aligned.m64n256k16.f32.f16.f16 {"
        "%0, %1, %2, %3, %4, %5, %6, %7, %8, %9, %10, %11, %12, %13, %14, %15, %16, %17, %18, %19, %20, %21, %22, %23, %24, %25, %26, %27, %28, %29, %30, %31, "
        "%32, %33, %34, %35, %36, %37, %38, %39, %40, %41, %42, %43, %44, %45, %46, %47, %48, %49, %50, %51, %52, %53, %54, %55, %56, %57, %58, %59, %60, %61, %62, %63, "
        "%64, %65, %66, %67, %68, %69, %70, %71, %72, %73, %74, %75, %76, %77, %78, %79, %80, %81, %82, %83, %84, %85, %86, %87, %88, %89, %90, %91, %92, %93, %94, %95, "
        "%96, %97, %98, %99, %100, %101, %102, %103, %104, %105, %106, %107, %108, %109, %110, %111, %112, %113, %114, %115, %116, %117, %118, %119, %120, %121, %122, %123, %124, %125, %126, %127}, {%128, %129, %130, %131}, %132, p, 1, 1, 1;\n}\n"
        : "+f"(d[0]), "+f"(d[1]), "+f"(d[2]), "+f"(d[3]), "+f"(d[4]), "+f"(d[5]), "+f"(d[6]), "+f"(d[7]),
          "+f"(d[8]), "+f"(d[9]), "+f"(d[10]), "+f"(d[11]), "+f"(d[12]), "+f"(d[13]), "+f"(d[14]), "+f"(d[15]),
          "+f"(d[16]), "+f"(d[17]), "+f"(d[18]), "+f"(d[19]), "+f"(d[20]), "+f"(d[21]), "+f"(d[22]), "+f"(d[23]),
          "+f"(d[24]), "+f"(d[25]), "+f"(d[26]), "+f"(d[27]), "+f"(d[28]), "+f"(d[29]), "+f"(d[30]), "+f"(d[31]),
          "+f"(d[32]), "+f"(d[33]), "+f"(d[34]), "+f"(d[35]), "+f"(d[36]), "+f"(d[37]), "+f"(d[38]), "+f"(d[39]),
          "+f"(d[40]), "+f"(d[41]), "+f"(d[42]), "+f"(d[43]), "+f"(d[44]), "+f"(d[45]), "+f"(d[46]), "+f"(d[47]),
          "+f"(d[48]), "+f"(d[49]), "+f"(d[50]), "+f"(d[51]), "+f"(d[52]), "+f"(d[53]), "+f"(d[54]), "+f"(d[55]),
          "+f"(d[56]), "+f"(d[57]), "+f"(d[58]), "+f"(d[59]), "+f"(d[60]), "+f"(d[61]), "+f"(d[62]), "+f"(d[63]),
          "+f"(d[64]), "+f"(d[65]), "+f"(d[66]), "+f"(d[67]), "+f"(d[68]), "+f"(d[69]), "+f"(d[70]), "+f"(d[71]),
          "+f"(d[72]), "+f"(d[73]), "+f"(d[74]), "+f"(d[75]), "+f"(d[76]), "+f"(d[77]), "+f"(d[78]), "+f"(d[79]),
          "+f"(d[80]), "+f"(d[81]), "+f"(d[82]), "+f"(d[83]), "+f"(d[84]), "+f"(d[85]), "+f"(d[86]), "+f"(d[87]),
          "+f"(d[88]), "+f"(d[89]), "+f"(d[90]), "+f"(d[91]), "+f"(d[92]), "+f"(d[93]), "+f"(d[94]), "+f"(d[95]),
          "+f"(d[96]), "+f"(d[97]), "+f"(d[98]), "+f"(d[99]), "+f"(d[100]), "+f"(d[101]), "+f"(d[102]), "+f"(d[103]),
          "+f"(d[104]), "+f"(d[105]), "+f"(d[106]), "+f"(d[107]), "+f"(d[108]), "+f"(d[109]), "+f"(d[110]), "+f"(d[111]),
          "+f"(d[112]), "+f"(d[113]), "+f"(d[114]), "+f"(d[115]), "+f"(d[116]), "+f"(d[117]), "+f"(d[118]), "+f"(d[119]),
          "+f"(d[120]), "+f"(d[121]), "+f"(d[122]), "+f"(d[123]), "+f"(d[124]), "+f"(d[125]), "+f"(d[126]), "+f"(d[127])
        : "r"(a0), "r"(a1), "r"(a2), "r"(a3), "l"(db), "r"(acc));
}
__device__ __forceinline__ void wgmma_ss_n256_tb(float (&d)[128], uint64_t da, uint64_t db) {
    asm volatile("wgmma.mma_async.sync.aligned.m64n256k16.f32.bf16.bf16 {"
        "%0, %1, %2, %3, %4, %5, %6, %7, %8, %9, %10, %11, %12, %13, %14, %15, %16, %17, %18, %19, %20, %21, %22, %23, %24, %25, %26, %27, %28, %29, %30, %31, "
        "%32, %33, %34, %35, %36, %37, %38, %39, %40, %41, %42, %43, %44, %45, %46, %47, %48, %49, %50, %51, %52, %53, %54, %55, %56, %57, %58, %59, %60, %61, %62, %63, "
        "%64, %65, %66, %67, %68, %69, %70, %71, %72, %73, %74, %75, %76, %77, %78, %79, %80, %81, %82, %83, %84, %85, %86, %87, %88, %89, %90, %91, %92, %93, %94, %95, "
        "%96, %97, %98, %99, %100, %101, %102, %103, %104, %105, %106, %107, %108, %109, %110, %111, %112, %113, %114, %115, %116, %117, %118, %119, %120, %121, %122, %123, %124, %125, %126, %127}, %128, %129, 1, 1, 1, 0, 1;\n"
        : "+f"(d[0]), "+f"(d[1]), "+f"(d[2]), "+f"(d[3]), "+f"(d[4]), "+f"(d[5]), "+f"(d[6]), "+f"(d[7]),
          "+f"(d[8]), "+f"(d[9]), "+f"(d[10]), "+f"(d[11]), "+f"(d[12]), "+f"(d[13]), "+f"(d[14]), "+f"(d[15]),
          "+f"(d[16]), "+f"(d[17]), "+f"(d[18]), "+f"(d[19]), "+f"(d[20]), "+f"(d[21]), "+f"(d[22]), "+f"(d[23]),
          "+f"(d[24]), "+f"(d[25]), "+f"(d[26]), "+f"(d[27]), "+f"(d[28]), "+f"(d[29]), "+f"(d[30]), "+f"(d[31]),
          "+f"(d[32]), "+f"(d[33]), "+f"(d[34]), "+f"(d[35]), "+f"(d[36]), "+f"(d[37]), "+f"(d[38]), "+f"(d[39]),
          "+f"(d[40]), "+f"(d[41]), "+f"(d[42]), "+f"(d[43]), "+f"(d[44]), "+f"(d[45]), "+f"(d[46]), "+f"(d[47]),
          "+f"(d[48]), "+f"(d[49]), "+f"(d[50]), "+f"(d[51]), "+f"(d[52]), "+f"(d[53]), "+f"(d[54]), "+f"(d[55]),
          "+f"(d[56]), "+f"(d[57]), "+f"(d[58]), "+f"(d[59]), "+f"(d[60]), "+f"(d[61]), "+f"(d[62]), "+f"(d[63]),
          "+f"(d[64]), "+f"(d[65]), "+f"(d[66]), "+f"(d[67]), "+f"(d[68]), "+f"(d[69]), "+f"(d[70]), "+f"(d[71]),
          "+f"(d[72]), "+f"(d[73]), "+f"(d[74]), "+f"(d[75]), "+f"(d[76]), "+f"(d[77]), "+f"(d[78]), "+f"(d[79]),
          "+f"(d[80]), "+f"(d[81]), "+f"(d[82]), "+f"(d[83]), "+f"(d[84]), "+f"(d[85]), "+f"(d[86]), "+f"(d[87]),
          "+f"(d[88]), "+f"(d[89]), "+f"(d[90]), "+f"(d[91]), "+f"(d[92]), "+f"(d[93]), "+f"(d[94]), "+f"(d[95]),
          "+f"(d[96]), "+f"(d[97]), "+f"(d[98]), "+f"(d[99]), "+f"(d[100]), "+f"(d[101]), "+f"(d[102]), "+f"(d[103]),
          "+f"(d[104]), "+f"(d[105]), "+f"(d[106]), "+f"(d[107]), "+f"(d[108]), "+f"(d[109]), "+f"(d[110]), "+f"(d[111]),
          "+f"(d[112]), "+f"(d[113]), "+f"(d[114]), "+f"(d[115]), "+f"(d[116]), "+f"(d[117]), "+f"(d[118]), "+f"(d[119]),
          "+f"(d[120]), "+f"(d[121]), "+f"(d[122]), "+f"(d[123]), "+f"(d[124]), "+f"(d[125]), "+f"(d[126]), "+f"(d[127])
        : "l"(da), "l"(db));
}
__device__ __forceinline__ void wgmma_ss_n256_tb_init(float (&d)[128], uint64_t da, uint64_t db) {
    asm volatile("wgmma.mma_async.sync.aligned.m64n256k16.f32.bf16.bf16 {"
        "%0, %1, %2, %3, %4, %5, %6, %7, %8, %9, %10, %11, %12, %13, %14, %15, %16, %17, %18, %19, %20, %21, %22, %23, %24, %25, %26, %27, %28, %29, %30, %31, "
        "%32, %33, %34, %35, %36, %37, %38, %39, %40, %41, %42, %43, %44, %45, %46, %47, %48, %49, %50, %51, %52, %53, %54, %55, %56, %57, %58, %59, %60, %61, %62, %63, "
        "%64, %65, %66, %67, %68, %69, %70, %71, %72, %73, %74, %75, %76, %77, %78, %79, %80, %81, %82, %83, %84, %85, %86, %87, %88, %89, %90, %91, %92, %93, %94, %95, "
        "%96, %97, %98, %99, %100, %101, %102, %103, %104, %105, %106, %107, %108, %109, %110, %111, %112, %113, %114, %115, %116, %117, %118, %119, %120, %121, %122, %123, %124, %125, %126, %127}, %128, %129, 0, 1, 1, 0, 1;\n"
        : "=f"(d[0]), "=f"(d[1]), "=f"(d[2]), "=f"(d[3]), "=f"(d[4]), "=f"(d[5]), "=f"(d[6]), "=f"(d[7]),
          "=f"(d[8]), "=f"(d[9]), "=f"(d[10]), "=f"(d[11]), "=f"(d[12]), "=f"(d[13]), "=f"(d[14]), "=f"(d[15]),
          "=f"(d[16]), "=f"(d[17]), "=f"(d[18]), "=f"(d[19]), "=f"(d[20]), "=f"(d[21]), "=f"(d[22]), "=f"(d[23]),
          "=f"(d[24]), "=f"(d[25]), "=f"(d[26]), "=f"(d[27]), "=f"(d[28]), "=f"(d[29]), "=f"(d[30]), "=f"(d[31]),
          "=f"(d[32]), "=f"(d[33]), "=f"(d[34]), "=f"(d[35]), "=f"(d[36]), "=f"(d[37]), "=f"(d[38]), "=f"(d[39]),
          "=f"(d[40]), "=f"(d[41]), "=f"(d[42]), "=f"(d[43]), "=f"(d[44]), "=f"(d[45]), "=f"(d[46]), "=f"(d[47]),
          "=f"(d[48]), "=f"(d[49]), "=f"(d[50]), "=f"(d[51]), "=f"(d[52]), "=f"(d[53]), "=f"(d[54]), "=f"(d[55]),
          "=f"(d[56]), "=f"(d[57]), "=f"(d[58]), "=f"(d[59]), "=f"(d[60]), "=f"(d[61]), "=f"(d[62]), "=f"(d[63]),
          "=f"(d[64]), "=f"(d[65]), "=f"(d[66]), "=f"(d[67]), "=f"(d[68]), "=f"(d[69]), "=f"(d[70]), "=f"(d[71]),
          "=f"(d[72]), "=f"(d[73]), "=f"(d[74]), "=f"(d[75]), "=f"(d[76]), "=f"(d[77]), "=f"(d[78]), "=f"(d[79]),
          "=f"(d[80]), "=f"(d[81]), "=f"(d[82]), "=f"(d[83]), "=f"(d[84]), "=f"(d[85]), "=f"(d[86]), "=f"(d[87]),
          "=f"(d[88]), "=f"(d[89]), "=f"(d[90]), "=f"(d[91]), "=f"(d[92]), "=f"(d[93]), "=f"(d[94]), "=f"(d[95]),
          "=f"(d[96]), "=f"(d[97]), "=f"(d[98]), "=f"(d[99]), "=f"(d[100]), "=f"(d[101]), "=f"(d[102]), "=f"(d[103]),
          "=f"(d[104]), "=f"(d[105]), "=f"(d[106]), "=f"(d[107]), "=f"(d[108]), "=f"(d[109]), "=f"(d[110]), "=f"(d[111]),
          "=f"(d[112]), "=f"(d[113]), "=f"(d[114]), "=f"(d[115]), "=f"(d[116]), "=f"(d[117]), "=f"(d[118]), "=f"(d[119]),
          "=f"(d[120]), "=f"(d[121]), "=f"(d[122]), "=f"(d[123]), "=f"(d[124]), "=f"(d[125]), "=f"(d[126]), "=f"(d[127])
        : "l"(da), "l"(db));
}
__device__ __forceinline__ void wgmma_ss_n256_tb_pred(float (&d)[128], uint64_t da, uint64_t db, int acc) {
    asm volatile("{\n.reg .pred p;\nsetp.ne.s32 p, %130, 0;\nwgmma.mma_async.sync.aligned.m64n256k16.f32.bf16.bf16 {"
        "%0, %1, %2, %3, %4, %5, %6, %7, %8, %9, %10, %11, %12, %13, %14, %15, %16, %17, %18, %19, %20, %21, %22, %23, %24, %25, %26, %27, %28, %29, %30, %31, "
        "%32, %33, %34, %35, %36, %37, %38, %39, %40, %41, %42, %43, %44, %45, %46, %47, %48, %49, %50, %51, %52, %53, %54, %55, %56, %57, %58, %59, %60, %61, %62, %63, "
        "%64, %65, %66, %67, %68, %69, %70, %71, %72, %73, %74, %75, %76, %77, %78, %79, %80, %81, %82, %83, %84, %85, %86, %87, %88, %89, %90, %91, %92, %93, %94, %95, "
        "%96, %97, %98, %99, %100, %101, %102, %103, %104, %105, %106, %107, %108, %109, %110, %111, %112, %113, %114, %115, %116, %117, %118, %119, %120, %121, %122, %123, %124, %125, %126, %127}, %128, %129, p, 1, 1, 0, 1;\n}\n"
        : "+f"(d[0]), "+f"(d[1]), "+f"(d[2]), "+f"(d[3]), "+f"(d[4]), "+f"(d[5]), "+f"(d[6]), "+f"(d[7]),
          "+f"(d[8]), "+f"(d[9]), "+f"(d[10]), "+f"(d[11]), "+f"(d[12]), "+f"(d[13]), "+f"(d[14]), "+f"(d[15]),
          "+f"(d[16]), "+f"(d[17]), "+f"(d[18]), "+f"(d[19]), "+f"(d[20]), "+f"(d[21]), "+f"(d[22]), "+f"(d[23]),
          "+f"(d[24]), "+f"(d[25]), "+f"(d[26]), "+f"(d[27]), "+f"(d[28]), "+f"(d[29]), "+f"(d[30]), "+f"(d[31]),
          "+f"(d[32]), "+f"(d[33]), "+f"(d[34]), "+f"(d[35]), "+f"(d[36]), "+f"(d[37]), "+f"(d[38]), "+f"(d[39]),
          "+f"(d[40]), "+f"(d[41]), "+f"(d[42]), "+f"(d[43]), "+f"(d[44]), "+f"(d[45]), "+f"(d[46]), "+f"(d[47]),
          "+f"(d[48]), "+f"(d[49]), "+f"(d[50]), "+f"(d[51]), "+f"(d[52]), "+f"(d[53]), "+f"(d[54]), "+f"(d[55]),
          "+f"(d[56]), "+f"(d[57]), "+f"(d[58]), "+f"(d[59]), "+f"(d[60]), "+f"(d[61]), "+f"(d[62]), "+f"(d[63]),
          "+f"(d[64]), "+f"(d[65]), "+f"(d[66]), "+f"(d[67]), "+f"(d[68]), "+f"(d[69]), "+f"(d[70]), "+f"(d[71]),
          "+f"(d[72]), "+f"(d[73]), "+f"(d[74]), "+f"(d[75]), "+f"(d[76]), "+f"(d[77]), "+f"(d[78]), "+f"(d[79]),
          "+f"(d[80]), "+f"(d[81]), "+f"(d[82]), "+f"(d[83]), "+f"(d[84]), "+f"(d[85]), "+f"(d[86]), "+f"(d[87]),
          "+f"(d[88]), "+f"(d[89]), "+f"(d[90]), "+f"(d[91]), "+f"(d[92]), "+f"(d[93]), "+f"(d[94]), "+f"(d[95]),
          "+f"(d[96]), "+f"(d[97]), "+f"(d[98]), "+f"(d[99]), "+f"(d[100]), "+f"(d[101]), "+f"(d[102]), "+f"(d[103]),
          "+f"(d[104]), "+f"(d[105]), "+f"(d[106]), "+f"(d[107]), "+f"(d[108]), "+f"(d[109]), "+f"(d[110]), "+f"(d[111]),
          "+f"(d[112]), "+f"(d[113]), "+f"(d[114]), "+f"(d[115]), "+f"(d[116]), "+f"(d[117]), "+f"(d[118]), "+f"(d[119]),
          "+f"(d[120]), "+f"(d[121]), "+f"(d[122]), "+f"(d[123]), "+f"(d[124]), "+f"(d[125]), "+f"(d[126]), "+f"(d[127])
        : "l"(da), "l"(db), "r"(acc));
}
__device__ __forceinline__ void wgmma_rs_n64_tb(float (&d)[32], uint32_t a0, uint32_t a1, uint32_t a2, uint32_t a3, uint64_t db) {
    asm volatile("wgmma.mma_async.sync.aligned.m64n64k16.f32.bf16.bf16 {"
        "%0, %1, %2, %3, %4, %5, %6, %7, %8, %9, %10, %11, %12, %13, %14, %15, %16, %17, %18, %19, %20, %21, %22, %23, %24, %25, %26, %27, %28, %29, %30, %31}, {%32, %33, %34, %35}, %36, 1, 1, 1, 1;\n"
        : "+f"(d[0]), "+f"(d[1]), "+f"(d[2]), "+f"(d[3]), "+f"(d[4]), "+f"(d[5]), "+f"(d[6]), "+f"(d[7]),
          "+f"(d[8]), "+f"(d[9]), "+f"(d[10]), "+f"(d[11]), "+f"(d[12]), "+f"(d[13]), "+f"(d[14]), "+f"(d[15]),
          "+f"(d[16]), "+f"(d[17]), "+f"(d[18]), "+f"(d[19]), "+f"(d[20]), "+f"(d[21]), "+f"(d[22]), "+f"(d[23]),
          "+f"(d[24]), "+f"(d[25]), "+f"(d[26]), "+f"(d[27]), "+f"(d[28]), "+f"(d[29]), "+f"(d[30]), "+f"(d[31])
        : "r"(a0), "r"(a1), "r"(a2), "r"(a3), "l"(db));
}
__device__ __forceinline__ void wgmma_rs_n64_tb_init(float (&d)[32], uint32_t a0, uint32_t a1, uint32_t a2, uint32_t a3, uint64_t db) {
    asm volatile("wgmma.mma_async.sync.aligned.m64n64k16.f32.bf16.bf16 {"
        "%0, %1, %2, %3, %4, %5, %6, %7, %8, %9, %10, %11, %12, %13, %14, %15, %16, %17, %18, %19, %20, %21, %22, %23, %24, %25, %26, %27, %28, %29, %30, %31}, {%32, %33, %34, %35}, %36, 0, 1, 1, 1;\n"
        : "=f"(d[0]), "=f"(d[1]), "=f"(d[2]), "=f"(d[3]), "=f"(d[4]), "=f"(d[5]), "=f"(d[6]), "=f"(d[7]),
          "=f"(d[8]), "=f"(d[9]), "=f"(d[10]), "=f"(d[11]), "=f"(d[12]), "=f"(d[13]), "=f"(d[14]), "=f"(d[15]),
          "=f"(d[16]), "=f"(d[17]), "=f"(d[18]), "=f"(d[19]), "=f"(d[20]), "=f"(d[21]), "=f"(d[22]), "=f"(d[23]),
          "=f"(d[24]), "=f"(d[25]), "=f"(d[26]), "=f"(d[27]), "=f"(d[28]), "=f"(d[29]), "=f"(d[30]), "=f"(d[31])
        : "r"(a0), "r"(a1), "r"(a2), "r"(a3), "l"(db));
}

__device__ __forceinline__ void wg_fence() { asm volatile("wgmma.fence.sync.aligned;\n" ::: "memory"); }
__device__ __forceinline__ void wg_commit() { asm volatile("wgmma.commit_group.sync.aligned;\n" ::: "memory"); }
template <int N> __device__ __forceinline__ void wg_wait() { asm volatile("wgmma.wait_group.sync.aligned %0;\n" ::"n"(N) : "memory"); }
template <int N> __device__ __forceinline__ void fence_regs(float (&a)[N]) {
#pragma unroll
    for (int i = 0; i < N; i++) asm volatile("" : "+f"(a[i])::"memory");
}
template <int N> __device__ __forceinline__ void fence_regs(uint32_t (&a)[N]) {
#pragma unroll
    for (int i = 0; i < N; i++) asm volatile("" : "+r"(a[i])::"memory");
}
__device__ __forceinline__ void mbar_init(uint32_t bar, uint32_t cnt) {
    asm volatile("mbarrier.init.shared::cta.b64 [%0], %1;\n" ::"r"(bar), "r"(cnt) : "memory");
}
__device__ __forceinline__ void mbar_expect_tx(uint32_t bar, uint32_t bytes) {
    asm volatile("mbarrier.arrive.expect_tx.shared::cta.b64 _, [%0], %1;\n" ::"r"(bar), "r"(bytes) : "memory");
}
__device__ __forceinline__ void mbar_wait(uint32_t bar, uint32_t parity) {
    asm volatile("{\n.reg .pred p;\nLW:\nmbarrier.try_wait.parity.shared::cta.b64 p, [%0], %1;\n@!p pmevent 0;\n@!p bra LW;\n}\n" ::"r"(bar), "r"(parity) : "memory");
}
__device__ __forceinline__ void mbar_wait_sleep(uint32_t bar, uint32_t parity) {
    asm volatile("{\n.reg .pred p;\nLW:\nmbarrier.try_wait.parity.shared::cta.b64 p, [%0], %1, 20000;\n@!p pmevent 0;\n@!p bra LW;\n}\n" ::"r"(bar), "r"(parity) : "memory");
}
__device__ __forceinline__ void mbar_wait_bounded(uint32_t bar, uint32_t parity) {
    asm volatile("{\n.reg .pred p;\n.reg .u32 c;\nmov.u32 c, 0;\nLW:\nmbarrier.try_wait.parity.shared::cta.b64 p, [%0], %1, 20000;\n@p bra LD;\n"
                 "add.u32 c, c, 1;\nsetp.ge.u32 p, c, 262144;\n@p trap;\nbra LW;\nLD:\n}\n" ::"r"(bar), "r"(parity) : "memory");
}
__device__ __forceinline__ void flag_wait(const int* p, int v) {
    asm volatile("{\n.reg .pred p;\n.reg .s32 f;\nLW:\nld.acquire.gpu.global.s32 f, [%0];\nsub.s32 f, f, %1;\nsetp.lt.s32 p, f, 0;\n@p bra LW;\n}\n" ::"l"(p), "r"(v) : "memory");
}
__device__ __forceinline__ void flag_wait_bounded(const int* p, int v) {
    asm volatile("{\n.reg .pred p;\n.reg .u32 c;\n.reg .s32 f;\nmov.u32 c, 0;\nLW:\nld.acquire.gpu.global.s32 f, [%0];\nsub.s32 f, f, %1;\nsetp.ge.s32 p, f, 0;\n@p bra LD;\n"
                 "nanosleep.u32 500;\nadd.u32 c, c, 1;\nsetp.ge.u32 p, c, 4194304;\n@p trap;\nbra LW;\nLD:\n}\n" ::"l"(p), "r"(v) : "memory");
}
__device__ __forceinline__ bool elect() {
    uint32_t p; asm volatile("{\n.reg .pred p;\nelect.sync _|p, -1;\nselp.u32 %0, 1, 0, p;\n}\n" : "=r"(p)); return p;
}
__device__ __forceinline__ void bulk_g2s(uint32_t dst, const void* src, uint32_t bytes, uint32_t bar) {
    asm volatile("cp.async.bulk.shared::cluster.global.mbarrier::complete_tx::bytes [%0], [%1], %2, [%3];\n"
                 ::"r"(dst), "l"(src), "r"(bytes), "r"(bar) : "memory");
}
__device__ __forceinline__ void bulk_g2s_mc(uint32_t dst, const void* src, uint32_t bytes, uint32_t bar, uint16_t mask) {
    asm volatile("cp.async.bulk.shared::cluster.global.mbarrier::complete_tx::bytes.multicast::cluster [%0], [%1], %2, [%3], %4;\n"
                 ::"r"(dst), "l"(src), "r"(bytes), "r"(bar), "h"(mask) : "memory");
}
__device__ __forceinline__ void tma_g2s(uint32_t dst, const CUtensorMap* tm, int rowgroup, uint32_t bar) {
    asm volatile("cp.async.bulk.tensor.4d.shared::cluster.global.tile.mbarrier::complete_tx::bytes [%0], [%1, {0, 0, 0, %2}], [%3];\n"
                 ::"r"(dst), "l"(tm), "r"(rowgroup), "r"(bar) : "memory");
}
__device__ __forceinline__ void bar_sync(int id, int n) { asm volatile("bar.sync %0, %1;\n" ::"r"(id), "r"(n) : "memory"); }
__device__ __forceinline__ void bar_arrive(int id, int n) { asm volatile("bar.arrive %0, %1;\n" ::"r"(id), "r"(n) : "memory"); }
__device__ __forceinline__ float quad_last(float v) {
    float r; asm volatile("shfl.sync.idx.b32 %0, %1, 3, 0x1c1f, -1;\n" : "=f"(r) : "f"(v)); return r;
}
__device__ __forceinline__ float ex2(float x) { float y; asm("ex2.approx.ftz.f32 %0, %1;\n" : "=f"(y) : "f"(x)); return y; }
__device__ __forceinline__ float rcp(float x) { float y; asm("rcp.approx.ftz.f32 %0, %1;\n" : "=f"(y) : "f"(x)); return y; }
__device__ __forceinline__ uint32_t pack_bf16(float lo, float hi) {
    uint32_t r; asm("cvt.rn.bf16x2.f32 %0, %1, %2;\n" : "=r"(r) : "f"(hi), "f"(lo)); return r;
}
__device__ __forceinline__ uint32_t pack_f16(float lo, float hi) {
    uint32_t r; asm("cvt.rn.f16x2.f32 %0, %1, %2;\n" : "=r"(r) : "f"(hi), "f"(lo)); return r;
}
__device__ __forceinline__ uint32_t pack_f16_sat(float lo, float hi) {
    uint32_t r; asm("cvt.rn.satfinite.f16x2.f32 %0, %1, %2;\n" : "=r"(r) : "f"(hi), "f"(lo)); return r;
}
__device__ __forceinline__ float f16_lo(uint32_t v) { float r; asm("cvt.f32.f16 %0, %1;\n" : "=f"(r) : "h"((unsigned short)v)); return r; }
__device__ __forceinline__ float f16_hi(uint32_t v) { return f16_lo(v >> 16); }
__device__ __forceinline__ float bf_lo(uint32_t v) { return __uint_as_float(v << 16); }
__device__ __forceinline__ float bf_hi(uint32_t v) { return __uint_as_float(v & 0xFFFF0000u); }
__device__ __forceinline__ float bf_round(float x) { return __uint_as_float(pack_bf16(0.f, x)); }
__device__ __forceinline__ void st_release(int* p, int v) {
    asm volatile("st.release.gpu.global.s32 [%0], %1;\n" ::"l"(p), "r"(v) : "memory");
}
__device__ __forceinline__ uint4 ldg_pinned(const uint4* p) {
    uint4 v; asm volatile("ld.global.nc.v4.u32 {%0, %1, %2, %3}, [%4];\n" : "=r"(v.x), "=r"(v.y), "=r"(v.z), "=r"(v.w) : "l"(p) : "memory"); return v;
}
__device__ __forceinline__ void stmatrix_x4(uint32_t addr, uint32_t r0, uint32_t r1, uint32_t r2, uint32_t r3) {
    asm volatile("stmatrix.sync.aligned.m8n8.x4.shared.b16 [%0], {%1, %2, %3, %4};\n" ::"r"(addr), "r"(r0), "r"(r1), "r"(r2), "r"(r3) : "memory");
}

__device__ __forceinline__ uint32_t tile_off(int r, int ch) {
    return (uint32_t)((r >> 3) * 4096 + (ch >> 3) * 1024 + (r & 7) * 128 + (((ch ^ r) & 7) << 4));
}
__device__ __forceinline__ int h_unit(int qt, int u) { return qt < 78 ? u * 78 + qt : 624; }
__device__ __forceinline__ int row_off(int r) { return 4096 + h_unit(r >> 7, (r >> 4) & 7) * 8192 + (r & 8) * 512 + (r & 7) * 144; }

__device__ __forceinline__ float4 lds128f(uint32_t a) {
    float4 v; asm volatile("ld.shared.v4.f32 {%0, %1, %2, %3}, [%4];\n" : "=f"(v.x), "=f"(v.y), "=f"(v.z), "=f"(v.w) : "r"(a) : "memory"); return v;
}
__device__ __forceinline__ uint64_t lds64(uint32_t a) { uint64_t v; asm volatile("ld.shared.u64 %0, [%1];\n" : "=l"(v) : "r"(a) : "memory"); return v; }
__device__ __forceinline__ uint4 lds128(uint32_t a) {
    uint4 v; asm volatile("ld.shared.v4.u32 {%0, %1, %2, %3}, [%4];\n" : "=r"(v.x), "=r"(v.y), "=r"(v.z), "=r"(v.w) : "r"(a) : "memory"); return v;
}
__device__ __forceinline__ void sts128(uint32_t a, uint32_t x, uint32_t y, uint32_t z, uint32_t w) {
    asm volatile("st.shared.v4.u32 [%0], {%1, %2, %3, %4};\n" ::"r"(a), "r"(x), "r"(y), "r"(z), "r"(w) : "memory");
}
__device__ __forceinline__ void mbar_arrive(uint32_t bar) {
    asm volatile("mbarrier.arrive.shared::cta.b64 _, [%0];\n" ::"r"(bar) : "memory");
}
__device__ __forceinline__ uint64_t mkaddr(uint32_t lo, uint32_t hi) { uint64_t a; asm("mov.b64 %0, {%1, %2};\n" : "=l"(a) : "r"(lo), "r"(hi)); return a; }
__device__ __forceinline__ void red_add(int* p) { asm volatile("red.relaxed.gpu.global.add.s32 [%0], 1;\n" ::"l"(p) : "memory"); }
__device__ __forceinline__ void red_release(int* p) {
    asm volatile("fence.proxy.async.global;\nfence.acq_rel.gpu;\nred.relaxed.gpu.global.add.s32 [%0], 1;\n" ::"l"(p) : "memory");
}
__device__ __forceinline__ void fence_async_global() { asm volatile("fence.proxy.async.global;\n" ::: "memory"); }
__device__ __forceinline__ void fence_async_smem() { asm volatile("fence.proxy.async.shared::cta;\n" ::: "memory"); }
__device__ __forceinline__ void bulk_s2g(void* dst, uint32_t src, uint32_t bytes) {
    asm volatile("cp.async.bulk.global.shared::cta.bulk_group [%0], [%1], %2;\ncp.async.bulk.commit_group;\n" ::"l"(dst), "r"(src), "r"(bytes) : "memory");
}
__device__ __forceinline__ void mma16816(float (&c)[4], uint32_t a0, uint32_t a1, uint32_t a2, uint32_t a3, uint32_t b0, uint32_t b1) {
    asm("mma.sync.aligned.m16n8k16.row.col.f32.bf16.bf16.f32 {%0, %1, %2, %3}, {%4, %5, %6, %7}, {%8, %9}, {%0, %1, %2, %3};\n"
        : "+f"(c[0]), "+f"(c[1]), "+f"(c[2]), "+f"(c[3]) : "r"(a0), "r"(a1), "r"(a2), "r"(a3), "r"(b0), "r"(b1));
}
__device__ __forceinline__ void mma1688(float (&c)[4], uint32_t a0, uint32_t a1, uint32_t b0) {
    asm("mma.sync.aligned.m16n8k8.row.col.f32.bf16.bf16.f32 {%0, %1, %2, %3}, {%4, %5}, {%6}, {%0, %1, %2, %3};\n"
        : "+f"(c[0]), "+f"(c[1]), "+f"(c[2]), "+f"(c[3]) : "r"(a0), "r"(a1), "r"(b0));
}
__device__ __forceinline__ uint32_t hadd2_f16(uint32_t a, uint32_t b) { uint32_t r; asm("add.rn.f16x2 %0, %1, %2;\n" : "=r"(r) : "r"(a), "r"(b)); return r; }
__device__ __forceinline__ uint32_t hadd2(uint32_t a, uint32_t b) { uint32_t r; asm("add.rn.bf16x2 %0, %1, %2;\n" : "=r"(r) : "r"(a), "r"(b)); return r; }
__device__ __forceinline__ uint32_t hmul2(uint32_t a, uint32_t b) { uint32_t r; asm("mul.rn.bf16x2 %0, %1, %2;\n" : "=r"(r) : "r"(a), "r"(b)); return r; }
__device__ __forceinline__ uint32_t hfma2(uint32_t a, uint32_t b, uint32_t c) { uint32_t r; asm("fma.rn.bf16x2 %0, %1, %2, %3;\n" : "=r"(r) : "r"(a), "r"(b), "r"(c)); return r; }

constexpr int SM_Q = 0;
constexpr int SM_KV = 65536;
constexpr int SM_ML = SM_KV + STAGES * KV_BYTES;
constexpr int SM_BAR = SM_ML + 1024;
constexpr int SM_TOTAL = SM_BAR + 256;
constexpr float SCALE_LOG2 = 1.4426950408889634f / 16.0f;
constexpr float KV_SCALE = 0.75f;
constexpr float KV_OFF = 6.f;
constexpr uint32_t KV_OFF2 = 0x46004600u;
constexpr uint32_t KV_NEG4 = 0xCE00CE00u;
constexpr uint32_t P_LIMIT = 0x78007800u;
constexpr float REF_UP = REFUP;
__device__ __forceinline__ uint32_t kvf(uint32_t a) {
    uint32_t r; asm("fma.rn.f16x2 %0, %1, %2, %3;\n" : "=r"(r) : "r"(a), "r"(pack_f16(KV_SCALE, KV_SCALE)), "r"(KV_OFF2)); return r;
}
enum { BAR_PP0 = 1, BAR_PP1 = 2, BAR_WG0 = 3, BAR_WG1 = 4, BAR_H0 = 5, BAR_H1 = 6, BAR_AUX = 7, BAR_BF = 8, BAR_H2 = 9, BAR_X = 10, BAR_GO = 11, BAR_WG2 = 12, BAR_ST = 13 };

struct Hot {
    const __nv_bfloat16 *wk, *wq, *x;
    Scratch* s;
};
struct Params {
    const __nv_bfloat16* deg_inv;
    const int *src, *dst;
    __nv_bfloat16* out;
    uint32_t dhi;
    int E;
    CUtensorMap tm_out;
    CUtensorMap tm_outc;
    CUtensorMap tm_w[3];
};
static_assert(offsetof(Params, tm_outc) == offsetof(Params, tm_out) + 128, "layout");
#define SC_PAIR (blockIdx.x < 104)
#define SC_TAIL (blockIdx.x >= NCTA - 2)
#define SC_LAST (blockIdx.x == NCTA - 1)
#define SC_HELP (SC_PAIR && rank)
#define SC_OWNER (!SC_HELP && !SC_LAST)
#define SC_QT1 (26 + (int)(blockIdx.x >> 1))
#define SC_QT0 (SC_PAIR ? (rank ? (int)(blockIdx.x >> 2) : SC_QT1) : SC_TAIL ? 78 : (int)blockIdx.x - 104)
#define SC_NKV (SC_LAST ? 50 : 75)
#define SC_NMC (SC_PAIR ? 25 : SC_TAIL ? 0 : 75)
#define SC_CLS (SC_PAIR ? (rank ? 0x120 ^ (blockIdx.x & 2) * 0x80 : 0x430) | (blockIdx.x & 2) >> 1 : SC_LAST ? 0x10 : 0x432)
#define SC_NW (SC_PAIR ? 8 : SC_LAST ? 0 : 4)
#define SC_ZB (2 * SC_QT1 + 1 - (int)rank)
#define SC_TZB(k) (rank && !(k) ? 156 : 2 * (k) - (int)rank)

__global__ void __cluster_dims__(2, 1, 1) __launch_bounds__(384, 1) k_main(const __grid_constant__ Hot H, const __grid_constant__ Params P) {
    extern __shared__ __align__(1024) uint8_t smem[];
    const uint32_t sb = (uint32_t)__cvta_generic_to_shared(smem);
    const int tid = threadIdx.x, wg = __shfl_sync(~0u, tid >> 7, 0);
    const int lane = tid & 31, g = lane >> 2, q = lane & 3;
    const uint32_t rank = blockIdx.x & 1;
    const uint32_t bar_full = sb + SM_BAR, bar_q = bar_full + 32, bar_go = bar_full + 48;
    const uint32_t bar_pin = bar_full + 56;
    const uint32_t bar_qfree = bar_full + 72, bar_pdone = bar_full + 88, bar_zst = bar_full + 104, bar_rfree = bar_full + 120;
    const uint32_t bar_empty = bar_full + 128, bar_end = bar_full + 160, s_tm = bar_full + 184, bar_x = bar_full + 192;
    const uint32_t bar_a = sb + SM_ML;

    const int t = tid & 127, warp = __shfl_sync(~0u, t >> 5, 0);
    int ep = 0;
    if (wg & 2) {
        unsigned done;
        {
            uint4 ra[2], rb[2], rk[5][2];
            if (blockIdx.x < 128) {
                const int e = (blockIdx.x >> 4) * 32 + (g >> 1) * 8 + (blockIdx.x & 8) / 2 + (g & 1);
                const uint4* pq = (const uint4*)(H.wq + e * 256) + warp * 8 + q;
                const uint4* pk = (const uint4*)(H.wk + ((blockIdx.x & 7) * 32 + g) * 256) + warp * 8 + q;
                const uint4* pz = (const uint4*)(H.wk + 255 * 256) + warp * 8 + q;
#pragma unroll
                for (int s = 0; s < 2; s++) {
                    ra[s] = ldg_pinned(pq + 4 * s);
                    rb[s] = ldg_pinned(pq + 4 * s + 64);
#pragma unroll
                    for (int n = 0; n < 4; n++) rk[n][s] = ldg_pinned(pk + 4 * s + n * 256);
                    rk[4][s] = ldg_pinned(pz + 4 * s);
                }
            }
            asm volatile("{\n.reg .pred p;\nsetp.eq.s32 p, %2, 0;\nmov.u32 %0, 0;\n@p ld.global.cg.u32 %0, [%1];\n}\n" : "=r"(done) : "l"(&g_sync[SY_DONE * 32]), "r"(lane) : "memory");
            bar_arrive(BAR_X, 384);
            if (warp == 0 && elect()) {
#pragma unroll
                for (int i = 0; i < 21; i++) mbar_init(bar_full + 8 * i, i < 9 ? 1 : i < 16 ? 4 : i == 20 ? 11 : SC_TAIL ? 8 : 16);
#pragma unroll
                for (int i = 0; i < 4; i++) mbar_init(bar_a + 8 * i, 1);
                mbar_expect_tx(bar_pin, QB_BYTES / 2 + 512); mbar_expect_tx(bar_pin + 8, QB_BYTES / 2);
                asm volatile("fence.mbarrier_init.release.cluster;\n" ::: "memory");
            }
            __syncwarp();
            asm volatile("barrier.cluster.arrive.relaxed.aligned;\n" ::: "memory");
            if (blockIdx.x < 128) {
                float c[5][4] = {};
#pragma unroll
                for (int s = 0; s < 2; s++) {
#pragma unroll
                    for (int n = 0; n < 5; n++) mma16816(c[n], ra[s].x, rb[s].x, ra[s].y, rb[s].y, rk[n][s].x, rk[n][s].y);
#pragma unroll
                    for (int n = 0; n < 5; n++) mma16816(c[n], ra[s].z, rb[s].z, ra[s].w, rb[s].w, rk[n][s].z, rk[n][s].w);
                }
#pragma unroll
                for (int i = 0; i < 4; i++) {
                    const int r = i & 2, n = (i & 1) * 2;
                    sts128(sb + SM_KV + 3 * KV_BYTES + QB_BYTES + i * 2048 + t * 16, __float_as_uint(c[n][r] - c[4][r]), __float_as_uint(c[n][r + 1] - c[4][r]),
                           __float_as_uint(c[n + 1][r] - c[4][r]), __float_as_uint(c[n + 1][r + 1] - c[4][r]));
                }
            }
        }
        asm volatile("setmaxnreg.dec.sync.aligned.u32 %0;\n" ::"n"(REG_P));
        if (blockIdx.x < 128) {
            bar_sync(BAR_WG2, 128);
            float4 v[4];
#pragma unroll
            for (int i = 0; i < 4; i++) v[i] = lds128f(sb + SM_KV + 3 * KV_BYTES + QB_BYTES + (warp & 2) * 2048 + (lane & 1) * 2048 + i * 512 + ((warp & 1) * 16 + (lane >> 1)) * 16);
            constexpr float SC = SCALE_LOG2 / KV_SCALE;
            const int r = (warp & 1) * 4 + (lane >> 3);
            *(uint2*)(g_w + tile_off((blockIdx.x >> 3) * 16 + (warp & 2) * 4 + r, (blockIdx.x & 7) * 4 + ((lane >> 1) & 3)) + (lane & 1) * 8) =
                make_uint2(pack_f16_sat(((v[0].x + v[1].x) + (v[2].x + v[3].x)) * SC, ((v[0].y + v[1].y) + (v[2].y + v[3].y)) * SC) | 1,
                           pack_f16_sat(((v[0].z + v[1].z) + (v[2].z + v[3].z)) * SC, ((v[0].w + v[1].w) + (v[2].w + v[3].w)) * SC) | 1);
            if (warp != 1) {
                bar_arrive(BAR_AUX, 128);
            } else {
                bar_sync(BAR_AUX, 128);
                if (elect()) { red_add(&g_sync[SY_DONE * 32 + 4 + (blockIdx.x >> 5)]); }
                __syncwarp();
            }
        }
        else bar_sync(BAR_WG2, 128);
        if (warp == 1) bar_arrive(BAR_GO, 160);
        auto load_a = [&](int j) {
            if (elect()) {
                mbar_expect_tx(bar_a + 8 * j, QB_BYTES);
                bulk_g2s(sb + SM_KV + j * KV_BYTES, g_w + j * QB_BYTES, QB_BYTES, bar_a + 8 * j);
            }
            __syncwarp();
        };
        if (warp == 0) {
            auto poll = [&]() { int c; asm volatile("ld.relaxed.gpu.global.s32 %0, [%1];\n" : "=r"(c) : "l"(&g_sync[SY_DONE * 32 + 4 + (lane & 3)]) : "memory"); return c; };
#pragma unroll 1
            for (int j = 0; j < 4;) {
#pragma unroll 1
                for (const uint32_t mk = __ballot_sync(~0u, poll() >= 32) & 15; (mk >> j) & 1; j++) load_a(j);
            }
        } else if (warp & 1) {
#pragma unroll 1
            for (int j = 0, n = 0; j < 4;) {
                mbar_wait_bounded(bar_a + 8 * j, n & 1);
                uint32_t ok = 1;
#pragma unroll
                for (int i = 0; i < 16; i++) {
                    uint32_t v;
                    asm volatile("ld.shared.u32 %0, [%1];\n" : "=r"(v) : "r"(sb + SM_KV + j * KV_BYTES + (warp & 2) * 8192 + i * 1024 + lane * 32 + g * 4) : "memory");
                    ok &= v;
                }
                asm volatile("{\n.reg .pred p;\nsetp.ne.u32 p, %0, 0;\nbar.red.and.pred p, %1, 64, p;\nselp.u32 %0, 1, 0, p;\n}\n" : "+r"(ok) : "n"((int)BAR_WG2) : "memory");
                if (__any_sync(~0u, ok)) {
                    if (warp == 1 && elect()) asm volatile("mbarrier.arrive.shared::cta.b64 _, [%0];\nmbarrier.inval.shared::cta.b64 [%1];\n" ::"r"(bar_full + 8 * j), "r"(bar_a + 8 * j) : "memory");
                    __syncwarp();
                    j++; n = 0;
                } else {
                    asm volatile("{\n.reg .pred p;\nsetp.gt.s32 p, %0, 1000000;\n@p trap;\n}\n" ::"r"(++n) : "memory");
                    fence_async_smem();
                    if (warp == 1) load_a(j);
                }
            }
        }
        done = __shfl_sync(~0u, done, 0);
        ep = (int)(done / NCTA) + 1;
        asm volatile("barrier.cluster.wait.acquire.aligned;\n" ::: "memory");
        if (warp == 0) {
            asm volatile("st.shared.u64 [%0], %1;\n" ::"r"(s_tm), "l"(&P.tm_outc) : "memory");
            __syncwarp();
            if (elect()) {
                const uint8_t* base = (const uint8_t*)H.s;
                uint32_t cls = SC_CLS, bytes = KV_BYTES, moff = SC_NMC ? rank * (KV_BYTES / 2) : 0, step = 5 * KV_BYTES;
                const uint8_t* src = base;
                int next = 0;
                const int nit = SC_NKV + SC_NW;
#pragma unroll 1
                for (int j = 0; j < nit; j++) {
                    const uint32_t slot = sb + SM_KV + (j & 3) * KV_BYTES, fb = bar_full + 8 * (j & 3);
                    if (j == next) {
                        const int k = j - SC_NKV;
                        const int sw = SC_HELP ? j - 25 : -1;
                        next = j + 1;
                        if (j >= 3 && (unsigned)sw >= 5) next = k >= 0 ? next : j < GO0 ? GO0 : j < 25 ? 25 : j < GO1 ? GO1 : j < 49 ? 49 : j < 50 ? 50 : 75;
                        if (j == SC_NMC) moff = 0;
                        if (j == 0 || j == 25 || j == 50) { src = base + (4096 + (cls & 15) * KV_BYTES + moff); cls >>= 4; }
                        if (SC_TAIL ? j == nit - 1 : j == GO0 || j == GO1) mbar_arrive(bar_go);
                        int fo = -1, fv = 1;
                        if (j < 3) { fo = (SY_H0 + 5 * j + (SC_CLS & 15)) * 32; fv = 5; }
                        if (j == 3) { fo = SY_H1 * 32; fv = 79; }
                        if (sw == 1) fo = 25 * 32 + SC_QT1;
                        if (k == 0) fo = SY_B * 32;
                        if (k == 1 && !SC_PAIR) { fo = SY_AUX0 * 32; fv = NAUX; }
                        if (k == 2 && SC_PAIR) { fo = SY_AUX * 32; fv = NAUX / 3; }
                        if (fo >= 0) {
                            flag_wait(g_sync + fo, fv * ep);
                            fence_async_global();
                        }
                        if (sw == 2 || (k == 2 && !SC_TAIL)) {
                            uint32_t qs = sw == 2 ? offsetof(Scratch, q) + (2 * SC_QT1 + 1) * QB_BYTES : SC_PAIR ? offsetof(Scratch, agg) + SC_ZB * QB_BYTES : offsetof(Scratch, part) + SC_QT0 * (4 * PART_BYTES);
#pragma unroll 1
                            for (int w = 0; w < (k == 2 && SC_PAIR ? 1 : 2); w++) {
                                mbar_wait_sleep(bar_qfree + 8 * w, k == 2 && SC_HELP);
                                mbar_expect_tx(bar_q + 8 * w, SC_PAIR ? QB_BYTES : PART_BYTES);
                                if (!SC_PAIR) bulk_g2s(sb + SM_ML + w * 512, base + (qs + (w ? -512 : QB_BYTES)), 512, bar_q + 8 * w);
                                bulk_g2s(sb + SM_Q + w * QB_BYTES, base + qs, QB_BYTES, bar_q + 8 * w);
                                qs += sw == 2 ? -QB_BYTES : PART_BYTES + 512;
                            }
                        }
                        if ((sw | 1) == 3) {
                            mbar_wait_sleep(bar_pdone + 8 * (sw - 2), 0);
                            bulk_s2g(g_part + (blockIdx.x - 3 + sw) * PART_BYTES, slot, PART_BYTES);
                            asm volatile("cp.async.bulk.wait_group.read 0;\n" ::: "memory");
                        }
                        if (sw == 5) {
                            asm volatile("cp.async.bulk.wait_group 0;\n" ::: "memory");
                            red_release(&g_sync[SY_PART * 32]);
                        }
                        if (k == 0) {
                            asm volatile("prefetch.tensormap [%0];\n" ::"l"(&P.tm_outc) : "memory");
                            src = g_w + (12 - SC_NW) * QB_BYTES; bytes = step = QB_BYTES;
                        }
                        if (k == 2) next = SC_TAIL ? nit - 1 : nit;
                    }
                    mbar_wait_sleep(fb + (bar_empty - bar_full), (j >> 2) & 1);
                    mbar_expect_tx(fb, bytes);
                    if (j < SC_NMC) bulk_g2s_mc(slot + moff, src, KV_BYTES / 2, fb, 3);
                    else bulk_g2s(slot, src, bytes, fb);
                    src += step;
                }
            }
        } else {
            if (warp == 2 && SC_OWNER) {
                uint8_t* dst = g_hz + 4096 + h_unit(SC_QT0, 0) * 8192;
                auto send = [&](int u0, int u1) {
#pragma unroll
                    for (int u = u0; u < u1; u++) {
                        bulk_s2g(dst + u * (78 * 8192), sb + SM_Q + u * 8192, 8192);
                        asm volatile("cp.async.bulk.wait_group 0;\n" ::: "memory");
                    }
                };
                int* f0 = &g_sync[(SY_H0 + SC_QT0 / 5) * 32];
                bar_sync(BAR_H0, 64);
                if (elect()) {
                    send(0, 1);
                    if (SC_QT0 < 65) red_release(f0);
                }
                bar_sync(BAR_H1, 160);
                if (elect()) {
                    if (!SC_TAIL) send(1, 4);
                    mbar_arrive(bar_q);
                }
                bar_sync(BAR_H2, 160);
                if (elect()) {
                    if (!SC_TAIL) { send(4, 8); mbar_arrive(bar_q + 8); }
                    red_release(&g_sync[SY_H1 * 32]);
                }
                __syncwarp();
            }
        }
    } else {
        const uint32_t sq = sb + SM_Q + wg * QB_BYTES;
        const uint32_t qbar = bar_q + 8 * wg;
        const uint32_t dq0 = __shfl_sync(~0u, ((sq & 0x3FFFF) >> 4) | (64u << 16), 0);
        const uint32_t dk0 = __shfl_sync(~0u, (((sb + SM_KV) & 0x3FFFF) >> 4) | (64u << 16), 0);
        float o[128];
        int it = 4;
        const uint32_t dhi = P.dhi;
        uint32_t rel_addr;
        auto rel_target = [&](uint32_t r) {
            asm("mapa.shared::cluster.u32 %0, %1, %2;\n" : "=r"(rel_addr) : "r"(bar_empty), "r"(r));
            if (lane >= 2) rel_addr = 0;
            asm volatile("" : "+r"(rel_addr));
        };
        rel_target(SC_NMC ? rank ^ (lane & 1) : rank);
        auto release = [&](int st) {
            asm volatile("{\n.reg .pred p;\nsetp.ne.u32 p, %1, 0;\n@p mbarrier.arrive.shared::cluster.b64 _, [%0];\n}\n"
                         ::"r"(rel_addr + 8 * st), "r"(rel_addr) : "memory");
        };
        const bool active = !(SC_TAIL && wg == 1);
        auto pp_sync = [&]() { if (!SC_TAIL) bar_sync(BAR_PP0 + wg, 256); };
        auto pp_arrive = [&]() { if (!SC_TAIL) bar_arrive(BAR_PP1 - wg, 256); };
        auto warp_arrive = [&](uint32_t bar) {
            __syncwarp();
            asm volatile("{\n.reg .pred p;\nelect.sync _|p, -1;\n@p mbarrier.arrive.shared::cta.b64 _, [%0];\n}\n" ::"r"(bar + 8 * wg) : "memory");
        };
        auto peer_arrive = [&]() {
            asm volatile("{\n.reg .pred p;\n.reg .b32 a;\nelect.sync _|p, -1;\nmapa.shared::cluster.u32 a, %0, %1;\n"
                         "@p mbarrier.arrive.shared::cluster.b64 _, [a];\n}\n" ::"r"(bar_rfree), "r"(rank ^ 1) : "memory");
        };
        auto stage_q = [&]() {
            auto pk = [&](int i) { return QRND(pack_f16_sat(o[i], o[i + 1])); };
#pragma unroll
            for (int i = 0; i < 16; i++)
                stmatrix_x4(sq + warp * 8192 + tile_off(lane & 15, 2 * i + (lane >> 4)), pk(8 * i), pk(8 * i + 2), pk(8 * i + 4), pk(8 * i + 6));
        };
        float s[40];
        auto issue_qk = [&](int st, int sh = 24) {
            const uint64_t kb = mkaddr(dk0 + st * (KV_BYTES >> 4), dhi);
            const uint64_t qd = mkaddr(dq0 + ((uint32_t)it >> sh), dhi);
            wgmma_ss_n80_init(s, qd + 198, kb + 198);
#pragma unroll
            for (int kk = 0; kk < 15; kk++) wgmma_ss_n80(s, qd + ((kk >> 2) * 64 + (kk & 3) * 2), kb + ((kk >> 2) * 64 + (kk & 3) * 2));
            wg_commit();
        };

        {
            const int rb = (2 * SC_QT0 + wg) * 64 + warp * 16;
            const uint32_t xbar = bar_x + 32 * wg + 8 * warp;
            if (elect()) {
                mbar_init(xbar, 1);
                asm volatile("fence.mbarrier_init.release.cluster;\nfence.proxy.async.shared::cta;\n" ::: "memory");
                mbar_expect_tx(xbar, rb < NN ? 8192 : 0);
            }
            asm volatile("barrier.cluster.arrive.relaxed.aligned;\n" ::: "memory");
            if (wg == 1) pp_arrive();
            bar_sync(BAR_X, 384);
            if (wg == 1) bar_sync(BAR_GO, 160);
            if (rb < NN && elect()) bulk_g2s(sq + warp * 8192, H.x + (size_t)rb * 256, 8192, xbar);
            if (rb >= NN) {
#pragma unroll 1
                for (int i = 0; i < 16; i++) sts128(sq + warp * 8192 + i * 512 + lane * 16, 0, 0, 0, 0);
            }
            __syncwarp();
            mbar_wait(xbar, 0);
            uint4 xa[8], xb[8];
#pragma unroll
            for (int s = 0; s < 8; s++) {
                xa[s] = lds128(sq + (warp * 16 + g) * 512 + (4 * s + q) * 16);
                xb[s] = lds128(sq + (warp * 16 + g + 8) * 512 + (4 * s + q) * 16);
            }
            float sm[2][4], sq2[2][4][4];
#pragma unroll
            for (int i = 0; i < 4; i++) {
                sm[0][i] = sm[1][i] = 0.f;
#pragma unroll
                for (int k = 0; k < 4; k++) sq2[0][k][i] = sq2[1][k][i] = 0.f;
            }
#pragma unroll
            for (int s = 0; s < 8; s++) {
#pragma unroll
                for (int hh = 0; hh < 2; hh++) {
                    const uint4 v = hh ? xb[s] : xa[s];
                    mma16816(sm[hh], v.x, v.y, v.z, v.w, 0x3F803F80u, 0x3F803F80u);
                    mma1688(sq2[hh][0], v.x, v.y, v.x); mma1688(sq2[hh][1], v.x, v.y, v.y);
                    mma1688(sq2[hh][2], v.z, v.w, v.z); mma1688(sq2[hh][3], v.z, v.w, v.w);
                }
            }
            float inv[2], off[2];
#pragma unroll
            for (int hh = 0; hh < 2; hh++) {
                const float mean = (sm[hh][0] + sm[hh][2]) * (1.f / 256.f);
                const float d0 = (sq2[hh][0][0] + sq2[hh][2][0]) + (sq2[hh][1][2] + sq2[hh][3][2]);
                const float d1 = (sq2[hh][0][1] + sq2[hh][2][1]) + (sq2[hh][1][3] + sq2[hh][3][3]);
                const float ss = __shfl_sync(~0u, (g & 1) ? d1 : d0, g * 4 + (g >> 1));
                const float var = fmaxf(ss * (1.f / 256.f) - mean * mean, 0.f);
                float sd;
                asm("sqrt.approx.ftz.f32 %0, %1;\n" : "=f"(sd) : "f"(bf_round(bf_round(var) + 1e-5f)));
                asm("rcp.approx.ftz.f32 %0, %1;\n" : "=f"(inv[hh]) : "f"(bf_round(sd)));
                off[hh] = -mean * inv[hh];
            }
            uint32_t a[64];
#pragma unroll
            for (int s = 0; s < 8; s++) {
                a[8 * s] = xa[s].x; a[8 * s + 1] = xb[s].x; a[8 * s + 2] = xa[s].y; a[8 * s + 3] = xb[s].y;
                a[8 * s + 4] = xa[s].z; a[8 * s + 5] = xb[s].z; a[8 * s + 6] = xa[s].w; a[8 * s + 7] = xb[s].w;
            }
            fence_regs(a);
            if (wg == 1 && __any_sync(~0u, inv[0] + inv[1] != -1.f)) bar_arrive(BAR_ST, 256);
            asm volatile("setmaxnreg.inc.sync.aligned.u32 %0;\n" ::"n"(REG_C));
            fence_regs(a);
#pragma unroll
            for (int i = 0; i < 64; i++)
                a[i] = pack_f16(fmaf(bf_lo(a[i]), inv[i & 1], off[i & 1]), fmaf(bf_hi(a[i]), inv[i & 1], off[i & 1]));
            if (SC_OWNER) {
#pragma unroll
                for (int i = 0; i < 16; i++) {
                    const uint32_t mk = (i == 15 && q == 3) ? 0xFFFFu : ~0u;
                    stmatrix_x4(sq + warp * 8192 + tile_off(lane & 15, 2 * i + (lane >> 4)), kvf(a[4 * i]), kvf(a[4 * i + 1]),
                                kvf(a[4 * i + 2] & mk), kvf(a[4 * i + 3] & mk));
                }
                fence_async_smem();
                if (tid < 32) bar_arrive(BAR_H0, 64);
                bar_arrive(wg ? BAR_H2 : BAR_H1, 160);
            }
            asm volatile("barrier.cluster.wait.acquire.aligned;\n" ::: "memory");
            if (wg == 0) bar_sync(BAR_ST, 256);
            if (active) {
                fence_regs(a);
#pragma unroll
                for (int c = 0; c < 4; c++) {
                    if (c == 1) {
                        if (wg == 1) {
                            wg_wait<0>();
                            release(0);
                        }
                        pp_sync();
                    }
                    mbar_wait(bar_full + 8 * c, 0);
                    const uint64_t wb = mkaddr(dk0 + c * (KV_BYTES >> 4), dhi);
                    wg_fence();
#pragma unroll
                    for (int kk = 0; kk < 4; kk++) {
                        if (c | kk) wgmma_rs_n256_tb(o, a[16 * c + 4 * kk], a[16 * c + 4 * kk + 1], a[16 * c + 4 * kk + 2], a[16 * c + 4 * kk + 3], wb + kk * 512);
                        else wgmma_rs_n256_tb_init(o, a[0], a[1], a[2], a[3], wb);
                    }
                    wg_commit();
                    if (c > 0) { wg_wait<1>(); if (c > 1 || wg == 0) release(c - 1); }
                }
                if (wg == 0) pp_arrive();
                wg_wait<0>();
                fence_regs(o);
                release(3);
                if (SC_OWNER) mbar_wait(qbar, 0);
                stage_q();
                fence_async_smem();
                bar_sync(BAR_WG0 + wg, 128);
                mbar_wait(bar_full, 1);
                wg_fence();
                issue_qk(0);
                if (wg == 1) pp_arrive();
            } else {
                peer_arrive();
            }
        }

        uint32_t p[20];
        float m0 = 0.f, m1 = 0.f, e0, e1, l0, l1;
        uint32_t plim;
        uint32_t qphase = (SC_OWNER && active) ? 1 : 0;
        auto issue_pv = [&](int st, int acc) {
            const uint64_t vb = mkaddr(dk0 + st * (KV_BYTES >> 4), dhi);
            wgmma_rs_n256_tb_pred(o, p[0], p[1], p[2], p[3], vb, acc);
#pragma unroll
            for (int kk = 1; kk < 5; kk++)
                wgmma_rs_n256_tb(o, p[4 * kk], p[4 * kk + 1], p[4 * kk + 2], p[4 * kk + 3], vb + kk * 512);
            wg_commit();
        };
        const uint32_t mq_addr = sq + tile_off(warp * 16 + g, 31) + 14;
        auto exceeds = [&](const uint32_t (&p)[20]) {
            uint32_t a = __vimax3_s16x2(P_LIMIT, p[0], p[1]), b = __vimax3_s16x2(p[2], p[3], p[4]);
#pragma unroll
            for (int i = 5; i < 17; i += 4) { a = __vimax3_s16x2(a, p[i], p[i + 1]); b = __vimax3_s16x2(b, p[i + 2], p[i + 3]); }
            a = __vimax3_s16x2(a, p[17], p[18]);
            return __any_sync(~0u, __vimax3_s16x2(a, b, p[19]) != plim);
        };
        auto remax = [&](float& a, float& b, bool store) {
            float a1 = fmaxf(s[0], s[1]), b1 = fmaxf(s[2], s[3]), a2 = fmaxf(s[4], s[5]), b2 = fmaxf(s[6], s[7]);
#pragma unroll
            for (int i = 2; i < 10; i++) {
                a1 = fmaxf(a1, s[4 * i]); a2 = fmaxf(a2, s[4 * i + 1]);
                b1 = fmaxf(b1, s[4 * i + 2]); b2 = fmaxf(b2, s[4 * i + 3]);
            }
            a1 = fmaxf(a1, a2); b1 = fmaxf(b1, b2);
            a1 = fmaxf(a1, __shfl_xor_sync(~0u, a1, 1)); b1 = fmaxf(b1, __shfl_xor_sync(~0u, b1, 1));
            a1 = fmaxf(a1, __shfl_xor_sync(~0u, a1, 2)); b1 = fmaxf(b1, __shfl_xor_sync(~0u, b1, 2));
            a = fmaxf(a, a1 - e0 + REF_UP); b = fmaxf(b, b1 - e1 + REF_UP);
            const uint32_t u = pack_f16_sat((m0 + a) * (-1.f / KV_OFF), (m1 + b) * (-1.f / KV_OFF));
            const float g0 = (m0 + a) + KV_OFF * f16_lo(u), g1 = (m1 + b) + KV_OFF * f16_hi(u);
            const bool x0 = fabsf(g0) <= 1.f, x1 = fabsf(g1) <= 1.f;
            if (x0) a -= g0;
            if (x1) b -= g1;
            const float da = a + e0, db = b + e1;
            m0 += a; m1 += b;
            e0 = x0 ? 0.f : g0; e1 = x1 ? 0.f : g1;
            plim = (x0 && x1) ? P_LIMIT : 0u;
            asm volatile("{\n.reg .pred p;\nsetp.ne.s32 p, %3, 0;\n@p st.shared.u16 [%0], %1;\n@p st.shared.u16 [%0 + 4096], %2;\n}\n"
                         ::"r"(mq_addr), "h"((unsigned short)u), "h"((unsigned short)(u >> 16)), "r"((int)(store && q == 0)) : "memory");
#pragma unroll
            for (int i = 0; i < 10; i++) {
                p[2 * i] = pack_f16(ex2(s[4 * i] - da), ex2(s[4 * i + 1] - da));
                p[2 * i + 1] = pack_f16(ex2(s[4 * i + 2] - db), ex2(s[4 * i + 3] - db));
            }
            fence_regs(p);
            fence_async_smem();
            __syncwarp();
        };

        auto row_sums = [&](float& z0, float& z1) {
            z0 = quad_last(o[125]); z1 = quad_last(o[127]);
            l0 = z0 * (KV_SCALE / KV_OFF); l1 = z1 * (KV_SCALE / KV_OFF);
        };
        auto cut = [&]() { asm volatile("{\n.reg .pred p;\nsetp.lt.s32 p, %0, 0;\nL:\n@p pmevent 0;\n@p bra L;\n}\n" ::"r"(it) : "memory"); };
        auto stats = [&]() { return (q & 2) ? ((q & 1) ? l1 : m1) : ((q & 1) ? l0 : m0); };
        const int nseg = SC_HELP ? 2 : 1;
        if (active) {
#pragma unroll 1
        for (int seg = 0;; seg++) {
            wg_wait<0>();
            fence_regs(s);
            e0 = e1 = 0.f;
            const int it0 = it, itl = __shfl_sync(~0u, seg + 1 < nseg ? 3 + 25 : 3 + SC_NKV, 0);
            const int itx = (wg == 1 && seg + 1 == nseg) ? itl : -1;
            bool redo = true, have = !seg;
#pragma unroll 1
            for (;;) {
                if (!have) {
#pragma unroll
                    for (int i = 0; i < 20; i++) p[i] = pack_f16(ex2(s[2 * i]), ex2(s[2 * i + 1]));
                    redo = exceeds(p);
                }
                if (redo) {
                    float d0 = it != it0 ? 0.f : -INFINITY, d1 = d0;
                    remax(d0, d1, it != itl);
                    if (it != it0) {
                        const float a0 = ex2(-d0), a1 = ex2(-d1);
#pragma unroll
                        for (int i = 0; i < 32; i++) { o[4 * i] *= a0; o[4 * i + 1] *= a0; o[4 * i + 2] *= a1; o[4 * i + 3] *= a1; }
                    } else if (SC_OWNER) {
                        warp_arrive(bar_pdone);
                    }
                }
                if (it == itl) break;
                const int stp = it & 3;
                it++;
                pp_sync();
                fence_regs(o); fence_regs(p);
                have = SC_TAIL || it == itx;
                if (!have) {
                    wg_fence();
                    issue_pv(stp, it - 1 - it0);
                    mbar_wait(bar_full + 8 * (it & 3), (it >> 2) & 1);
                    wg_fence();
                    issue_qk(it & 3);
                    pp_arrive();
                    wg_wait<0>();
                    fence_regs(s); fence_regs(o); fence_regs(p);
                    if (it == itl) warp_arrive(bar_qfree);
                } else {
                    uint32_t p2[20];
                    const int zero = (uint32_t)it >> 23;
                    mbar_wait(bar_full + 8 * (it & 3), (it >> 2) & 1);
                    wg_fence();
                    issue_qk((it & 3) + zero, 25);
                    if (it == itl) {
                        wg_wait<0>();
                        if (SC_PAIR) peer_arrive(); else warp_arrive(bar_qfree);
                        if (wg) bar_sync(BAR_ST, 256);
                    }
                    wg_fence();
                    issue_pv(stp + zero, it - 1 - it0);
                    pp_arrive();
                    wg_wait<1>();
                    fence_regs(s);
#pragma unroll
                    for (int i = 0; i < 20; i++) p2[i] = pack_f16(ex2(s[2 * i]), ex2(s[2 * i + 1]));
                    redo = exceeds(p2);
                    if (redo) asm volatile("wgmma.wait_group.sync.aligned 0;\nnanosleep.u32 0;\n" ::: "memory");
                    else wg_wait<0>();
                    fence_regs(o); fence_regs(p);
#pragma unroll
                    for (int i = 0; i < 20; i++) p[i] = p2[i];
                }
                release(stp);
                if (it == SC_NMC) rel_target(rank);
            }
            if (seg + 1 < nseg) pp_sync();
            fence_regs(o); fence_regs(p);
            wg_fence();
            issue_pv(it & 3, 1);
            asm volatile("{\n.reg .pred p;\nsetp.ne.s32 p, %0, 0;\n@p bar.arrive %1, 256;\n}\n" ::"r"((int)(seg + 1 == nseg && (wg ? SC_PAIR : !SC_TAIL))), "r"(BAR_ST + wg) : "memory");
            it++;
            if (seg + 1 == nseg) break;
            const int is = it - 2 + wg;
            uint32_t dst = sb + SM_KV + (is & 3) * KV_BYTES + wg * 512 + warp * 8192 + lane * 16;
            uint32_t dml = sb + SM_KV + (is & 3) * KV_BYTES + (wg ? 0 : QB_BYTES) + t * 4;
            asm volatile("" : "+r"(dst), "+r"(dml));
            mbar_wait(qbar, qphase); qphase ^= 1;
            unsigned short u0, u1;
            asm volatile("ld.shared.u16 %0, [%2];\nld.shared.u16 %1, [%2 + 4096];\n" : "=h"(u0), "=h"(u1) : "r"(mq_addr) : "memory");
            mbar_wait(bar_full + 8 * (it & 3), (it >> 2) & 1);
            mbar_wait(bar_empty + 8 * ((it - 2) & 3), ((it - 2) >> 2) & 1);
            wg_wait<0>();
            fence_regs(o);
            float z0, z1;
            row_sums(z0, z1);
            release((it - 1) & 3);
            wg_fence();
            issue_qk(it & 3);
            pp_arrive();
            bar_sync(BAR_WG0 + wg, 128);
#pragma unroll
            for (int i = 0; i < 128; i++) o[i] -= (i & 2) ? z1 : z0;
            fence_regs(o);
            cut();
            asm volatile("st.shared.f32 [%0], %1;\n" ::"r"(dml), "f"(stats()) : "memory");
            m0 = -KV_OFF * f16_lo(u0); m1 = -KV_OFF * f16_lo(u1);
            plim = fmaxf(fabsf(m0), fabsf(m1)) <= 3072.f ? P_LIMIT : 0u;
            uint32_t v[2][8] = {};
#pragma unroll
            for (int i = 0; i < 8; i++) {
                uint32_t *w = v[i & 1], *u = v[(i & 1) ^ 1];
#pragma unroll
                for (int j = 0; j < 8; j++) w[j] = pack_bf16(o[16 * i + 2 * j], o[16 * i + 2 * j + 1]);
                sts128(dst + i * 1024, w[0], w[1], w[2], w[3]);
                sts128(dst + i * 1024 + 512, w[4], w[5], w[6], w[7]);
                if (i) asm volatile("{\n.reg .pred p;\nsetp.lt.s32 p, %9, 0;\nL:\n@p st.shared.v4.u32 [%0], {%1, %2, %3, %4};\n@p st.shared.v4.u32 [%0 + 16], {%5, %6, %7, %8};\n@p bra L;\n}\n"
                             ::"r"(dst), "r"(u[0]), "r"(u[1]), "r"(u[2]), "r"(u[3]), "r"(u[4]), "r"(u[5]), "r"(u[6]), "r"(u[7]), "r"(it) : "memory");
            }
            fence_async_smem();
            warp_arrive(bar_pdone);
        }
        constexpr int IW = 4 + 75;
        uint32_t a[64];
        if (wg == 0 && (SC_PAIR || SC_LAST)) {
            uint32_t rq, rml, rbar;
            asm volatile("mapa.shared::cluster.u32 %0, %3, %6;\nmapa.shared::cluster.u32 %1, %4, %6;\nmapa.shared::cluster.u32 %2, %5, %6;\n"
                         : "=r"(rq), "=r"(rml), "=r"(rbar) : "r"(sb + SM_Q + QB_BYTES + warp * 8192 + lane * 16), "r"(sb + SM_ML + 512 + t * 4),
                         "r"(bar_pin), "r"(rank ^ 1));
            auto send = [&](int i) {
                asm volatile("st.async.weak.shared::cluster.mbarrier::complete_tx::bytes.v4.b32 [%0], {%1, %2, %3, %4}, [%5];\n"
                             ::"r"(rq + i * 512), "r"(a[4 * i]), "r"(a[4 * i + 1]), "r"(a[4 * i + 2]), "r"(a[4 * i + 3]), "r"(rbar + (i & 8)) : "memory");
            };
            mbar_wait(bar_rfree, 0);
            wg_wait<0>();
            fence_regs(o);
            release((it - 1) & 3);
            float z0, z1;
            row_sums(z0, z1);
            asm volatile("st.async.weak.shared::cluster.mbarrier::complete_tx::bytes.f32 [%0], %1, [%2];\n" ::"r"(rml), "f"(stats()), "r"(rbar) : "memory");
#pragma unroll
            for (int i = 0; i < 16; i++) {
                a[4 * i] = pack_bf16(o[8 * i] - z0, o[8 * i + 1] - z0); a[4 * i + 1] = pack_bf16(o[8 * i + 2] - z1, o[8 * i + 3] - z1);
                a[4 * i + 2] = pack_bf16(o[8 * i + 4] - z0, o[8 * i + 5] - z0); a[4 * i + 3] = pack_bf16(o[8 * i + 6] - z1, o[8 * i + 7] - z1);
                if (i * SND0 / 16 != (i + 1) * SND0 / 16) send(i * SND0 / 16);
                if (i % CUT2 == CUT2 - 1) cut();
            }
            if (SC_PAIR) {
                float z[128];
                const uint32_t dkz = dk0 + ((uint32_t)it >> 24), dqz = dq0 + ((uint32_t)it >> 24);
                auto gemm = [&](int c) {
                    mbar_wait(bar_full + 8 * ((IW + c) & 3), ((IW + c) >> 2) & 1);
                    const uint64_t wb = mkaddr(dkz + ((IW + c) & 3) * (KV_BYTES >> 4), dhi), ab = mkaddr(dqz + c * 64, dhi);
                    wg_fence();
#pragma unroll
                    for (int kk = 0; kk < 4; kk++) {
                        if (c | kk) wgmma_ss_n256_tb(z, ab + kk * 2, wb + kk * 512);
                        else wgmma_ss_n256_tb_init(z, ab, wb);
                    }
                    wg_commit();
                };
                auto release2 = [&](int c) {
                    asm volatile("{\n.reg .pred p;\nsetp.ne.u32 p, %1, 0;\n@p mbarrier.arrive.shared::cluster.b64 _, [%0], 2;\n}\n"
                                 ::"r"(rel_addr + 8 * ((IW + c) & 3)), "r"(rel_addr) : "memory");
                };
                mbar_wait(qbar, qphase);
                bar_sync(BAR_ST + 1, 256);
                gemm(0);
#pragma unroll
                for (int i = SND0; i < 16; i++) send(i);
#pragma unroll
                for (int c = 1; c < 4; c++) { gemm(c); if (c == 3) pp_arrive(); wg_wait<1>(); release2(c - 1); }
                wg_wait<0>();
                fence_regs(z);
                release2(3);
#pragma unroll
                for (int i = 0; i < 16; i++) {
                    sts128(sq + warp * 8192 + lane * 16 + i * 512, pack_bf16(z[8 * i], z[8 * i + 1]), pack_bf16(z[8 * i + 2], z[8 * i + 3]),
                           pack_bf16(z[8 * i + 4], z[8 * i + 5]), pack_bf16(z[8 * i + 6], z[8 * i + 7]));
                    if (i == 3 || i == 15) bar_arrive(i == 3 ? BAR_BF : BAR_H0, 256);
                    if (i == 3) cut();
                }
            } else {
#pragma unroll
                for (int i = SND0; i < 16; i++) send(i);
            }
        } else {
            const int pair = SC_PAIR;
            const bool glob = !(pair || SC_TAIL);
            const uint32_t ml = sb + SM_ML + (t & ~3) * 4, src = (glob ? sq : sb + SM_Q + QB_BYTES) + warp * 8192 + lane * 16;
            const uint64_t tm = lds64(s_tm);
            wg_wait<0>();
            fence_regs(o);
            release((IW - 1) & 3);
            float c0, c1;
            row_sums(c0, c1);
            mbar_wait(glob ? qbar : bar_pin, glob ? qphase : 0);
            const float4 ps = lds128f(ml + (glob ? wg * 512 : 512));
            auto load = [&](int i) {
                asm volatile("ld.shared.v4.u32 {%0, %1, %2, %3}, [%4];\n" : "=r"(a[4 * i]), "=r"(a[4 * i + 1]), "=r"(a[4 * i + 2]), "=r"(a[4 * i + 3]) : "r"(src + i * 512) : "memory");
            };
#pragma unroll
            for (int i = 0; i < 8; i++) load(i);
            const float n0 = fmaxf(m0, ps.x), n1 = fmaxf(m1, ps.z);
            const float a0 = ex2(m0 - n0), a1 = ex2(m1 - n1), b0 = ex2(ps.x - n0), b1 = ex2(ps.z - n1);
            const float i0 = rcp(l0 * a0 + ps.y * b0), i1 = rcp(l1 * a1 + ps.w * b1);
            const float r0 = a0 * i0, r1 = a1 * i1;
            c0 *= -r0; c1 *= -r1;
            const uint32_t u0 = pack_bf16(b0 * i0, b0 * i0), u1 = pack_bf16(b1 * i1, b1 * i1);
#pragma unroll
            for (int i = 0; i < 32; i++) {
                if (i == 16) {
                    if (!glob) mbar_wait(bar_pin + 8, 0);
#pragma unroll
                    for (int j = 8; j < 16; j++) load(j);
                }
                a[2 * i] = hfma2(a[2 * i], u0, pack_bf16(fmaf(o[4 * i], r0, c0), fmaf(o[4 * i + 1], r0, c0)));
                a[2 * i + 1] = hfma2(a[2 * i + 1], u1, pack_bf16(fmaf(o[4 * i + 2], r1, c1), fmaf(o[4 * i + 3], r1, c1)));
            }
            float y[2][32];
            auto gemm = [&](int c, int kh) {
                if (!kh) mbar_wait(bar_full + 8 * ((IW + c) & 3), (((IW + c) >> 2) & 1) ^ pair);
                const uint64_t wb = mkaddr(dk0 + ((IW + c) & 3) * (KV_BYTES >> 4), dhi - 192);
                wg_fence();
#pragma unroll
                for (int kk = 8 * kh; kk < 8 * kh + 8; kk++) {
                    if (kk) wgmma_rs_n64_tb(y[c & 1], a[4 * kk], a[4 * kk + 1], a[4 * kk + 2], a[4 * kk + 3], wb + kk * 128);
                    else wgmma_rs_n64_tb_init(y[c & 1], a[0], a[1], a[2], a[3], wb);
                }
                wg_commit();
            };
            const uint32_t stg = sq + warp * 8192 + (lane & 15) * 128 + (((lane >> 4) ^ lane) & 7) * 16;
            uint4 z[4] = {};
            auto load_z = [&](int cb) {
                if (cb < 2) asm volatile("{\n.reg .pred p;\nsetp.ne.s32 p, %0, 0;\n@p bar.sync %1, 256;\n}\n" ::"r"(pair), "r"(cb ? BAR_H0 : BAR_BF) : "memory");
#pragma unroll
                for (int i = 0; i < 4; i++)
                    asm volatile("{\n.reg .pred p;\nsetp.ne.u32 p, %4, 0;\n@p ld.shared.v4.u32 {%0, %1, %2, %3}, [%5];\n}\n"
                                 : "+r"(z[i].x), "+r"(z[i].y), "+r"(z[i].z), "+r"(z[i].w) : "r"(pair), "r"(src - QB_BYTES + (4 * cb + i) * 512) : "memory");
            };
            pp_sync();
            gemm(0, 0);
            gemm(0, 1);
#pragma unroll
            for (int c = 0; c < 4; c++) {
                if (c) load_z(c);
                if (c < 3) gemm(c + 1, 0);
                if (!c) load_z(0);
                if (c < 3) wg_wait<1>(); else wg_wait<0>();
                fence_regs(y[c & 1]);
                const float* x = y[c & 1];
#pragma unroll
                for (int i = 0; i < 4; i++)
                    stmatrix_x4((stg ^ (32 * i)) + c * 2048, hadd2(pack_bf16(x[8 * i], x[8 * i + 1]), z[i].x), hadd2(pack_bf16(x[8 * i + 2], x[8 * i + 3]), z[i].y),
                                hadd2(pack_bf16(x[8 * i + 4], x[8 * i + 5]), z[i].z), hadd2(pack_bf16(x[8 * i + 6], x[8 * i + 7]), z[i].w));
                if (c < 3) gemm(c + 1, 1);
                fence_async_smem();
                __syncwarp();
                asm volatile("{\n.reg .pred p;\nelect.sync _|p, -1;\n"
                             "@p cp.reduce.async.bulk.tensor.4d.global.shared::cta.add.tile.bulk_group [%0, {0, 0, %1, %2}], [%3];\n}\n"
                             ::"l"(tm), "r"(c), "r"((pair ? SC_ZB : 2 * SC_QT0 + wg) * 8 + warp * 2), "r"(sq + warp * 8192 + c * 2048) : "memory");
                if (c == 2 && glob) pp_arrive();
            }
            asm volatile("cp.async.bulk.commit_group;\ncp.async.bulk.wait_group.read 0;\n" ::: "memory");
        }
        } else {
            wg_wait<0>();
        }
        if (SC_TAIL) {
        float o[128];
        auto emit = [&](uint32_t base, int lane, int row0, uint8_t* wdst, int turn) {
#pragma unroll
            for (int hh = 0; hh < 2; hh++) {
                if (turn > 0) mbar_wait(bar_zst + 8 * hh, (turn - 1) & 1);
#pragma unroll
                for (int i = 0; i < 8; i++)
                    stmatrix_x4(base + tile_off(8 * hh + (lane & 7), 4 * i + (lane >> 3)),
                                pack_bf16(o[16 * i + 2 * hh], o[16 * i + 2 * hh + 1]), pack_bf16(o[16 * i + 4 + 2 * hh], o[16 * i + 5 + 2 * hh]),
                                pack_bf16(o[16 * i + 8 + 2 * hh], o[16 * i + 9 + 2 * hh]), pack_bf16(o[16 * i + 12 + 2 * hh], o[16 * i + 13 + 2 * hh]));
                fence_async_smem();
                __syncwarp();
                if (wdst) {
                    if (lane < 4)
                        asm volatile("cp.async.bulk.global.shared::cta.bulk_group [%0], [%1], 1024;\n"
                                     ::"l"(wdst + ((turn & 1) ? hh * 4096 + lane * 1024 : hh * 1024 + lane * QB_BYTES)), "r"(base + hh * 4096 + lane * 1024) : "memory");
                    asm volatile("cp.async.bulk.commit_group;\n" ::: "memory");
                } else {
                    asm volatile("{\n.reg .pred p;\nsetp.eq.s32 p, %3, 0;\n"
                                 "@p cp.reduce.async.bulk.tensor.4d.global.shared::cta.add.tile.bulk_group [%0, {0, 0, 0, %1}], [%2];\n"
                                 "cp.async.bulk.commit_group;\n}\n"
                                 ::"l"(&P.tm_out), "r"((row0 >> 3) + hh), "r"(base + hh * 4096), "r"(lane) : "memory");
                }
            }
            asm volatile("cp.async.bulk.wait_group.read 1;\n" ::: "memory");
            warp_arrive(bar_zst - 8 * wg);
        };
        auto emit_done = [&](bool pending) {
            asm volatile("cp.async.bulk.wait_group.read 0;\n" ::: "memory");
            __syncwarp();
            asm volatile("{\n.reg .pred p;\nsetp.eq.s32 p, %1, 0;\n@p mbarrier.arrive.shared::cta.b64 _, [%0];\n}\n"
                         ::"r"(bar_zst + 8), "r"(pending ? lane : 1) : "memory");
        };
        if (!(rank | wg)) { release(0); release(1); release(2); release(3); }
        bar_sync(BAR_BF, 256);
        warp_arrive(bar_qfree);
        const int nf = rank ? 8 : 0;
        const int nz = nf + 26 + rank;
        const int itz = 4 + SC_NKV + SC_NW;
        bool pend = false;
#pragma unroll 1
        for (int k = wg; k < nz; k += 2) {
            const int iz = itz + (k < nf ? 0 : nf >> 1);
            mbar_wait(qbar, qphase); qphase ^= 1;
#pragma unroll 1
            for (int c = 0; c < 4; c++) {
                mbar_wait(bar_full + 8 * ((iz + c) & 3), ((iz + c) >> 2) & 1);
                const uint64_t wb = mkaddr(dk0 + ((iz + c) & 3) * (KV_BYTES >> 4), dhi), ab = mkaddr(dq0 + c * 64, dhi);
                wg_fence();
                wgmma_ss_n256_tb_pred(o, ab, wb, c);
#pragma unroll
                for (int kk = 1; kk < 4; kk++) wgmma_ss_n256_tb(o, ab + kk * 2, wb + kk * 512);
                wg_commit();
                emit_done(pend);
                pend = false;
            }
            wg_wait<0>();
            fence_regs(o);
            warp_arrive(bar_qfree);
            const int fb = ((k >> 1) + 3) & 3;
            if (k < nf) {
                float2* r255 = (float2*)H.s->r255 + wg * 128 + q;
                if (k < 2) {
                    if (t >= 124) {
#pragma unroll
                        for (int i = 0; i < 32; i++) r255[4 * i] = make_float2(o[4 * i + 2], o[4 * i + 3]);
                    }
                    bar_sync(BAR_WG0 + wg, 128);
                }
#pragma unroll
                for (int i = 0; i < 32; i++) {
                    const float2 v = __ldcg(r255 + 4 * i);
                    o[4 * i] -= v.x; o[4 * i + 1] -= v.y; o[4 * i + 2] -= v.x; o[4 * i + 3] -= v.y;
                }
            }
            int ln = lane;
            asm volatile("" : "+r"(ln));
            emit(sb + SM_KV + QB_BYTES + warp * KV_BYTES, ln, SC_TZB(k - nf) * 64 + warp * 16,
                 k >= nf ? nullptr : (k & 1) ? g_w + (4 + fb) * QB_BYTES + warp * 8192 : g_w + 8 * QB_BYTES + fb * 8192 + warp * 2048, k);
            pend = k + 2 < nz && (k | 1) != nf - 1;
            if (!pend) emit_done(true);
            if ((k | 1) == nf - 1) {
                asm volatile("cp.async.bulk.wait_group 0;\nfence.proxy.async.global;\nfence.acq_rel.gpu;\n" ::: "memory");
                bar_sync(BAR_BF, 256);
                if (tid == 0) red_release(&g_sync[SY_B * 32]);
                if (wg == 0) { release(0); release(1); release(2); release(3); }
            }
        }
        }
        if (wg == 0) pp_sync();
        warp_arrive(bar_end - 8 * wg);
        asm volatile("barrier.cluster.arrive.relaxed.aligned;\n" ::: "memory");
        if (P.E >= 0) return;
        asm volatile("setmaxnreg.dec.sync.aligned.u32 %0;\n" ::"n"(REG_P));
    }
    {
        if (warp != 0) {
            if (warp == 3 && SC_OWNER && SC_PAIR && elect()) {
                flag_wait_bounded(&g_sync[SY_H1 * 32], 79 * ep);
                mbar_wait_sleep(bar_pdone, 0);
                mbar_wait_sleep(bar_pdone + 8, 0);
#pragma unroll 1
                for (int u = 0; u < 16; u++) {
                    bulk_s2g(g_q + SC_QT0 * (2 * QB_BYTES) + u * 4096, sb + SM_Q + u * 4096, 4096);
                    asm volatile("cp.async.bulk.wait_group 0;\n" ::: "memory");
                }
                fence_async_global();
                st_release(&g_qflag[SC_QT0], ep);
            }
            __syncwarp();
            if (SC_TAIL) {
                bar_sync(BAR_AUX, 96);
                if (warp == 1 && elect()) red_release(&g_sync[SY_CSR * 32]);
                __syncwarp();
            }
            mbar_wait_bounded(bar_go, 0);
            if (SC_TAIL) {
                if (warp == 1 && elect()) red_add(&g_sync[SY_DONE * 32]);
                if (warp == 3 && elect()) {
                    int it = 4 + SC_NKV + SC_NW;
                    asm volatile("prefetch.tensormap [%0];\n" ::"l"(&P.tm_out) : "memory");
                    if (rank) {
#pragma unroll 1
                        for (int j = 0; j < 4; j++, it++) {
                            mbar_wait_sleep(bar_empty + 8 * (it & 3), ((it >> 2) & 1) ^ 1);
                            mbar_expect_tx(bar_full + 8 * (it & 3), QB_BYTES);
                            tma_g2s(sb + SM_KV + (it & 3) * KV_BYTES, &P.tm_w[2], 8 * j, bar_full + 8 * (it & 3));
                        }
#pragma unroll 1
                        for (int k = 0; k < 8; k++) {
                            mbar_wait_sleep(bar_qfree + 8 * (k & 1), ((k >> 1) ^ (k & 1) ^ 1) & 1);
                            mbar_expect_tx(bar_q + 8 * (k & 1), QB_BYTES);
#pragma unroll 1
                            for (int hf = 0; hf < 2; hf++)
                                asm volatile("cp.async.bulk.tensor.5d.shared::cluster.global.tile.mbarrier::complete_tx::bytes [%0], [%1, {0, 0, %2, 0, 0}], [%3];\n"
                                             ::"r"(sb + SM_Q + (k & 1) * QB_BYTES + hf * 16384), "l"(&P.tm_w[k & 1]),
                                             "r"(8 * (((k >> 1) + 3) & 3) + 4 * hf), "r"(bar_q + 8 * (k & 1)) : "memory");
                        }
                        flag_wait_bounded(&g_sync[SY_B * 32], ep);
                        fence_async_global();
                    }
#pragma unroll 1
                    for (int j = 0; j < 4; j++, it++) {
                        mbar_wait_sleep(bar_empty + 8 * (it & 3), ((it >> 2) & 1) ^ 1);
                        mbar_expect_tx(bar_full + 8 * (it & 3), QB_BYTES);
                        bulk_g2s(sb + SM_KV + (it & 3) * KV_BYTES, g_w + (4 + j) * QB_BYTES, QB_BYTES, bar_full + 8 * (it & 3));
                    }
#pragma unroll 1
                    for (int k = 0; k < 26 + rank; k++) {
                        if (k == 0 || k == ((GF0 + 1) * NAUX - 16) / 128) { flag_wait_bounded(&g_sync[(k ? SY_AUX1 : SY_AUX0) * 32], NAUX * ep); fence_async_global(); }
                        mbar_wait_sleep(bar_qfree + 8 * (k & 1), ((k >> 1) ^ (k & 1) ^ 1) & 1);
                        mbar_expect_tx(bar_q + 8 * (k & 1), QB_BYTES);
                        bulk_g2s(sb + SM_Q + (k & 1) * QB_BYTES, g_agg + SC_TZB(k) * QB_BYTES, QB_BYTES, bar_q + 8 * (k & 1));
                    }
                }
            } else {
            const int par = ep & 1;
            if (blockIdx.x == 0 && t == 32) g_ovf_n[par ^ 1] = 0;
            if (blockIdx.x == 0 && warp == 1) *(uint4*)(g_hz + (lane >> 3) * 1024 + (lane & 7) * 16) = make_uint4(KV_OFF2, KV_OFF2, KV_OFF2, KV_OFF2);
            const uint32_t wlo = (uint32_t)(uintptr_t)H.s, whi = (uint32_t)((uintptr_t)H.s >> 32);
            const uint32_t blo = wlo + (uint32_t)offsetof(Scratch, bucket);
            {
                const int* pd = P.dst + blockIdx.x * 96 + (t - 32);
                const int* ps = P.src + blockIdx.x * 96 + (t - 32);
#pragma unroll 1
                for (int e = P.E - (blockIdx.x * 96 + (t - 32)); e > 0; e -= CSRU * NAUX * 32, pd += CSRU * NAUX * 32, ps += CSRU * NAUX * 32) {
                    int d[CSRU], sr[CSRU], sl[CSRU];
#pragma unroll
                    for (int i = 0; i < CSRU; i++) {
                        d[i] = e > i * NAUX * 32 ? __ldg(pd + i * NAUX * 32) : NN;
                        sr[i] = e > i * NAUX * 32 ? __ldg(ps + i * NAUX * 32) : 0;
                    }
#pragma unroll
                    for (int i = 0; i < CSRU; i++) {
                        sl[i] = 0;
                        asm volatile("{\n.reg .pred p;\nsetp.lt.s32 p, %2, %3;\n@p atom.relaxed.gpu.global.add.s32 %0, [%1], 1;\n}\n"
                                     : "+r"(sl[i]) : "l"(mkaddr(wlo + (uint32_t)offsetof(Scratch, cnt) + d[i] * 4, whi)), "r"(d[i]), "n"(NN) : "memory");
                    }
                    uint32_t ov = 0;
#pragma unroll
                    for (int i = 0; i < CSRU; i++) {
                        asm volatile("{\n.reg .pred p;\nsetp.lt.s32 p, %3, %4;\n@p st.global.u16 [%1], %2;\n@!p or.b32 %0, %0, %5;\n}\n"
                                     : "+r"(ov) : "l"(mkaddr(blo + d[i] * 128 + (sl[i] & 31) * 4 + (sl[i] >> 5) * 2, whi)), "h"((unsigned short)sr[i]), "r"(sl[i]), "n"(CAP), "r"(1 << i) : "memory");
                    }
#pragma unroll 1
                    for (; ov; ov &= ov - 1) {
                        const int i = (__ffs(ov) - 1) * (NAUX * 32);
                        int at;
                        asm volatile("atom.relaxed.gpu.global.add.s32 %0, [%1], 1;\n" : "=r"(at) : "l"(&g_ovf_n[par]) : "memory");
                        g_ovf[at] = make_int2(__ldg(pd + i), __ldg(ps + i));
                    }
                }
            }
            bar_sync(BAR_AUX, 96);
            if (warp == 1 && elect()) { red_release(&g_sync[SY_CSR * 32]); }
            __syncwarp();
            {
                const int r0 = blockIdx.x * 3 + warp - 1;
                const uint4* xp = (const uint4*)(H.x + r0 * 256) + lane;
                uint4* op = (uint4*)(P.out + r0 * 256) + lane;
#pragma unroll 1
                for (int r = r0; r < NN; r += CPYU * NAUX, xp += CPYU * NAUX * 32, op += CPYU * NAUX * 32) {
                    uint4 v[CPYU];
#pragma unroll
                    for (int i = 0; i < CPYU; i++) if (r + i * NAUX < NN) v[i] = ldg_pinned(xp + i * NAUX * 32);
#pragma unroll
                    for (int i = 0; i < CPYU; i++) if (r + i * NAUX < NN) op[i * NAUX * 32] = v[i];
                }
            }
            mbar_wait_bounded(bar_go, 1);
            if (const int un = (3 - warp) * (NAUX / 3) + (NAUX / 3 - 1) - blockIdx.x; un < 208) {
                flag_wait_bounded(&g_sync[SY_PART * 32], 52 * ep);
                uint8_t* pp = g_part + (un >> 3) * (4 * PART_BYTES);
                float* ml = (float*)(pp + QB_BYTES) + (un & 7) * 32;
                const float4 sa = __ldcg((const float4*)ml + g), sc = __ldcg((const float4*)ml + g + 2 * PART_BYTES / 16);
                const float n0 = fmaxf(sa.x, sc.x), n1 = fmaxf(sa.z, sc.z);
                const uint32_t a0 = pack_bf16(ex2(sa.x - n0), ex2(sa.x - n0)), a1 = pack_bf16(ex2(sa.z - n1), ex2(sa.z - n1));
                const uint32_t b0 = pack_bf16(ex2(sc.x - n0), ex2(sc.x - n0)), b1 = pack_bf16(ex2(sc.z - n1), ex2(sc.z - n1));
                __syncwarp();
                if (q == 0) ((float4*)ml)[g] = make_float4(n0, sa.y * bf_hi(a0) + sc.y * bf_hi(b0), n1, sa.w * bf_hi(a1) + sc.w * bf_hi(b1));
                uint4* d = (uint4*)(pp + (un & 4) * 256 + (un & 7) * 8192) + lane;
#pragma unroll 1
                for (int i = 0; i < 4; i++, d += 128) {
                    uint4 u[4], v[4];
#pragma unroll
                    for (int j = 0; j < 4; j++) { u[j] = __ldcg(d + j * 32); v[j] = __ldcg(d + j * 32 + 2 * PART_BYTES / 16); }
#pragma unroll
                    for (int j = 0; j < 4; j++)
                        d[j * 32] = make_uint4(hfma2(v[j].x, b0, hmul2(u[j].x, a0)), hfma2(v[j].y, b1, hmul2(u[j].y, a1)),
                                               hfma2(v[j].z, b0, hmul2(u[j].z, a0)), hfma2(v[j].w, b1, hmul2(u[j].w, a1)));
                }
            }
            flag_wait_bounded(&g_sync[SY_CSR * 32], NCTA * ep);
            if (warp == 2 && blockIdx.x < 129) {
                uint4* z = blockIdx.x < 128 ? (uint4*)(g_w + blockIdx.x * 1024) + lane : (uint4*)&g_sync[SY_DONE * 32 + 4];
                z[0] = make_uint4(0, 0, 0, 0);
                if (blockIdx.x < 128) z[32] = make_uint4(0, 0, 0, 0);
            }
            {
                const uint32_t lc = (lane >> 3) * 1024 + (lane & 7) * 16;
                const uint32_t alo = wlo ^ lc;
                const int node0 = blockIdx.x * 3 + warp - 17;
                auto node = [&](int i) { const int nd = node0 + i * NAUX; return (int)min((unsigned)nd, (unsigned)(nd + NN)); };
                const int num = (NN - 17 - node0) / NAUX + 1;
                uint32_t mine = 0;
                if (lane < num) {
                    mine = min(__ldcg(&g_cnt[node(lane)]), CAP + 1) | (uint32_t)__ldg((const unsigned short*)P.deg_inv + node(lane)) << 16;
                    g_cnt[node(lane)] = 0;
                }
                auto row = [&](int off) {
                    uint4 v;
                    asm volatile("ld.global.v4.u32 {%0, %1, %2, %3}, [%4];\n"
                                 : "=r"(v.x), "=r"(v.y), "=r"(v.z), "=r"(v.w) : "l"(mkaddr(alo ^ off, whi)));
                    return v;
                };
                auto ents = [&](int i) {
                    uint32_t e;
                    asm volatile("ld.global.cg.u32 %0, [%1];\n" : "=r"(e) : "l"(mkaddr(blo + (min(node(i), NN - 1) * 32 + lane) * 4, whi)));
                    return e;
                };
                auto store = [&](int i, const float (&a)[8]) {
                    const float di = bf_hi(__shfl_sync(~0u, mine, i)) * (1.f / KV_SCALE);
                    const int nd = node(i);
                    *(uint4*)(g_agg + (uint32_t)(((nd >> 3) * 4096 + (nd & 7) * 144) ^ lc)) =
                        make_uint4(pack_bf16(a[0] * di, a[1] * di), pack_bf16(a[2] * di, a[3] * di), pack_bf16(a[4] * di, a[5] * di), pack_bf16(a[6] * di, a[7] * di));
                };
#pragma unroll 1
                for (uint32_t big = __ballot_sync(~0u, (mine & 0xFFFF) > CAP); big; big &= big - 1) {
                    const int i = __ffs(big) - 1, no = __ldcg(&g_ovf_n[par]);
                    float a[8] = {};
#pragma unroll 1
                    for (int k = -64; k < no; k += 32) {
                        const int2 pr = k < 0 ? make_int2(node(i), (ents(i) >> (k & 32) / 2) & 0xFFFF) : k + lane < no ? __ldcg(&g_ovf[k + lane]) : make_int2(-1, 0);
#pragma unroll 1
                        for (uint32_t mk = __ballot_sync(~0u, pr.x == node(i)); mk; mk &= mk - 1) {
                            const uint4 v = row(row_off(__shfl_sync(~0u, pr.y, __ffs(mk) - 1)));
                            a[0] += f16_lo(v.x) - KV_OFF; a[1] += f16_hi(v.x) - KV_OFF; a[2] += f16_lo(v.y) - KV_OFF; a[3] += f16_hi(v.y) - KV_OFF;
                            a[4] += f16_lo(v.z) - KV_OFF; a[5] += f16_hi(v.z) - KV_OFF; a[6] += f16_lo(v.w) - KV_OFF; a[7] += f16_hi(v.w) - KV_OFF;
                        }
                    }
                    store(i, a);
                }
                auto add4 = [&](const uint4& a, const uint4& b) { return make_uint4(hadd2_f16(a.x, b.x), hadd2_f16(a.y, b.y), hadd2_f16(a.z, b.z), hadd2_f16(a.w, b.w)); };
                int ni = -1, left = 0, pos = 0, ec = 0;
                uint32_t en = ents(0);
                uint4 acc = make_uint4(0, 0, 0, 0);
                auto step = [&](uint4 (&v)[4], int& tag) {
                    if (left <= 0 || pos == 32) {
                        if (left > 0) {
                            en = ents(ni) >> 16;
                        } else {
                            ni++;
                            left = __shfl_sync(~0u, mine, ni) & 0xFFFF;
                            if (left > CAP) left = 0;
                        }
                        ec = lane < left ? row_off(en & 0xFFFF) : 0;
                        en = ents(ni + 1);
                        pos = 0;
                    }
                    int of[4];
#pragma unroll
                    for (int j = 0; j < 4; j++) asm volatile("shfl.sync.idx.b32 %0, %1, %2, 31, -1;\n" : "=r"(of[j]) : "r"(ec), "r"(pos + j));
                    acc = add4(acc, add4(add4(add4(v[0], v[1]), make_uint4(KV_NEG4, KV_NEG4, KV_NEG4, KV_NEG4)), add4(v[2], v[3])));
                    asm volatile("" : "+r"(acc.x), "+r"(acc.y), "+r"(acc.z), "+r"(acc.w));
                    asm volatile("{\n.reg .pred p;\nsetp.lt.s32 p, %0, 0;\nL:\n@p pmevent 0;\n@p bra L;\n}\n" ::"r"(ni) : "memory");
#pragma unroll
                    for (int j = 0; j < 4; j++) v[j] = row(of[j]);
                    pos += 4; left -= 4;
                    const int i = tag;
                    tag = left <= 0 ? ni : -1;
                    if (i >= 0) {
                        const float a[8] = {f16_lo(acc.x), f16_hi(acc.x), f16_lo(acc.y), f16_hi(acc.y), f16_lo(acc.z), f16_hi(acc.z), f16_lo(acc.w), f16_hi(acc.w)};
                        if ((__shfl_sync(~0u, mine, i) & 0xFFFF) <= CAP) store(i, a);
                        acc = make_uint4(0, 0, 0, 0);
                        if (i == GF0 || i == 8) {
                            __syncwarp();
                            if (elect()) red_release(&g_sync[(i == 8 ? SY_AUX1 : SY_AUX0) * 32]);
                            __syncwarp();
                        }
                    }
                    return i == num - 1;
                };
                uint4 va[4], vb[4];
#pragma unroll
                for (int j = 0; j < 4; j++) va[j] = vb[j] = make_uint4(KV_OFF2, KV_OFF2, KV_OFF2, KV_OFF2);
                int ta = -1, tb = -1;
#pragma unroll 1
                while (!step(va, ta) && !step(vb, tb)) {}
            }
            bar_sync(BAR_AUX, 96);
            if (warp == 1 && elect()) {
                red_release(&g_sync[SY_AUX * 32]);
                red_add(&g_sync[SY_DONE * 32]);
            }
            }
        }
        __syncwarp();
        asm volatile("barrier.cluster.arrive.relaxed.aligned;\n" ::: "memory");
        if (warp == 1) mbar_wait_bounded(bar_end, 0);
        else if (elect()) mbar_arrive(bar_end);
        __syncwarp();
        asm volatile("barrier.cluster.wait.acquire.aligned;\n" ::: "memory");
    }
}

}

extern "C" void kernel_launch(void* const* d_in, const int* in_sizes, int n_in, void* d_out, int out_size) {
    Hot H;
    Params P;
    H.x = (const __nv_bfloat16*)d_in[0];
    P.src = (const int*)d_in[1];
    P.dst = (const int*)d_in[2];
    P.deg_inv = (const __nv_bfloat16*)d_in[3];
    H.wq = (const __nv_bfloat16*)d_in[5];
    H.wk = (const __nv_bfloat16*)d_in[6];
    P.out = (__nv_bfloat16*)d_out;
    typedef CUresult (*EncodeFn)(CUtensorMap*, CUtensorMapDataType, cuuint32_t, void*, const cuuint64_t*, const cuuint64_t*, const cuuint32_t*,
                                 const cuuint32_t*, CUtensorMapInterleave, CUtensorMapSwizzle, CUtensorMapL2promotion, CUtensorMapFloatOOBfill);
    void* fn = nullptr;
    cudaDriverEntryPointQueryResult qr;
    cudaGetDriverEntryPoint("cuTensorMapEncodeTiled", &fn, cudaEnableDefault, &qr);
    auto encode = [&](CUtensorMap* tm, const void* ptr, int rows, int box_rows, int box_cb = 4) {
        const cuuint64_t dims[4] = {64, 8, 4, (cuuint64_t)rows / 8};
        const cuuint64_t strides[3] = {512, 128, 4096};
        const cuuint32_t box[4] = {64, 8, (cuuint32_t)box_cb, (cuuint32_t)box_rows / 8}, es[4] = {1, 1, 1, 1};
        ((EncodeFn)fn)(tm, CU_TENSOR_MAP_DATA_TYPE_BFLOAT16, 4, (void*)ptr, dims, strides, box, es, CU_TENSOR_MAP_INTERLEAVE_NONE,
                       CU_TENSOR_MAP_SWIZZLE_128B, CU_TENSOR_MAP_L2_PROMOTION_NONE, CU_TENSOR_MAP_FLOAT_OOB_FILL_NONE);
    };
    encode(&P.tm_out, d_out, NN, 8);
    encode(&P.tm_outc, d_out, NN, 16, 1);
    for (int i = 0; i < 2; i++) {
        const cuuint64_t dims[5] = {64, 2, 32, 4, 4};
        const cuuint64_t strides[4] = {512, 4096, 128, 1024};
        const cuuint32_t box[5] = {64, 2, 4, 4, 4}, es[5] = {1, 1, 1, 1, 1};
        ((EncodeFn)fn)(&P.tm_w[i], CU_TENSOR_MAP_DATA_TYPE_BFLOAT16, 5, d_in[i ? 4 : 7], dims, strides, box, es, CU_TENSOR_MAP_INTERLEAVE_NONE,
                       CU_TENSOR_MAP_SWIZZLE_128B, CU_TENSOR_MAP_L2_PROMOTION_NONE, CU_TENSOR_MAP_FLOAT_OOB_FILL_NONE);
    }
    encode(&P.tm_w[2], d_in[8], 256, 64);
    void* raw = nullptr;
    cudaGetSymbolAddress(&raw, g_raw);
    H.s = (Scratch*)(((uintptr_t)raw + ((8 << 20) - 1)) & ~(uintptr_t)((8 << 20) - 1));
    P.dhi = 0x40000100u;
    P.E = in_sizes[1] < MAXE ? in_sizes[1] : MAXE;
    cudaFuncSetAttribute(k_main, cudaFuncAttributeMaxDynamicSharedMemorySize, SM_TOTAL);
    k_main<<<NCTA, 384, SM_TOTAL>>>(H, P);
}
```

```cpp
#include <cuda_runtime.h>
#include <cuda.h>
#include <cuda_bf16.h>
#include <stdint.h>
#include <stddef.h>

namespace {

constexpr int NN = 10000;
constexpr int BN = 80;
constexpr int NKV = NN / BN;
constexpr int NQB = 158;
constexpr int NCTA = 132;
constexpr int NAUX = 3 * (NCTA - 2);
constexpr int STAGES = 4;
constexpr int KV_BYTES = BN * 512;
constexpr int QB_BYTES = 64 * 512;
constexpr int PART_BYTES = QB_BYTES + 512;
constexpr int CAP = 64;
constexpr int MAXE = 160000;

#define QRND(v) (((v) + 0x00040004u) & 0xFFF8FFF8u)
#define GO0 5
#define GO1 35
#define GF0 2
#define CSRU 3
#define CPYU 9
#define REFUP 2.f
#define SND0 10
#define CUT2 2
#define TICK 1024
#define TSL 30
#define REG_C 224
#define REG_P 56

enum { SY_PART = 4, SY_H1 = 5, SY_CSR = 6, SY_AUX = 7, SY_DONE = 8, SY_AUX0 = 9, SY_B = 10, SY_AUX1 = 11, SY_H0 = 12 };
struct Scratch {
    uint8_t hz[4096 + NN * 512];
    uint8_t w[12 * QB_BYTES];
    int sync[25 * 32];
    int qflag[96];
    int ovf_n[32];
    float r255[512];
    int cnt[NN + 16];
    int bucket[(NN + 1) * 32];
    int2 ovf[MAXE];
    uint8_t q[NQB * QB_BYTES];
    uint8_t agg[NQB * QB_BYTES];
    uint8_t part[52 * 2 * PART_BYTES];
};
static_assert(offsetof(Scratch, ovf) <= (8 << 20), "window");
static_assert(offsetof(Scratch, qflag) == offsetof(Scratch, sync) + 25 * 128, "flags");
static_assert(offsetof(Scratch, w) % 1024 == 0 && offsetof(Scratch, sync) % 128 == 0 &&
              offsetof(Scratch, bucket) % 128 == 0 && offsetof(Scratch, q) % 128 == 0, "alignment");
__device__ uint8_t g_raw[(8 << 20) + sizeof(Scratch)];
#define g_hz (H.s->hz)
#define g_w (H.s->w)
#define g_sync (H.s->sync)
#define g_qflag (H.s->qflag)
#define g_ovf_n (H.s->ovf_n)
#define g_cnt (H.s->cnt)
#define g_bucket (H.s->bucket)
#define g_ovf (H.s->ovf)
#define g_q (H.s->q)
#define g_agg (H.s->agg)
#define g_part (H.s->part)

__device__ __forceinline__ void wgmma_ss_n80(float (&d)[40], uint64_t da, uint64_t db) {
    asm volatile("wgmma.mma_async.sync.aligned.m64n80k16.f32.f16.f16 {"
        "%0, %1, %2, %3, %4, %5, %6, %7, %8, %9, %10, %11, %12, %13, %14, %15, %16, %17, %18, %19, %20, %21, %22, %23, %24, %25, %26, %27, %28, %29, %30, %31, "
        "%32, %33, %34, %35, %36, %37, %38, %39}, %40, %41, 1, 1, 1, 0, 0;\n"
        : "+f"(d[0]), "+f"(d[1]), "+f"(d[2]), "+f"(d[3]), "+f"(d[4]), "+f"(d[5]), "+f"(d[6]), "+f"(d[7]),
          "+f"(d[8]), "+f"(d[9]), "+f"(d[10]), "+f"(d[11]), "+f"(d[12]), "+f"(d[13]), "+f"(d[14]), "+f"(d[15]),
          "+f"(d[16]), "+f"(d[17]), "+f"(d[18]), "+f"(d[19]), "+f"(d[20]), "+f"(d[21]), "+f"(d[22]), "+f"(d[23]),
          "+f"(d[24]), "+f"(d[25]), "+f"(d[26]), "+f"(d[27]), "+f"(d[28]), "+f"(d[29]), "+f"(d[30]), "+f"(d[31]),
          "+f"(d[32]), "+f"(d[33]), "+f"(d[34]), "+f"(d[35]), "+f"(d[36]), "+f"(d[37]), "+f"(d[38]), "+f"(d[39])
        : "l"(da), "l"(db));
}
__device__ __forceinline__ void wgmma_ss_n80_init(float (&d)[40], uint64_t da, uint64_t db) {
    asm volatile("wgmma.mma_async.sync.aligned.m64n80k16.f32.f16.f16 {"
        "%0, %1, %2, %3, %4, %5, %6, %7, %8, %9, %10, %11, %12, %13, %14, %15, %16, %17, %18, %19, %20, %21, %22, %23, %24, %25, %26, %27, %28, %29, %30, %31, "
        "%32, %33, %34, %35, %36, %37, %38, %39}, %40, %41, 0, 1, 1, 0, 0;\n"
        : "=f"(d[0]), "=f"(d[1]), "=f"(d[2]), "=f"(d[3]), "=f"(d[4]), "=f"(d[5]), "=f"(d[6]), "=f"(d[7]),
          "=f"(d[8]), "=f"(d[9]), "=f"(d[10]), "=f"(d[11]), "=f"(d[12]), "=f"(d[13]), "=f"(d[14]), "=f"(d[15]),
          "=f"(d[16]), "=f"(d[17]), "=f"(d[18]), "=f"(d[19]), "=f"(d[20]), "=f"(d[21]), "=f"(d[22]), "=f"(d[23]),
          "=f"(d[24]), "=f"(d[25]), "=f"(d[26]), "=f"(d[27]), "=f"(d[28]), "=f"(d[29]), "=f"(d[30]), "=f"(d[31]),
          "=f"(d[32]), "=f"(d[33]), "=f"(d[34]), "=f"(d[35]), "=f"(d[36]), "=f"(d[37]), "=f"(d[38]), "=f"(d[39])
        : "l"(da), "l"(db));
}
__device__ __forceinline__ void wgmma_rs_n256_tb(float (&d)[128], uint32_t a0, uint32_t a1, uint32_t a2, uint32_t a3, uint64_t db) {
    asm volatile("wgmma.mma_async.sync.aligned.m64n256k16.f32.f16.f16 {"
        "%0, %1, %2, %3, %4, %5, %6, %7, %8, %9, %10, %11, %12, %13, %14, %15, %16, %17, %18, %19, %20, %21, %22, %23, %24, %25, %26, %27, %28, %29, %30, %31, "
        "%32, %33, %34, %35, %36, %37, %38, %39, %40, %41, %42, %43, %44, %45, %46, %47, %48, %49, %50, %51, %52, %53, %54, %55, %56, %57, %58, %59, %60, %61, %62, %63, "
        "%64, %65, %66, %67, %68, %69, %70, %71, %72, %73, %74, %75, %76, %77, %78, %79, %80, %81, %82, %83, %84, %85, %86, %87, %88, %89, %90, %91, %92, %93, %94, %95, "
        "%96, %97, %98, %99, %100, %101, %102, %103, %104, %105, %106, %107, %108, %109, %110, %111, %112, %113, %114, %115, %116, %117, %118, %119, %120, %121, %122, %123, %124, %125, %126, %127}, {%128, %129, %130, %131}, %132, 1, 1, 1, 1;\n"
        : "+f"(d[0]), "+f"(d[1]), "+f"(d[2]), "+f"(d[3]), "+f"(d[4]), "+f"(d[5]), "+f"(d[6]), "+f"(d[7]),
          "+f"(d[8]), "+f"(d[9]), "+f"(d[10]), "+f"(d[11]), "+f"(d[12]), "+f"(d[13]), "+f"(d[14]), "+f"(d[15]),
          "+f"(d[16]), "+f"(d[17]), "+f"(d[18]), "+f"(d[19]), "+f"(d[20]), "+f"(d[21]), "+f"(d[22]), "+f"(d[23]),
          "+f"(d[24]), "+f"(d[25]), "+f"(d[26]), "+f"(d[27]), "+f"(d[28]), "+f"(d[29]), "+f"(d[30]), "+f"(d[31]),
          "+f"(d[32]), "+f"(d[33]), "+f"(d[34]), "+f"(d[35]), "+f"(d[36]), "+f"(d[37]), "+f"(d[38]), "+f"(d[39]),
          "+f"(d[40]), "+f"(d[41]), "+f"(d[42]), "+f"(d[43]), "+f"(d[44]), "+f"(d[45]), "+f"(d[46]), "+f"(d[47]),
          "+f"(d[48]), "+f"(d[49]), "+f"(d[50]), "+f"(d[51]), "+f"(d[52]), "+f"(d[53]), "+f"(d[54]), "+f"(d[55]),
          "+f"(d[56]), "+f"(d[57]), "+f"(d[58]), "+f"(d[59]), "+f"(d[60]), "+f"(d[61]), "+f"(d[62]), "+f"(d[63]),
          "+f"(d[64]), "+f"(d[65]), "+f"(d[66]), "+f"(d[67]), "+f"(d[68]), "+f"(d[69]), "+f"(d[70]), "+f"(d[71]),
          "+f"(d[72]), "+f"(d[73]), "+f"(d[74]), "+f"(d[75]), "+f"(d[76]), "+f"(d[77]), "+f"(d[78]), "+f"(d[79]),
          "+f"(d[80]), "+f"(d[81]), "+f"(d[82]), "+f"(d[83]), "+f"(d[84]), "+f"(d[85]), "+f"(d[86]), "+f"(d[87]),
          "+f"(d[88]), "+f"(d[89]), "+f"(d[90]), "+f"(d[91]), "+f"(d[92]), "+f"(d[93]), "+f"(d[94]), "+f"(d[95]),
          "+f"(d[96]), "+f"(d[97]), "+f"(d[98]), "+f"(d[99]), "+f"(d[100]), "+f"(d[101]), "+f"(d[102]), "+f"(d[103]),
          "+f"(d[104]), "+f"(d[105]), "+f"(d[106]), "+f"(d[107]), "+f"(d[108]), "+f"(d[109]), "+f"(d[110]), "+f"(d[111]),
          "+f"(d[112]), "+f"(d[113]), "+f"(d[114]), "+f"(d[115]), "+f"(d[116]), "+f"(d[117]), "+f"(d[118]), "+f"(d[119]),
          "+f"(d[120]), "+f"(d[121]), "+f"(d[122]), "+f"(d[123]), "+f"(d[124]), "+f"(d[125]), "+f"(d[126]), "+f"(d[127])
        : "r"(a0), "r"(a1), "r"(a2), "r"(a3), "l"(db));
}
__device__ __forceinline__ void wgmma_rs_n256_tb_init(float (&d)[128], uint32_t a0, uint32_t a1, uint32_t a2, uint32_t a3, uint64_t db) {
    asm volatile("wgmma.mma_async.sync.aligned.m64n256k16.f32.f16.f16 {"
        "%0, %1, %2, %3, %4, %5, %6, %7, %8, %9, %10, %11, %12, %13, %14, %15, %16, %17, %18, %19, %20, %21, %22, %23, %24, %25, %26, %27, %28, %29, %30, %31, "
        "%32, %33, %34, %35, %36, %37, %38, %39, %40, %41, %42, %43, %44, %45, %46, %47, %48, %49, %50, %51, %52, %53, %54, %55, %56, %57, %58, %59, %60, %61, %62, %63, "
        "%64, %65, %66, %67, %68, %69, %70, %71, %72, %73, %74, %75, %76, %77, %78, %79, %80, %81, %82, %83, %84, %85, %86, %87, %88, %89, %90, %91, %92, %93, %94, %95, "
        "%96, %97, %98, %99, %100, %101, %102, %103, %104, %105, %106, %107, %108, %109, %110, %111, %112, %113, %114, %115, %116, %117, %118, %119, %120, %121, %122, %123, %124, %125, %126, %127}, {%128, %129, %130, %131}, %132, 0, 1, 1, 1;\n"
        : "=f"(d[0]), "=f"(d[1]), "=f"(d[2]), "=f"(d[3]), "=f"(d[4]), "=f"(d[5]), "=f"(d[6]), "=f"(d[7]),
          "=f"(d[8]), "=f"(d[9]), "=f"(d[10]), "=f"(d[11]), "=f"(d[12]), "=f"(d[13]), "=f"(d[14]), "=f"(d[15]),
          "=f"(d[16]), "=f"(d[17]), "=f"(d[18]), "=f"(d[19]), "=f"(d[20]), "=f"(d[21]), "=f"(d[22]), "=f"(d[23]),
          "=f"(d[24]), "=f"(d[25]), "=f"(d[26]), "=f"(d[27]), "=f"(d[28]), "=f"(d[29]), "=f"(d[30]), "=f"(d[31]),
          "=f"(d[32]), "=f"(d[33]), "=f"(d[34]), "=f"(d[35]), "=f"(d[36]), "=f"(d[37]), "=f"(d[38]), "=f"(d[39]),
          "=f"(d[40]), "=f"(d[41]), "=f"(d[42]), "=f"(d[43]), "=f"(d[44]), "=f"(d[45]), "=f"(d[46]), "=f"(d[47]),
          "=f"(d[48]), "=f"(d[49]), "=f"(d[50]), "=f"(d[51]), "=f"(d[52]), "=f"(d[53]), "=f"(d[54]), "=f"(d[55]),
          "=f"(d[56]), "=f"(d[57]), "=f"(d[58]), "=f"(d[59]), "=f"(d[60]), "=f"(d[61]), "=f"(d[62]), "=f"(d[63]),
          "=f"(d[64]), "=f"(d[65]), "=f"(d[66]), "=f"(d[67]), "=f"(d[68]), "=f"(d[69]), "=f"(d[70]), "=f"(d[71]),
          "=f"(d[72]), "=f"(d[73]), "=f"(d[74]), "=f"(d[75]), "=f"(d[76]), "=f"(d[77]), "=f"(d[78]), "=f"(d[79]),
          "=f"(d[80]), "=f"(d[81]), "=f"(d[82]), "=f"(d[83]), "=f"(d[84]), "=f"(d[85]), "=f"(d[86]), "=f"(d[87]),
          "=f"(d[88]), "=f"(d[89]), "=f"(d[90]), "=f"(d[91]), "=f"(d[92]), "=f"(d[93]), "=f"(d[94]), "=f"(d[95]),
          "=f"(d[96]), "=f"(d[97]), "=f"(d[98]), "=f"(d[99]), "=f"(d[100]), "=f"(d[101]), "=f"(d[102]), "=f"(d[103]),
          "=f"(d[104]), "=f"(d[105]), "=f"(d[106]), "=f"(d[107]), "=f"(d[108]), "=f"(d[109]), "=f"(d[110]), "=f"(d[111]),
          "=f"(d[112]), "=f"(d[113]), "=f"(d[114]), "=f"(d[115]), "=f"(d[116]), "=f"(d[117]), "=f"(d[118]), "=f"(d[119]),
          "=f"(d[120]), "=f"(d[121]), "=f"(d[122]), "=f"(d[123]), "=f"(d[124]), "=f"(d[125]), "=f"(d[126]), "=f"(d[127])
        : "r"(a0), "r"(a1), "r"(a2), "r"(a3), "l"(db));
}
__device__ __forceinline__ void wgmma_rs_n256_tb_pred(float (&d)[128], uint32_t a0, uint32_t a1, uint32_t a2, uint32_t a3, uint64_t db, int acc) {
    asm volatile("{\n.reg .pred p;\nsetp.ne.s32 p, %133, 0;\nwgmma.mma_async.sync.aligned.m64n256k16.f32.f16.f16 {"
        "%0, %1, %2, %3, %4, %5, %6, %7, %8, %9, %10, %11, %12, %13, %14, %15, %16, %17, %18, %19, %20, %21, %22, %23, %24, %25, %26, %27, %28, %29, %30, %31, "
        "%32, %33, %34, %35, %36, %37, %38, %39, %40, %41, %42, %43, %44, %45, %46, %47, %48, %49, %50, %51, %52, %53, %54, %55, %56, %57, %58, %59, %60, %61, %62, %63, "
        "%64, %65, %66, %67, %68, %69, %70, %71, %72, %73, %74, %75, %76, %77, %78, %79, %80, %81, %82, %83, %84, %85, %86, %87, %88, %89, %90, %91, %92, %93, %94, %95, "
        "%96, %97, %98, %99, %100, %101, %102, %103, %104, %105, %106, %107, %108, %109, %110, %111, %112, %113, %114, %115, %116, %117, %118, %119, %120, %121, %122, %123, %124, %125, %126, %127}, {%128, %129, %130, %131}, %132, p, 1, 1, 1;\n}\n"
        : "+f"(d[0]), "+f"(d[1]), "+f"(d[2]), "+f"(d[3]), "+f"(d[4]), "+f"(d[5]), "+f"(d[6]), "+f"(d[7]),
          "+f"(d[8]), "+f"(d[9]), "+f"(d[10]), "+f"(d[11]), "+f"(d[12]), "+f"(d[13]), "+f"(d[14]), "+f"(d[15]),
          "+f"(d[16]), "+f"(d[17]), "+f"(d[18]), "+f"(d[19]), "+f"(d[20]), "+f"(d[21]), "+f"(d[22]), "+f"(d[23]),
          "+f"(d[24]), "+f"(d[25]), "+f"(d[26]), "+f"(d[27]), "+f"(d[28]), "+f"(d[29]), "+f"(d[30]), "+f"(d[31]),
          "+f"(d[32]), "+f"(d[33]), "+f"(d[34]), "+f"(d[35]), "+f"(d[36]), "+f"(d[37]), "+f"(d[38]), "+f"(d[39]),
          "+f"(d[40]), "+f"(d[41]), "+f"(d[42]), "+f"(d[43]), "+f"(d[44]), "+f"(d[45]), "+f"(d[46]), "+f"(d[47]),
          "+f"(d[48]), "+f"(d[49]), "+f"(d[50]), "+f"(d[51]), "+f"(d[52]), "+f"(d[53]), "+f"(d[54]), "+f"(d[55]),
          "+f"(d[56]), "+f"(d[57]), "+f"(d[58]), "+f"(d[59]), "+f"(d[60]), "+f"(d[61]), "+f"(d[62]), "+f"(d[63]),
          "+f"(d[64]), "+f"(d[65]), "+f"(d[66]), "+f"(d[67]), "+f"(d[68]), "+f"(d[69]), "+f"(d[70]), "+f"(d[71]),
          "+f"(d[72]), "+f"(d[73]), "+f"(d[74]), "+f"(d[75]), "+f"(d[76]), "+f"(d[77]), "+f"(d[78]), "+f"(d[79]),
          "+f"(d[80]), "+f"(d[81]), "+f"(d[82]), "+f"(d[83]), "+f"(d[84]), "+f"(d[85]), "+f"(d[86]), "+f"(d[87]),
          "+f"(d[88]), "+f"(d[89]), "+f"(d[90]), "+f"(d[91]), "+f"(d[92]), "+f"(d[93]), "+f"(d[94]), "+f"(d[95]),
          "+f"(d[96]), "+f"(d[97]), "+f"(d[98]), "+f"(d[99]), "+f"(d[100]), "+f"(d[101]), "+f"(d[102]), "+f"(d[103]),
          "+f"(d[104]), "+f"(d[105]), "+f"(d[106]), "+f"(d[107]), "+f"(d[108]), "+f"(d[109]), "+f"(d[110]), "+f"(d[111]),
          "+f"(d[112]), "+f"(d[113]), "+f"(d[114]), "+f"(d[115]), "+f"(d[116]), "+f"(d[117]), "+f"(d[118]), "+f"(d[119]),
          "+f"(d[120]), "+f"(d[121]), "+f"(d[122]), "+f"(d[123]), "+f"(d[124]), "+f"(d[125]), "+f"(d[126]), "+f"(d[127])
        : "r"(a0), "r"(a1), "r"(a2), "r"(a3), "l"(db), "r"(acc));
}
__device__ __forceinline__ void wgmma_ss_n256_tb(float (&d)[128], uint64_t da, uint64_t db) {
    asm volatile("wgmma.mma_async.sync.aligned.m64n256k16.f32.bf16.bf16 {"
        "%0, %1, %2, %3, %4, %5, %6, %7, %8, %9, %10, %11, %12, %13, %14, %15, %16, %17, %18, %19, %20, %21, %22, %23, %24, %25, %26, %27, %28, %29, %30, %31, "
        "%32, %33, %34, %35, %36, %37, %38, %39, %40, %41, %42, %43, %44, %45, %46, %47, %48, %49, %50, %51, %52, %53, %54, %55, %56, %57, %58, %59, %60, %61, %62, %63, "
        "%64, %65, %66, %67, %68, %69, %70, %71, %72, %73, %74, %75, %76, %77, %78, %79, %80, %81, %82, %83, %84, %85, %86, %87, %88, %89, %90, %91, %92, %93, %94, %95, "
        "%96, %97, %98, %99, %100, %101, %102, %103, %104, %105, %106, %107, %108, %109, %110, %111, %112, %113, %114, %115, %116, %117, %118, %119, %120, %121, %122, %123, %124, %125, %126, %127}, %128, %129, 1, 1, 1, 0, 1;\n"
        : "+f"(d[0]), "+f"(d[1]), "+f"(d[2]), "+f"(d[3]), "+f"(d[4]), "+f"(d[5]), "+f"(d[6]), "+f"(d[7]),
          "+f"(d[8]), "+f"(d[9]), "+f"(d[10]), "+f"(d[11]), "+f"(d[12]), "+f"(d[13]), "+f"(d[14]), "+f"(d[15]),
          "+f"(d[16]), "+f"(d[17]), "+f"(d[18]), "+f"(d[19]), "+f"(d[20]), "+f"(d[21]), "+f"(d[22]), "+f"(d[23]),
          "+f"(d[24]), "+f"(d[25]), "+f"(d[26]), "+f"(d[27]), "+f"(d[28]), "+f"(d[29]), "+f"(d[30]), "+f"(d[31]),
          "+f"(d[32]), "+f"(d[33]), "+f"(d[34]), "+f"(d[35]), "+f"(d[36]), "+f"(d[37]), "+f"(d[38]), "+f"(d[39]),
          "+f"(d[40]), "+f"(d[41]), "+f"(d[42]), "+f"(d[43]), "+f"(d[44]), "+f"(d[45]), "+f"(d[46]), "+f"(d[47]),
          "+f"(d[48]), "+f"(d[49]), "+f"(d[50]), "+f"(d[51]), "+f"(d[52]), "+f"(d[53]), "+f"(d[54]), "+f"(d[55]),
          "+f"(d[56]), "+f"(d[57]), "+f"(d[58]), "+f"(d[59]), "+f"(d[60]), "+f"(d[61]), "+f"(d[62]), "+f"(d[63]),
          "+f"(d[64]), "+f"(d[65]), "+f"(d[66]), "+f"(d[67]), "+f"(d[68]), "+f"(d[69]), "+f"(d[70]), "+f"(d[71]),
          "+f"(d[72]), "+f"(d[73]), "+f"(d[74]), "+f"(d[75]), "+f"(d[76]), "+f"(d[77]), "+f"(d[78]), "+f"(d[79]),
          "+f"(d[80]), "+f"(d[81]), "+f"(d[82]), "+f"(d[83]), "+f"(d[84]), "+f"(d[85]), "+f"(d[86]), "+f"(d[87]),
          "+f"(d[88]), "+f"(d[89]), "+f"(d[90]), "+f"(d[91]), "+f"(d[92]), "+f"(d[93]), "+f"(d[94]), "+f"(d[95]),
          "+f"(d[96]), "+f"(d[97]), "+f"(d[98]), "+f"(d[99]), "+f"(d[100]), "+f"(d[101]), "+f"(d[102]), "+f"(d[103]),
          "+f"(d[104]), "+f"(d[105]), "+f"(d[106]), "+f"(d[107]), "+f"(d[108]), "+f"(d[109]), "+f"(d[110]), "+f"(d[111]),
          "+f"(d[112]), "+f"(d[113]), "+f"(d[114]), "+f"(d[115]), "+f"(d[116]), "+f"(d[117]), "+f"(d[118]), "+f"(d[119]),
          "+f"(d[120]), "+f"(d[121]), "+f"(d[122]), "+f"(d[123]), "+f"(d[124]), "+f"(d[125]), "+f"(d[126]), "+f"(d[127])
        : "l"(da), "l"(db));
}
__device__ __forceinline__ void wgmma_ss_n256_tb_init(float (&d)[128], uint64_t da, uint64_t db) {
    asm volatile("wgmma.mma_async.sync.aligned.m64n256k16.f32.bf16.bf16 {"
        "%0, %1, %2, %3, %4, %5, %6, %7, %8, %9, %10, %11, %12, %13, %14, %15, %16, %17, %18, %19, %20, %21, %22, %23, %24, %25, %26, %27, %28, %29, %30, %31, "
        "%32, %33, %34, %35, %36, %37, %38, %39, %40, %41, %42, %43, %44, %45, %46, %47, %48, %49, %50, %51, %52, %53, %54, %55, %56, %57, %58, %59, %60, %61, %62, %63, "
        "%64, %65, %66, %67, %68, %69, %70, %71, %72, %73, %74, %75, %76, %77, %78, %79, %80, %81, %82, %83, %84, %85, %86, %87, %88, %89, %90, %91, %92, %93, %94, %95, "
        "%96, %97, %98, %99, %100, %101, %102, %103, %104, %105, %106, %107, %108, %109, %110, %111, %112, %113, %114, %115, %116, %117, %118, %119, %120, %121, %122, %123, %124, %125, %126, %127}, %128, %129, 0, 1, 1, 0, 1;\n"
        : "=f"(d[0]), "=f"(d[1]), "=f"(d[2]), "=f"(d[3]), "=f"(d[4]), "=f"(d[5]), "=f"(d[6]), "=f"(d[7]),
          "=f"(d[8]), "=f"(d[9]), "=f"(d[10]), "=f"(d[11]), "=f"(d[12]), "=f"(d[13]), "=f"(d[14]), "=f"(d[15]),
          "=f"(d[16]), "=f"(d[17]), "=f"(d[18]), "=f"(d[19]), "=f"(d[20]), "=f"(d[21]), "=f"(d[22]), "=f"(d[23]),
          "=f"(d[24]), "=f"(d[25]), "=f"(d[26]), "=f"(d[27]), "=f"(d[28]), "=f"(d[29]), "=f"(d[30]), "=f"(d[31]),
          "=f"(d[32]), "=f"(d[33]), "=f"(d[34]), "=f"(d[35]), "=f"(d[36]), "=f"(d[37]), "=f"(d[38]), "=f"(d[39]),
          "=f"(d[40]), "=f"(d[41]), "=f"(d[42]), "=f"(d[43]), "=f"(d[44]), "=f"(d[45]), "=f"(d[46]), "=f"(d[47]),
          "=f"(d[48]), "=f"(d[49]), "=f"(d[50]), "=f"(d[51]), "=f"(d[52]), "=f"(d[53]), "=f"(d[54]), "=f"(d[55]),
          "=f"(d[56]), "=f"(d[57]), "=f"(d[58]), "=f"(d[59]), "=f"(d[60]), "=f"(d[61]), "=f"(d[62]), "=f"(d[63]),
          "=f"(d[64]), "=f"(d[65]), "=f"(d[66]), "=f"(d[67]), "=f"(d[68]), "=f"(d[69]), "=f"(d[70]), "=f"(d[71]),
          "=f"(d[72]), "=f"(d[73]), "=f"(d[74]), "=f"(d[75]), "=f"(d[76]), "=f"(d[77]), "=f"(d[78]), "=f"(d[79]),
          "=f"(d[80]), "=f"(d[81]), "=f"(d[82]), "=f"(d[83]), "=f"(d[84]), "=f"(d[85]), "=f"(d[86]), "=f"(d[87]),
          "=f"(d[88]), "=f"(d[89]), "=f"(d[90]), "=f"(d[91]), "=f"(d[92]), "=f"(d[93]), "=f"(d[94]), "=f"(d[95]),
          "=f"(d[96]), "=f"(d[97]), "=f"(d[98]), "=f"(d[99]), "=f"(d[100]), "=f"(d[101]), "=f"(d[102]), "=f"(d[103]),
          "=f"(d[104]), "=f"(d[105]), "=f"(d[106]), "=f"(d[107]), "=f"(d[108]), "=f"(d[109]), "=f"(d[110]), "=f"(d[111]),
          "=f"(d[112]), "=f"(d[113]), "=f"(d[114]), "=f"(d[115]), "=f"(d[116]), "=f"(d[117]), "=f"(d[118]), "=f"(d[119]),
          "=f"(d[120]), "=f"(d[121]), "=f"(d[122]), "=f"(d[123]), "=f"(d[124]), "=f"(d[125]), "=f"(d[126]), "=f"(d[127])
        : "l"(da), "l"(db));
}
__device__ __forceinline__ void wgmma_ss_n256_tb_pred(float (&d)[128], uint64_t da, uint64_t db, int acc) {
    asm volatile("{\n.reg .pred p;\nsetp.ne.s32 p, %130, 0;\nwgmma.mma_async.sync.aligned.m64n256k16.f32.bf16.bf16 {"
        "%0, %1, %2, %3, %4, %5, %6, %7, %8, %9, %10, %11, %12, %13, %14, %15, %16, %17, %18, %19, %20, %21, %22, %23, %24, %25, %26, %27, %28, %29, %30, %31, "
        "%32, %33, %34, %35, %36, %37, %38, %39, %40, %41, %42, %43, %44, %45, %46, %47, %48, %49, %50, %51, %52, %53, %54, %55, %56, %57, %58, %59, %60, %61, %62, %63, "
        "%64, %65, %66, %67, %68, %69, %70, %71, %72, %73, %74, %75, %76, %77, %78, %79, %80, %81, %82, %83, %84, %85, %86, %87, %88, %89, %90, %91, %92, %93, %94, %95, "
        "%96, %97, %98, %99, %100, %101, %102, %103, %104, %105, %106, %107, %108, %109, %110, %111, %112, %113, %114, %115, %116, %117, %118, %119, %120, %121, %122, %123, %124, %125, %126, %127}, %128, %129, p, 1, 1, 0, 1;\n}\n"
        : "+f"(d[0]), "+f"(d[1]), "+f"(d[2]), "+f"(d[3]), "+f"(d[4]), "+f"(d[5]), "+f"(d[6]), "+f"(d[7]),
          "+f"(d[8]), "+f"(d[9]), "+f"(d[10]), "+f"(d[11]), "+f"(d[12]), "+f"(d[13]), "+f"(d[14]), "+f"(d[15]),
          "+f"(d[16]), "+f"(d[17]), "+f"(d[18]), "+f"(d[19]), "+f"(d[20]), "+f"(d[21]), "+f"(d[22]), "+f"(d[23]),
          "+f"(d[24]), "+f"(d[25]), "+f"(d[26]), "+f"(d[27]), "+f"(d[28]), "+f"(d[29]), "+f"(d[30]), "+f"(d[31]),
          "+f"(d[32]), "+f"(d[33]), "+f"(d[34]), "+f"(d[35]), "+f"(d[36]), "+f"(d[37]), "+f"(d[38]), "+f"(d[39]),
          "+f"(d[40]), "+f"(d[41]), "+f"(d[42]), "+f"(d[43]), "+f"(d[44]), "+f"(d[45]), "+f"(d[46]), "+f"(d[47]),
          "+f"(d[48]), "+f"(d[49]), "+f"(d[50]), "+f"(d[51]), "+f"(d[52]), "+f"(d[53]), "+f"(d[54]), "+f"(d[55]),
          "+f"(d[56]), "+f"(d[57]), "+f"(d[58]), "+f"(d[59]), "+f"(d[60]), "+f"(d[61]), "+f"(d[62]), "+f"(d[63]),
          "+f"(d[64]), "+f"(d[65]), "+f"(d[66]), "+f"(d[67]), "+f"(d[68]), "+f"(d[69]), "+f"(d[70]), "+f"(d[71]),
          "+f"(d[72]), "+f"(d[73]), "+f"(d[74]), "+f"(d[75]), "+f"(d[76]), "+f"(d[77]), "+f"(d[78]), "+f"(d[79]),
          "+f"(d[80]), "+f"(d[81]), "+f"(d[82]), "+f"(d[83]), "+f"(d[84]), "+f"(d[85]), "+f"(d[86]), "+f"(d[87]),
          "+f"(d[88]), "+f"(d[89]), "+f"(d[90]), "+f"(d[91]), "+f"(d[92]), "+f"(d[93]), "+f"(d[94]), "+f"(d[95]),
          "+f"(d[96]), "+f"(d[97]), "+f"(d[98]), "+f"(d[99]), "+f"(d[100]), "+f"(d[101]), "+f"(d[102]), "+f"(d[103]),
          "+f"(d[104]), "+f"(d[105]), "+f"(d[106]), "+f"(d[107]), "+f"(d[108]), "+f"(d[109]), "+f"(d[110]), "+f"(d[111]),
          "+f"(d[112]), "+f"(d[113]), "+f"(d[114]), "+f"(d[115]), "+f"(d[116]), "+f"(d[117]), "+f"(d[118]), "+f"(d[119]),
          "+f"(d[120]), "+f"(d[121]), "+f"(d[122]), "+f"(d[123]), "+f"(d[124]), "+f"(d[125]), "+f"(d[126]), "+f"(d[127])
        : "l"(da), "l"(db), "r"(acc));
}
__device__ __forceinline__ void wgmma_rs_n64_tb(float (&d)[32], uint32_t a0, uint32_t a1, uint32_t a2, uint32_t a3, uint64_t db) {
    asm volatile("wgmma.mma_async.sync.aligned.m64n64k16.f32.bf16.bf16 {"
        "%0, %1, %2, %3, %4, %5, %6, %7, %8, %9, %10, %11, %12, %13, %14, %15, %16, %17, %18, %19, %20, %21, %22, %23, %24, %25, %26, %27, %28, %29, %30, %31}, {%32, %33, %34, %35}, %36, 1, 1, 1, 1;\n"
        : "+f"(d[0]), "+f"(d[1]), "+f"(d[2]), "+f"(d[3]), "+f"(d[4]), "+f"(d[5]), "+f"(d[6]), "+f"(d[7]),
          "+f"(d[8]), "+f"(d[9]), "+f"(d[10]), "+f"(d[11]), "+f"(d[12]), "+f"(d[13]), "+f"(d[14]), "+f"(d[15]),
          "+f"(d[16]), "+f"(d[17]), "+f"(d[18]), "+f"(d[19]), "+f"(d[20]), "+f"(d[21]), "+f"(d[22]), "+f"(d[23]),
          "+f"(d[24]), "+f"(d[25]), "+f"(d[26]), "+f"(d[27]), "+f"(d[28]), "+f"(d[29]), "+f"(d[30]), "+f"(d[31])
        : "r"(a0), "r"(a1), "r"(a2), "r"(a3), "l"(db));
}
__device__ __forceinline__ void wgmma_rs_n64_tb_init(float (&d)[32], uint32_t a0, uint32_t a1, uint32_t a2, uint32_t a3, uint64_t db) {
    asm volatile("wgmma.mma_async.sync.aligned.m64n64k16.f32.bf16.bf16 {"
        "%0, %1, %2, %3, %4, %5, %6, %7, %8, %9, %10, %11, %12, %13, %14, %15, %16, %17, %18, %19, %20, %21, %22, %23, %24, %25, %26, %27, %28, %29, %30, %31}, {%32, %33, %34, %35}, %36, 0, 1, 1, 1;\n"
        : "=f"(d[0]), "=f"(d[1]), "=f"(d[2]), "=f"(d[3]), "=f"(d[4]), "=f"(d[5]), "=f"(d[6]), "=f"(d[7]),
          "=f"(d[8]), "=f"(d[9]), "=f"(d[10]), "=f"(d[11]), "=f"(d[12]), "=f"(d[13]), "=f"(d[14]), "=f"(d[15]),
          "=f"(d[16]), "=f"(d[17]), "=f"(d[18]), "=f"(d[19]), "=f"(d[20]), "=f"(d[21]), "=f"(d[22]), "=f"(d[23]),
          "=f"(d[24]), "=f"(d[25]), "=f"(d[26]), "=f"(d[27]), "=f"(d[28]), "=f"(d[29]), "=f"(d[30]), "=f"(d[31])
        : "r"(a0), "r"(a1), "r"(a2), "r"(a3), "l"(db));
}

__device__ __forceinline__ void wg_fence() { asm volatile("wgmma.fence.sync.aligned;\n" ::: "memory"); }
__device__ __forceinline__ void wg_commit() { asm volatile("wgmma.commit_group.sync.aligned;\n" ::: "memory"); }
template <int N> __device__ __forceinline__ void wg_wait() { asm volatile("wgmma.wait_group.sync.aligned %0;\n" ::"n"(N) : "memory"); }
template <int N> __device__ __forceinline__ void fence_regs(float (&a)[N]) {
#pragma unroll
    for (int i = 0; i < N; i++) asm volatile("" : "+f"(a[i])::"memory");
}
template <int N> __device__ __forceinline__ void fence_regs(uint32_t (&a)[N]) {
#pragma unroll
    for (int i = 0; i < N; i++) asm volatile("" : "+r"(a[i])::"memory");
}
__device__ __forceinline__ void mbar_init(uint32_t bar, uint32_t cnt) {
    asm volatile("mbarrier.init.shared::cta.b64 [%0], %1;\n" ::"r"(bar), "r"(cnt) : "memory");
}
__device__ __forceinline__ void mbar_expect_tx(uint32_t bar, uint32_t bytes) {
    asm volatile("mbarrier.arrive.expect_tx.shared::cta.b64 _, [%0], %1;\n" ::"r"(bar), "r"(bytes) : "memory");
}
__device__ __forceinline__ void mbar_wait(uint32_t bar, uint32_t parity) {
    asm volatile("{\n.reg .pred p;\nLW:\nmbarrier.try_wait.parity.shared::cta.b64 p, [%0], %1;\n@!p pmevent 0;\n@!p bra LW;\n}\n" ::"r"(bar), "r"(parity) : "memory");
}
__device__ __forceinline__ void mbar_wait_sleep(uint32_t bar, uint32_t parity) {
    asm volatile("{\n.reg .pred p;\nLW:\nmbarrier.try_wait.parity.shared::cta.b64 p, [%0], %1, 20000;\n@!p pmevent 0;\n@!p bra LW;\n}\n" ::"r"(bar), "r"(parity) : "memory");
}
__device__ __forceinline__ void mbar_wait_bounded(uint32_t bar, uint32_t parity) {
    asm volatile("{\n.reg .pred p;\n.reg .u32 c;\nmov.u32 c, 0;\nLW:\nmbarrier.try_wait.parity.shared::cta.b64 p, [%0], %1, 20000;\n@p bra LD;\n"
                 "add.u32 c, c, 1;\nsetp.ge.u32 p, c, 262144;\n@p trap;\nbra LW;\nLD:\n}\n" ::"r"(bar), "r"(parity) : "memory");
}
__device__ __forceinline__ void flag_wait(const int* p, int v) {
    asm volatile("{\n.reg .pred p;\n.reg .s32 f;\nLW:\nld.acquire.gpu.global.s32 f, [%0];\nsub.s32 f, f, %1;\nsetp.lt.s32 p, f, 0;\n@p bra LW;\n}\n" ::"l"(p), "r"(v) : "memory");
}
__device__ __forceinline__ void flag_wait_bounded(const int* p, int v) {
    asm volatile("{\n.reg .pred p;\n.reg .u32 c;\n.reg .s32 f;\nmov.u32 c, 0;\nLW:\nld.acquire.gpu.global.s32 f, [%0];\nsub.s32 f, f, %1;\nsetp.ge.s32 p, f, 0;\n@p bra LD;\n"
                 "nanosleep.u32 500;\nadd.u32 c, c, 1;\nsetp.ge.u32 p, c, 4194304;\n@p trap;\nbra LW;\nLD:\n}\n" ::"l"(p), "r"(v) : "memory");
}
__device__ __forceinline__ bool elect() {
    uint32_t p; asm volatile("{\n.reg .pred p;\nelect.sync _|p, -1;\nselp.u32 %0, 1, 0, p;\n}\n" : "=r"(p)); return p;
}
__device__ __forceinline__ void bulk_g2s(uint32_t dst, const void* src, uint32_t bytes, uint32_t bar) {
    asm volatile("cp.async.bulk.shared::cluster.global.mbarrier::complete_tx::bytes [%0], [%1], %2, [%3];\n"
                 ::"r"(dst), "l"(src), "r"(bytes), "r"(bar) : "memory");
}
__device__ __forceinline__ void tma_g2s(uint32_t dst, const CUtensorMap* tm, int rowgroup, uint32_t bar) {
    asm volatile("cp.async.bulk.tensor.4d.shared::cluster.global.tile.mbarrier::complete_tx::bytes [%0], [%1, {0, 0, 0, %2}], [%3];\n"
                 ::"r"(dst), "l"(tm), "r"(rowgroup), "r"(bar) : "memory");
}
__device__ __forceinline__ void bar_sync(int id, int n) { asm volatile("bar.sync %0, %1;\n" ::"r"(id), "r"(n) : "memory"); }
__device__ __forceinline__ void bar_arrive(int id, int n) { asm volatile("bar.arrive %0, %1;\n" ::"r"(id), "r"(n) : "memory"); }
__device__ __forceinline__ float quad_last(float v) {
    float r; asm volatile("shfl.sync.idx.b32 %0, %1, 3, 0x1c1f, -1;\n" : "=f"(r) : "f"(v)); return r;
}
__device__ __forceinline__ float ex2(float x) { float y; asm("ex2.approx.ftz.f32 %0, %1;\n" : "=f"(y) : "f"(x)); return y; }
__device__ __forceinline__ float rcp(float x) { float y; asm("rcp.approx.ftz.f32 %0, %1;\n" : "=f"(y) : "f"(x)); return y; }
__device__ __forceinline__ uint32_t pack_bf16(float lo, float hi) {
    uint32_t r; asm("cvt.rn.bf16x2.f32 %0, %1, %2;\n" : "=r"(r) : "f"(hi), "f"(lo)); return r;
}
__device__ __forceinline__ uint32_t pack_f16(float lo, float hi) {
    uint32_t r; asm("cvt.rn.f16x2.f32 %0, %1, %2;\n" : "=r"(r) : "f"(hi), "f"(lo)); return r;
}
__device__ __forceinline__ uint32_t pack_f16_sat(float lo, float hi) {
    uint32_t r; asm("cvt.rn.satfinite.f16x2.f32 %0, %1, %2;\n" : "=r"(r) : "f"(hi), "f"(lo)); return r;
}
__device__ __forceinline__ float f16_lo(uint32_t v) { float r; asm("cvt.f32.f16 %0, %1;\n" : "=f"(r) : "h"((unsigned short)v)); return r; }
__device__ __forceinline__ float f16_hi(uint32_t v) { return f16_lo(v >> 16); }
__device__ __forceinline__ float bf_lo(uint32_t v) { return __uint_as_float(v << 16); }
__device__ __forceinline__ float bf_hi(uint32_t v) { return __uint_as_float(v & 0xFFFF0000u); }
__device__ __forceinline__ float bf_round(float x) { return __uint_as_float(pack_bf16(0.f, x)); }
__device__ __forceinline__ void st_release(int* p, int v) {
    asm volatile("st.release.gpu.global.s32 [%0], %1;\n" ::"l"(p), "r"(v) : "memory");
}
__device__ __forceinline__ uint4 ldg_pinned(const uint4* p) {
    uint4 v; asm volatile("ld.global.nc.v4.u32 {%0, %1, %2, %3}, [%4];\n" : "=r"(v.x), "=r"(v.y), "=r"(v.z), "=r"(v.w) : "l"(p) : "memory"); return v;
}
__device__ __forceinline__ void stmatrix_x4(uint32_t addr, uint32_t r0, uint32_t r1, uint32_t r2, uint32_t r3) {
    asm volatile("stmatrix.sync.aligned.m8n8.x4.shared.b16 [%0], {%1, %2, %3, %4};\n" ::"r"(addr), "r"(r0), "r"(r1), "r"(r2), "r"(r3) : "memory");
}

__device__ __forceinline__ uint32_t tile_off(int r, int ch) {
    return (uint32_t)((r >> 3) * 4096 + (ch >> 3) * 1024 + (r & 7) * 128 + (((ch ^ r) & 7) << 4));
}
__device__ __forceinline__ int h_unit(int qt, int u) { return qt < 78 ? u * 78 + qt : 624; }
__device__ __forceinline__ int row_off(int r) { return 4096 + h_unit(r >> 7, (r >> 4) & 7) * 8192 + (r & 8) * 512 + (r & 7) * 144; }

__device__ __forceinline__ float4 lds128f(uint32_t a) {
    float4 v; asm volatile("ld.shared.v4.f32 {%0, %1, %2, %3}, [%4];\n" : "=f"(v.x), "=f"(v.y), "=f"(v.z), "=f"(v.w) : "r"(a) : "memory"); return v;
}
__device__ __forceinline__ uint64_t lds64(uint32_t a) { uint64_t v; asm volatile("ld.shared.u64 %0, [%1];\n" : "=l"(v) : "r"(a) : "memory"); return v; }
__device__ __forceinline__ uint4 lds128(uint32_t a) {
    uint4 v; asm volatile("ld.shared.v4.u32 {%0, %1, %2, %3}, [%4];\n" : "=r"(v.x), "=r"(v.y), "=r"(v.z), "=r"(v.w) : "r"(a) : "memory"); return v;
}
__device__ __forceinline__ void sts128(uint32_t a, uint32_t x, uint32_t y, uint32_t z, uint32_t w) {
    asm volatile("st.shared.v4.u32 [%0], {%1, %2, %3, %4};\n" ::"r"(a), "r"(x), "r"(y), "r"(z), "r"(w) : "memory");
}
__device__ __forceinline__ void mbar_arrive(uint32_t bar) {
    asm volatile("mbarrier.arrive.shared::cta.b64 _, [%0];\n" ::"r"(bar) : "memory");
}
__device__ __forceinline__ uint64_t mkaddr(uint32_t lo, uint32_t hi) { uint64_t a; asm("mov.b64 %0, {%1, %2};\n" : "=l"(a) : "r"(lo), "r"(hi)); return a; }
__device__ __forceinline__ void red_add(int* p) { asm volatile("red.relaxed.gpu.global.add.s32 [%0], 1;\n" ::"l"(p) : "memory"); }
__device__ __forceinline__ void red_release(int* p) {
    asm volatile("fence.proxy.async.global;\nfence.acq_rel.gpu;\nred.relaxed.gpu.global.add.s32 [%0], 1;\n" ::"l"(p) : "memory");
}
__device__ __forceinline__ void fence_async_global() { asm volatile("fence.proxy.async.global;\n" ::: "memory"); }
__device__ __forceinline__ void fence_async_smem() { asm volatile("fence.proxy.async.shared::cta;\n" ::: "memory"); }
__device__ __forceinline__ void bulk_s2g(void* dst, uint32_t src, uint32_t bytes) {
    asm volatile("cp.async.bulk.global.shared::cta.bulk_group [%0], [%1], %2;\ncp.async.bulk.commit_group;\n" ::"l"(dst), "r"(src), "r"(bytes) : "memory");
}
__device__ __forceinline__ void mma16816(float (&c)[4], uint32_t a0, uint32_t a1, uint32_t a2, uint32_t a3, uint32_t b0, uint32_t b1) {
    asm("mma.sync.aligned.m16n8k16.row.col.f32.bf16.bf16.f32 {%0, %1, %2, %3}, {%4, %5, %6, %7}, {%8, %9}, {%0, %1, %2, %3};\n"
        : "+f"(c[0]), "+f"(c[1]), "+f"(c[2]), "+f"(c[3]) : "r"(a0), "r"(a1), "r"(a2), "r"(a3), "r"(b0), "r"(b1));
}
__device__ __forceinline__ void mma1688(float (&c)[4], uint32_t a0, uint32_t a1, uint32_t b0) {
    asm("mma.sync.aligned.m16n8k8.row.col.f32.bf16.bf16.f32 {%0, %1, %2, %3}, {%4, %5}, {%6}, {%0, %1, %2, %3};\n"
        : "+f"(c[0]), "+f"(c[1]), "+f"(c[2]), "+f"(c[3]) : "r"(a0), "r"(a1), "r"(b0));
}
__device__ __forceinline__ uint32_t hadd2_f16(uint32_t a, uint32_t b) { uint32_t r; asm("add.rn.f16x2 %0, %1, %2;\n" : "=r"(r) : "r"(a), "r"(b)); return r; }
__device__ __forceinline__ uint32_t hadd2(uint32_t a, uint32_t b) { uint32_t r; asm("add.rn.bf16x2 %0, %1, %2;\n" : "=r"(r) : "r"(a), "r"(b)); return r; }
__device__ __forceinline__ uint32_t hmul2(uint32_t a, uint32_t b) { uint32_t r; asm("mul.rn.bf16x2 %0, %1, %2;\n" : "=r"(r) : "r"(a), "r"(b)); return r; }
__device__ __forceinline__ uint32_t hfma2(uint32_t a, uint32_t b, uint32_t c) { uint32_t r; asm("fma.rn.bf16x2 %0, %1, %2, %3;\n" : "=r"(r) : "r"(a), "r"(b), "r"(c)); return r; }

constexpr int SM_Q = 0;
constexpr int SM_KV = 65536;
constexpr int SM_ML = SM_KV + STAGES * KV_BYTES;
constexpr int SM_BAR = SM_ML + 1024;
constexpr int SM_TOTAL = SM_BAR + 256;
constexpr float SCALE_LOG2 = 1.4426950408889634f / 16.0f;
constexpr float KV_SCALE = 0.75f;
constexpr float KV_OFF = 6.f;
constexpr uint32_t KV_OFF2 = 0x46004600u;
constexpr uint32_t KV_NEG4 = 0xCE00CE00u;
constexpr uint32_t P_LIMIT = 0x78007800u;
constexpr float REF_UP = REFUP;
__device__ __forceinline__ uint32_t kvf(uint32_t a) {
    uint32_t r; asm("fma.rn.f16x2 %0, %1, %2, %3;\n" : "=r"(r) : "r"(a), "r"(pack_f16(KV_SCALE, KV_SCALE)), "r"(KV_OFF2)); return r;
}
enum { BAR_PP0 = 1, BAR_PP1 = 2, BAR_WG0 = 3, BAR_WG1 = 4, BAR_H0 = 5, BAR_H1 = 6, BAR_AUX = 7, BAR_BF = 8, BAR_H2 = 9, BAR_X = 10, BAR_GO = 11, BAR_WG2 = 12, BAR_ST = 13 };

struct Hot {
    const __nv_bfloat16 *wk, *wq, *x;
    Scratch* s;
};
struct Params {
    const __nv_bfloat16* deg_inv;
    const int *src, *dst;
    __nv_bfloat16* out;
    uint32_t dhi;
    int E;
    CUtensorMap tm_out;
    CUtensorMap tm_outc;
    CUtensorMap tm_w[3];
};
static_assert(offsetof(Params, tm_outc) == offsetof(Params, tm_out) + 128, "layout");
#define SC_PAIR (blockIdx.x < 104)
#define SC_TAIL (blockIdx.x >= NCTA - 2)
#define SC_LAST (blockIdx.x == NCTA - 1)
#define SC_HELP (SC_PAIR && rank)
#define SC_OWNER (!SC_HELP && !SC_LAST)
#define SC_QT1 (26 + (int)(blockIdx.x >> 1))
#define SC_QT0 (SC_PAIR ? (rank ? (int)(blockIdx.x >> 2) : SC_QT1) : SC_TAIL ? 78 : (int)blockIdx.x - 104)
#define SC_NKV (SC_LAST ? 50 : 75)
#define SC_CLS (SC_PAIR ? (rank ? 0x120 ^ (blockIdx.x & 2) * 0x80 : 0x430) | (blockIdx.x & 2) >> 1 : SC_LAST ? 0x10 : 0x432)
#define SC_NW (SC_PAIR ? 8 : SC_LAST ? 0 : 4)
#define SC_ZB (2 * SC_QT1 + 1 - (int)rank)
#define SC_TZB(k) (rank && !(k) ? 156 : 2 * (k) - (int)rank)

__global__ void __cluster_dims__(2, 1, 1) __launch_bounds__(384, 1) k_main(const __grid_constant__ Hot H, const __grid_constant__ Params P) {
    extern __shared__ __align__(1024) uint8_t smem[];
    const uint32_t sb = (uint32_t)__cvta_generic_to_shared(smem);
    const int tid = threadIdx.x, wg = __shfl_sync(~0u, tid >> 7, 0);
    const int lane = tid & 31, g = lane >> 2, q = lane & 3;
    const uint32_t rank = blockIdx.x & 1;
    const uint32_t bar_full = sb + SM_BAR, bar_q = bar_full + 32, bar_go = bar_full + 48;
    const uint32_t bar_pin = bar_full + 56;
    const uint32_t bar_qfree = bar_full + 72, bar_pdone = bar_full + 88, bar_zst = bar_full + 104, bar_rfree = bar_full + 120;
    const uint32_t bar_empty = bar_full + 128, bar_end = bar_full + 160, s_tm = bar_full + 184, bar_x = bar_full + 192;
    const uint32_t bar_a = sb + SM_ML;

    const int t = tid & 127, warp = __shfl_sync(~0u, t >> 5, 0);
    int ep = 0;
    if (wg & 2) {
        unsigned done;
        {
            uint4 ra[2], rb[2], rk[5][2];
            if (blockIdx.x < 128) {
                const int e = (blockIdx.x >> 4) * 32 + (g >> 1) * 8 + (blockIdx.x & 8) / 2 + (g & 1);
                const uint4* pq = (const uint4*)(H.wq + e * 256) + warp * 8 + q;
                const uint4* pk = (const uint4*)(H.wk + ((blockIdx.x & 7) * 32 + g) * 256) + warp * 8 + q;
                const uint4* pz = (const uint4*)(H.wk + 255 * 256) + warp * 8 + q;
#pragma unroll
                for (int s = 0; s < 2; s++) {
                    ra[s] = ldg_pinned(pq + 4 * s);
                    rb[s] = ldg_pinned(pq + 4 * s + 64);
#pragma unroll
                    for (int n = 0; n < 4; n++) rk[n][s] = ldg_pinned(pk + 4 * s + n * 256);
                    rk[4][s] = ldg_pinned(pz + 4 * s);
                }
            }
            asm volatile("{\n.reg .pred p;\nsetp.eq.s32 p, %2, 0;\nmov.u32 %0, 0;\n@p ld.global.cg.u32 %0, [%1];\n}\n" : "=r"(done) : "l"(&g_sync[SY_DONE * 32]), "r"(lane) : "memory");
            bar_arrive(BAR_X, 384);
            if (warp == 0 && elect()) {
#pragma unroll
                for (int i = 0; i < 21; i++) mbar_init(bar_full + 8 * i, i < 9 ? 1 : i < 16 ? 4 : i == 20 ? 11 : SC_TAIL ? 4 : 8);
#pragma unroll
                for (int i = 0; i < 4; i++) mbar_init(bar_a + 8 * i, 1);
                mbar_expect_tx(bar_pin, QB_BYTES / 2 + 512); mbar_expect_tx(bar_pin + 8, QB_BYTES / 2);
                asm volatile("fence.mbarrier_init.release.cluster;\n" ::: "memory");
            }
            __syncwarp();
            asm volatile("barrier.cluster.arrive.relaxed.aligned;\n" ::: "memory");
            if (blockIdx.x < 128) {
                float c[5][4] = {};
#pragma unroll
                for (int s = 0; s < 2; s++) {
#pragma unroll
                    for (int n = 0; n < 5; n++) mma16816(c[n], ra[s].x, rb[s].x, ra[s].y, rb[s].y, rk[n][s].x, rk[n][s].y);
#pragma unroll
                    for (int n = 0; n < 5; n++) mma16816(c[n], ra[s].z, rb[s].z, ra[s].w, rb[s].w, rk[n][s].z, rk[n][s].w);
                }
#pragma unroll
                for (int i = 0; i < 4; i++) {
                    const int r = i & 2, n = (i & 1) * 2;
                    sts128(sb + SM_KV + 3 * KV_BYTES + QB_BYTES + i * 2048 + t * 16, __float_as_uint(c[n][r] - c[4][r]), __float_as_uint(c[n][r + 1] - c[4][r]),
                           __float_as_uint(c[n + 1][r] - c[4][r]), __float_as_uint(c[n + 1][r + 1] - c[4][r]));
                }
            }
        }
        asm volatile("setmaxnreg.dec.sync.aligned.u32 %0;\n" ::"n"(REG_P));
        if (blockIdx.x < 128) {
            bar_sync(BAR_WG2, 128);
            float4 v[4];
#pragma unroll
            for (int i = 0; i < 4; i++) v[i] = lds128f(sb + SM_KV + 3 * KV_BYTES + QB_BYTES + (warp & 2) * 2048 + (lane & 1) * 2048 + i * 512 + ((warp & 1) * 16 + (lane >> 1)) * 16);
            constexpr float SC = SCALE_LOG2 / KV_SCALE;
            const int r = (warp & 1) * 4 + (lane >> 3);
            *(uint2*)(g_w + tile_off((blockIdx.x >> 3) * 16 + (warp & 2) * 4 + r, (blockIdx.x & 7) * 4 + ((lane >> 1) & 3)) + (lane & 1) * 8) =
                make_uint2(pack_f16_sat(((v[0].x + v[1].x) + (v[2].x + v[3].x)) * SC, ((v[0].y + v[1].y) + (v[2].y + v[3].y)) * SC) | 1,
                           pack_f16_sat(((v[0].z + v[1].z) + (v[2].z + v[3].z)) * SC, ((v[0].w + v[1].w) + (v[2].w + v[3].w)) * SC) | 1);
            if (warp != 1) {
                bar_arrive(BAR_AUX, 128);
            } else {
                bar_sync(BAR_AUX, 128);
                if (elect()) { red_add(&g_sync[SY_DONE * 32 + 4 + (blockIdx.x >> 5)]); }
                __syncwarp();
            }
        }
        else bar_sync(BAR_WG2, 128);
        if (warp == 1) bar_arrive(BAR_GO, 160);
        auto load_a = [&](int j) {
            if (elect()) {
                mbar_expect_tx(bar_a + 8 * j, QB_BYTES);
                bulk_g2s(sb + SM_KV + j * KV_BYTES, g_w + j * QB_BYTES, QB_BYTES, bar_a + 8 * j);
            }
            __syncwarp();
        };
        if (warp == 0) {
            auto poll = [&]() { int c; asm volatile("ld.relaxed.gpu.global.s32 %0, [%1];\n" : "=r"(c) : "l"(&g_sync[SY_DONE * 32 + 4 + (lane & 3)]) : "memory"); return c; };
#pragma unroll 1
            for (int j = 0; j < 4;) {
#pragma unroll 1
                for (const uint32_t mk = __ballot_sync(~0u, poll() >= 32) & 15; (mk >> j) & 1; j++) load_a(j);
            }
        } else if (warp & 1) {
#pragma unroll 1
            for (int j = 0, n = 0; j < 4;) {
                mbar_wait_bounded(bar_a + 8 * j, n & 1);
                uint32_t ok = 1;
#pragma unroll
                for (int i = 0; i < 16; i++) {
                    uint32_t v;
                    asm volatile("ld.shared.u32 %0, [%1];\n" : "=r"(v) : "r"(sb + SM_KV + j * KV_BYTES + (warp & 2) * 8192 + i * 1024 + lane * 32 + g * 4) : "memory");
                    ok &= v;
                }
                asm volatile("{\n.reg .pred p;\nsetp.ne.u32 p, %0, 0;\nbar.red.and.pred p, %1, 64, p;\nselp.u32 %0, 1, 0, p;\n}\n" : "+r"(ok) : "n"((int)BAR_WG2) : "memory");
                if (__any_sync(~0u, ok)) {
                    if (warp == 1 && elect()) asm volatile("mbarrier.arrive.shared::cta.b64 _, [%0];\nmbarrier.inval.shared::cta.b64 [%1];\n" ::"r"(bar_full + 8 * j), "r"(bar_a + 8 * j) : "memory");
                    __syncwarp();
                    j++; n = 0;
                } else {
                    asm volatile("{\n.reg .pred p;\nsetp.gt.s32 p, %0, 1000000;\n@p trap;\n}\n" ::"r"(++n) : "memory");
                    fence_async_smem();
                    if (warp == 1) load_a(j);
                }
            }
        }
        done = __shfl_sync(~0u, done, 0);
        ep = (int)(done / NCTA) + 1;
        asm volatile("barrier.cluster.wait.acquire.aligned;\n" ::: "memory");
        if (warp == 0) {
            asm volatile("st.shared.u64 [%0], %1;\n" ::"r"(s_tm), "l"(&P.tm_outc) : "memory");
            __syncwarp();
            if (elect()) {
                const uint8_t* base = (const uint8_t*)H.s;
                uint32_t cls = SC_CLS, bytes = KV_BYTES, step = 5 * KV_BYTES;
                const uint8_t* src = base;
                bool tick;
                int next = 0;
                const int nit = SC_NKV + SC_NW;
#pragma unroll 1
                for (int j = 0; j < nit; j++) {
                    const uint32_t slot = sb + SM_KV + (j & 3) * KV_BYTES, fb = bar_full + 8 * (j & 3);
                    if (j == next) {
                        const int k = j - SC_NKV;
                        const int sw = SC_HELP ? j - 25 : -1;
                        next = j + 1;
                        tick = j >= 3 && k < 0 && (sw | 1) != 3 && !SC_TAIL;
                        if (j >= 3 && (unsigned)sw >= 5) next = k >= 0 ? next : j < GO0 ? GO0 : j < 25 ? 25 : j < GO1 ? GO1 : j < 49 ? 49 : j < 50 ? 50 : 75;
                        if (j == 0 || j == 25 || j == 50) { src = base + (4096 + (cls & 15) * KV_BYTES); cls >>= 4; }
                        if (SC_TAIL ? j == nit - 1 : j == GO0 || j == GO1) mbar_arrive(bar_go);
                        int fo = -1, fv = 1;
                        if (j < 3) { fo = (SY_H0 + 5 * j + (SC_CLS & 15)) * 32; fv = 5; }
                        if (j == 3) { fo = SY_H1 * 32; fv = 79; }
                        if (sw == 1) fo = 25 * 32 + SC_QT1;
                        if (k == 0) fo = SY_B * 32;
                        if (k == 1 && !SC_PAIR) { fo = SY_AUX0 * 32; fv = NAUX; }
                        if (k == 2 && SC_PAIR) { fo = SY_AUX * 32; fv = NAUX / 3; }
                        if (fo >= 0) {
                            flag_wait(g_sync + fo, fv * ep);
                            fence_async_global();
                        }
                        if (sw == 2 || (k == 2 && !SC_TAIL)) {
                            uint32_t qs = sw == 2 ? offsetof(Scratch, q) + (2 * SC_QT1 + 1) * QB_BYTES : SC_PAIR ? offsetof(Scratch, agg) + SC_ZB * QB_BYTES : offsetof(Scratch, part) + SC_QT0 * (4 * PART_BYTES);
#pragma unroll 1
                            for (int w = 0; w < (k == 2 && SC_PAIR ? 1 : 2); w++) {
                                mbar_wait_sleep(bar_qfree + 8 * w, k == 2 && SC_HELP);
                                mbar_expect_tx(bar_q + 8 * w, SC_PAIR ? QB_BYTES : PART_BYTES);
                                if (!SC_PAIR) bulk_g2s(sb + SM_ML + w * 512, base + (qs + (w ? -512 : QB_BYTES)), 512, bar_q + 8 * w);
                                bulk_g2s(sb + SM_Q + w * QB_BYTES, base + qs, QB_BYTES, bar_q + 8 * w);
                                qs += sw == 2 ? -QB_BYTES : PART_BYTES + 512;
                            }
                        }
                        if ((sw | 1) == 3) {
                            mbar_wait_sleep(bar_pdone + 8 * (sw - 2), 0);
                            bulk_s2g(g_part + (blockIdx.x - 3 + sw) * PART_BYTES, slot, PART_BYTES);
                            asm volatile("cp.async.bulk.wait_group.read 0;\n" ::: "memory");
                        }
                        if (sw == 5) {
                            asm volatile("cp.async.bulk.wait_group 0;\n" ::: "memory");
                            red_release(&g_sync[SY_PART * 32]);
                        }
                        if (k == 0) {
                            asm volatile("prefetch.tensormap [%0];\n" ::"l"(&P.tm_outc) : "memory");
                            src = g_w + (12 - SC_NW) * QB_BYTES; bytes = step = QB_BYTES;
                        }
                        if (k == 2) next = SC_TAIL ? nit - 1 : nit;
                    }
                    mbar_wait_sleep(fb + (bar_empty - bar_full), (j >> 2) & 1);
                    mbar_expect_tx(fb, bytes);
                    if (tick)
                        asm volatile("{\n.reg .pred p;\n.reg .u32 a, b;\nmov.u32 a, %%globaltimer_lo;\nnot.b32 b, a;\nand.b32 b, b, %0;\nshr.u32 b, b, 1;\nnanosleep.u32 b;\n"
                                     "L:\nmov.u32 b, %%globaltimer_lo;\nxor.b32 b, b, a;\nsetp.le.u32 p, b, %0;\n@p nanosleep.u32 %1;\n@p bra L;\n}\n" ::"n"(TICK - 1), "n"(TSL) : "memory");
                    bulk_g2s(slot, src, bytes, fb);
                    src += step;
                }
            }
        } else {
            if (warp == 2 && SC_OWNER) {
                uint8_t* dst = g_hz + 4096 + h_unit(SC_QT0, 0) * 8192;
                auto send = [&](int u0, int u1) {
#pragma unroll
                    for (int u = u0; u < u1; u++) {
                        bulk_s2g(dst + u * (78 * 8192), sb + SM_Q + u * 8192, 8192);
                        asm volatile("cp.async.bulk.wait_group 0;\n" ::: "memory");
                    }
                };
                int* f0 = &g_sync[(SY_H0 + SC_QT0 / 5) * 32];
                bar_sync(BAR_H0, 64);
                if (elect()) {
                    send(0, 1);
                    if (SC_QT0 < 65) red_release(f0);
                }
                bar_sync(BAR_H1, 160);
                if (elect()) {
                    if (!SC_TAIL) send(1, 4);
                    mbar_arrive(bar_q);
                }
                bar_sync(BAR_H2, 160);
                if (elect()) {
                    if (!SC_TAIL) { send(4, 8); mbar_arrive(bar_q + 8); }
                    red_release(&g_sync[SY_H1 * 32]);
                }
                __syncwarp();
            }
        }
    } else {
        const uint32_t sq = sb + SM_Q + wg * QB_BYTES;
        const uint32_t qbar = bar_q + 8 * wg;
        const uint32_t dq0 = __shfl_sync(~0u, ((sq & 0x3FFFF) >> 4) | (64u << 16), 0);
        const uint32_t dk0 = __shfl_sync(~0u, (((sb + SM_KV) & 0x3FFFF) >> 4) | (64u << 16), 0);
        float o[128];
        int it = 4;
        const uint32_t dhi = P.dhi;
        auto release = [&](int st, int n = 1) {
            if (n == 1) asm volatile("{\n.reg .pred p;\nelect.sync _|p, -1;\n@p mbarrier.arrive.shared::cta.b64 _, [%0];\n}\n" ::"r"(bar_empty + 8 * st) : "memory");
            else asm volatile("{\n.reg .pred p;\nelect.sync _|p, -1;\n@p mbarrier.arrive.shared::cta.b64 _, [%0], 2;\n}\n" ::"r"(bar_empty + 8 * st) : "memory");
        };
        const bool active = !(SC_TAIL && wg == 1);
        auto pp_sync = [&]() { if (!SC_TAIL) bar_sync(BAR_PP0 + wg, 256); };
        auto pp_arrive = [&]() { if (!SC_TAIL) bar_arrive(BAR_PP1 - wg, 256); };
        auto warp_arrive = [&](uint32_t bar) {
            __syncwarp();
            asm volatile("{\n.reg .pred p;\nelect.sync _|p, -1;\n@p mbarrier.arrive.shared::cta.b64 _, [%0];\n}\n" ::"r"(bar + 8 * wg) : "memory");
        };
        auto peer_arrive = [&]() {
            asm volatile("{\n.reg .pred p;\n.reg .b32 a;\nelect.sync _|p, -1;\nmapa.shared::cluster.u32 a, %0, %1;\n"
                         "@p mbarrier.arrive.shared::cluster.b64 _, [a];\n}\n" ::"r"(bar_rfree), "r"(rank ^ 1) : "memory");
        };
        auto stage_q = [&]() {
            auto pk = [&](int i) { return QRND(pack_f16_sat(o[i], o[i + 1])); };
#pragma unroll
            for (int i = 0; i < 16; i++)
                stmatrix_x4(sq + warp * 8192 + tile_off(lane & 15, 2 * i + (lane >> 4)), pk(8 * i), pk(8 * i + 2), pk(8 * i + 4), pk(8 * i + 6));
        };
        float s[40];
        auto issue_qk = [&](int st, int sh = 24) {
            const uint64_t kb = mkaddr(dk0 + st * (KV_BYTES >> 4), dhi);
            const uint64_t qd = mkaddr(dq0 + ((uint32_t)it >> sh), dhi);
            wgmma_ss_n80_init(s, qd + 198, kb + 198);
#pragma unroll
            for (int kk = 0; kk < 15; kk++) wgmma_ss_n80(s, qd + ((kk >> 2) * 64 + (kk & 3) * 2), kb + ((kk >> 2) * 64 + (kk & 3) * 2));
            wg_commit();
        };

        {
            const int rb = (2 * SC_QT0 + wg) * 64 + warp * 16;
            const uint32_t xbar = bar_x + 32 * wg + 8 * warp;
            if (elect()) {
                mbar_init(xbar, 1);
                asm volatile("fence.mbarrier_init.release.cluster;\nfence.proxy.async.shared::cta;\n" ::: "memory");
                mbar_expect_tx(xbar, rb < NN ? 8192 : 0);
            }
            asm volatile("barrier.cluster.arrive.relaxed.aligned;\n" ::: "memory");
            if (wg == 1) pp_arrive();
            bar_sync(BAR_X, 384);
            if (wg == 1) bar_sync(BAR_GO, 160);
            if (rb < NN && elect()) bulk_g2s(sq + warp * 8192, H.x + (size_t)rb * 256, 8192, xbar);
            if (rb >= NN) {
#pragma unroll 1
                for (int i = 0; i < 16; i++) sts128(sq + warp * 8192 + i * 512 + lane * 16, 0, 0, 0, 0);
            }
            __syncwarp();
            mbar_wait(xbar, 0);
            uint4 xa[8], xb[8];
#pragma unroll
            for (int s = 0; s < 8; s++) {
                xa[s] = lds128(sq + (warp * 16 + g) * 512 + (4 * s + q) * 16);
                xb[s] = lds128(sq + (warp * 16 + g + 8) * 512 + (4 * s + q) * 16);
            }
            float sm[2][4], sq2[2][4][4];
#pragma unroll
            for (int i = 0; i < 4; i++) {
                sm[0][i] = sm[1][i] = 0.f;
#pragma unroll
                for (int k = 0; k < 4; k++) sq2[0][k][i] = sq2[1][k][i] = 0.f;
            }
#pragma unroll
            for (int s = 0; s < 8; s++) {
#pragma unroll
                for (int hh = 0; hh < 2; hh++) {
                    const uint4 v = hh ? xb[s] : xa[s];
                    mma16816(sm[hh], v.x, v.y, v.z, v.w, 0x3F803F80u, 0x3F803F80u);
                    mma1688(sq2[hh][0], v.x, v.y, v.x); mma1688(sq2[hh][1], v.x, v.y, v.y);
                    mma1688(sq2[hh][2], v.z, v.w, v.z); mma1688(sq2[hh][3], v.z, v.w, v.w);
                }
            }
            float inv[2], off[2];
#pragma unroll
            for (int hh = 0; hh < 2; hh++) {
                const float mean = (sm[hh][0] + sm[hh][2]) * (1.f / 256.f);
                const float d0 = (sq2[hh][0][0] + sq2[hh][2][0]) + (sq2[hh][1][2] + sq2[hh][3][2]);
                const float d1 = (sq2[hh][0][1] + sq2[hh][2][1]) + (sq2[hh][1][3] + sq2[hh][3][3]);
                const float ss = __shfl_sync(~0u, (g & 1) ? d1 : d0, g * 4 + (g >> 1));
                const float var = fmaxf(ss * (1.f / 256.f) - mean * mean, 0.f);
                float sd;
                asm("sqrt.approx.ftz.f32 %0, %1;\n" : "=f"(sd) : "f"(bf_round(bf_round(var) + 1e-5f)));
                asm("rcp.approx.ftz.f32 %0, %1;\n" : "=f"(inv[hh]) : "f"(bf_round(sd)));
                off[hh] = -mean * inv[hh];
            }
            uint32_t a[64];
#pragma unroll
            for (int s = 0; s < 8; s++) {
                a[8 * s] = xa[s].x; a[8 * s + 1] = xb[s].x; a[8 * s + 2] = xa[s].y; a[8 * s + 3] = xb[s].y;
                a[8 * s + 4] = xa[s].z; a[8 * s + 5] = xb[s].z; a[8 * s + 6] = xa[s].w; a[8 * s + 7] = xb[s].w;
            }
            fence_regs(a);
            if (wg == 1 && __any_sync(~0u, inv[0] + inv[1] != -1.f)) bar_arrive(BAR_ST, 256);
            asm volatile("setmaxnreg.inc.sync.aligned.u32 %0;\n" ::"n"(REG_C));
            fence_regs(a);
#pragma unroll
            for (int i = 0; i < 64; i++)
                a[i] = pack_f16(fmaf(bf_lo(a[i]), inv[i & 1], off[i & 1]), fmaf(bf_hi(a[i]), inv[i & 1], off[i & 1]));
            if (SC_OWNER) {
#pragma unroll
                for (int i = 0; i < 16; i++) {
                    const uint32_t mk = (i == 15 && q == 3) ? 0xFFFFu : ~0u;
                    stmatrix_x4(sq + warp * 8192 + tile_off(lane & 15, 2 * i + (lane >> 4)), kvf(a[4 * i]), kvf(a[4 * i + 1]),
                                kvf(a[4 * i + 2] & mk), kvf(a[4 * i + 3] & mk));
                }
                fence_async_smem();
                if (tid < 32) bar_arrive(BAR_H0, 64);
                bar_arrive(wg ? BAR_H2 : BAR_H1, 160);
            }
            asm volatile("barrier.cluster.wait.acquire.aligned;\n" ::: "memory");
            if (wg == 0) bar_sync(BAR_ST, 256);
            if (active) {
                fence_regs(a);
#pragma unroll
                for (int c = 0; c < 4; c++) {
                    if (c == 1) {
                        if (wg == 1) {
                            wg_wait<0>();
                            release(0);
                        }
                        pp_sync();
                    }
                    mbar_wait(bar_full + 8 * c, 0);
                    const uint64_t wb = mkaddr(dk0 + c * (KV_BYTES >> 4), dhi);
                    wg_fence();
#pragma unroll
                    for (int kk = 0; kk < 4; kk++) {
                        if (c | kk) wgmma_rs_n256_tb(o, a[16 * c + 4 * kk], a[16 * c + 4 * kk + 1], a[16 * c + 4 * kk + 2], a[16 * c + 4 * kk + 3], wb + kk * 512);
                        else wgmma_rs_n256_tb_init(o, a[0], a[1], a[2], a[3], wb);
                    }
                    wg_commit();
                    if (c > 0) { wg_wait<1>(); if (c > 1 || wg == 0) release(c - 1); }
                }
                if (wg == 0) pp_arrive();
                wg_wait<0>();
                fence_regs(o);
                release(3);
                if (SC_OWNER) mbar_wait(qbar, 0);
                stage_q();
                fence_async_smem();
                bar_sync(BAR_WG0 + wg, 128);
                mbar_wait(bar_full, 1);
                wg_fence();
                issue_qk(0);
                if (wg == 1) pp_arrive();
            } else {
                peer_arrive();
            }
        }

        uint32_t p[20];
        float m0 = 0.f, m1 = 0.f, e0, e1, l0, l1;
        uint32_t plim;
        uint32_t qphase = (SC_OWNER && active) ? 1 : 0;
        auto issue_pv = [&](int st, int acc) {
            const uint64_t vb = mkaddr(dk0 + st * (KV_BYTES >> 4), dhi);
            wgmma_rs_n256_tb_pred(o, p[0], p[1], p[2], p[3], vb, acc);
#pragma unroll
            for (int kk = 1; kk < 5; kk++)
                wgmma_rs_n256_tb(o, p[4 * kk], p[4 * kk + 1], p[4 * kk + 2], p[4 * kk + 3], vb + kk * 512);
            wg_commit();
        };
        const uint32_t mq_addr = sq + tile_off(warp * 16 + g, 31) + 14;
        auto exceeds = [&](const uint32_t (&p)[20]) {
            uint32_t a = __vimax3_s16x2(P_LIMIT, p[0], p[1]), b = __vimax3_s16x2(p[2], p[3], p[4]);
#pragma unroll
            for (int i = 5; i < 17; i += 4) { a = __vimax3_s16x2(a, p[i], p[i + 1]); b = __vimax3_s16x2(b, p[i + 2], p[i + 3]); }
            a = __vimax3_s16x2(a, p[17], p[18]);
            return __any_sync(~0u, __vimax3_s16x2(a, b, p[19]) != plim);
        };
        auto remax = [&](float& a, float& b, bool store) {
            float a1 = fmaxf(s[0], s[1]), b1 = fmaxf(s[2], s[3]), a2 = fmaxf(s[4], s[5]), b2 = fmaxf(s[6], s[7]);
#pragma unroll
            for (int i = 2; i < 10; i++) {
                a1 = fmaxf(a1, s[4 * i]); a2 = fmaxf(a2, s[4 * i + 1]);
                b1 = fmaxf(b1, s[4 * i + 2]); b2 = fmaxf(b2, s[4 * i + 3]);
            }
            a1 = fmaxf(a1, a2); b1 = fmaxf(b1, b2);
            a1 = fmaxf(a1, __shfl_xor_sync(~0u, a1, 1)); b1 = fmaxf(b1, __shfl_xor_sync(~0u, b1, 1));
            a1 = fmaxf(a1, __shfl_xor_sync(~0u, a1, 2)); b1 = fmaxf(b1, __shfl_xor_sync(~0u, b1, 2));
            a = fmaxf(a, a1 - e0 + REF_UP); b = fmaxf(b, b1 - e1 + REF_UP);
            const uint32_t u = pack_f16_sat((m0 + a) * (-1.f / KV_OFF), (m1 + b) * (-1.f / KV_OFF));
            const float g0 = (m0 + a) + KV_OFF * f16_lo(u), g1 = (m1 + b) + KV_OFF * f16_hi(u);
            const bool x0 = fabsf(g0) <= 1.f, x1 = fabsf(g1) <= 1.f;
            if (x0) a -= g0;
            if (x1) b -= g1;
            const float da = a + e0, db = b + e1;
            m0 += a; m1 += b;
            e0 = x0 ? 0.f : g0; e1 = x1 ? 0.f : g1;
            plim = (x0 && x1) ? P_LIMIT : 0u;
            asm volatile("{\n.reg .pred p;\nsetp.ne.s32 p, %3, 0;\n@p st.shared.u16 [%0], %1;\n@p st.shared.u16 [%0 + 4096], %2;\n}\n"
                         ::"r"(mq_addr), "h"((unsigned short)u), "h"((unsigned short)(u >> 16)), "r"((int)(store && q == 0)) : "memory");
#pragma unroll
            for (int i = 0; i < 10; i++) {
                p[2 * i] = pack_f16(ex2(s[4 * i] - da), ex2(s[4 * i + 1] - da));
                p[2 * i + 1] = pack_f16(ex2(s[4 * i + 2] - db), ex2(s[4 * i + 3] - db));
            }
            fence_regs(p);
            fence_async_smem();
            __syncwarp();
        };

        auto row_sums = [&](float& z0, float& z1) {
            z0 = quad_last(o[125]); z1 = quad_last(o[127]);
            l0 = z0 * (KV_SCALE / KV_OFF); l1 = z1 * (KV_SCALE / KV_OFF);
        };
        auto cut = [&]() { asm volatile("{\n.reg .pred p;\nsetp.lt.s32 p, %0, 0;\nL:\n@p pmevent 0;\n@p bra L;\n}\n" ::"r"(it) : "memory"); };
        auto stats = [&]() { return (q & 2) ? ((q & 1) ? l1 : m1) : ((q & 1) ? l0 : m0); };
        const int nseg = SC_HELP ? 2 : 1;
        if (active) {
#pragma unroll 1
        for (int seg = 0;; seg++) {
            wg_wait<0>();
            fence_regs(s);
            e0 = e1 = 0.f;
            const int it0 = it, itl = __shfl_sync(~0u, seg + 1 < nseg ? 3 + 25 : 3 + SC_NKV, 0);
            const int itx = (wg == 1 && seg + 1 == nseg) ? itl : -1;
            bool redo = true, have = !seg;
#pragma unroll 1
            for (;;) {
                if (!have) {
#pragma unroll
                    for (int i = 0; i < 20; i++) p[i] = pack_f16(ex2(s[2 * i]), ex2(s[2 * i + 1]));
                    redo = exceeds(p);
                }
                if (redo) {
                    float d0 = it != it0 ? 0.f : -INFINITY, d1 = d0;
                    remax(d0, d1, it != itl);
                    if (it != it0) {
                        const float a0 = ex2(-d0), a1 = ex2(-d1);
#pragma unroll
                        for (int i = 0; i < 32; i++) { o[4 * i] *= a0; o[4 * i + 1] *= a0; o[4 * i + 2] *= a1; o[4 * i + 3] *= a1; }
                    } else if (SC_OWNER) {
                        warp_arrive(bar_pdone);
                    }
                }
                if (it == itl) break;
                const int stp = it & 3;
                it++;
                pp_sync();
                fence_regs(o); fence_regs(p);
                have = SC_TAIL || it == itx;
                if (!have) {
                    wg_fence();
                    issue_pv(stp, it - 1 - it0);
                    mbar_wait(bar_full + 8 * (it & 3), (it >> 2) & 1);
                    wg_fence();
                    issue_qk(it & 3);
                    pp_arrive();
                    wg_wait<0>();
                    fence_regs(s); fence_regs(o); fence_regs(p);
                    if (it == itl) warp_arrive(bar_qfree);
                } else {
                    uint32_t p2[20];
                    const int zero = (uint32_t)it >> 23;
                    mbar_wait(bar_full + 8 * (it & 3), (it >> 2) & 1);
                    wg_fence();
                    issue_qk((it & 3) + zero, 25);
                    if (it == itl) {
                        wg_wait<0>();
                        if (SC_PAIR) peer_arrive(); else warp_arrive(bar_qfree);
                        if (wg) bar_sync(BAR_ST, 256);
                    }
                    wg_fence();
                    issue_pv(stp + zero, it - 1 - it0);
                    pp_arrive();
                    wg_wait<1>();
                    fence_regs(s);
#pragma unroll
                    for (int i = 0; i < 20; i++) p2[i] = pack_f16(ex2(s[2 * i]), ex2(s[2 * i + 1]));
                    redo = exceeds(p2);
                    if (redo) asm volatile("wgmma.wait_group.sync.aligned 0;\nnanosleep.u32 0;\n" ::: "memory");
                    else wg_wait<0>();
                    fence_regs(o); fence_regs(p);
#pragma unroll
                    for (int i = 0; i < 20; i++) p[i] = p2[i];
                }
                release(stp);
            }
            if (seg + 1 < nseg) pp_sync();
            fence_regs(o); fence_regs(p);
            wg_fence();
            issue_pv(it & 3, 1);
            asm volatile("{\n.reg .pred p;\nsetp.ne.s32 p, %0, 0;\n@p bar.arrive %1, 256;\n}\n" ::"r"((int)(seg + 1 == nseg && (wg ? SC_PAIR : !SC_TAIL))), "r"(BAR_ST + wg) : "memory");
            it++;
            if (seg + 1 == nseg) break;
            const int is = it - 2 + wg;
            uint32_t dst = sb + SM_KV + (is & 3) * KV_BYTES + wg * 512 + warp * 8192 + lane * 16;
            uint32_t dml = sb + SM_KV + (is & 3) * KV_BYTES + (wg ? 0 : QB_BYTES) + t * 4;
            asm volatile("" : "+r"(dst), "+r"(dml));
            mbar_wait(qbar, qphase); qphase ^= 1;
            unsigned short u0, u1;
            asm volatile("ld.shared.u16 %0, [%2];\nld.shared.u16 %1, [%2 + 4096];\n" : "=h"(u0), "=h"(u1) : "r"(mq_addr) : "memory");
            mbar_wait(bar_full + 8 * (it & 3), (it >> 2) & 1);
            mbar_wait(bar_empty + 8 * ((it - 2) & 3), ((it - 2) >> 2) & 1);
            wg_wait<0>();
            fence_regs(o);
            float z0, z1;
            row_sums(z0, z1);
            release((it - 1) & 3);
            wg_fence();
            issue_qk(it & 3);
            pp_arrive();
            bar_sync(BAR_WG0 + wg, 128);
#pragma unroll
            for (int i = 0; i < 128; i++) o[i] -= (i & 2) ? z1 : z0;
            fence_regs(o);
            cut();
            asm volatile("st.shared.f32 [%0], %1;\n" ::"r"(dml), "f"(stats()) : "memory");
            m0 = -KV_OFF * f16_lo(u0); m1 = -KV_OFF * f16_lo(u1);
            plim = fmaxf(fabsf(m0), fabsf(m1)) <= 3072.f ? P_LIMIT : 0u;
            uint32_t v[2][8] = {};
#pragma unroll
            for (int i = 0; i < 8; i++) {
                uint32_t *w = v[i & 1], *u = v[(i & 1) ^ 1];
#pragma unroll
                for (int j = 0; j < 8; j++) w[j] = pack_bf16(o[16 * i + 2 * j], o[16 * i + 2 * j + 1]);
                sts128(dst + i * 1024, w[0], w[1], w[2], w[3]);
                sts128(dst + i * 1024 + 512, w[4], w[5], w[6], w[7]);
                if (i) asm volatile("{\n.reg .pred p;\nsetp.lt.s32 p, %9, 0;\nL:\n@p st.shared.v4.u32 [%0], {%1, %2, %3, %4};\n@p st.shared.v4.u32 [%0 + 16], {%5, %6, %7, %8};\n@p bra L;\n}\n"
                             ::"r"(dst), "r"(u[0]), "r"(u[1]), "r"(u[2]), "r"(u[3]), "r"(u[4]), "r"(u[5]), "r"(u[6]), "r"(u[7]), "r"(it) : "memory");
            }
            fence_async_smem();
            warp_arrive(bar_pdone);
        }
        constexpr int IW = 4 + 75;
        uint32_t a[64];
        if (wg == 0 && (SC_PAIR || SC_LAST)) {
            uint32_t rq, rml, rbar;
            asm volatile("mapa.shared::cluster.u32 %0, %3, %6;\nmapa.shared::cluster.u32 %1, %4, %6;\nmapa.shared::cluster.u32 %2, %5, %6;\n"
                         : "=r"(rq), "=r"(rml), "=r"(rbar) : "r"(sb + SM_Q + QB_BYTES + warp * 8192 + lane * 16), "r"(sb + SM_ML + 512 + t * 4),
                         "r"(bar_pin), "r"(rank ^ 1));
            auto send = [&](int i) {
                asm volatile("st.async.weak.shared::cluster.mbarrier::complete_tx::bytes.v4.b32 [%0], {%1, %2, %3, %4}, [%5];\n"
                             ::"r"(rq + i * 512), "r"(a[4 * i]), "r"(a[4 * i + 1]), "r"(a[4 * i + 2]), "r"(a[4 * i + 3]), "r"(rbar + (i & 8)) : "memory");
            };
            mbar_wait(bar_rfree, 0);
            wg_wait<0>();
            fence_regs(o);
            release((it - 1) & 3);
            float z0, z1;
            row_sums(z0, z1);
            asm volatile("st.async.weak.shared::cluster.mbarrier::complete_tx::bytes.f32 [%0], %1, [%2];\n" ::"r"(rml), "f"(stats()), "r"(rbar) : "memory");
#pragma unroll
            for (int i = 0; i < 16; i++) {
                a[4 * i] = pack_bf16(o[8 * i] - z0, o[8 * i + 1] - z0); a[4 * i + 1] = pack_bf16(o[8 * i + 2] - z1, o[8 * i + 3] - z1);
                a[4 * i + 2] = pack_bf16(o[8 * i + 4] - z0, o[8 * i + 5] - z0); a[4 * i + 3] = pack_bf16(o[8 * i + 6] - z1, o[8 * i + 7] - z1);
                if (i * SND0 / 16 != (i + 1) * SND0 / 16) send(i * SND0 / 16);
                if (i % CUT2 == CUT2 - 1) cut();
            }
            if (SC_PAIR) {
                float z[128];
                const uint32_t dkz = dk0 + ((uint32_t)it >> 24), dqz = dq0 + ((uint32_t)it >> 24);
                auto gemm = [&](int c) {
                    mbar_wait(bar_full + 8 * ((IW + c) & 3), ((IW + c) >> 2) & 1);
                    const uint64_t wb = mkaddr(dkz + ((IW + c) & 3) * (KV_BYTES >> 4), dhi), ab = mkaddr(dqz + c * 64, dhi);
                    wg_fence();
#pragma unroll
                    for (int kk = 0; kk < 4; kk++) {
                        if (c | kk) wgmma_ss_n256_tb(z, ab + kk * 2, wb + kk * 512);
                        else wgmma_ss_n256_tb_init(z, ab, wb);
                    }
                    wg_commit();
                };
                mbar_wait(qbar, qphase);
                bar_sync(BAR_ST + 1, 256);
                gemm(0);
#pragma unroll
                for (int i = SND0; i < 16; i++) send(i);
#pragma unroll
                for (int c = 1; c < 4; c++) { gemm(c); if (c == 3) pp_arrive(); wg_wait<1>(); release((IW + c - 1) & 3, 2); }
                wg_wait<0>();
                fence_regs(z);
                release((IW + 3) & 3, 2);
#pragma unroll
                for (int i = 0; i < 16; i++) {
                    sts128(sq + warp * 8192 + lane * 16 + i * 512, pack_bf16(z[8 * i], z[8 * i + 1]), pack_bf16(z[8 * i + 2], z[8 * i + 3]),
                           pack_bf16(z[8 * i + 4], z[8 * i + 5]), pack_bf16(z[8 * i + 6], z[8 * i + 7]));
                    if (i == 3 || i == 15) bar_arrive(i == 3 ? BAR_BF : BAR_H0, 256);
                    if (i == 3) cut();
                }
            } else {
#pragma unroll
                for (int i = SND0; i < 16; i++) send(i);
            }
        } else {
            const int pair = SC_PAIR;
            const bool glob = !(pair || SC_TAIL);
            const uint32_t ml = sb + SM_ML + (t & ~3) * 4, src = (glob ? sq : sb + SM_Q + QB_BYTES) + warp * 8192 + lane * 16;
            const uint64_t tm = lds64(s_tm);
            wg_wait<0>();
            fence_regs(o);
            release((IW - 1) & 3);
            float c0, c1;
            row_sums(c0, c1);
            mbar_wait(glob ? qbar : bar_pin, glob ? qphase : 0);
            const float4 ps = lds128f(ml + (glob ? wg * 512 : 512));
            auto load = [&](int i) {
                asm volatile("ld.shared.v4.u32 {%0, %1, %2, %3}, [%4];\n" : "=r"(a[4 * i]), "=r"(a[4 * i + 1]), "=r"(a[4 * i + 2]), "=r"(a[4 * i + 3]) : "r"(src + i * 512) : "memory");
            };
#pragma unroll
            for (int i = 0; i < 8; i++) load(i);
            const float n0 = fmaxf(m0, ps.x), n1 = fmaxf(m1, ps.z);
            const float a0 = ex2(m0 - n0), a1 = ex2(m1 - n1), b0 = ex2(ps.x - n0), b1 = ex2(ps.z - n1);
            const float i0 = rcp(l0 * a0 + ps.y * b0), i1 = rcp(l1 * a1 + ps.w * b1);
            const float r0 = a0 * i0, r1 = a1 * i1;
            c0 *= -r0; c1 *= -r1;
            const uint32_t u0 = pack_bf16(b0 * i0, b0 * i0), u1 = pack_bf16(b1 * i1, b1 * i1);
#pragma unroll
            for (int i = 0; i < 32; i++) {
                if (i == 16) {
                    if (!glob) mbar_wait(bar_pin + 8, 0);
#pragma unroll
                    for (int j = 8; j < 16; j++) load(j);
                }
                a[2 * i] = hfma2(a[2 * i], u0, pack_bf16(fmaf(o[4 * i], r0, c0), fmaf(o[4 * i + 1], r0, c0)));
                a[2 * i + 1] = hfma2(a[2 * i + 1], u1, pack_bf16(fmaf(o[4 * i + 2], r1, c1), fmaf(o[4 * i + 3], r1, c1)));
            }
            float y[2][32];
            auto gemm = [&](int c, int kh) {
                if (!kh) mbar_wait(bar_full + 8 * ((IW + c) & 3), (((IW + c) >> 2) & 1) ^ pair);
                const uint64_t wb = mkaddr(dk0 + ((IW + c) & 3) * (KV_BYTES >> 4), dhi - 192);
                wg_fence();
#pragma unroll
                for (int kk = 8 * kh; kk < 8 * kh + 8; kk++) {
                    if (kk) wgmma_rs_n64_tb(y[c & 1], a[4 * kk], a[4 * kk + 1], a[4 * kk + 2], a[4 * kk + 3], wb + kk * 128);
                    else wgmma_rs_n64_tb_init(y[c & 1], a[0], a[1], a[2], a[3], wb);
                }
                wg_commit();
            };
            const uint32_t stg = sq + warp * 8192 + (lane & 15) * 128 + (((lane >> 4) ^ lane) & 7) * 16;
            uint4 z[4] = {};
            auto load_z = [&](int cb) {
                if (cb < 2) asm volatile("{\n.reg .pred p;\nsetp.ne.s32 p, %0, 0;\n@p bar.sync %1, 256;\n}\n" ::"r"(pair), "r"(cb ? BAR_H0 : BAR_BF) : "memory");
#pragma unroll
                for (int i = 0; i < 4; i++)
                    asm volatile("{\n.reg .pred p;\nsetp.ne.u32 p, %4, 0;\n@p ld.shared.v4.u32 {%0, %1, %2, %3}, [%5];\n}\n"
                                 : "+r"(z[i].x), "+r"(z[i].y), "+r"(z[i].z), "+r"(z[i].w) : "r"(pair), "r"(src - QB_BYTES + (4 * cb + i) * 512) : "memory");
            };
            pp_sync();
            gemm(0, 0);
            gemm(0, 1);
#pragma unroll
            for (int c = 0; c < 4; c++) {
                if (c) load_z(c);
                if (c < 3) gemm(c + 1, 0);
                if (!c) load_z(0);
                if (c < 3) wg_wait<1>(); else wg_wait<0>();
                fence_regs(y[c & 1]);
                const float* x = y[c & 1];
#pragma unroll
                for (int i = 0; i < 4; i++)
                    stmatrix_x4((stg ^ (32 * i)) + c * 2048, hadd2(pack_bf16(x[8 * i], x[8 * i + 1]), z[i].x), hadd2(pack_bf16(x[8 * i + 2], x[8 * i + 3]), z[i].y),
                                hadd2(pack_bf16(x[8 * i + 4], x[8 * i + 5]), z[i].z), hadd2(pack_bf16(x[8 * i + 6], x[8 * i + 7]), z[i].w));
                if (c < 3) gemm(c + 1, 1);
                fence_async_smem();
                __syncwarp();
                asm volatile("{\n.reg .pred p;\nelect.sync _|p, -1;\n"
                             "@p cp.reduce.async.bulk.tensor.4d.global.shared::cta.add.tile.bulk_group [%0, {0, 0, %1, %2}], [%3];\n}\n"
                             ::"l"(tm), "r"(c), "r"((pair ? SC_ZB : 2 * SC_QT0 + wg) * 8 + warp * 2), "r"(sq + warp * 8192 + c * 2048) : "memory");
                if (c == 2 && glob) pp_arrive();
            }
            asm volatile("cp.async.bulk.commit_group;\ncp.async.bulk.wait_group.read 0;\n" ::: "memory");
        }
        } else {
            wg_wait<0>();
        }
        if (SC_TAIL) {
        float o[128];
        auto emit = [&](uint32_t base, int lane, int row0, uint8_t* wdst, int turn) {
#pragma unroll
            for (int hh = 0; hh < 2; hh++) {
                if (turn > 0) mbar_wait(bar_zst + 8 * hh, (turn - 1) & 1);
#pragma unroll
                for (int i = 0; i < 8; i++)
                    stmatrix_x4(base + tile_off(8 * hh + (lane & 7), 4 * i + (lane >> 3)),
                                pack_bf16(o[16 * i + 2 * hh], o[16 * i + 2 * hh + 1]), pack_bf16(o[16 * i + 4 + 2 * hh], o[16 * i + 5 + 2 * hh]),
                                pack_bf16(o[16 * i + 8 + 2 * hh], o[16 * i + 9 + 2 * hh]), pack_bf16(o[16 * i + 12 + 2 * hh], o[16 * i + 13 + 2 * hh]));
                fence_async_smem();
                __syncwarp();
                if (wdst) {
                    if (lane < 4)
                        asm volatile("cp.async.bulk.global.shared::cta.bulk_group [%0], [%1], 1024;\n"
                                     ::"l"(wdst + ((turn & 1) ? hh * 4096 + lane * 1024 : hh * 1024 + lane * QB_BYTES)), "r"(base + hh * 4096 + lane * 1024) : "memory");
                    asm volatile("cp.async.bulk.commit_group;\n" ::: "memory");
                } else {
                    asm volatile("{\n.reg .pred p;\nsetp.eq.s32 p, %3, 0;\n"
                                 "@p cp.reduce.async.bulk.tensor.4d.global.shared::cta.add.tile.bulk_group [%0, {0, 0, 0, %1}], [%2];\n"
                                 "cp.async.bulk.commit_group;\n}\n"
                                 ::"l"(&P.tm_out), "r"((row0 >> 3) + hh), "r"(base + hh * 4096), "r"(lane) : "memory");
                }
            }
            asm volatile("cp.async.bulk.wait_group.read 1;\n" ::: "memory");
            warp_arrive(bar_zst - 8 * wg);
        };
        auto emit_done = [&](bool pending) {
            asm volatile("cp.async.bulk.wait_group.read 0;\n" ::: "memory");
            __syncwarp();
            asm volatile("{\n.reg .pred p;\nsetp.eq.s32 p, %1, 0;\n@p mbarrier.arrive.shared::cta.b64 _, [%0];\n}\n"
                         ::"r"(bar_zst + 8), "r"(pending ? lane : 1) : "memory");
        };
        if (!(rank | wg)) { release(0); release(1); release(2); release(3); }
        bar_sync(BAR_BF, 256);
        warp_arrive(bar_qfree);
        const int nf = rank ? 8 : 0;
        const int nz = nf + 26 + rank;
        const int itz = 4 + SC_NKV + SC_NW;
        bool pend = false;
#pragma unroll 1
        for (int k = wg; k < nz; k += 2) {
            const int iz = itz + (k < nf ? 0 : nf >> 1);
            mbar_wait(qbar, qphase); qphase ^= 1;
#pragma unroll 1
            for (int c = 0; c < 4; c++) {
                mbar_wait(bar_full + 8 * ((iz + c) & 3), ((iz + c) >> 2) & 1);
                const uint64_t wb = mkaddr(dk0 + ((iz + c) & 3) * (KV_BYTES >> 4), dhi), ab = mkaddr(dq0 + c * 64, dhi);
                wg_fence();
                wgmma_ss_n256_tb_pred(o, ab, wb, c);
#pragma unroll
                for (int kk = 1; kk < 4; kk++) wgmma_ss_n256_tb(o, ab + kk * 2, wb + kk * 512);
                wg_commit();
                emit_done(pend);
                pend = false;
            }
            wg_wait<0>();
            fence_regs(o);
            warp_arrive(bar_qfree);
            const int fb = ((k >> 1) + 3) & 3;
            if (k < nf) {
                float2* r255 = (float2*)H.s->r255 + wg * 128 + q;
                if (k < 2) {
                    if (t >= 124) {
#pragma unroll
                        for (int i = 0; i < 32; i++) r255[4 * i] = make_float2(o[4 * i + 2], o[4 * i + 3]);
                    }
                    bar_sync(BAR_WG0 + wg, 128);
                }
#pragma unroll
                for (int i = 0; i < 32; i++) {
                    const float2 v = __ldcg(r255 + 4 * i);
                    o[4 * i] -= v.x; o[4 * i + 1] -= v.y; o[4 * i + 2] -= v.x; o[4 * i + 3] -= v.y;
                }
            }
            int ln = lane;
            asm volatile("" : "+r"(ln));
            emit(sb + SM_KV + QB_BYTES + warp * KV_BYTES, ln, SC_TZB(k - nf) * 64 + warp * 16,
                 k >= nf ? nullptr : (k & 1) ? g_w + (4 + fb) * QB_BYTES + warp * 8192 : g_w + 8 * QB_BYTES + fb * 8192 + warp * 2048, k);
            pend = k + 2 < nz && (k | 1) != nf - 1;
            if (!pend) emit_done(true);
            if ((k | 1) == nf - 1) {
                asm volatile("cp.async.bulk.wait_group 0;\nfence.proxy.async.global;\nfence.acq_rel.gpu;\n" ::: "memory");
                bar_sync(BAR_BF, 256);
                if (tid == 0) red_release(&g_sync[SY_B * 32]);
                if (wg == 0) { release(0); release(1); release(2); release(3); }
            }
        }
        }
        if (wg == 0) pp_sync();
        warp_arrive(bar_end - 8 * wg);
        asm volatile("barrier.cluster.arrive.relaxed.aligned;\n" ::: "memory");
        if (P.E >= 0) return;
        asm volatile("setmaxnreg.dec.sync.aligned.u32 %0;\n" ::"n"(REG_P));
    }
    {
        if (warp != 0) {
            if (warp == 3 && SC_OWNER && SC_PAIR && elect()) {
                flag_wait_bounded(&g_sync[SY_H1 * 32], 79 * ep);
                mbar_wait_sleep(bar_pdone, 0);
                mbar_wait_sleep(bar_pdone + 8, 0);
#pragma unroll 1
                for (int u = 0; u < 16; u++) {
                    bulk_s2g(g_q + SC_QT0 * (2 * QB_BYTES) + u * 4096, sb + SM_Q + u * 4096, 4096);
                    asm volatile("cp.async.bulk.wait_group 0;\n" ::: "memory");
                }
                fence_async_global();
                st_release(&g_qflag[SC_QT0], ep);
            }
            __syncwarp();
            if (SC_TAIL) {
                bar_sync(BAR_AUX, 96);
                if (warp == 1 && elect()) red_release(&g_sync[SY_CSR * 32]);
                __syncwarp();
            }
            mbar_wait_bounded(bar_go, 0);
            if (SC_TAIL) {
                if (warp == 1 && elect()) red_add(&g_sync[SY_DONE * 32]);
                if (warp == 3 && elect()) {
                    int it = 4 + SC_NKV + SC_NW;
                    asm volatile("prefetch.tensormap [%0];\n" ::"l"(&P.tm_out) : "memory");
                    if (rank) {
#pragma unroll 1
                        for (int j = 0; j < 4; j++, it++) {
                            mbar_wait_sleep(bar_empty + 8 * (it & 3), ((it >> 2) & 1) ^ 1);
                            mbar_expect_tx(bar_full + 8 * (it & 3), QB_BYTES);
                            tma_g2s(sb + SM_KV + (it & 3) * KV_BYTES, &P.tm_w[2], 8 * j, bar_full + 8 * (it & 3));
                        }
#pragma unroll 1
                        for (int k = 0; k < 8; k++) {
                            mbar_wait_sleep(bar_qfree + 8 * (k & 1), ((k >> 1) ^ (k & 1) ^ 1) & 1);
                            mbar_expect_tx(bar_q + 8 * (k & 1), QB_BYTES);
#pragma unroll 1
                            for (int hf = 0; hf < 2; hf++)
                                asm volatile("cp.async.bulk.tensor.5d.shared::cluster.global.tile.mbarrier::complete_tx::bytes [%0], [%1, {0, 0, %2, 0, 0}], [%3];\n"
                                             ::"r"(sb + SM_Q + (k & 1) * QB_BYTES + hf * 16384), "l"(&P.tm_w[k & 1]),
                                             "r"(8 * (((k >> 1) + 3) & 3) + 4 * hf), "r"(bar_q + 8 * (k & 1)) : "memory");
                        }
                        flag_wait_bounded(&g_sync[SY_B * 32], ep);
                        fence_async_global();
                    }
#pragma unroll 1
                    for (int j = 0; j < 4; j++, it++) {
                        mbar_wait_sleep(bar_empty + 8 * (it & 3), ((it >> 2) & 1) ^ 1);
                        mbar_expect_tx(bar_full + 8 * (it & 3), QB_BYTES);
                        bulk_g2s(sb + SM_KV + (it & 3) * KV_BYTES, g_w + (4 + j) * QB_BYTES, QB_BYTES, bar_full + 8 * (it & 3));
                    }
#pragma unroll 1
                    for (int k = 0; k < 26 + rank; k++) {
                        if (k == 0 || k == ((GF0 + 1) * NAUX - 16) / 128) { flag_wait_bounded(&g_sync[(k ? SY_AUX1 : SY_AUX0) * 32], NAUX * ep); fence_async_global(); }
                        mbar_wait_sleep(bar_qfree + 8 * (k & 1), ((k >> 1) ^ (k & 1) ^ 1) & 1);
                        mbar_expect_tx(bar_q + 8 * (k & 1), QB_BYTES);
                        bulk_g2s(sb + SM_Q + (k & 1) * QB_BYTES, g_agg + SC_TZB(k) * QB_BYTES, QB_BYTES, bar_q + 8 * (k & 1));
                    }
                }
            } else {
            const int par = ep & 1;
            if (blockIdx.x == 0 && t == 32) g_ovf_n[par ^ 1] = 0;
            if (blockIdx.x == 0 && warp == 1) *(uint4*)(g_hz + (lane >> 3) * 1024 + (lane & 7) * 16) = make_uint4(KV_OFF2, KV_OFF2, KV_OFF2, KV_OFF2);
            const uint32_t wlo = (uint32_t)(uintptr_t)H.s, whi = (uint32_t)((uintptr_t)H.s >> 32);
            const uint32_t blo = wlo + (uint32_t)offsetof(Scratch, bucket);
            {
                const int* pd = P.dst + blockIdx.x * 96 + (t - 32);
                const int* ps = P.src + blockIdx.x * 96 + (t - 32);
#pragma unroll 1
                for (int e = P.E - (blockIdx.x * 96 + (t - 32)); e > 0; e -= CSRU * NAUX * 32, pd += CSRU * NAUX * 32, ps += CSRU * NAUX * 32) {
                    int d[CSRU], sr[CSRU], sl[CSRU];
#pragma unroll
                    for (int i = 0; i < CSRU; i++) {
                        d[i] = e > i * NAUX * 32 ? __ldg(pd + i * NAUX * 32) : NN;
                        sr[i] = e > i * NAUX * 32 ? __ldg(ps + i * NAUX * 32) : 0;
                    }
#pragma unroll
                    for (int i = 0; i < CSRU; i++) {
                        sl[i] = 0;
                        asm volatile("{\n.reg .pred p;\nsetp.lt.s32 p, %2, %3;\n@p atom.relaxed.gpu.global.add.s32 %0, [%1], 1;\n}\n"
                                     : "+r"(sl[i]) : "l"(mkaddr(wlo + (uint32_t)offsetof(Scratch, cnt) + d[i] * 4, whi)), "r"(d[i]), "n"(NN) : "memory");
                    }
                    uint32_t ov = 0;
#pragma unroll
                    for (int i = 0; i < CSRU; i++) {
                        asm volatile("{\n.reg .pred p;\nsetp.lt.s32 p, %3, %4;\n@p st.global.u16 [%1], %2;\n@!p or.b32 %0, %0, %5;\n}\n"
                                     : "+r"(ov) : "l"(mkaddr(blo + d[i] * 128 + (sl[i] & 31) * 4 + (sl[i] >> 5) * 2, whi)), "h"((unsigned short)sr[i]), "r"(sl[i]), "n"(CAP), "r"(1 << i) : "memory");
                    }
#pragma unroll 1
                    for (; ov; ov &= ov - 1) {
                        const int i = (__ffs(ov) - 1) * (NAUX * 32);
                        int at;
                        asm volatile("atom.relaxed.gpu.global.add.s32 %0, [%1], 1;\n" : "=r"(at) : "l"(&g_ovf_n[par]) : "memory");
                        g_ovf[at] = make_int2(__ldg(pd + i), __ldg(ps + i));
                    }
                }
            }
            bar_sync(BAR_AUX, 96);
            if (warp == 1 && elect()) { red_release(&g_sync[SY_CSR * 32]); }
            __syncwarp();
            {
                const int r0 = blockIdx.x * 3 + warp - 1;
                const uint4* xp = (const uint4*)(H.x + r0 * 256) + lane;
                uint4* op = (uint4*)(P.out + r0 * 256) + lane;
#pragma unroll 1
                for (int r = r0; r < NN; r += CPYU * NAUX, xp += CPYU * NAUX * 32, op += CPYU * NAUX * 32) {
                    uint4 v[CPYU];
#pragma unroll
                    for (int i = 0; i < CPYU; i++) if (r + i * NAUX < NN) v[i] = ldg_pinned(xp + i * NAUX * 32);
#pragma unroll
                    for (int i = 0; i < CPYU; i++) if (r + i * NAUX < NN) op[i * NAUX * 32] = v[i];
                }
            }
            mbar_wait_bounded(bar_go, 1);
            if (const int un = (3 - warp) * (NAUX / 3) + (NAUX / 3 - 1) - blockIdx.x; un < 208) {
                flag_wait_bounded(&g_sync[SY_PART * 32], 52 * ep);
                uint8_t* pp = g_part + (un >> 3) * (4 * PART_BYTES);
                float* ml = (float*)(pp + QB_BYTES) + (un & 7) * 32;
                const float4 sa = __ldcg((const float4*)ml + g), sc = __ldcg((const float4*)ml + g + 2 * PART_BYTES / 16);
                const float n0 = fmaxf(sa.x, sc.x), n1 = fmaxf(sa.z, sc.z);
                const uint32_t a0 = pack_bf16(ex2(sa.x - n0), ex2(sa.x - n0)), a1 = pack_bf16(ex2(sa.z - n1), ex2(sa.z - n1));
                const uint32_t b0 = pack_bf16(ex2(sc.x - n0), ex2(sc.x - n0)), b1 = pack_bf16(ex2(sc.z - n1), ex2(sc.z - n1));
                __syncwarp();
                if (q == 0) ((float4*)ml)[g] = make_float4(n0, sa.y * bf_hi(a0) + sc.y * bf_hi(b0), n1, sa.w * bf_hi(a1) + sc.w * bf_hi(b1));
                uint4* d = (uint4*)(pp + (un & 4) * 256 + (un & 7) * 8192) + lane;
#pragma unroll 1
                for (int i = 0; i < 4; i++, d += 128) {
                    uint4 u[4], v[4];
#pragma unroll
                    for (int j = 0; j < 4; j++) { u[j] = __ldcg(d + j * 32); v[j] = __ldcg(d + j * 32 + 2 * PART_BYTES / 16); }
#pragma unroll
                    for (int j = 0; j < 4; j++)
                        d[j * 32] = make_uint4(hfma2(v[j].x, b0, hmul2(u[j].x, a0)), hfma2(v[j].y, b1, hmul2(u[j].y, a1)),
                                               hfma2(v[j].z, b0, hmul2(u[j].z, a0)), hfma2(v[j].w, b1, hmul2(u[j].w, a1)));
                }
            }
            flag_wait_bounded(&g_sync[SY_CSR * 32], NCTA * ep);
            if (warp == 2 && blockIdx.x < 129) {
                uint4* z = blockIdx.x < 128 ? (uint4*)(g_w + blockIdx.x * 1024) + lane : (uint4*)&g_sync[SY_DONE * 32 + 4];
                z[0] = make_uint4(0, 0, 0, 0);
                if (blockIdx.x < 128) z[32] = make_uint4(0, 0, 0, 0);
            }
            {
                const uint32_t lc = (lane >> 3) * 1024 + (lane & 7) * 16;
                const uint32_t alo = wlo ^ lc;
                const int node0 = blockIdx.x * 3 + warp - 17;
                auto node = [&](int i) { const int nd = node0 + i * NAUX; return (int)min((unsigned)nd, (unsigned)(nd + NN)); };
                const int num = (NN - 17 - node0) / NAUX + 1;
                uint32_t mine = 0;
                if (lane < num) {
                    mine = min(__ldcg(&g_cnt[node(lane)]), CAP + 1) | (uint32_t)__ldg((const unsigned short*)P.deg_inv + node(lane)) << 16;
                    g_cnt[node(lane)] = 0;
                }
                auto row = [&](int off) {
                    uint4 v;
                    asm volatile("ld.global.v4.u32 {%0, %1, %2, %3}, [%4];\n"
                                 : "=r"(v.x), "=r"(v.y), "=r"(v.z), "=r"(v.w) : "l"(mkaddr(alo ^ off, whi)));
                    return v;
                };
                auto ents = [&](int i) {
                    uint32_t e;
                    asm volatile("ld.global.cg.u32 %0, [%1];\n" : "=r"(e) : "l"(mkaddr(blo + (min(node(i), NN - 1) * 32 + lane) * 4, whi)));
                    return e;
                };
                auto store = [&](int i, const float (&a)[8]) {
                    const float di = bf_hi(__shfl_sync(~0u, mine, i)) * (1.f / KV_SCALE);
                    const int nd = node(i);
                    *(uint4*)(g_agg + (uint32_t)(((nd >> 3) * 4096 + (nd & 7) * 144) ^ lc)) =
                        make_uint4(pack_bf16(a[0] * di, a[1] * di), pack_bf16(a[2] * di, a[3] * di), pack_bf16(a[4] * di, a[5] * di), pack_bf16(a[6] * di, a[7] * di));
                };
#pragma unroll 1
                for (uint32_t big = __ballot_sync(~0u, (mine & 0xFFFF) > CAP); big; big &= big - 1) {
                    const int i = __ffs(big) - 1, no = __ldcg(&g_ovf_n[par]);
                    float a[8] = {};
#pragma unroll 1
                    for (int k = -64; k < no; k += 32) {
                        const int2 pr = k < 0 ? make_int2(node(i), (ents(i) >> (k & 32) / 2) & 0xFFFF) : k + lane < no ? __ldcg(&g_ovf[k + lane]) : make_int2(-1, 0);
#pragma unroll 1
                        for (uint32_t mk = __ballot_sync(~0u, pr.x == node(i)); mk; mk &= mk - 1) {
                            const uint4 v = row(row_off(__shfl_sync(~0u, pr.y, __ffs(mk) - 1)));
                            a[0] += f16_lo(v.x) - KV_OFF; a[1] += f16_hi(v.x) - KV_OFF; a[2] += f16_lo(v.y) - KV_OFF; a[3] += f16_hi(v.y) - KV_OFF;
                            a[4] += f16_lo(v.z) - KV_OFF; a[5] += f16_hi(v.z) - KV_OFF; a[6] += f16_lo(v.w) - KV_OFF; a[7] += f16_hi(v.w) - KV_OFF;
                        }
                    }
                    store(i, a);
                }
                auto add4 = [&](const uint4& a, const uint4& b) { return make_uint4(hadd2_f16(a.x, b.x), hadd2_f16(a.y, b.y), hadd2_f16(a.z, b.z), hadd2_f16(a.w, b.w)); };
                int ni = -1, left = 0, pos = 0, ec = 0;
                uint32_t en = ents(0);
                uint4 acc = make_uint4(0, 0, 0, 0);
                auto step = [&](uint4 (&v)[4], int& tag) {
                    if (left <= 0 || pos == 32) {
                        if (left > 0) {
                            en = ents(ni) >> 16;
                        } else {
                            ni++;
                            left = __shfl_sync(~0u, mine, ni) & 0xFFFF;
                            if (left > CAP) left = 0;
                        }
                        ec = lane < left ? row_off(en & 0xFFFF) : 0;
                        en = ents(ni + 1);
                        pos = 0;
                    }
                    int of[4];
#pragma unroll
                    for (int j = 0; j < 4; j++) asm volatile("shfl.sync.idx.b32 %0, %1, %2, 31, -1;\n" : "=r"(of[j]) : "r"(ec), "r"(pos + j));
                    acc = add4(acc, add4(add4(add4(v[0], v[1]), make_uint4(KV_NEG4, KV_NEG4, KV_NEG4, KV_NEG4)), add4(v[2], v[3])));
                    asm volatile("" : "+r"(acc.x), "+r"(acc.y), "+r"(acc.z), "+r"(acc.w));
                    asm volatile("{\n.reg .pred p;\nsetp.lt.s32 p, %0, 0;\nL:\n@p pmevent 0;\n@p bra L;\n}\n" ::"r"(ni) : "memory");
#pragma unroll
                    for (int j = 0; j < 4; j++) v[j] = row(of[j]);
                    pos += 4; left -= 4;
                    const int i = tag;
                    tag = left <= 0 ? ni : -1;
                    if (i >= 0) {
                        const float a[8] = {f16_lo(acc.x), f16_hi(acc.x), f16_lo(acc.y), f16_hi(acc.y), f16_lo(acc.z), f16_hi(acc.z), f16_lo(acc.w), f16_hi(acc.w)};
                        if ((__shfl_sync(~0u, mine, i) & 0xFFFF) <= CAP) store(i, a);
                        acc = make_uint4(0, 0, 0, 0);
                        if (i == GF0 || i == 8) {
                            __syncwarp();
                            if (elect()) red_release(&g_sync[(i == 8 ? SY_AUX1 : SY_AUX0) * 32]);
                            __syncwarp();
                        }
                    }
                    return i == num - 1;
                };
                uint4 va[4], vb[4];
#pragma unroll
                for (int j = 0; j < 4; j++) va[j] = vb[j] = make_uint4(KV_OFF2, KV_OFF2, KV_OFF2, KV_OFF2);
                int ta = -1, tb = -1;
#pragma unroll 1
                while (!step(va, ta) && !step(vb, tb)) {}
            }
            bar_sync(BAR_AUX, 96);
            if (warp == 1 && elect()) {
                red_release(&g_sync[SY_AUX * 32]);
                red_add(&g_sync[SY_DONE * 32]);
            }
            }
        }
        __syncwarp();
        asm volatile("barrier.cluster.arrive.relaxed.aligned;\n" ::: "memory");
        if (warp == 1) mbar_wait_bounded(bar_end, 0);
        else if (elect()) mbar_arrive(bar_end);
        __syncwarp();
        asm volatile("barrier.cluster.wait.acquire.aligned;\n" ::: "memory");
    }
}

}

extern "C" void kernel_launch(void* const* d_in, const int* in_sizes, int n_in, void* d_out, int out_size) {
    Hot H;
    Params P;
    H.x = (const __nv_bfloat16*)d_in[0];
    P.src = (const int*)d_in[1];
    P.dst = (const int*)d_in[2];
    P.deg_inv = (const __nv_bfloat16*)d_in[3];
    H.wq = (const __nv_bfloat16*)d_in[5];
    H.wk = (const __nv_bfloat16*)d_in[6];
    P.out = (__nv_bfloat16*)d_out;
    typedef CUresult (*EncodeFn)(CUtensorMap*, CUtensorMapDataType, cuuint32_t, void*, const cuuint64_t*, const cuuint64_t*, const cuuint32_t*,
                                 const cuuint32_t*, CUtensorMapInterleave, CUtensorMapSwizzle, CUtensorMapL2promotion, CUtensorMapFloatOOBfill);
    void* fn = nullptr;
    cudaDriverEntryPointQueryResult qr;
    cudaGetDriverEntryPoint("cuTensorMapEncodeTiled", &fn, cudaEnableDefault, &qr);
    auto encode = [&](CUtensorMap* tm, const void* ptr, int rows, int box_rows, int box_cb = 4) {
        const cuuint64_t dims[4] = {64, 8, 4, (cuuint64_t)rows / 8};
        const cuuint64_t strides[3] = {512, 128, 4096};
        const cuuint32_t box[4] = {64, 8, (cuuint32_t)box_cb, (cuuint32_t)box_rows / 8}, es[4] = {1, 1, 1, 1};
        ((EncodeFn)fn)(tm, CU_TENSOR_MAP_DATA_TYPE_BFLOAT16, 4, (void*)ptr, dims, strides, box, es, CU_TENSOR_MAP_INTERLEAVE_NONE,
                       CU_TENSOR_MAP_SWIZZLE_128B, CU_TENSOR_MAP_L2_PROMOTION_NONE, CU_TENSOR_MAP_FLOAT_OOB_FILL_NONE);
    };
    encode(&P.tm_out, d_out, NN, 8);
    encode(&P.tm_outc, d_out, NN, 16, 1);
    for (int i = 0; i < 2; i++) {
        const cuuint64_t dims[5] = {64, 2, 32, 4, 4};
        const cuuint64_t strides[4] = {512, 4096, 128, 1024};
        const cuuint32_t box[5] = {64, 2, 4, 4, 4}, es[5] = {1, 1, 1, 1, 1};
        ((EncodeFn)fn)(&P.tm_w[i], CU_TENSOR_MAP_DATA_TYPE_BFLOAT16, 5, d_in[i ? 4 : 7], dims, strides, box, es, CU_TENSOR_MAP_INTERLEAVE_NONE,
                       CU_TENSOR_MAP_SWIZZLE_128B, CU_TENSOR_MAP_L2_PROMOTION_NONE, CU_TENSOR_MAP_FLOAT_OOB_FILL_NONE);
    }
    encode(&P.tm_w[2], d_in[8], 256, 64);
    void* raw = nullptr;
    cudaGetSymbolAddress(&raw, g_raw);
    H.s = (Scratch*)(((uintptr_t)raw + ((8 << 20) - 1)) & ~(uintptr_t)((8 << 20) - 1));
    P.dhi = 0x40000100u;
    P.E = in_sizes[1] < MAXE ? in_sizes[1] : MAXE;
    cudaFuncSetAttribute(k_main, cudaFuncAttributeMaxDynamicSharedMemorySize, SM_TOTAL);
    k_main<<<NCTA, 384, SM_TOTAL>>>(H, P);
}
```

```cpp
#include <cuda_runtime.h>
#include <cuda.h>
#include <cuda_bf16.h>
#include <stdint.h>
#include <stddef.h>

namespace {

constexpr int NN = 10000;
constexpr int BN = 80;
constexpr int NKV = NN / BN;
constexpr int NQB = 158;
constexpr int NCTA = 132;
constexpr int NAUX = 3 * (NCTA - 2);
constexpr int STAGES = 4;
constexpr int KV_BYTES = BN * 512;
constexpr int QB_BYTES = 64 * 512;
constexpr int PART_BYTES = QB_BYTES + 512;
constexpr int CAP = 64;
constexpr int MAXE = 160000;

#define QRND(v) (((v) + 0x00040004u) & 0xFFF8FFF8u)
#define GO0 5
#define GO1 40
#define GF0 2
#define CSRU 3
#define CPYU 9
#define REFUP 2.f
#define SND0 10
#define CUT2 2
#define TICK 1024
#define TSL 30
#define NQR 5
#define QSTEP 3
#define QREG(kk) ((kk) % QSTEP == 1 % QSTEP && (kk) > 0 && ((kk) - 1) / QSTEP < NQR ? ((kk) - 1) / QSTEP : -1)
#define REG_C 224
#define REG_P 56

enum { SY_PART = 4, SY_H1 = 5, SY_CSR = 6, SY_AUX = 7, SY_DONE = 8, SY_AUX0 = 9, SY_B = 10, SY_AUX1 = 11, SY_H0 = 12 };
struct Scratch {
    uint8_t hz[4096 + NN * 512];
    uint8_t w[12 * QB_BYTES];
    int sync[25 * 32];
    int qflag[96];
    int ovf_n[32];
    float r255[512];
    int cnt[NN + 16];
    int bucket[(NN + 1) * 32];
    int2 ovf[MAXE];
    uint8_t q[NQB * QB_BYTES];
    uint8_t agg[NQB * QB_BYTES];
    uint8_t part[52 * 2 * PART_BYTES];
};
static_assert(offsetof(Scratch, ovf) <= (8 << 20), "window");
static_assert(offsetof(Scratch, qflag) == offsetof(Scratch, sync) + 25 * 128, "flags");
static_assert(offsetof(Scratch, w) % 1024 == 0 && offsetof(Scratch, sync) % 128 == 0 &&
              offsetof(Scratch, bucket) % 128 == 0 && offsetof(Scratch, q) % 128 == 0, "alignment");
__device__ uint8_t g_raw[(8 << 20) + sizeof(Scratch)];
#define g_hz (H.s->hz)
#define g_w (H.s->w)
#define g_sync (H.s->sync)
#define g_qflag (H.s->qflag)
#define g_ovf_n (H.s->ovf_n)
#define g_cnt (H.s->cnt)
#define g_bucket (H.s->bucket)
#define g_ovf (H.s->ovf)
#define g_q (H.s->q)
#define g_agg (H.s->agg)
#define g_part (H.s->part)

__device__ __forceinline__ void wgmma_ss_n80(uint32_t (&d)[20], uint64_t da, uint64_t db) {
    asm volatile("wgmma.mma_async.sync.aligned.m64n80k16.f16.f16.f16 {"
        "%0, %1, %2, %3, %4, %5, %6, %7, %8, %9, %10, %11, %12, %13, %14, %15, %16, %17, %18, %19}, %20, %21, 1, 1, 1, 0, 0;\n"
        : "+r"(d[0]), "+r"(d[1]), "+r"(d[2]), "+r"(d[3]), "+r"(d[4]), "+r"(d[5]), "+r"(d[6]), "+r"(d[7]),
          "+r"(d[8]), "+r"(d[9]), "+r"(d[10]), "+r"(d[11]), "+r"(d[12]), "+r"(d[13]), "+r"(d[14]), "+r"(d[15]),
          "+r"(d[16]), "+r"(d[17]), "+r"(d[18]), "+r"(d[19])
        : "l"(da), "l"(db));
}
__device__ __forceinline__ void wgmma_ss_n80_init(uint32_t (&d)[20], uint64_t da, uint64_t db) {
    asm volatile("wgmma.mma_async.sync.aligned.m64n80k16.f16.f16.f16 {"
        "%0, %1, %2, %3, %4, %5, %6, %7, %8, %9, %10, %11, %12, %13, %14, %15, %16, %17, %18, %19}, %20, %21, 0, 1, 1, 0, 0;\n"
        : "=r"(d[0]), "=r"(d[1]), "=r"(d[2]), "=r"(d[3]), "=r"(d[4]), "=r"(d[5]), "=r"(d[6]), "=r"(d[7]),
          "=r"(d[8]), "=r"(d[9]), "=r"(d[10]), "=r"(d[11]), "=r"(d[12]), "=r"(d[13]), "=r"(d[14]), "=r"(d[15]),
          "=r"(d[16]), "=r"(d[17]), "=r"(d[18]), "=r"(d[19])
        : "l"(da), "l"(db));
}
__device__ __forceinline__ void wgmma_rs_n80(uint32_t (&d)[20], uint32_t a0, uint32_t a1, uint32_t a2, uint32_t a3, uint64_t db) {
    asm volatile("wgmma.mma_async.sync.aligned.m64n80k16.f16.f16.f16 {"
        "%0, %1, %2, %3, %4, %5, %6, %7, %8, %9, %10, %11, %12, %13, %14, %15, %16, %17, %18, %19}, {%20, %21, %22, %23}, %24, 1, 1, 1, 0;\n"
        : "+r"(d[0]), "+r"(d[1]), "+r"(d[2]), "+r"(d[3]), "+r"(d[4]), "+r"(d[5]), "+r"(d[6]), "+r"(d[7]),
          "+r"(d[8]), "+r"(d[9]), "+r"(d[10]), "+r"(d[11]), "+r"(d[12]), "+r"(d[13]), "+r"(d[14]), "+r"(d[15]),
          "+r"(d[16]), "+r"(d[17]), "+r"(d[18]), "+r"(d[19])
        : "r"(a0), "r"(a1), "r"(a2), "r"(a3), "l"(db));
}
__device__ __forceinline__ void wgmma_rs_n256_tb(float (&d)[128], uint32_t a0, uint32_t a1, uint32_t a2, uint32_t a3, uint64_t db) {
    asm volatile("wgmma.mma_async.sync.aligned.m64n256k16.f32.f16.f16 {"
        "%0, %1, %2, %3, %4, %5, %6, %7, %8, %9, %10, %11, %12, %13, %14, %15, %16, %17, %18, %19, %20, %21, %22, %23, %24, %25, %26, %27, %28, %29, %30, %31, "
        "%32, %33, %34, %35, %36, %37, %38, %39, %40, %41, %42, %43, %44, %45, %46, %47, %48, %49, %50, %51, %52, %53, %54, %55, %56, %57, %58, %59, %60, %61, %62, %63, "
        "%64, %65, %66, %67, %68, %69, %70, %71, %72, %73, %74, %75, %76, %77, %78, %79, %80, %81, %82, %83, %84, %85, %86, %87, %88, %89, %90, %91, %92, %93, %94, %95, "
        "%96, %97, %98, %99, %100, %101, %102, %103, %104, %105, %106, %107, %108, %109, %110, %111, %112, %113, %114, %115, %116, %117, %118, %119, %120, %121, %122, %123, %124, %125, %126, %127}, {%128, %129, %130, %131}, %132, 1, 1, 1, 1;\n"
        : "+f"(d[0]), "+f"(d[1]), "+f"(d[2]), "+f"(d[3]), "+f"(d[4]), "+f"(d[5]), "+f"(d[6]), "+f"(d[7]),
          "+f"(d[8]), "+f"(d[9]), "+f"(d[10]), "+f"(d[11]), "+f"(d[12]), "+f"(d[13]), "+f"(d[14]), "+f"(d[15]),
          "+f"(d[16]), "+f"(d[17]), "+f"(d[18]), "+f"(d[19]), "+f"(d[20]), "+f"(d[21]), "+f"(d[22]), "+f"(d[23]),
          "+f"(d[24]), "+f"(d[25]), "+f"(d[26]), "+f"(d[27]), "+f"(d[28]), "+f"(d[29]), "+f"(d[30]), "+f"(d[31]),
          "+f"(d[32]), "+f"(d[33]), "+f"(d[34]), "+f"(d[35]), "+f"(d[36]), "+f"(d[37]), "+f"(d[38]), "+f"(d[39]),
          "+f"(d[40]), "+f"(d[41]), "+f"(d[42]), "+f"(d[43]), "+f"(d[44]), "+f"(d[45]), "+f"(d[46]), "+f"(d[47]),
          "+f"(d[48]), "+f"(d[49]), "+f"(d[50]), "+f"(d[51]), "+f"(d[52]), "+f"(d[53]), "+f"(d[54]), "+f"(d[55]),
          "+f"(d[56]), "+f"(d[57]), "+f"(d[58]), "+f"(d[59]), "+f"(d[60]), "+f"(d[61]), "+f"(d[62]), "+f"(d[63]),
          "+f"(d[64]), "+f"(d[65]), "+f"(d[66]), "+f"(d[67]), "+f"(d[68]), "+f"(d[69]), "+f"(d[70]), "+f"(d[71]),
          "+f"(d[72]), "+f"(d[73]), "+f"(d[74]), "+f"(d[75]), "+f"(d[76]), "+f"(d[77]), "+f"(d[78]), "+f"(d[79]),
          "+f"(d[80]), "+f"(d[81]), "+f"(d[82]), "+f"(d[83]), "+f"(d[84]), "+f"(d[85]), "+f"(d[86]), "+f"(d[87]),
          "+f"(d[88]), "+f"(d[89]), "+f"(d[90]), "+f"(d[91]), "+f"(d[92]), "+f"(d[93]), "+f"(d[94]), "+f"(d[95]),
          "+f"(d[96]), "+f"(d[97]), "+f"(d[98]), "+f"(d[99]), "+f"(d[100]), "+f"(d[101]), "+f"(d[102]), "+f"(d[103]),
          "+f"(d[104]), "+f"(d[105]), "+f"(d[106]), "+f"(d[107]), "+f"(d[108]), "+f"(d[109]), "+f"(d[110]), "+f"(d[111]),
          "+f"(d[112]), "+f"(d[113]), "+f"(d[114]), "+f"(d[115]), "+f"(d[116]), "+f"(d[117]), "+f"(d[118]), "+f"(d[119]),
          "+f"(d[120]), "+f"(d[121]), "+f"(d[122]), "+f"(d[123]), "+f"(d[124]), "+f"(d[125]), "+f"(d[126]), "+f"(d[127])
        : "r"(a0), "r"(a1), "r"(a2), "r"(a3), "l"(db));
}
__device__ __forceinline__ void wgmma_rs_n256_tb_init(float (&d)[128], uint32_t a0, uint32_t a1, uint32_t a2, uint32_t a3, uint64_t db) {
    asm volatile("wgmma.mma_async.sync.aligned.m64n256k16.f32.f16.f16 {"
        "%0, %1, %2, %3, %4, %5, %6, %7, %8, %9, %10, %11, %12, %13, %14, %15, %16, %17, %18, %19, %20, %21, %22, %23, %24, %25, %26, %27, %28, %29, %30, %31, "
        "%32, %33, %34, %35, %36, %37, %38, %39, %40, %41, %42, %43, %44, %45, %46, %47, %48, %49, %50, %51, %52, %53, %54, %55, %56, %57, %58, %59, %60, %61, %62, %63, "
        "%64, %65, %66, %67, %68, %69, %70, %71, %72, %73, %74, %75, %76, %77, %78, %79, %80, %81, %82, %83, %84, %85, %86, %87, %88, %89, %90, %91, %92, %93, %94, %95, "
        "%96, %97, %98, %99, %100, %101, %102, %103, %104, %105, %106, %107, %108, %109, %110, %111, %112, %113, %114, %115, %116, %117, %118, %119, %120, %121, %122, %123, %124, %125, %126, %127}, {%128, %129, %130, %131}, %132, 0, 1, 1, 1;\n"
        : "=f"(d[0]), "=f"(d[1]), "=f"(d[2]), "=f"(d[3]), "=f"(d[4]), "=f"(d[5]), "=f"(d[6]), "=f"(d[7]),
          "=f"(d[8]), "=f"(d[9]), "=f"(d[10]), "=f"(d[11]), "=f"(d[12]), "=f"(d[13]), "=f"(d[14]), "=f"(d[15]),
          "=f"(d[16]), "=f"(d[17]), "=f"(d[18]), "=f"(d[19]), "=f"(d[20]), "=f"(d[21]), "=f"(d[22]), "=f"(d[23]),
          "=f"(d[24]), "=f"(d[25]), "=f"(d[26]), "=f"(d[27]), "=f"(d[28]), "=f"(d[29]), "=f"(d[30]), "=f"(d[31]),
          "=f"(d[32]), "=f"(d[33]), "=f"(d[34]), "=f"(d[35]), "=f"(d[36]), "=f"(d[37]), "=f"(d[38]), "=f"(d[39]),
          "=f"(d[40]), "=f"(d[41]), "=f"(d[42]), "=f"(d[43]), "=f"(d[44]), "=f"(d[45]), "=f"(d[46]), "=f"(d[47]),
          "=f"(d[48]), "=f"(d[49]), "=f"(d[50]), "=f"(d[51]), "=f"(d[52]), "=f"(d[53]), "=f"(d[54]), "=f"(d[55]),
          "=f"(d[56]), "=f"(d[57]), "=f"(d[58]), "=f"(d[59]), "=f"(d[60]), "=f"(d[61]), "=f"(d[62]), "=f"(d[63]),
          "=f"(d[64]), "=f"(d[65]), "=f"(d[66]), "=f"(d[67]), "=f"(d[68]), "=f"(d[69]), "=f"(d[70]), "=f"(d[71]),
          "=f"(d[72]), "=f"(d[73]), "=f"(d[74]), "=f"(d[75]), "=f"(d[76]), "=f"(d[77]), "=f"(d[78]), "=f"(d[79]),
          "=f"(d[80]), "=f"(d[81]), "=f"(d[82]), "=f"(d[83]), "=f"(d[84]), "=f"(d[85]), "=f"(d[86]), "=f"(d[87]),
          "=f"(d[88]), "=f"(d[89]), "=f"(d[90]), "=f"(d[91]), "=f"(d[92]), "=f"(d[93]), "=f"(d[94]), "=f"(d[95]),
          "=f"(d[96]), "=f"(d[97]), "=f"(d[98]), "=f"(d[99]), "=f"(d[100]), "=f"(d[101]), "=f"(d[102]), "=f"(d[103]),
          "=f"(d[104]), "=f"(d[105]), "=f"(d[106]), "=f"(d[107]), "=f"(d[108]), "=f"(d[109]), "=f"(d[110]), "=f"(d[111]),
          "=f"(d[112]), "=f"(d[113]), "=f"(d[114]), "=f"(d[115]), "=f"(d[116]), "=f"(d[117]), "=f"(d[118]), "=f"(d[119]),
          "=f"(d[120]), "=f"(d[121]), "=f"(d[122]), "=f"(d[123]), "=f"(d[124]), "=f"(d[125]), "=f"(d[126]), "=f"(d[127])
        : "r"(a0), "r"(a1), "r"(a2), "r"(a3), "l"(db));
}
__device__ __forceinline__ void wgmma_rs_n256_tb_pred(float (&d)[128], uint32_t a0, uint32_t a1, uint32_t a2, uint32_t a3, uint64_t db, int acc) {
    asm volatile("{\n.reg .pred p;\nsetp.ne.s32 p, %133, 0;\nwgmma.mma_async.sync.aligned.m64n256k16.f32.f16.f16 {"
        "%0, %1, %2, %3, %4, %5, %6, %7, %8, %9, %10, %11, %12, %13, %14, %15, %16, %17, %18, %19, %20, %21, %22, %23, %24, %25, %26, %27, %28, %29, %30, %31, "
        "%32, %33, %34, %35, %36, %37, %38, %39, %40, %41, %42, %43, %44, %45, %46, %47, %48, %49, %50, %51, %52, %53, %54, %55, %56, %57, %58, %59, %60, %61, %62, %63, "
        "%64, %65, %66, %67, %68, %69, %70, %71, %72, %73, %74, %75, %76, %77, %78, %79, %80, %81, %82, %83, %84, %85, %86, %87, %88, %89, %90, %91, %92, %93, %94, %95, "
        "%96, %97, %98, %99, %100, %101, %102, %103, %104, %105, %106, %107, %108, %109, %110, %111, %112, %113, %114, %115, %116, %117, %118, %119, %120, %121, %122, %123, %124, %125, %126, %127}, {%128, %129, %130, %131}, %132, p, 1, 1, 1;\n}\n"
        : "+f"(d[0]), "+f"(d[1]), "+f"(d[2]), "+f"(d[3]), "+f"(d[4]), "+f"(d[5]), "+f"(d[6]), "+f"(d[7]),
          "+f"(d[8]), "+f"(d[9]), "+f"(d[10]), "+f"(d[11]), "+f"(d[12]), "+f"(d[13]), "+f"(d[14]), "+f"(d[15]),
          "+f"(d[16]), "+f"(d[17]), "+f"(d[18]), "+f"(d[19]), "+f"(d[20]), "+f"(d[21]), "+f"(d[22]), "+f"(d[23]),
          "+f"(d[24]), "+f"(d[25]), "+f"(d[26]), "+f"(d[27]), "+f"(d[28]), "+f"(d[29]), "+f"(d[30]), "+f"(d[31]),
          "+f"(d[32]), "+f"(d[33]), "+f"(d[34]), "+f"(d[35]), "+f"(d[36]), "+f"(d[37]), "+f"(d[38]), "+f"(d[39]),
          "+f"(d[40]), "+f"(d[41]), "+f"(d[42]), "+f"(d[43]), "+f"(d[44]), "+f"(d[45]), "+f"(d[46]), "+f"(d[47]),
          "+f"(d[48]), "+f"(d[49]), "+f"(d[50]), "+f"(d[51]), "+f"(d[52]), "+f"(d[53]), "+f"(d[54]), "+f"(d[55]),
          "+f"(d[56]), "+f"(d[57]), "+f"(d[58]), "+f"(d[59]), "+f"(d[60]), "+f"(d[61]), "+f"(d[62]), "+f"(d[63]),
          "+f"(d[64]), "+f"(d[65]), "+f"(d[66]), "+f"(d[67]), "+f"(d[68]), "+f"(d[69]), "+f"(d[70]), "+f"(d[71]),
          "+f"(d[72]), "+f"(d[73]), "+f"(d[74]), "+f"(d[75]), "+f"(d[76]), "+f"(d[77]), "+f"(d[78]), "+f"(d[79]),
          "+f"(d[80]), "+f"(d[81]), "+f"(d[82]), "+f"(d[83]), "+f"(d[84]), "+f"(d[85]), "+f"(d[86]), "+f"(d[87]),
          "+f"(d[88]), "+f"(d[89]), "+f"(d[90]), "+f"(d[91]), "+f"(d[92]), "+f"(d[93]), "+f"(d[94]), "+f"(d[95]),
          "+f"(d[96]), "+f"(d[97]), "+f"(d[98]), "+f"(d[99]), "+f"(d[100]), "+f"(d[101]), "+f"(d[102]), "+f"(d[103]),
          "+f"(d[104]), "+f"(d[105]), "+f"(d[106]), "+f"(d[107]), "+f"(d[108]), "+f"(d[109]), "+f"(d[110]), "+f"(d[111]),
          "+f"(d[112]), "+f"(d[113]), "+f"(d[114]), "+f"(d[115]), "+f"(d[116]), "+f"(d[117]), "+f"(d[118]), "+f"(d[119]),
          "+f"(d[120]), "+f"(d[121]), "+f"(d[122]), "+f"(d[123]), "+f"(d[124]), "+f"(d[125]), "+f"(d[126]), "+f"(d[127])
        : "r"(a0), "r"(a1), "r"(a2), "r"(a3), "l"(db), "r"(acc));
}
__device__ __forceinline__ void wgmma_ss_n256_tb(float (&d)[128], uint64_t da, uint64_t db) {
    asm volatile("wgmma.mma_async.sync.aligned.m64n256k16.f32.bf16.bf16 {"
        "%0, %1, %2, %3, %4, %5, %6, %7, %8, %9, %10, %11, %12, %13, %14, %15, %16, %17, %18, %19, %20, %21, %22, %23, %24, %25, %26, %27, %28, %29, %30, %31, "
        "%32, %33, %34, %35, %36, %37, %38, %39, %40, %41, %42, %43, %44, %45, %46, %47, %48, %49, %50, %51, %52, %53, %54, %55, %56, %57, %58, %59, %60, %61, %62, %63, "
        "%64, %65, %66, %67, %68, %69, %70, %71, %72, %73, %74, %75, %76, %77, %78, %79, %80, %81, %82, %83, %84, %85, %86, %87, %88, %89, %90, %91, %92, %93, %94, %95, "
        "%96, %97, %98, %99, %100, %101, %102, %103, %104, %105, %106, %107, %108, %109, %110, %111, %112, %113, %114, %115, %116, %117, %118, %119, %120, %121, %122, %123, %124, %125, %126, %127}, %128, %129, 1, 1, 1, 0, 1;\n"
        : "+f"(d[0]), "+f"(d[1]), "+f"(d[2]), "+f"(d[3]), "+f"(d[4]), "+f"(d[5]), "+f"(d[6]), "+f"(d[7]),
          "+f"(d[8]), "+f"(d[9]), "+f"(d[10]), "+f"(d[11]), "+f"(d[12]), "+f"(d[13]), "+f"(d[14]), "+f"(d[15]),
          "+f"(d[16]), "+f"(d[17]), "+f"(d[18]), "+f"(d[19]), "+f"(d[20]), "+f"(d[21]), "+f"(d[22]), "+f"(d[23]),
          "+f"(d[24]), "+f"(d[25]), "+f"(d[26]), "+f"(d[27]), "+f"(d[28]), "+f"(d[29]), "+f"(d[30]), "+f"(d[31]),
          "+f"(d[32]), "+f"(d[33]), "+f"(d[34]), "+f"(d[35]), "+f"(d[36]), "+f"(d[37]), "+f"(d[38]), "+f"(d[39]),
          "+f"(d[40]), "+f"(d[41]), "+f"(d[42]), "+f"(d[43]), "+f"(d[44]), "+f"(d[45]), "+f"(d[46]), "+f"(d[47]),
          "+f"(d[48]), "+f"(d[49]), "+f"(d[50]), "+f"(d[51]), "+f"(d[52]), "+f"(d[53]), "+f"(d[54]), "+f"(d[55]),
          "+f"(d[56]), "+f"(d[57]), "+f"(d[58]), "+f"(d[59]), "+f"(d[60]), "+f"(d[61]), "+f"(d[62]), "+f"(d[63]),
          "+f"(d[64]), "+f"(d[65]), "+f"(d[66]), "+f"(d[67]), "+f"(d[68]), "+f"(d[69]), "+f"(d[70]), "+f"(d[71]),
          "+f"(d[72]), "+f"(d[73]), "+f"(d[74]), "+f"(d[75]), "+f"(d[76]), "+f"(d[77]), "+f"(d[78]), "+f"(d[79]),
          "+f"(d[80]), "+f"(d[81]), "+f"(d[82]), "+f"(d[83]), "+f"(d[84]), "+f"(d[85]), "+f"(d[86]), "+f"(d[87]),
          "+f"(d[88]), "+f"(d[89]), "+f"(d[90]), "+f"(d[91]), "+f"(d[92]), "+f"(d[93]), "+f"(d[94]), "+f"(d[95]),
          "+f"(d[96]), "+f"(d[97]), "+f"(d[98]), "+f"(d[99]), "+f"(d[100]), "+f"(d[101]), "+f"(d[102]), "+f"(d[103]),
          "+f"(d[104]), "+f"(d[105]), "+f"(d[106]), "+f"(d[107]), "+f"(d[108]), "+f"(d[109]), "+f"(d[110]), "+f"(d[111]),
          "+f"(d[112]), "+f"(d[113]), "+f"(d[114]), "+f"(d[115]), "+f"(d[116]), "+f"(d[117]), "+f"(d[118]), "+f"(d[119]),
          "+f"(d[120]), "+f"(d[121]), "+f"(d[122]), "+f"(d[123]), "+f"(d[124]), "+f"(d[125]), "+f"(d[126]), "+f"(d[127])
        : "l"(da), "l"(db));
}
__device__ __forceinline__ void wgmma_ss_n256_tb_init(float (&d)[128], uint64_t da, uint64_t db) {
    asm volatile("wgmma.mma_async.sync.aligned.m64n256k16.f32.bf16.bf16 {"
        "%0, %1, %2, %3, %4, %5, %6, %7, %8, %9, %10, %11, %12, %13, %14, %15, %16, %17, %18, %19, %20, %21, %22, %23, %24, %25, %26, %27, %28, %29, %30, %31, "
        "%32, %33, %34, %35, %36, %37, %38, %39, %40, %41, %42, %43, %44, %45, %46, %47, %48, %49, %50, %51, %52, %53, %54, %55, %56, %57, %58, %59, %60, %61, %62, %63, "
        "%64, %65, %66, %67, %68, %69, %70, %71, %72, %73, %74, %75, %76, %77, %78, %79, %80, %81, %82, %83, %84, %85, %86, %87, %88, %89, %90, %91, %92, %93, %94, %95, "
        "%96, %97, %98, %99, %100, %101, %102, %103, %104, %105, %106, %107, %108, %109, %110, %111, %112, %113, %114, %115, %116, %117, %118, %119, %120, %121, %122, %123, %124, %125, %126, %127}, %128, %129, 0, 1, 1, 0, 1;\n"
        : "=f"(d[0]), "=f"(d[1]), "=f"(d[2]), "=f"(d[3]), "=f"(d[4]), "=f"(d[5]), "=f"(d[6]), "=f"(d[7]),
          "=f"(d[8]), "=f"(d[9]), "=f"(d[10]), "=f"(d[11]), "=f"(d[12]), "=f"(d[13]), "=f"(d[14]), "=f"(d[15]),
          "=f"(d[16]), "=f"(d[17]), "=f"(d[18]), "=f"(d[19]), "=f"(d[20]), "=f"(d[21]), "=f"(d[22]), "=f"(d[23]),
          "=f"(d[24]), "=f"(d[25]), "=f"(d[26]), "=f"(d[27]), "=f"(d[28]), "=f"(d[29]), "=f"(d[30]), "=f"(d[31]),
          "=f"(d[32]), "=f"(d[33]), "=f"(d[34]), "=f"(d[35]), "=f"(d[36]), "=f"(d[37]), "=f"(d[38]), "=f"(d[39]),
          "=f"(d[40]), "=f"(d[41]), "=f"(d[42]), "=f"(d[43]), "=f"(d[44]), "=f"(d[45]), "=f"(d[46]), "=f"(d[47]),
          "=f"(d[48]), "=f"(d[49]), "=f"(d[50]), "=f"(d[51]), "=f"(d[52]), "=f"(d[53]), "=f"(d[54]), "=f"(d[55]),
          "=f"(d[56]), "=f"(d[57]), "=f"(d[58]), "=f"(d[59]), "=f"(d[60]), "=f"(d[61]), "=f"(d[62]), "=f"(d[63]),
          "=f"(d[64]), "=f"(d[65]), "=f"(d[66]), "=f"(d[67]), "=f"(d[68]), "=f"(d[69]), "=f"(d[70]), "=f"(d[71]),
          "=f"(d[72]), "=f"(d[73]), "=f"(d[74]), "=f"(d[75]), "=f"(d[76]), "=f"(d[77]), "=f"(d[78]), "=f"(d[79]),
          "=f"(d[80]), "=f"(d[81]), "=f"(d[82]), "=f"(d[83]), "=f"(d[84]), "=f"(d[85]), "=f"(d[86]), "=f"(d[87]),
          "=f"(d[88]), "=f"(d[89]), "=f"(d[90]), "=f"(d[91]), "=f"(d[92]), "=f"(d[93]), "=f"(d[94]), "=f"(d[95]),
          "=f"(d[96]), "=f"(d[97]), "=f"(d[98]), "=f"(d[99]), "=f"(d[100]), "=f"(d[101]), "=f"(d[102]), "=f"(d[103]),
          "=f"(d[104]), "=f"(d[105]), "=f"(d[106]), "=f"(d[107]), "=f"(d[108]), "=f"(d[109]), "=f"(d[110]), "=f"(d[111]),
          "=f"(d[112]), "=f"(d[113]), "=f"(d[114]), "=f"(d[115]), "=f"(d[116]), "=f"(d[117]), "=f"(d[118]), "=f"(d[119]),
          "=f"(d[120]), "=f"(d[121]), "=f"(d[122]), "=f"(d[123]), "=f"(d[124]), "=f"(d[125]), "=f"(d[126]), "=f"(d[127])
        : "l"(da), "l"(db));
}
__device__ __forceinline__ void wgmma_ss_n256_tb_pred(float (&d)[128], uint64_t da, uint64_t db, int acc) {
    asm volatile("{\n.reg .pred p;\nsetp.ne.s32 p, %130, 0;\nwgmma.mma_async.sync.aligned.m64n256k16.f32.bf16.bf16 {"
        "%0, %1, %2, %3, %4, %5, %6, %7, %8, %9, %10, %11, %12, %13, %14, %15, %16, %17, %18, %19, %20, %21, %22, %23, %24, %25, %26, %27, %28, %29, %30, %31, "
        "%32, %33, %34, %35, %36, %37, %38, %39, %40, %41, %42, %43, %44, %45, %46, %47, %48, %49, %50, %51, %52, %53, %54, %55, %56, %57, %58, %59, %60, %61, %62, %63, "
        "%64, %65, %66, %67, %68, %69, %70, %71, %72, %73, %74, %75, %76, %77, %78, %79, %80, %81, %82, %83, %84, %85, %86, %87, %88, %89, %90, %91, %92, %93, %94, %95, "
        "%96, %97, %98, %99, %100, %101, %102, %103, %104, %105, %106, %107, %108, %109, %110, %111, %112, %113, %114, %115, %116, %117, %118, %119, %120, %121, %122, %123, %124, %125, %126, %127}, %128, %129, p, 1, 1, 0, 1;\n}\n"
        : "+f"(d[0]), "+f"(d[1]), "+f"(d[2]), "+f"(d[3]), "+f"(d[4]), "+f"(d[5]), "+f"(d[6]), "+f"(d[7]),
          "+f"(d[8]), "+f"(d[9]), "+f"(d[10]), "+f"(d[11]), "+f"(d[12]), "+f"(d[13]), "+f"(d[14]), "+f"(d[15]),
          "+f"(d[16]), "+f"(d[17]), "+f"(d[18]), "+f"(d[19]), "+f"(d[20]), "+f"(d[21]), "+f"(d[22]), "+f"(d[23]),
          "+f"(d[24]), "+f"(d[25]), "+f"(d[26]), "+f"(d[27]), "+f"(d[28]), "+f"(d[29]), "+f"(d[30]), "+f"(d[31]),
          "+f"(d[32]), "+f"(d[33]), "+f"(d[34]), "+f"(d[35]), "+f"(d[36]), "+f"(d[37]), "+f"(d[38]), "+f"(d[39]),
          "+f"(d[40]), "+f"(d[41]), "+f"(d[42]), "+f"(d[43]), "+f"(d[44]), "+f"(d[45]), "+f"(d[46]), "+f"(d[47]),
          "+f"(d[48]), "+f"(d[49]), "+f"(d[50]), "+f"(d[51]), "+f"(d[52]), "+f"(d[53]), "+f"(d[54]), "+f"(d[55]),
          "+f"(d[56]), "+f"(d[57]), "+f"(d[58]), "+f"(d[59]), "+f"(d[60]), "+f"(d[61]), "+f"(d[62]), "+f"(d[63]),
          "+f"(d[64]), "+f"(d[65]), "+f"(d[66]), "+f"(d[67]), "+f"(d[68]), "+f"(d[69]), "+f"(d[70]), "+f"(d[71]),
          "+f"(d[72]), "+f"(d[73]), "+f"(d[74]), "+f"(d[75]), "+f"(d[76]), "+f"(d[77]), "+f"(d[78]), "+f"(d[79]),
          "+f"(d[80]), "+f"(d[81]), "+f"(d[82]), "+f"(d[83]), "+f"(d[84]), "+f"(d[85]), "+f"(d[86]), "+f"(d[87]),
          "+f"(d[88]), "+f"(d[89]), "+f"(d[90]), "+f"(d[91]), "+f"(d[92]), "+f"(d[93]), "+f"(d[94]), "+f"(d[95]),
          "+f"(d[96]), "+f"(d[97]), "+f"(d[98]), "+f"(d[99]), "+f"(d[100]), "+f"(d[101]), "+f"(d[102]), "+f"(d[103]),
          "+f"(d[104]), "+f"(d[105]), "+f"(d[106]), "+f"(d[107]), "+f"(d[108]), "+f"(d[109]), "+f"(d[110]), "+f"(d[111]),
          "+f"(d[112]), "+f"(d[113]), "+f"(d[114]), "+f"(d[115]), "+f"(d[116]), "+f"(d[117]), "+f"(d[118]), "+f"(d[119]),
          "+f"(d[120]), "+f"(d[121]), "+f"(d[122]), "+f"(d[123]), "+f"(d[124]), "+f"(d[125]), "+f"(d[126]), "+f"(d[127])
        : "l"(da), "l"(db), "r"(acc));
}
__device__ __forceinline__ void wgmma_rs_n64_tb(float (&d)[32], uint32_t a0, uint32_t a1, uint32_t a2, uint32_t a3, uint64_t db) {
    asm volatile("wgmma.mma_async.sync.aligned.m64n64k16.f32.bf16.bf16 {"
        "%0, %1, %2, %3, %4, %5, %6, %7, %8, %9, %10, %11, %12, %13, %14, %15, %16, %17, %18, %19, %20, %21, %22, %23, %24, %25, %26, %27, %28, %29, %30, %31}, {%32, %33, %34, %35}, %36, 1, 1, 1, 1;\n"
        : "+f"(d[0]), "+f"(d[1]), "+f"(d[2]), "+f"(d[3]), "+f"(d[4]), "+f"(d[5]), "+f"(d[6]), "+f"(d[7]),
          "+f"(d[8]), "+f"(d[9]), "+f"(d[10]), "+f"(d[11]), "+f"(d[12]), "+f"(d[13]), "+f"(d[14]), "+f"(d[15]),
          "+f"(d[16]), "+f"(d[17]), "+f"(d[18]), "+f"(d[19]), "+f"(d[20]), "+f"(d[21]), "+f"(d[22]), "+f"(d[23]),
          "+f"(d[24]), "+f"(d[25]), "+f"(d[26]), "+f"(d[27]), "+f"(d[28]), "+f"(d[29]), "+f"(d[30]), "+f"(d[31])
        : "r"(a0), "r"(a1), "r"(a2), "r"(a3), "l"(db));
}
__device__ __forceinline__ void wgmma_rs_n64_tb_init(float (&d)[32], uint32_t a0, uint32_t a1, uint32_t a2, uint32_t a3, uint64_t db) {
    asm volatile("wgmma.mma_async.sync.aligned.m64n64k16.f32.bf16.bf16 {"
        "%0, %1, %2, %3, %4, %5, %6, %7, %8, %9, %10, %11, %12, %13, %14, %15, %16, %17, %18, %19, %20, %21, %22, %23, %24, %25, %26, %27, %28, %29, %30, %31}, {%32, %33, %34, %35}, %36, 0, 1, 1, 1;\n"
        : "=f"(d[0]), "=f"(d[1]), "=f"(d[2]), "=f"(d[3]), "=f"(d[4]), "=f"(d[5]), "=f"(d[6]), "=f"(d[7]),
          "=f"(d[8]), "=f"(d[9]), "=f"(d[10]), "=f"(d[11]), "=f"(d[12]), "=f"(d[13]), "=f"(d[14]), "=f"(d[15]),
          "=f"(d[16]), "=f"(d[17]), "=f"(d[18]), "=f"(d[19]), "=f"(d[20]), "=f"(d[21]), "=f"(d[22]), "=f"(d[23]),
          "=f"(d[24]), "=f"(d[25]), "=f"(d[26]), "=f"(d[27]), "=f"(d[28]), "=f"(d[29]), "=f"(d[30]), "=f"(d[31])
        : "r"(a0), "r"(a1), "r"(a2), "r"(a3), "l"(db));
}

__device__ __forceinline__ void wg_fence() { asm volatile("wgmma.fence.sync.aligned;\n" ::: "memory"); }
__device__ __forceinline__ void wg_commit() { asm volatile("wgmma.commit_group.sync.aligned;\n" ::: "memory"); }
template <int N> __device__ __forceinline__ void wg_wait() { asm volatile("wgmma.wait_group.sync.aligned %0;\n" ::"n"(N) : "memory"); }
template <int N> __device__ __forceinline__ void fence_regs(float (&a)[N]) {
#pragma unroll
    for (int i = 0; i < N; i++) asm volatile("" : "+f"(a[i])::"memory");
}
template <int N> __device__ __forceinline__ void fence_regs(uint32_t (&a)[N]) {
#pragma unroll
    for (int i = 0; i < N; i++) asm volatile("" : "+r"(a[i])::"memory");
}
__device__ __forceinline__ void mbar_init(uint32_t bar, uint32_t cnt) {
    asm volatile("mbarrier.init.shared::cta.b64 [%0], %1;\n" ::"r"(bar), "r"(cnt) : "memory");
}
__device__ __forceinline__ void mbar_expect_tx(uint32_t bar, uint32_t bytes) {
    asm volatile("mbarrier.arrive.expect_tx.shared::cta.b64 _, [%0], %1;\n" ::"r"(bar), "r"(bytes) : "memory");
}
__device__ __forceinline__ void mbar_wait(uint32_t bar, uint32_t parity) {
    asm volatile("{\n.reg .pred p;\nLW:\nmbarrier.try_wait.parity.shared::cta.b64 p, [%0], %1;\n@!p pmevent 0;\n@!p bra LW;\n}\n" ::"r"(bar), "r"(parity) : "memory");
}
__device__ __forceinline__ void mbar_wait_sleep(uint32_t bar, uint32_t parity) {
    asm volatile("{\n.reg .pred p;\nLW:\nmbarrier.try_wait.parity.shared::cta.b64 p, [%0], %1, 20000;\n@!p pmevent 0;\n@!p bra LW;\n}\n" ::"r"(bar), "r"(parity) : "memory");
}
__device__ __forceinline__ void mbar_wait_bounded(uint32_t bar, uint32_t parity) {
    asm volatile("{\n.reg .pred p;\n.reg .u32 c;\nmov.u32 c, 0;\nLW:\nmbarrier.try_wait.parity.shared::cta.b64 p, [%0], %1, 20000;\n@p bra LD;\n"
                 "add.u32 c, c, 1;\nsetp.ge.u32 p, c, 262144;\n@p trap;\nbra LW;\nLD:\n}\n" ::"r"(bar), "r"(parity) : "memory");
}
__device__ __forceinline__ void flag_wait(const int* p, int v) {
    asm volatile("{\n.reg .pred p;\n.reg .s32 f;\nLW:\nld.acquire.gpu.global.s32 f, [%0];\nsub.s32 f, f, %1;\nsetp.lt.s32 p, f, 0;\n@p bra LW;\n}\n" ::"l"(p), "r"(v) : "memory");
}
__device__ __forceinline__ void flag_wait_bounded(const int* p, int v) {
    asm volatile("{\n.reg .pred p;\n.reg .u32 c;\n.reg .s32 f;\nmov.u32 c, 0;\nLW:\nld.acquire.gpu.global.s32 f, [%0];\nsub.s32 f, f, %1;\nsetp.ge.s32 p, f, 0;\n@p bra LD;\n"
                 "nanosleep.u32 500;\nadd.u32 c, c, 1;\nsetp.ge.u32 p, c, 4194304;\n@p trap;\nbra LW;\nLD:\n}\n" ::"l"(p), "r"(v) : "memory");
}
__device__ __forceinline__ int lane_now() {
    int l; asm volatile("mov.u32 %0, %%laneid;\n" : "=r"(l)); return l;
}
__device__ __forceinline__ bool elect() {
    uint32_t p; asm volatile("{\n.reg .pred p;\nelect.sync _|p, -1;\nselp.u32 %0, 1, 0, p;\n}\n" : "=r"(p)); return p;
}
__device__ __forceinline__ void bulk_g2s(uint32_t dst, const void* src, uint32_t bytes, uint32_t bar) {
    asm volatile("cp.async.bulk.shared::cluster.global.mbarrier::complete_tx::bytes [%0], [%1], %2, [%3];\n"
                 ::"r"(dst), "l"(src), "r"(bytes), "r"(bar) : "memory");
}
__device__ __forceinline__ void tma_g2s(uint32_t dst, const CUtensorMap* tm, int rowgroup, uint32_t bar) {
    asm volatile("cp.async.bulk.tensor.4d.shared::cluster.global.tile.mbarrier::complete_tx::bytes [%0], [%1, {0, 0, 0, %2}], [%3];\n"
                 ::"r"(dst), "l"(tm), "r"(rowgroup), "r"(bar) : "memory");
}
__device__ __forceinline__ void bar_sync(int id, int n) { asm volatile("bar.sync %0, %1;\n" ::"r"(id), "r"(n) : "memory"); }
__device__ __forceinline__ void bar_arrive(int id, int n) { asm volatile("bar.arrive %0, %1;\n" ::"r"(id), "r"(n) : "memory"); }
__device__ __forceinline__ float quad_last(float v) {
    float r; asm volatile("shfl.sync.idx.b32 %0, %1, 3, 0x1c1f, -1;\n" : "=f"(r) : "f"(v)); return r;
}
__device__ __forceinline__ float ex2(float x) { float y; asm("ex2.approx.ftz.f32 %0, %1;\n" : "=f"(y) : "f"(x)); return y; }
__device__ __forceinline__ uint32_t ex2_f16(uint32_t x) { uint32_t y; asm("ex2.approx.f16x2 %0, %1;\n" : "=r"(y) : "r"(x)); return y; }
__device__ __forceinline__ uint32_t hmax2_f16(uint32_t a, uint32_t b) { uint32_t r; asm("max.f16x2 %0, %1, %2;\n" : "=r"(r) : "r"(a), "r"(b)); return r; }
__device__ __forceinline__ float rcp(float x) { float y; asm("rcp.approx.ftz.f32 %0, %1;\n" : "=f"(y) : "f"(x)); return y; }
__device__ __forceinline__ uint32_t pack_bf16(float lo, float hi) {
    uint32_t r; asm("cvt.rn.bf16x2.f32 %0, %1, %2;\n" : "=r"(r) : "f"(hi), "f"(lo)); return r;
}
__device__ __forceinline__ uint32_t pack_f16(float lo, float hi) {
    uint32_t r; asm("cvt.rn.f16x2.f32 %0, %1, %2;\n" : "=r"(r) : "f"(hi), "f"(lo)); return r;
}
__device__ __forceinline__ uint32_t pack_f16_sat(float lo, float hi) {
    uint32_t r; asm("cvt.rn.satfinite.f16x2.f32 %0, %1, %2;\n" : "=r"(r) : "f"(hi), "f"(lo)); return r;
}
__device__ __forceinline__ float f16_lo(uint32_t v) { float r; asm("cvt.f32.f16 %0, %1;\n" : "=f"(r) : "h"((unsigned short)v)); return r; }
__device__ __forceinline__ float f16_hi(uint32_t v) { return f16_lo(v >> 16); }
__device__ __forceinline__ float bf_lo(uint32_t v) { return __uint_as_float(v << 16); }
__device__ __forceinline__ float bf_hi(uint32_t v) { return __uint_as_float(v & 0xFFFF0000u); }
__device__ __forceinline__ float bf_round(float x) { return __uint_as_float(pack_bf16(0.f, x)); }
__device__ __forceinline__ void st_release(int* p, int v) {
    asm volatile("st.release.gpu.global.s32 [%0], %1;\n" ::"l"(p), "r"(v) : "memory");
}
__device__ __forceinline__ uint4 ldg_pinned(const uint4* p) {
    uint4 v; asm volatile("ld.global.nc.v4.u32 {%0, %1, %2, %3}, [%4];\n" : "=r"(v.x), "=r"(v.y), "=r"(v.z), "=r"(v.w) : "l"(p) : "memory"); return v;
}
__device__ __forceinline__ void stmatrix_x4(uint32_t addr, uint32_t r0, uint32_t r1, uint32_t r2, uint32_t r3) {
    asm volatile("stmatrix.sync.aligned.m8n8.x4.shared.b16 [%0], {%1, %2, %3, %4};\n" ::"r"(addr), "r"(r0), "r"(r1), "r"(r2), "r"(r3) : "memory");
}

__device__ __forceinline__ uint32_t tile_off(int r, int ch) {
    return (uint32_t)((r >> 3) * 4096 + (ch >> 3) * 1024 + (r & 7) * 128 + (((ch ^ r) & 7) << 4));
}
__device__ __forceinline__ int h_unit(int qt, int u) { return qt < 78 ? u * 78 + qt : 624; }
__device__ __forceinline__ int row_off(int r) { return 4096 + h_unit(r >> 7, (r >> 4) & 7) * 8192 + (r & 8) * 512 + (r & 7) * 144; }

__device__ __forceinline__ float4 lds128f(uint32_t a) {
    float4 v; asm volatile("ld.shared.v4.f32 {%0, %1, %2, %3}, [%4];\n" : "=f"(v.x), "=f"(v.y), "=f"(v.z), "=f"(v.w) : "r"(a) : "memory"); return v;
}
__device__ __forceinline__ uint64_t lds64(uint32_t a) { uint64_t v; asm volatile("ld.shared.u64 %0, [%1];\n" : "=l"(v) : "r"(a) : "memory"); return v; }
__device__ __forceinline__ uint4 lds128(uint32_t a) {
    uint4 v; asm volatile("ld.shared.v4.u32 {%0, %1, %2, %3}, [%4];\n" : "=r"(v.x), "=r"(v.y), "=r"(v.z), "=r"(v.w) : "r"(a) : "memory"); return v;
}
__device__ __forceinline__ void sts128(uint32_t a, uint32_t x, uint32_t y, uint32_t z, uint32_t w) {
    asm volatile("st.shared.v4.u32 [%0], {%1, %2, %3, %4};\n" ::"r"(a), "r"(x), "r"(y), "r"(z), "r"(w) : "memory");
}
__device__ __forceinline__ void mbar_arrive(uint32_t bar) {
    asm volatile("mbarrier.arrive.shared::cta.b64 _, [%0];\n" ::"r"(bar) : "memory");
}
__device__ __forceinline__ uint64_t mkaddr(uint32_t lo, uint32_t hi) { uint64_t a; asm("mov.b64 %0, {%1, %2};\n" : "=l"(a) : "r"(lo), "r"(hi)); return a; }
__device__ __forceinline__ void red_add(int* p) { asm volatile("red.relaxed.gpu.global.add.s32 [%0], 1;\n" ::"l"(p) : "memory"); }
__device__ __forceinline__ void red_release(int* p) {
    asm volatile("fence.proxy.async.global;\nfence.acq_rel.gpu;\nred.relaxed.gpu.global.add.s32 [%0], 1;\n" ::"l"(p) : "memory");
}
__device__ __forceinline__ void fence_async_global() { asm volatile("fence.proxy.async.global;\n" ::: "memory"); }
__device__ __forceinline__ void fence_async_smem() { asm volatile("fence.proxy.async.shared::cta;\n" ::: "memory"); }
__device__ __forceinline__ void bulk_s2g(void* dst, uint32_t src, uint32_t bytes) {
    asm volatile("cp.async.bulk.global.shared::cta.bulk_group [%0], [%1], %2;\ncp.async.bulk.commit_group;\n" ::"l"(dst), "r"(src), "r"(bytes) : "memory");
}
__device__ __forceinline__ void mma16816(float (&c)[4], uint32_t a0, uint32_t a1, uint32_t a2, uint32_t a3, uint32_t b0, uint32_t b1) {
    asm("mma.sync.aligned.m16n8k16.row.col.f32.bf16.bf16.f32 {%0, %1, %2, %3}, {%4, %5, %6, %7}, {%8, %9}, {%0, %1, %2, %3};\n"
        : "+f"(c[0]), "+f"(c[1]), "+f"(c[2]), "+f"(c[3]) : "r"(a0), "r"(a1), "r"(a2), "r"(a3), "r"(b0), "r"(b1));
}
__device__ __forceinline__ void mma1688(float (&c)[4], uint32_t a0, uint32_t a1, uint32_t b0) {
    asm("mma.sync.aligned.m16n8k8.row.col.f32.bf16.bf16.f32 {%0, %1, %2, %3}, {%4, %5}, {%6}, {%0, %1, %2, %3};\n"
        : "+f"(c[0]), "+f"(c[1]), "+f"(c[2]), "+f"(c[3]) : "r"(a0), "r"(a1), "r"(b0));
}
__device__ __forceinline__ uint32_t hadd2_f16(uint32_t a, uint32_t b) { uint32_t r; asm("add.rn.f16x2 %0, %1, %2;\n" : "=r"(r) : "r"(a), "r"(b)); return r; }
__device__ __forceinline__ uint32_t hadd2(uint32_t a, uint32_t b) { uint32_t r; asm("add.rn.bf16x2 %0, %1, %2;\n" : "=r"(r) : "r"(a), "r"(b)); return r; }
__device__ __forceinline__ uint32_t hmul2(uint32_t a, uint32_t b) { uint32_t r; asm("mul.rn.bf16x2 %0, %1, %2;\n" : "=r"(r) : "r"(a), "r"(b)); return r; }
__device__ __forceinline__ uint32_t hfma2(uint32_t a, uint32_t b, uint32_t c) { uint32_t r; asm("fma.rn.bf16x2 %0, %1, %2, %3;\n" : "=r"(r) : "r"(a), "r"(b), "r"(c)); return r; }

constexpr int SM_Q = 0;
constexpr int SM_KV = 65536;
constexpr int SM_ML = SM_KV + STAGES * KV_BYTES;
constexpr int SM_BAR = SM_ML + 1024;
constexpr int SM_TOTAL = SM_BAR + 256;
constexpr float SCALE_LOG2 = 1.4426950408889634f / 16.0f;
constexpr float KV_SCALE = 6.f;
constexpr float KV_OFF = 48.f;
constexpr uint32_t KV_OFF2 = 0x52005200u;
constexpr uint32_t KV_OFF8 = 0x5A005A00u;
constexpr uint32_t NEG2 = 0x80008000u;
constexpr uint32_t P_LIMIT = 0x78007800u;
constexpr float REF_UP = REFUP;
__device__ __forceinline__ uint32_t kvf(uint32_t a, uint32_t off) {
    uint32_t r; asm("fma.rn.f16x2 %0, %1, %2, %3;\n" : "=r"(r) : "r"(a), "r"(pack_f16(KV_SCALE, KV_SCALE)), "r"(off)); return r;
}
enum { BAR_PP0 = 1, BAR_PP1 = 2, BAR_WG0 = 3, BAR_WG1 = 4, BAR_H0 = 5, BAR_H1 = 6, BAR_AUX = 7, BAR_BF = 8, BAR_H2 = 9, BAR_X = 10, BAR_GO = 11, BAR_WG2 = 12, BAR_ST = 13 };

struct Hot {
    const __nv_bfloat16 *wk, *wq, *x;
    Scratch* s;
};
struct Params {
    const __nv_bfloat16* deg_inv;
    const int *src, *dst;
    __nv_bfloat16* out;
    uint32_t dhi;
    int E;
    CUtensorMap tm_out;
    CUtensorMap tm_outc;
    CUtensorMap tm_w[3];
};
static_assert(offsetof(Params, tm_outc) == offsetof(Params, tm_out) + 128, "layout");
#define SC_PAIR (blockIdx.x < 104)
#define SC_TAIL (blockIdx.x >= NCTA - 2)
#define SC_LAST (blockIdx.x == NCTA - 1)
#define SC_HELP (SC_PAIR && rank)
#define SC_OWNER (!SC_HELP && !SC_LAST)
#define SC_QT1 (26 + (int)(blockIdx.x >> 1))
#define SC_QT0 (SC_PAIR ? (rank ? (int)(blockIdx.x >> 2) : SC_QT1) : SC_TAIL ? 78 : (int)blockIdx.x - 104)
#define SC_NKV (SC_LAST ? 50 : 75)
#define SC_CLS (SC_PAIR ? (rank ? 0x120 ^ (blockIdx.x & 2) * 0x80 : 0x430) | (blockIdx.x & 2) >> 1 : SC_LAST ? 0x10 : 0x432)
#define SC_NW (SC_PAIR ? 8 : SC_LAST ? 0 : 4)
#define SC_ZB (2 * SC_QT1 + 1 - (int)rank)
#define SC_TZB(k) (rank && !(k) ? 156 : 2 * (k) - (int)rank)

__global__ void __cluster_dims__(2, 1, 1) __launch_bounds__(384, 1) k_main(const __grid_constant__ Hot H, const __grid_constant__ Params P) {
    extern __shared__ __align__(1024) uint8_t smem[];
    const uint32_t sb = (uint32_t)__cvta_generic_to_shared(smem);
    const int tid = threadIdx.x, wg = __shfl_sync(~0u, tid >> 7, 0);
    const int lane = tid & 31, g = lane >> 2, q = lane & 3;
    const uint32_t rank = blockIdx.x & 1;
    const uint32_t bar_full = sb + SM_BAR, bar_q = bar_full + 32, bar_go = bar_full + 48;
    const uint32_t bar_pin = bar_full + 56;
    const uint32_t bar_qfree = bar_full + 72, bar_pdone = bar_full + 88, bar_zst = bar_full + 104, bar_rfree = bar_full + 120;
    const uint32_t bar_empty = bar_full + 128, bar_end = bar_full + 160, s_tm = bar_full + 184, bar_x = bar_full + 192;
    const uint32_t bar_a = sb + SM_ML;

    const int t = tid & 127, warp = __shfl_sync(~0u, t >> 5, 0);
    int ep = 0;
    if (wg & 2) {
        unsigned done;
        {
            uint4 ra[2], rb[2], rk[5][2];
            if (blockIdx.x < 128) {
                const int e = (blockIdx.x >> 4) * 32 + (g >> 1) * 8 + (blockIdx.x & 8) / 2 + (g & 1);
                const uint4* pq = (const uint4*)(H.wq + e * 256) + warp * 8 + q;
                const uint4* pk = (const uint4*)(H.wk + ((blockIdx.x & 7) * 32 + g) * 256) + warp * 8 + q;
                const uint4* pz = (const uint4*)(H.wk + 255 * 256) + warp * 8 + q;
#pragma unroll
                for (int s = 0; s < 2; s++) {
                    ra[s] = ldg_pinned(pq + 4 * s);
                    rb[s] = ldg_pinned(pq + 4 * s + 64);
#pragma unroll
                    for (int n = 0; n < 4; n++) rk[n][s] = ldg_pinned(pk + 4 * s + n * 256);
                    rk[4][s] = ldg_pinned(pz + 4 * s);
                }
            }
            asm volatile("{\n.reg .pred p;\nsetp.eq.s32 p, %2, 0;\nmov.u32 %0, 0;\n@p ld.global.cg.u32 %0, [%1];\n}\n" : "=r"(done) : "l"(&g_sync[SY_DONE * 32]), "r"(lane) : "memory");
            bar_arrive(BAR_X, 384);
            if (warp == 0 && elect()) {
#pragma unroll
                for (int i = 0; i < 21; i++) mbar_init(bar_full + 8 * i, i < 9 ? 1 : i < 16 ? 4 : i == 20 ? 11 : SC_TAIL ? 4 : 8);
#pragma unroll
                for (int i = 0; i < 4; i++) mbar_init(bar_a + 8 * i, 1);
                mbar_expect_tx(bar_pin, QB_BYTES / 2 + 512); mbar_expect_tx(bar_pin + 8, QB_BYTES / 2);
                asm volatile("fence.mbarrier_init.release.cluster;\n" ::: "memory");
            }
            __syncwarp();
            asm volatile("barrier.cluster.arrive.relaxed.aligned;\n" ::: "memory");
            if (blockIdx.x < 128) {
                float c[5][4] = {};
#pragma unroll
                for (int s = 0; s < 2; s++) {
#pragma unroll
                    for (int n = 0; n < 5; n++) mma16816(c[n], ra[s].x, rb[s].x, ra[s].y, rb[s].y, rk[n][s].x, rk[n][s].y);
#pragma unroll
                    for (int n = 0; n < 5; n++) mma16816(c[n], ra[s].z, rb[s].z, ra[s].w, rb[s].w, rk[n][s].z, rk[n][s].w);
                }
#pragma unroll
                for (int i = 0; i < 4; i++) {
                    const int r = i & 2, n = (i & 1) * 2;
                    sts128(sb + SM_KV + 3 * KV_BYTES + QB_BYTES + i * 2048 + t * 16, __float_as_uint(c[n][r] - c[4][r]), __float_as_uint(c[n][r + 1] - c[4][r]),
                           __float_as_uint(c[n + 1][r] - c[4][r]), __float_as_uint(c[n + 1][r + 1] - c[4][r]));
                }
            }
        }
        asm volatile("setmaxnreg.dec.sync.aligned.u32 %0;\n" ::"n"(REG_P));
        if (blockIdx.x < 128) {
            bar_sync(BAR_WG2, 128);
            float4 v[4];
#pragma unroll
            for (int i = 0; i < 4; i++) v[i] = lds128f(sb + SM_KV + 3 * KV_BYTES + QB_BYTES + (warp & 2) * 2048 + (lane & 1) * 2048 + i * 512 + ((warp & 1) * 16 + (lane >> 1)) * 16);
            constexpr float SC = SCALE_LOG2 / KV_SCALE;
            const int r = (warp & 1) * 4 + (lane >> 3);
            *(uint2*)(g_w + tile_off((blockIdx.x >> 3) * 16 + (warp & 2) * 4 + r, (blockIdx.x & 7) * 4 + ((lane >> 1) & 3)) + (lane & 1) * 8) =
                make_uint2(pack_f16_sat(((v[0].x + v[1].x) + (v[2].x + v[3].x)) * SC, ((v[0].y + v[1].y) + (v[2].y + v[3].y)) * SC) | 1,
                           pack_f16_sat(((v[0].z + v[1].z) + (v[2].z + v[3].z)) * SC, ((v[0].w + v[1].w) + (v[2].w + v[3].w)) * SC) | 1);
            if (warp != 1) {
                bar_arrive(BAR_AUX, 128);
            } else {
                bar_sync(BAR_AUX, 128);
                if (elect()) { red_add(&g_sync[SY_DONE * 32 + 4 + (blockIdx.x >> 5)]); }
                __syncwarp();
            }
        }
        else bar_sync(BAR_WG2, 128);
        if (warp == 1) bar_arrive(BAR_GO, 160);
        auto load_a = [&](int j) {
            if (elect()) {
                mbar_expect_tx(bar_a + 8 * j, QB_BYTES);
                bulk_g2s(sb + SM_KV + j * KV_BYTES, g_w + j * QB_BYTES, QB_BYTES, bar_a + 8 * j);
            }
            __syncwarp();
        };
        if (warp == 0) {
            auto poll = [&]() { int c; asm volatile("ld.relaxed.gpu.global.s32 %0, [%1];\n" : "=r"(c) : "l"(&g_sync[SY_DONE * 32 + 4 + (lane & 3)]) : "memory"); return c; };
#pragma unroll 1
            for (int j = 0; j < 4;) {
#pragma unroll 1
                for (const uint32_t mk = __ballot_sync(~0u, poll() >= 32) & 15; (mk >> j) & 1; j++) load_a(j);
            }
        } else if (warp & 1) {
#pragma unroll 1
            for (int j = 0, n = 0; j < 4;) {
                mbar_wait_bounded(bar_a + 8 * j, n & 1);
                uint32_t ok = 1;
#pragma unroll
                for (int i = 0; i < 16; i++) {
                    uint32_t v;
                    asm volatile("ld.shared.u32 %0, [%1];\n" : "=r"(v) : "r"(sb + SM_KV + j * KV_BYTES + (warp & 2) * 8192 + i * 1024 + lane * 32 + g * 4) : "memory");
                    ok &= v;
                }
                asm volatile("{\n.reg .pred p;\nsetp.ne.u32 p, %0, 0;\nbar.red.and.pred p, %1, 64, p;\nselp.u32 %0, 1, 0, p;\n}\n" : "+r"(ok) : "n"((int)BAR_WG2) : "memory");
                if (__any_sync(~0u, ok)) {
                    if (warp == 1 && elect()) asm volatile("mbarrier.arrive.shared::cta.b64 _, [%0];\nmbarrier.inval.shared::cta.b64 [%1];\n" ::"r"(bar_full + 8 * j), "r"(bar_a + 8 * j) : "memory");
                    __syncwarp();
                    j++; n = 0;
                } else {
                    asm volatile("{\n.reg .pred p;\nsetp.gt.s32 p, %0, 1000000;\n@p trap;\n}\n" ::"r"(++n) : "memory");
                    fence_async_smem();
                    if (warp == 1) load_a(j);
                }
            }
        }
        done = __shfl_sync(~0u, done, 0);
        ep = (int)(done / NCTA) + 1;
        asm volatile("barrier.cluster.wait.acquire.aligned;\n" ::: "memory");
        if (warp == 0) {
            asm volatile("st.shared.u64 [%0], %1;\n" ::"r"(s_tm), "l"(&P.tm_outc) : "memory");
            __syncwarp();
            if (elect()) {
                const uint8_t* base = (const uint8_t*)H.s;
                uint32_t cls = SC_CLS, bytes = KV_BYTES, step = 5 * KV_BYTES;
                const uint8_t* src = base;
                bool tick;
                int next = 0;
                const int nit = SC_NKV + SC_NW;
#pragma unroll 1
                for (int j = 0; j < nit; j++) {
                    const uint32_t slot = sb + SM_KV + (j & 3) * KV_BYTES, fb = bar_full + 8 * (j & 3);
                    if (j == next) {
                        const int k = j - SC_NKV;
                        const int sw = SC_HELP ? j - 25 : -1;
                        next = j + 1;
                        tick = j >= 3 && k < 0 && (sw | 1) != 3 && !SC_TAIL;
                        if (j >= 3 && (unsigned)sw >= 5) next = k >= 0 ? next : j < GO0 ? GO0 : j < 25 ? 25 : j < GO1 ? GO1 : j < 49 ? 49 : j < 50 ? 50 : 75;
                        if (j == 0 || j == 25 || j == 50) { src = base + (4096 + (cls & 15) * KV_BYTES); cls >>= 4; }
                        if (SC_TAIL ? j == nit - 1 : j == GO0 || j == GO1) mbar_arrive(bar_go);
                        int fo = -1, fv = 1;
                        if (j < 3) { fo = (SY_H0 + 5 * j + (SC_CLS & 15)) * 32; fv = 5; }
                        if (j == 3) { fo = SY_H1 * 32; fv = 79; }
                        if (sw == 1) fo = 25 * 32 + SC_QT1;
                        if (k == 0) fo = SY_B * 32;
                        if (k == 1 && !SC_PAIR) { fo = SY_AUX0 * 32; fv = NAUX; }
                        if (k == 2 && SC_PAIR) { fo = SY_AUX * 32; fv = NAUX / 3; }
                        if (fo >= 0) {
                            flag_wait(g_sync + fo, fv * ep);
                            fence_async_global();
                        }
                        if (sw == 2 || (k == 2 && !SC_TAIL)) {
                            uint32_t qs = sw == 2 ? offsetof(Scratch, q) + (2 * SC_QT1 + 1) * QB_BYTES : SC_PAIR ? offsetof(Scratch, agg) + SC_ZB * QB_BYTES : offsetof(Scratch, part) + SC_QT0 * (4 * PART_BYTES);
#pragma unroll 1
                            for (int w = 0; w < (k == 2 && SC_PAIR ? 1 : 2); w++) {
                                mbar_wait_sleep(bar_qfree + 8 * w, k == 2 && SC_HELP);
                                mbar_expect_tx(bar_q + 8 * w, SC_PAIR ? QB_BYTES : PART_BYTES);
                                if (!SC_PAIR) bulk_g2s(sb + SM_ML + w * 512, base + (qs + (w ? -512 : QB_BYTES)), 512, bar_q + 8 * w);
                                bulk_g2s(sb + SM_Q + w * QB_BYTES, base + qs, QB_BYTES, bar_q + 8 * w);
                                qs += sw == 2 ? -QB_BYTES : PART_BYTES + 512;
                            }
                        }
                        if ((sw | 1) == 3) {
                            mbar_wait_sleep(bar_pdone + 8 * (sw - 2), 0);
                            bulk_s2g(g_part + (blockIdx.x - 3 + sw) * PART_BYTES, slot, PART_BYTES);
                            asm volatile("cp.async.bulk.wait_group.read 0;\n" ::: "memory");
                        }
                        if (sw == 5) {
                            asm volatile("cp.async.bulk.wait_group 0;\n" ::: "memory");
                            red_release(&g_sync[SY_PART * 32]);
                        }
                        if (k == 0) {
                            asm volatile("prefetch.tensormap [%0];\n" ::"l"(&P.tm_outc) : "memory");
                            src = g_w + (12 - SC_NW) * QB_BYTES; bytes = step = QB_BYTES;
                        }
                        if (k == 2) next = SC_TAIL ? nit - 1 : nit;
                    }
                    mbar_wait_sleep(fb + (bar_empty - bar_full), (j >> 2) & 1);
                    mbar_expect_tx(fb, bytes);
                    if (tick)
                        asm volatile("{\n.reg .pred p;\n.reg .u32 a, b;\nmov.u32 a, %%globaltimer_lo;\nnot.b32 b, a;\nand.b32 b, b, %0;\nshr.u32 b, b, 1;\nnanosleep.u32 b;\n"
                                     "L:\nmov.u32 b, %%globaltimer_lo;\nxor.b32 b, b, a;\nsetp.le.u32 p, b, %0;\n@p nanosleep.u32 %1;\n@p bra L;\n}\n" ::"n"(TICK - 1), "n"(TSL) : "memory");
                    bulk_g2s(slot, src, bytes, fb);
                    src += step;
                }
            }
        } else {
            if (warp == 2 && SC_OWNER) {
                uint8_t* dst = g_hz + 4096 + h_unit(SC_QT0, 0) * 8192;
                auto send = [&](int u0, int u1) {
#pragma unroll
                    for (int u = u0; u < u1; u++) {
                        bulk_s2g(dst + u * (78 * 8192), sb + SM_Q + u * 8192, 8192);
                        asm volatile("cp.async.bulk.wait_group 0;\n" ::: "memory");
                    }
                };
                int* f0 = &g_sync[(SY_H0 + SC_QT0 / 5) * 32];
                bar_sync(BAR_H0, 64);
                if (elect()) {
                    send(0, 1);
                    if (SC_QT0 < 65) red_release(f0);
                }
                bar_sync(BAR_H1, 160);
                if (elect()) {
                    if (!SC_TAIL) send(1, 4);
                    mbar_arrive(bar_q);
                }
                bar_sync(BAR_H2, 160);
                if (elect()) {
                    if (!SC_TAIL) { send(4, 8); mbar_arrive(bar_q + 8); }
                    red_release(&g_sync[SY_H1 * 32]);
                }
                __syncwarp();
            }
        }
    } else {
        const uint32_t sq = sb + SM_Q + wg * QB_BYTES;
        const uint32_t qbar = bar_q + 8 * wg;
        const uint32_t dq0 = __shfl_sync(~0u, ((sq & 0x3FFFF) >> 4) | (64u << 16), 0);
        const uint32_t dk0 = __shfl_sync(~0u, (((sb + SM_KV) & 0x3FFFF) >> 4) | (64u << 16), 0);
        float o[128];
        int it = 4;
        const uint32_t dhi = P.dhi;
        auto release = [&](int st, int n = 1) {
            if (n == 1) asm volatile("{\n.reg .pred p;\nelect.sync _|p, -1;\n@p mbarrier.arrive.shared::cta.b64 _, [%0];\n}\n" ::"r"(bar_empty + 8 * st) : "memory");
            else asm volatile("{\n.reg .pred p;\nelect.sync _|p, -1;\n@p mbarrier.arrive.shared::cta.b64 _, [%0], 2;\n}\n" ::"r"(bar_empty + 8 * st) : "memory");
        };
        const bool active = !(SC_TAIL && wg == 1);
        auto pp_sync = [&]() { if (!SC_TAIL) bar_sync(BAR_PP0 + wg, 256); };
        auto pp_arrive = [&]() { if (!SC_TAIL) bar_arrive(BAR_PP1 - wg, 256); };
        auto warp_arrive = [&](uint32_t bar) {
            __syncwarp();
            asm volatile("{\n.reg .pred p;\nelect.sync _|p, -1;\n@p mbarrier.arrive.shared::cta.b64 _, [%0];\n}\n" ::"r"(bar + 8 * wg) : "memory");
        };
        auto peer_arrive = [&]() {
            asm volatile("{\n.reg .pred p;\n.reg .b32 a;\nelect.sync _|p, -1;\nmapa.shared::cluster.u32 a, %0, %1;\n"
                         "@p mbarrier.arrive.shared::cluster.b64 _, [a];\n}\n" ::"r"(bar_rfree), "r"(rank ^ 1) : "memory");
        };
        float qs = 1.f;
        uint32_t qr[4 * NQR + 4];
        auto stage_q = [&]() {
            int k = dhi & 1;
            uint32_t big;
#pragma unroll 1
            do {
                if (k) {
                    qs *= 16.f;
#pragma unroll
                    for (int i = 0; i < 128; i++) o[i] *= 0.0625f;
                }
                big = 0;
                auto pk = [&](int i) { return QRND(pack_f16_sat(o[i], o[i + 1])); };
#pragma unroll
                for (int i = 0; i < 16; i++) {
                    const uint32_t v0 = pk(8 * i), v1 = pk(8 * i + 2), v2 = pk(8 * i + 4) | (i == 15 ? k : 0), v3 = pk(8 * i + 6);
                    stmatrix_x4(sq + warp * 8192 + tile_off(lane & 15, 2 * i + (lane >> 4)), v0, v1, v2, v3);
                    big |= v0 | v1; big |= v2 | v3;
                    if (const int r = QREG(i); r >= 0) { qr[4 * r] = v0; qr[4 * r + 1] = v1; qr[4 * r + 2] = v2; qr[4 * r + 3] = v3; }
                }
                k++;
            } while (__any_sync(~0u, (big & 0x40004000u) && k < 8));
        };
        uint32_t s[20];
        auto issue_qk = [&](int st, int sh = 24) {
            const uint64_t kb = mkaddr(dk0 + st * (KV_BYTES >> 4), dhi);
            const uint64_t qd = mkaddr(dq0 + ((uint32_t)it >> sh), dhi);
            wgmma_ss_n80_init(s, qd, kb);
#pragma unroll
            for (int j = 1; j < 16; j++) {
                const int kk = j == 8 ? 15 : j < 8 ? j : j - 1;
                const int r = QREG(kk);
                if (r >= 0) wgmma_rs_n80(s, qr[4 * r], qr[4 * r + 1], qr[4 * r + 2], qr[4 * r + 3], kb + ((kk >> 2) * 64 + (kk & 3) * 2));
                else wgmma_ss_n80(s, qd + ((kk >> 2) * 64 + (kk & 3) * 2), kb + ((kk >> 2) * 64 + (kk & 3) * 2));
            }
            wg_commit();
        };

        {
            const int rb = (2 * SC_QT0 + wg) * 64 + warp * 16;
            const uint32_t xbar = bar_x + 32 * wg + 8 * warp;
            if (elect()) {
                mbar_init(xbar, 1);
                asm volatile("fence.mbarrier_init.release.cluster;\nfence.proxy.async.shared::cta;\n" ::: "memory");
                mbar_expect_tx(xbar, rb < NN ? 8192 : 0);
            }
            asm volatile("barrier.cluster.arrive.relaxed.aligned;\n" ::: "memory");
            if (wg == 1) pp_arrive();
            bar_sync(BAR_X, 384);
            if (wg == 1) bar_sync(BAR_GO, 160);
            if (rb < NN && elect()) bulk_g2s(sq + warp * 8192, H.x + (size_t)rb * 256, 8192, xbar);
            if (rb >= NN) {
#pragma unroll 1
                for (int i = 0; i < 16; i++) sts128(sq + warp * 8192 + i * 512 + lane * 16, 0, 0, 0, 0);
            }
            __syncwarp();
            mbar_wait(xbar, 0);
            uint4 xa[8], xb[8];
#pragma unroll
            for (int s = 0; s < 8; s++) {
                xa[s] = lds128(sq + (warp * 16 + g) * 512 + (4 * s + q) * 16);
                xb[s] = lds128(sq + (warp * 16 + g + 8) * 512 + (4 * s + q) * 16);
            }
            float sm[2][4], sq2[2][4][4];
#pragma unroll
            for (int i = 0; i < 4; i++) {
                sm[0][i] = sm[1][i] = 0.f;
#pragma unroll
                for (int k = 0; k < 4; k++) sq2[0][k][i] = sq2[1][k][i] = 0.f;
            }
#pragma unroll
            for (int s = 0; s < 8; s++) {
#pragma unroll
                for (int hh = 0; hh < 2; hh++) {
                    const uint4 v = hh ? xb[s] : xa[s];
                    mma16816(sm[hh], v.x, v.y, v.z, v.w, 0x3F803F80u, 0x3F803F80u);
                    mma1688(sq2[hh][0], v.x, v.y, v.x); mma1688(sq2[hh][1], v.x, v.y, v.y);
                    mma1688(sq2[hh][2], v.z, v.w, v.z); mma1688(sq2[hh][3], v.z, v.w, v.w);
                }
            }
            float inv[2], off[2];
#pragma unroll
            for (int hh = 0; hh < 2; hh++) {
                const float mean = (sm[hh][0] + sm[hh][2]) * (1.f / 256.f);
                const float d0 = (sq2[hh][0][0] + sq2[hh][2][0]) + (sq2[hh][1][2] + sq2[hh][3][2]);
                const float d1 = (sq2[hh][0][1] + sq2[hh][2][1]) + (sq2[hh][1][3] + sq2[hh][3][3]);
                const float ss = __shfl_sync(~0u, (g & 1) ? d1 : d0, g * 4 + (g >> 1));
                const float var = fmaxf(ss * (1.f / 256.f) - mean * mean, 0.f);
                float sd;
                asm("sqrt.approx.ftz.f32 %0, %1;\n" : "=f"(sd) : "f"(bf_round(bf_round(var) + 1e-5f)));
                asm("rcp.approx.ftz.f32 %0, %1;\n" : "=f"(inv[hh]) : "f"(bf_round(sd)));
                off[hh] = -mean * inv[hh];
            }
            uint32_t a[64];
#pragma unroll
            for (int s = 0; s < 8; s++) {
                a[8 * s] = xa[s].x; a[8 * s + 1] = xb[s].x; a[8 * s + 2] = xa[s].y; a[8 * s + 3] = xb[s].y;
                a[8 * s + 4] = xa[s].z; a[8 * s + 5] = xb[s].z; a[8 * s + 6] = xa[s].w; a[8 * s + 7] = xb[s].w;
            }
            fence_regs(a);
            if (wg == 1 && __any_sync(~0u, inv[0] + inv[1] != -1.f)) bar_arrive(BAR_ST, 256);
            asm volatile("setmaxnreg.inc.sync.aligned.u32 %0;\n" ::"n"(REG_C));
            fence_regs(a);
#pragma unroll
            for (int i = 0; i < 64; i++)
                a[i] = pack_f16(fmaf(bf_lo(a[i]), inv[i & 1], off[i & 1]), fmaf(bf_hi(a[i]), inv[i & 1], off[i & 1]));
            if (SC_OWNER) {
                const uint32_t ko = (q & 2) ? KV_OFF2 : KV_OFF2 | NEG2;
#pragma unroll
                for (int i = 0; i < 16; i++) {
                    const uint32_t mk = (i == 15 && q == 3) ? 0xFFFFu : ~0u;
                    stmatrix_x4(sq + warp * 8192 + tile_off(lane & 15, 2 * i + (lane >> 4)), kvf(a[4 * i], ko), kvf(a[4 * i + 1], ko),
                                kvf(a[4 * i + 2] & mk, ko), kvf(a[4 * i + 3] & mk, ko));
                }
                fence_async_smem();
                if (tid < 32) bar_arrive(BAR_H0, 64);
                bar_arrive(wg ? BAR_H2 : BAR_H1, 160);
            }
            asm volatile("barrier.cluster.wait.acquire.aligned;\n" ::: "memory");
            if (wg == 0) bar_sync(BAR_ST, 256);
            if (active) {
                fence_regs(a);
#pragma unroll
                for (int c = 0; c < 4; c++) {
                    if (c == 1) {
                        if (wg == 1) {
                            wg_wait<0>();
                            release(0);
                        }
                        pp_sync();
                    }
                    mbar_wait(bar_full + 8 * c, 0);
                    const uint64_t wb = mkaddr(dk0 + c * (KV_BYTES >> 4), dhi);
                    wg_fence();
#pragma unroll
                    for (int kk = 0; kk < 4; kk++) {
                        if (c | kk) wgmma_rs_n256_tb(o, a[16 * c + 4 * kk], a[16 * c + 4 * kk + 1], a[16 * c + 4 * kk + 2], a[16 * c + 4 * kk + 3], wb + kk * 512);
                        else wgmma_rs_n256_tb_init(o, a[0], a[1], a[2], a[3], wb);
                    }
                    wg_commit();
                    if (c > 0) { wg_wait<1>(); if (c > 1 || wg == 0) release(c - 1); }
                }
                if (wg == 0) pp_arrive();
                wg_wait<0>();
                fence_regs(o);
                release(3);
                if (SC_OWNER) mbar_wait(qbar, 0);
                stage_q();
                fence_async_smem();
                bar_sync(BAR_WG0 + wg, 128);
                mbar_wait(bar_full, 1);
                wg_fence();
                issue_qk(0);
                if (wg == 1) pp_arrive();
            } else {
                peer_arrive();
            }
        }

        uint32_t p[20];
        float m0 = 0.f, m1 = 0.f, e0, e1, l0, l1;
        uint32_t plim;
        uint32_t qphase = (SC_OWNER && active) ? 1 : 0;
        auto issue_pv = [&](int st, int acc) {
            const uint64_t vb = mkaddr(dk0 + st * (KV_BYTES >> 4), dhi);
            wgmma_rs_n256_tb_pred(o, p[0], p[1], p[2], p[3], vb, acc);
#pragma unroll
            for (int kk = 1; kk < 5; kk++)
                wgmma_rs_n256_tb(o, p[4 * kk], p[4 * kk + 1], p[4 * kk + 2], p[4 * kk + 3], vb + kk * 512);
            wg_commit();
        };
        auto mq_addr = [&](int ln) { return sq + warp * 8192 + tile_off(ln >> 2, 31) + 12; };
        auto exceeds = [&](const uint32_t (&p)[20]) {
            uint32_t a = __vimax3_s16x2(P_LIMIT, p[0], p[1]), b = __vimax3_s16x2(p[2], p[3], p[4]);
#pragma unroll
            for (int i = 5; i < 17; i += 4) { a = __vimax3_s16x2(a, p[i], p[i + 1]); b = __vimax3_s16x2(b, p[i + 2], p[i + 3]); }
            a = __vimax3_s16x2(a, p[17], p[18]);
            return __any_sync(~0u, __vimax3_s16x2(a, b, p[19]) != plim);
        };
        auto remax = [&](float& a, float& b, bool store) {
            const int ln = lane_now();
            asm volatile("" : "+f"(qs));
            uint32_t ha = s[0], hb = s[1];
#pragma unroll
            for (int i = 1; i < 10; i++) { ha = hmax2_f16(ha, s[2 * i]); hb = hmax2_f16(hb, s[2 * i + 1]); }
            ha = hmax2_f16(__byte_perm(ha, hb, 0x5410), __byte_perm(ha, hb, 0x7632));
            ha = hmax2_f16(ha, __shfl_xor_sync(~0u, ha, 1));
            ha = hmax2_f16(ha, __shfl_xor_sync(~0u, ha, 2));
            a = fmaxf(a, f16_lo(ha) * qs - e0 + REF_UP); b = fmaxf(b, f16_hi(ha) * qs - e1 + REF_UP);
            const float qi = __uint_as_float(0x7F000000u - __float_as_uint(qs)) * (-1.f / KV_OFF);
            const uint32_t u = pack_f16((m0 + a) * qi, (m1 + b) * qi);
            const float g0 = (m0 + a) + KV_OFF * qs * f16_lo(u), g1 = (m1 + b) + KV_OFF * qs * f16_hi(u);
            const bool x0 = fabsf(g0) <= 1.f, x1 = fabsf(g1) <= 1.f;
            if (x0) a -= g0;
            if (x1) b -= g1;
            const float da = a + e0, db = b + e1;
            m0 += a; m1 += b;
            e0 = x0 ? 0.f : g0; e1 = x1 ? 0.f : g1;
            plim = (x0 && x1 && qs == 1.f) ? P_LIMIT : 0u;
            asm volatile("{\n.reg .pred p;\nsetp.ne.s32 p, %3, 0;\n@p st.shared.u16 [%0], %1;\n@p st.shared.u16 [%0 + 4096], %2;\n}\n"
                         ::"r"(mq_addr(ln) + 2), "h"((unsigned short)u), "h"((unsigned short)(u >> 16)), "r"((int)(store && (ln & 3) == 0)) : "memory");
#pragma unroll
            for (int i = 0; i < 10; i++) {
                p[2 * i] = pack_f16(ex2(fmaf(f16_lo(s[2 * i]), qs, -da)), ex2(fmaf(f16_hi(s[2 * i]), qs, -da)));
                p[2 * i + 1] = pack_f16(ex2(fmaf(f16_lo(s[2 * i + 1]), qs, -db)), ex2(fmaf(f16_hi(s[2 * i + 1]), qs, -db)));
            }
            fence_regs(p);
            fence_async_smem();
            __syncwarp();
        };

        auto row_sums = [&](float& z0, float& z1, int q) {
            z0 = quad_last(o[125]); z1 = quad_last(o[127]);
            l0 = z0 * (KV_SCALE / KV_OFF); l1 = z1 * (KV_SCALE / KV_OFF);
            if (!(q & 2)) { z0 = -z0; z1 = -z1; }
        };
        auto cut = [&]() { asm volatile("{\n.reg .pred p;\nsetp.lt.s32 p, %0, 0;\nL:\n@p pmevent 0;\n@p bra L;\n}\n" ::"r"(it) : "memory"); };
        auto stats = [&](int q) { return (q & 2) ? ((q & 1) ? l1 : m1) : ((q & 1) ? l0 : m0); };
        const int nseg = SC_HELP ? 2 : 1;
        if (active) {
#pragma unroll 1
        for (int seg = 0;; seg++) {
            wg_wait<0>();
            fence_regs(s);
            e0 = e1 = 0.f;
            const int it0 = it, itl = __shfl_sync(~0u, seg + 1 < nseg ? 3 + 25 : 3 + SC_NKV, 0);
            const int itx = (wg == 1 && seg + 1 == nseg) ? itl : -1;
            bool redo = true, have = !seg;
#pragma unroll 1
            for (;;) {
                if (!have) {
#pragma unroll
                    for (int i = 0; i < 20; i++) p[i] = ex2_f16(s[i]);
                    redo = exceeds(p);
                }
                if (redo) {
                    float d0 = it != it0 ? 0.f : -INFINITY, d1 = d0;
                    remax(d0, d1, it != itl);
                    if (it != it0) {
                        const float a0 = ex2(-d0), a1 = ex2(-d1);
#pragma unroll
                        for (int i = 0; i < 32; i++) { o[4 * i] *= a0; o[4 * i + 1] *= a0; o[4 * i + 2] *= a1; o[4 * i + 3] *= a1; }
                    } else if (SC_OWNER) {
                        warp_arrive(bar_pdone);
                    }
                }
                if (it == itl) break;
                const int stp = it & 3;
                it++;
                pp_sync();
                fence_regs(o); fence_regs(p);
                have = SC_TAIL || it == itx;
                if (!have) {
                    wg_fence();
                    issue_pv(stp, it - 1 - it0);
                    mbar_wait(bar_full + 8 * (it & 3), (it >> 2) & 1);
                    wg_fence();
                    issue_qk(it & 3);
                    pp_arrive();
                    wg_wait<0>();
                    fence_regs(s); fence_regs(o); fence_regs(p);
                    if (it == itl) warp_arrive(bar_qfree);
                } else {
                    uint32_t p2[20];
                    const int zero = (uint32_t)it >> 23;
                    mbar_wait(bar_full + 8 * (it & 3), (it >> 2) & 1);
                    wg_fence();
                    issue_qk((it & 3) + zero, 25);
                    if (it == itl) {
                        wg_wait<0>();
                        if (SC_PAIR) peer_arrive(); else warp_arrive(bar_qfree);
                        if (wg) bar_sync(BAR_ST, 256);
                    }
                    wg_fence();
                    issue_pv(stp + zero, it - 1 - it0);
                    pp_arrive();
                    wg_wait<1>();
                    fence_regs(s);
#pragma unroll
                    for (int i = 0; i < 20; i++) p2[i] = ex2_f16(s[i]);
                    redo = exceeds(p2);
                    if (redo) asm volatile("wgmma.wait_group.sync.aligned 0;\nnanosleep.u32 0;\n" ::: "memory");
                    else wg_wait<0>();
                    fence_regs(o); fence_regs(p);
#pragma unroll
                    for (int i = 0; i < 20; i++) p[i] = p2[i];
                }
                release(stp);
            }
            if (seg + 1 < nseg) pp_sync();
            fence_regs(o); fence_regs(p);
            wg_fence();
            issue_pv(it & 3, 1);
            asm volatile("{\n.reg .pred p;\nsetp.ne.s32 p, %0, 0;\n@p bar.arrive %1, 256;\n}\n" ::"r"((int)(seg + 1 == nseg && (wg ? SC_PAIR : !SC_TAIL))), "r"(BAR_ST + wg) : "memory");
            it++;
            if (seg + 1 == nseg) break;
            const int is = it - 2 + wg, ln = lane_now();
            uint32_t dst = sb + SM_KV + (is & 3) * KV_BYTES + wg * 512 + warp * 8192 + ln * 16;
            uint32_t dml = sb + SM_KV + (is & 3) * KV_BYTES + (wg ? 0 : QB_BYTES) + warp * 128 + ln * 4;
            asm volatile("" : "+r"(dst), "+r"(dml));
            mbar_wait(qbar, qphase); qphase ^= 1;
            uint32_t u0, u1;
            asm volatile("ld.shared.u32 %0, [%2];\nld.shared.u32 %1, [%2 + 4096];\n" : "=r"(u0), "=r"(u1) : "r"(mq_addr(ln)) : "memory");
#pragma unroll
            for (int i = 0; i < 16; i++)
                if (const int r = QREG(i); r >= 0)
                    asm volatile("ldmatrix.sync.aligned.m8n8.x4.shared.b16 {%0, %1, %2, %3}, [%4];\n" : "=r"(qr[4 * r]), "=r"(qr[4 * r + 1]), "=r"(qr[4 * r + 2]), "=r"(qr[4 * r + 3])
                                 : "r"(sq + warp * 8192 + tile_off(ln & 15, 2 * i + (ln >> 4))) : "memory");
            mbar_wait(bar_full + 8 * (it & 3), (it >> 2) & 1);
            mbar_wait(bar_empty + 8 * ((it - 2) & 3), ((it - 2) >> 2) & 1);
            wg_wait<0>();
            fence_regs(o);
            float z0, z1;
            row_sums(z0, z1, ln);
            release((it - 1) & 3);
            wg_fence();
            issue_qk(it & 3);
            pp_arrive();
            bar_sync(BAR_WG0 + wg, 128);
#pragma unroll
            for (int i = 0; i < 128; i++) o[i] -= (i & 2) ? z1 : z0;
            fence_regs(o);
            cut();
            asm volatile("st.shared.f32 [%0], %1;\n" ::"r"(dml), "f"(stats(ln)) : "memory");
            qs = __uint_as_float(0x3F800000u + ((u0 & 7) << 25));
            m0 = -KV_OFF * qs * f16_hi(u0); m1 = -KV_OFF * qs * f16_hi(u1);
            plim = fmaxf(fabsf(m0), fabsf(m1)) <= 3072.f && qs == 1.f ? P_LIMIT : 0u;
            uint32_t v[2][8] = {};
#pragma unroll
            for (int i = 0; i < 8; i++) {
                uint32_t *w = v[i & 1], *u = v[(i & 1) ^ 1];
#pragma unroll
                for (int j = 0; j < 8; j++) w[j] = pack_bf16(o[16 * i + 2 * j], o[16 * i + 2 * j + 1]);
                sts128(dst + i * 1024, w[0], w[1], w[2], w[3]);
                sts128(dst + i * 1024 + 512, w[4], w[5], w[6], w[7]);
                if (i) asm volatile("{\n.reg .pred p;\nsetp.lt.s32 p, %9, 0;\nL:\n@p st.shared.v4.u32 [%0], {%1, %2, %3, %4};\n@p st.shared.v4.u32 [%0 + 16], {%5, %6, %7, %8};\n@p bra L;\n}\n"
                             ::"r"(dst), "r"(u[0]), "r"(u[1]), "r"(u[2]), "r"(u[3]), "r"(u[4]), "r"(u[5]), "r"(u[6]), "r"(u[7]), "r"(it) : "memory");
            }
            fence_async_smem();
            warp_arrive(bar_pdone);
        }
        constexpr int IW = 4 + 75;
        uint32_t a[64];
        const int lane = lane_now(), t = warp * 32 + lane;
        if (wg == 0 && (SC_PAIR || SC_LAST)) {
            uint32_t rq, rml, rbar;
            asm volatile("mapa.shared::cluster.u32 %0, %3, %6;\nmapa.shared::cluster.u32 %1, %4, %6;\nmapa.shared::cluster.u32 %2, %5, %6;\n"
                         : "=r"(rq), "=r"(rml), "=r"(rbar) : "r"(sb + SM_Q + QB_BYTES + warp * 8192 + lane * 16), "r"(sb + SM_ML + 512 + t * 4),
                         "r"(bar_pin), "r"(rank ^ 1));
            auto send = [&](int i) {
                asm volatile("st.async.weak.shared::cluster.mbarrier::complete_tx::bytes.v4.b32 [%0], {%1, %2, %3, %4}, [%5];\n"
                             ::"r"(rq + i * 512), "r"(a[4 * i]), "r"(a[4 * i + 1]), "r"(a[4 * i + 2]), "r"(a[4 * i + 3]), "r"(rbar + (i & 8)) : "memory");
            };
            mbar_wait(bar_rfree, 0);
            wg_wait<0>();
            fence_regs(o);
            release((it - 1) & 3);
            float z0, z1;
            row_sums(z0, z1, lane);
            asm volatile("st.async.weak.shared::cluster.mbarrier::complete_tx::bytes.f32 [%0], %1, [%2];\n" ::"r"(rml), "f"(stats(lane)), "r"(rbar) : "memory");
#pragma unroll
            for (int i = 0; i < 16; i++) {
                a[4 * i] = pack_bf16(o[8 * i] - z0, o[8 * i + 1] - z0); a[4 * i + 1] = pack_bf16(o[8 * i + 2] - z1, o[8 * i + 3] - z1);
                a[4 * i + 2] = pack_bf16(o[8 * i + 4] - z0, o[8 * i + 5] - z0); a[4 * i + 3] = pack_bf16(o[8 * i + 6] - z1, o[8 * i + 7] - z1);
                if (i * SND0 / 16 != (i + 1) * SND0 / 16) send(i * SND0 / 16);
                if (i % CUT2 == CUT2 - 1) cut();
            }
            if (SC_PAIR) {
                float z[128];
                const uint32_t dkz = dk0 + ((uint32_t)it >> 24), dqz = dq0 + ((uint32_t)it >> 24);
                auto gemm = [&](int c) {
                    mbar_wait(bar_full + 8 * ((IW + c) & 3), ((IW + c) >> 2) & 1);
                    const uint64_t wb = mkaddr(dkz + ((IW + c) & 3) * (KV_BYTES >> 4), dhi), ab = mkaddr(dqz + c * 64, dhi);
                    wg_fence();
#pragma unroll
                    for (int kk = 0; kk < 4; kk++) {
                        if (c | kk) wgmma_ss_n256_tb(z, ab + kk * 2, wb + kk * 512);
                        else wgmma_ss_n256_tb_init(z, ab, wb);
                    }
                    wg_commit();
                };
                mbar_wait(qbar, qphase);
                bar_sync(BAR_ST + 1, 256);
                gemm(0);
#pragma unroll
                for (int i = SND0; i < 16; i++) send(i);
#pragma unroll
                for (int c = 1; c < 4; c++) { gemm(c); if (c == 3) pp_arrive(); wg_wait<1>(); release((IW + c - 1) & 3, 2); }
                wg_wait<0>();
                fence_regs(z);
                release((IW + 3) & 3, 2);
#pragma unroll
                for (int i = 0; i < 16; i++) {
                    sts128(sq + warp * 8192 + lane * 16 + i * 512, pack_bf16(z[8 * i], z[8 * i + 1]), pack_bf16(z[8 * i + 2], z[8 * i + 3]),
                           pack_bf16(z[8 * i + 4], z[8 * i + 5]), pack_bf16(z[8 * i + 6], z[8 * i + 7]));
                    if (i == 3 || i == 15) bar_arrive(i == 3 ? BAR_BF : BAR_H0, 256);
                    if (i == 3) cut();
                }
            } else {
#pragma unroll
                for (int i = SND0; i < 16; i++) send(i);
            }
        } else {
            const int pair = SC_PAIR;
            const bool glob = !(pair || SC_TAIL);
            const uint32_t ml = sb + SM_ML + (t & ~3) * 4, src = (glob ? sq : sb + SM_Q + QB_BYTES) + warp * 8192 + lane * 16;
            const uint64_t tm = lds64(s_tm);
            wg_wait<0>();
            fence_regs(o);
            release((IW - 1) & 3);
            float c0, c1;
            row_sums(c0, c1, lane);
            mbar_wait(glob ? qbar : bar_pin, glob ? qphase : 0);
            const float4 ps = lds128f(ml + (glob ? wg * 512 : 512));
            auto load = [&](int i) {
                asm volatile("ld.shared.v4.u32 {%0, %1, %2, %3}, [%4];\n" : "=r"(a[4 * i]), "=r"(a[4 * i + 1]), "=r"(a[4 * i + 2]), "=r"(a[4 * i + 3]) : "r"(src + i * 512) : "memory");
            };
#pragma unroll
            for (int i = 0; i < 8; i++) load(i);
            const float n0 = fmaxf(m0, ps.x), n1 = fmaxf(m1, ps.z);
            const float a0 = ex2(m0 - n0), a1 = ex2(m1 - n1), b0 = ex2(ps.x - n0), b1 = ex2(ps.z - n1);
            const float i0 = rcp(l0 * a0 + ps.y * b0), i1 = rcp(l1 * a1 + ps.w * b1);
            const float r0 = a0 * i0, r1 = a1 * i1;
            c0 *= -r0; c1 *= -r1;
            const uint32_t u0 = pack_bf16(b0 * i0, b0 * i0), u1 = pack_bf16(b1 * i1, b1 * i1);
#pragma unroll
            for (int i = 0; i < 32; i++) {
                if (i == 16) {
                    if (!glob) mbar_wait(bar_pin + 8, 0);
#pragma unroll
                    for (int j = 8; j < 16; j++) load(j);
                }
                a[2 * i] = hfma2(a[2 * i], u0, pack_bf16(fmaf(o[4 * i], r0, c0), fmaf(o[4 * i + 1], r0, c0)));
                a[2 * i + 1] = hfma2(a[2 * i + 1], u1, pack_bf16(fmaf(o[4 * i + 2], r1, c1), fmaf(o[4 * i + 3], r1, c1)));
            }
            float y[2][32];
            auto gemm = [&](int c, int kh) {
                if (!kh) mbar_wait(bar_full + 8 * ((IW + c) & 3), (((IW + c) >> 2) & 1) ^ pair);
                const uint64_t wb = mkaddr(dk0 + ((IW + c) & 3) * (KV_BYTES >> 4), dhi - 192);
                wg_fence();
#pragma unroll
                for (int kk = 8 * kh; kk < 8 * kh + 8; kk++) {
                    if (kk) wgmma_rs_n64_tb(y[c & 1], a[4 * kk], a[4 * kk + 1], a[4 * kk + 2], a[4 * kk + 3], wb + kk * 128);
                    else wgmma_rs_n64_tb_init(y[c & 1], a[0], a[1], a[2], a[3], wb);
                }
                wg_commit();
            };
            const uint32_t stg = sq + warp * 8192 + (lane & 15) * 128 + (((lane >> 4) ^ lane) & 7) * 16;
            uint4 z[4] = {};
            auto load_z = [&](int cb) {
                if (cb < 2) asm volatile("{\n.reg .pred p;\nsetp.ne.s32 p, %0, 0;\n@p bar.sync %1, 256;\n}\n" ::"r"(pair), "r"(cb ? BAR_H0 : BAR_BF) : "memory");
#pragma unroll
                for (int i = 0; i < 4; i++)
                    asm volatile("{\n.reg .pred p;\nsetp.ne.u32 p, %4, 0;\n@p ld.shared.v4.u32 {%0, %1, %2, %3}, [%5];\n}\n"
                                 : "+r"(z[i].x), "+r"(z[i].y), "+r"(z[i].z), "+r"(z[i].w) : "r"(pair), "r"(src - QB_BYTES + (4 * cb + i) * 512) : "memory");
            };
            pp_sync();
            gemm(0, 0);
            gemm(0, 1);
#pragma unroll
            for (int c = 0; c < 4; c++) {
                if (c) load_z(c);
                if (c < 3) gemm(c + 1, 0);
                if (!c) load_z(0);
                if (c < 3) wg_wait<1>(); else wg_wait<0>();
                fence_regs(y[c & 1]);
                const float* x = y[c & 1];
#pragma unroll
                for (int i = 0; i < 4; i++)
                    stmatrix_x4((stg ^ (32 * i)) + c * 2048, hadd2(pack_bf16(x[8 * i], x[8 * i + 1]), z[i].x), hadd2(pack_bf16(x[8 * i + 2], x[8 * i + 3]), z[i].y),
                                hadd2(pack_bf16(x[8 * i + 4], x[8 * i + 5]), z[i].z), hadd2(pack_bf16(x[8 * i + 6], x[8 * i + 7]), z[i].w));
                if (c < 3) gemm(c + 1, 1);
                fence_async_smem();
                __syncwarp();
                asm volatile("{\n.reg .pred p;\nelect.sync _|p, -1;\n"
                             "@p cp.reduce.async.bulk.tensor.4d.global.shared::cta.add.tile.bulk_group [%0, {0, 0, %1, %2}], [%3];\n}\n"
                             ::"l"(tm), "r"(c), "r"((pair ? SC_ZB : 2 * SC_QT0 + wg) * 8 + warp * 2), "r"(sq + warp * 8192 + c * 2048) : "memory");
                if (c == 2 && glob) pp_arrive();
            }
            asm volatile("cp.async.bulk.commit_group;\ncp.async.bulk.wait_group.read 0;\n" ::: "memory");
        }
        } else {
            wg_wait<0>();
        }
        if (SC_TAIL) {
        float o[128];
        const int lane = lane_now(), t = warp * 32 + lane, q = lane & 3;
        auto emit = [&](uint32_t base, int lane, int row0, uint8_t* wdst, int turn) {
#pragma unroll
            for (int hh = 0; hh < 2; hh++) {
                if (turn > 0) mbar_wait(bar_zst + 8 * hh, (turn - 1) & 1);
#pragma unroll
                for (int i = 0; i < 8; i++)
                    stmatrix_x4(base + tile_off(8 * hh + (lane & 7), 4 * i + (lane >> 3)),
                                pack_bf16(o[16 * i + 2 * hh], o[16 * i + 2 * hh + 1]), pack_bf16(o[16 * i + 4 + 2 * hh], o[16 * i + 5 + 2 * hh]),
                                pack_bf16(o[16 * i + 8 + 2 * hh], o[16 * i + 9 + 2 * hh]), pack_bf16(o[16 * i + 12 + 2 * hh], o[16 * i + 13 + 2 * hh]));
                fence_async_smem();
                __syncwarp();
                if (wdst) {
                    if (lane < 4)
                        asm volatile("cp.async.bulk.global.shared::cta.bulk_group [%0], [%1], 1024;\n"
                                     ::"l"(wdst + ((turn & 1) ? hh * 4096 + lane * 1024 : hh * 1024 + lane * QB_BYTES)), "r"(base + hh * 4096 + lane * 1024) : "memory");
                    asm volatile("cp.async.bulk.commit_group;\n" ::: "memory");
                } else {
                    asm volatile("{\n.reg .pred p;\nsetp.eq.s32 p, %3, 0;\n"
                                 "@p cp.reduce.async.bulk.tensor.4d.global.shared::cta.add.tile.bulk_group [%0, {0, 0, 0, %1}], [%2];\n"
                                 "cp.async.bulk.commit_group;\n}\n"
                                 ::"l"(&P.tm_out), "r"((row0 >> 3) + hh), "r"(base + hh * 4096), "r"(lane) : "memory");
                }
            }
            asm volatile("cp.async.bulk.wait_group.read 1;\n" ::: "memory");
            warp_arrive(bar_zst - 8 * wg);
        };
        auto emit_done = [&](bool pending) {
            asm volatile("cp.async.bulk.wait_group.read 0;\n" ::: "memory");
            __syncwarp();
            asm volatile("{\n.reg .pred p;\nsetp.eq.s32 p, %1, 0;\n@p mbarrier.arrive.shared::cta.b64 _, [%0];\n}\n"
                         ::"r"(bar_zst + 8), "r"(pending ? lane : 1) : "memory");
        };
        if (!(rank | wg)) { release(0); release(1); release(2); release(3); }
        bar_sync(BAR_BF, 256);
        warp_arrive(bar_qfree);
        const int nf = rank ? 8 : 0;
        const int nz = nf + 26 + rank;
        const int itz = 4 + SC_NKV + SC_NW;
        bool pend = false;
#pragma unroll 1
        for (int k = wg; k < nz; k += 2) {
            const int iz = itz + (k < nf ? 0 : nf >> 1);
            mbar_wait(qbar, qphase); qphase ^= 1;
#pragma unroll 1
            for (int c = 0; c < 4; c++) {
                mbar_wait(bar_full + 8 * ((iz + c) & 3), ((iz + c) >> 2) & 1);
                const uint64_t wb = mkaddr(dk0 + ((iz + c) & 3) * (KV_BYTES >> 4), dhi), ab = mkaddr(dq0 + c * 64, dhi);
                wg_fence();
                wgmma_ss_n256_tb_pred(o, ab, wb, c);
#pragma unroll
                for (int kk = 1; kk < 4; kk++) wgmma_ss_n256_tb(o, ab + kk * 2, wb + kk * 512);
                wg_commit();
                emit_done(pend);
                pend = false;
            }
            wg_wait<0>();
            fence_regs(o);
            warp_arrive(bar_qfree);
            const int fb = ((k >> 1) + 3) & 3;
            if (k < nf) {
                float2* r255 = (float2*)H.s->r255 + wg * 128 + q;
                if (k < 2) {
                    if (t >= 124) {
#pragma unroll
                        for (int i = 0; i < 32; i++) r255[4 * i] = make_float2(o[4 * i + 2], o[4 * i + 3]);
                    }
                    bar_sync(BAR_WG0 + wg, 128);
                }
#pragma unroll
                for (int i = 0; i < 32; i++) {
                    const float2 v = __ldcg(r255 + 4 * i);
                    o[4 * i] -= v.x; o[4 * i + 1] -= v.y; o[4 * i + 2] -= v.x; o[4 * i + 3] -= v.y;
                }
            }
            int ln = lane;
            asm volatile("" : "+r"(ln));
            emit(sb + SM_KV + QB_BYTES + warp * KV_BYTES, ln, SC_TZB(k - nf) * 64 + warp * 16,
                 k >= nf ? nullptr : (k & 1) ? g_w + (4 + fb) * QB_BYTES + warp * 8192 : g_w + 8 * QB_BYTES + fb * 8192 + warp * 2048, k);
            pend = k + 2 < nz && (k | 1) != nf - 1;
            if (!pend) emit_done(true);
            if ((k | 1) == nf - 1) {
                asm volatile("cp.async.bulk.wait_group 0;\nfence.proxy.async.global;\nfence.acq_rel.gpu;\n" ::: "memory");
                bar_sync(BAR_BF, 256);
                if (tid == 0) red_release(&g_sync[SY_B * 32]);
                if (wg == 0) { release(0); release(1); release(2); release(3); }
            }
        }
        }
        if (wg == 0) pp_sync();
        warp_arrive(bar_end - 8 * wg);
        asm volatile("barrier.cluster.arrive.relaxed.aligned;\n" ::: "memory");
        if (P.E >= 0) return;
        asm volatile("setmaxnreg.dec.sync.aligned.u32 %0;\n" ::"n"(REG_P));
    }
    {
        if (warp != 0) {
            if (warp == 3 && SC_OWNER && SC_PAIR && elect()) {
                flag_wait_bounded(&g_sync[SY_H1 * 32], 79 * ep);
                mbar_wait_sleep(bar_pdone, 0);
                mbar_wait_sleep(bar_pdone + 8, 0);
#pragma unroll 1
                for (int u = 0; u < 16; u++) {
                    bulk_s2g(g_q + SC_QT0 * (2 * QB_BYTES) + u * 4096, sb + SM_Q + u * 4096, 4096);
                    asm volatile("cp.async.bulk.wait_group 0;\n" ::: "memory");
                }
                fence_async_global();
                st_release(&g_qflag[SC_QT0], ep);
            }
            __syncwarp();
            if (SC_TAIL) {
                bar_sync(BAR_AUX, 96);
                if (warp == 1 && elect()) red_release(&g_sync[SY_CSR * 32]);
                __syncwarp();
            }
            mbar_wait_bounded(bar_go, 0);
            if (SC_TAIL) {
                if (warp == 1 && elect()) red_add(&g_sync[SY_DONE * 32]);
                if (warp == 3 && elect()) {
                    int it = 4 + SC_NKV + SC_NW;
                    asm volatile("prefetch.tensormap [%0];\n" ::"l"(&P.tm_out) : "memory");
                    if (rank) {
#pragma unroll 1
                        for (int j = 0; j < 4; j++, it++) {
                            mbar_wait_sleep(bar_empty + 8 * (it & 3), ((it >> 2) & 1) ^ 1);
                            mbar_expect_tx(bar_full + 8 * (it & 3), QB_BYTES);
                            tma_g2s(sb + SM_KV + (it & 3) * KV_BYTES, &P.tm_w[2], 8 * j, bar_full + 8 * (it & 3));
                        }
#pragma unroll 1
                        for (int k = 0; k < 8; k++) {
                            mbar_wait_sleep(bar_qfree + 8 * (k & 1), ((k >> 1) ^ (k & 1) ^ 1) & 1);
                            mbar_expect_tx(bar_q + 8 * (k & 1), QB_BYTES);
#pragma unroll 1
                            for (int hf = 0; hf < 2; hf++)
                                asm volatile("cp.async.bulk.tensor.5d.shared::cluster.global.tile.mbarrier::complete_tx::bytes [%0], [%1, {0, 0, %2, 0, 0}], [%3];\n"
                                             ::"r"(sb + SM_Q + (k & 1) * QB_BYTES + hf * 16384), "l"(&P.tm_w[k & 1]),
                                             "r"(8 * (((k >> 1) + 3) & 3) + 4 * hf), "r"(bar_q + 8 * (k & 1)) : "memory");
                        }
                        flag_wait_bounded(&g_sync[SY_B * 32], ep);
                        fence_async_global();
                    }
#pragma unroll 1
                    for (int j = 0; j < 4; j++, it++) {
                        mbar_wait_sleep(bar_empty + 8 * (it & 3), ((it >> 2) & 1) ^ 1);
                        mbar_expect_tx(bar_full + 8 * (it & 3), QB_BYTES);
                        bulk_g2s(sb + SM_KV + (it & 3) * KV_BYTES, g_w + (4 + j) * QB_BYTES, QB_BYTES, bar_full + 8 * (it & 3));
                    }
#pragma unroll 1
                    for (int k = 0; k < 26 + rank; k++) {
                        if (k == 0 || k == ((GF0 + 1) * NAUX - 16) / 128) { flag_wait_bounded(&g_sync[(k ? SY_AUX1 : SY_AUX0) * 32], NAUX * ep); fence_async_global(); }
                        mbar_wait_sleep(bar_qfree + 8 * (k & 1), ((k >> 1) ^ (k & 1) ^ 1) & 1);
                        mbar_expect_tx(bar_q + 8 * (k & 1), QB_BYTES);
                        bulk_g2s(sb + SM_Q + (k & 1) * QB_BYTES, g_agg + SC_TZB(k) * QB_BYTES, QB_BYTES, bar_q + 8 * (k & 1));
                    }
                }
            } else {
            const int par = ep & 1;
            if (blockIdx.x == 0 && t == 32) g_ovf_n[par ^ 1] = 0;
            if (blockIdx.x == 0 && warp == 1) *(uint4*)(g_hz + (lane >> 3) * 1024 + (lane & 7) * 16) = make_uint4(KV_OFF2 | NEG2, KV_OFF2 | NEG2, KV_OFF2, KV_OFF2);
            const uint32_t wlo = (uint32_t)(uintptr_t)H.s, whi = (uint32_t)((uintptr_t)H.s >> 32);
            const uint32_t blo = wlo + (uint32_t)offsetof(Scratch, bucket);
            {
                const int* pd = P.dst + blockIdx.x * 96 + (t - 32);
                const int* ps = P.src + blockIdx.x * 96 + (t - 32);
#pragma unroll 1
                for (int e = P.E - (blockIdx.x * 96 + (t - 32)); e > 0; e -= CSRU * NAUX * 32, pd += CSRU * NAUX * 32, ps += CSRU * NAUX * 32) {
                    int d[CSRU], sr[CSRU], sl[CSRU];
#pragma unroll
                    for (int i = 0; i < CSRU; i++) {
                        d[i] = e > i * NAUX * 32 ? __ldg(pd + i * NAUX * 32) : NN;
                        sr[i] = e > i * NAUX * 32 ? __ldg(ps + i * NAUX * 32) : 0;
                    }
#pragma unroll
                    for (int i = 0; i < CSRU; i++) {
                        sl[i] = 0;
                        asm volatile("{\n.reg .pred p;\nsetp.lt.s32 p, %2, %3;\n@p atom.relaxed.gpu.global.add.s32 %0, [%1], 1;\n}\n"
                                     : "+r"(sl[i]) : "l"(mkaddr(wlo + (uint32_t)offsetof(Scratch, cnt) + d[i] * 4, whi)), "r"(d[i]), "n"(NN) : "memory");
                    }
                    uint32_t ov = 0;
#pragma unroll
                    for (int i = 0; i < CSRU; i++) {
                        asm volatile("{\n.reg .pred p;\nsetp.lt.s32 p, %3, %4;\n@p st.global.u16 [%1], %2;\n@!p or.b32 %0, %0, %5;\n}\n"
                                     : "+r"(ov) : "l"(mkaddr(blo + d[i] * 128 + (sl[i] & 31) * 4 + (sl[i] >> 5) * 2, whi)), "h"((unsigned short)sr[i]), "r"(sl[i]), "n"(CAP), "r"(1 << i) : "memory");
                    }
#pragma unroll 1
                    for (; ov; ov &= ov - 1) {
                        const int i = (__ffs(ov) - 1) * (NAUX * 32);
                        int at;
                        asm volatile("atom.relaxed.gpu.global.add.s32 %0, [%1], 1;\n" : "=r"(at) : "l"(&g_ovf_n[par]) : "memory");
                        g_ovf[at] = make_int2(__ldg(pd + i), __ldg(ps + i));
                    }
                }
            }
            bar_sync(BAR_AUX, 96);
            if (warp == 1 && elect()) { red_release(&g_sync[SY_CSR * 32]); }
            __syncwarp();
            {
                const int r0 = blockIdx.x * 3 + warp - 1;
                const uint4* xp = (const uint4*)(H.x + r0 * 256) + lane;
                uint4* op = (uint4*)(P.out + r0 * 256) + lane;
#pragma unroll 1
                for (int r = r0; r < NN; r += CPYU * NAUX, xp += CPYU * NAUX * 32, op += CPYU * NAUX * 32) {
                    uint4 v[CPYU];
#pragma unroll
                    for (int i = 0; i < CPYU; i++) if (r + i * NAUX < NN) v[i] = ldg_pinned(xp + i * NAUX * 32);
#pragma unroll
                    for (int i = 0; i < CPYU; i++) if (r + i * NAUX < NN) op[i * NAUX * 32] = v[i];
                }
            }
            mbar_wait_bounded(bar_go, 1);
            if (const int un = (3 - warp) * (NAUX / 3) + (NAUX / 3 - 1) - blockIdx.x; un < 208) {
                flag_wait_bounded(&g_sync[SY_PART * 32], 52 * ep);
                uint8_t* pp = g_part + (un >> 3) * (4 * PART_BYTES);
                float* ml = (float*)(pp + QB_BYTES) + (un & 7) * 32;
                const float4 sa = __ldcg((const float4*)ml + g), sc = __ldcg((const float4*)ml + g + 2 * PART_BYTES / 16);
                const float n0 = fmaxf(sa.x, sc.x), n1 = fmaxf(sa.z, sc.z);
                const uint32_t a0 = pack_bf16(ex2(sa.x - n0), ex2(sa.x - n0)), a1 = pack_bf16(ex2(sa.z - n1), ex2(sa.z - n1));
                const uint32_t b0 = pack_bf16(ex2(sc.x - n0), ex2(sc.x - n0)), b1 = pack_bf16(ex2(sc.z - n1), ex2(sc.z - n1));
                __syncwarp();
                if (q == 0) ((float4*)ml)[g] = make_float4(n0, sa.y * bf_hi(a0) + sc.y * bf_hi(b0), n1, sa.w * bf_hi(a1) + sc.w * bf_hi(b1));
                uint4* d = (uint4*)(pp + (un & 4) * 256 + (un & 7) * 8192) + lane;
#pragma unroll 1
                for (int i = 0; i < 4; i++, d += 128) {
                    uint4 u[4], v[4];
#pragma unroll
                    for (int j = 0; j < 4; j++) { u[j] = __ldcg(d + j * 32); v[j] = __ldcg(d + j * 32 + 2 * PART_BYTES / 16); }
#pragma unroll
                    for (int j = 0; j < 4; j++)
                        d[j * 32] = make_uint4(hfma2(v[j].x, b0, hmul2(u[j].x, a0)), hfma2(v[j].y, b1, hmul2(u[j].y, a1)),
                                               hfma2(v[j].z, b0, hmul2(u[j].z, a0)), hfma2(v[j].w, b1, hmul2(u[j].w, a1)));
                }
            }
            flag_wait_bounded(&g_sync[SY_CSR * 32], NCTA * ep);
            if (warp == 2 && blockIdx.x < 129) {
                uint4* z = blockIdx.x < 128 ? (uint4*)(g_w + blockIdx.x * 1024) + lane : (uint4*)&g_sync[SY_DONE * 32 + 4];
                z[0] = make_uint4(0, 0, 0, 0);
                if (blockIdx.x < 128) z[32] = make_uint4(0, 0, 0, 0);
            }
            {
                const uint32_t lc = (lane >> 3) * 1024 + (lane & 7) * 16;
                const uint32_t alo = wlo ^ lc;
                const int node0 = blockIdx.x * 3 + warp - 17;
                auto node = [&](int i) { const int nd = node0 + i * NAUX; return (int)min((unsigned)nd, (unsigned)(nd + NN)); };
                const int num = (NN - 17 - node0) / NAUX + 1;
                uint32_t mine = 0;
                if (lane < num) {
                    mine = min(__ldcg(&g_cnt[node(lane)]), CAP + 1) | (uint32_t)__ldg((const unsigned short*)P.deg_inv + node(lane)) << 16;
                    g_cnt[node(lane)] = 0;
                }
                auto row = [&](int off) {
                    uint4 v;
                    asm volatile("ld.global.v4.u32 {%0, %1, %2, %3}, [%4];\n"
                                 : "=r"(v.x), "=r"(v.y), "=r"(v.z), "=r"(v.w) : "l"(mkaddr(alo ^ off, whi)));
                    return v;
                };
                auto ents = [&](int i) {
                    uint32_t e;
                    asm volatile("ld.global.cg.u32 %0, [%1];\n" : "=r"(e) : "l"(mkaddr(blo + (min(node(i), NN - 1) * 32 + lane) * 4, whi)));
                    return e;
                };
                auto store = [&](int i, const float (&a)[8]) {
                    const float di = bf_hi(__shfl_sync(~0u, mine, i)) * (1.f / KV_SCALE);
                    const int nd = node(i);
                    *(uint4*)(g_agg + (uint32_t)(((nd >> 3) * 4096 + (nd & 7) * 144) ^ lc)) =
                        make_uint4(pack_bf16(a[0] * di, a[1] * di), pack_bf16(a[2] * di, a[3] * di), pack_bf16(a[4] * di, a[5] * di), pack_bf16(a[6] * di, a[7] * di));
                };
#pragma unroll 1
                for (uint32_t big = __ballot_sync(~0u, (mine & 0xFFFF) > CAP); big; big &= big - 1) {
                    const int i = __ffs(big) - 1, no = __ldcg(&g_ovf_n[par]);
                    float a[8] = {};
#pragma unroll 1
                    for (int k = -64; k < no; k += 32) {
                        const int2 pr = k < 0 ? make_int2(node(i), (ents(i) >> (k & 32) / 2) & 0xFFFF) : k + lane < no ? __ldcg(&g_ovf[k + lane]) : make_int2(-1, 0);
#pragma unroll 1
                        for (uint32_t mk = __ballot_sync(~0u, pr.x == node(i)); mk; mk &= mk - 1) {
                            const uint4 v = row(row_off(__shfl_sync(~0u, pr.y, __ffs(mk) - 1)));
                            a[0] += f16_lo(v.x) + KV_OFF; a[1] += f16_hi(v.x) + KV_OFF; a[2] += f16_lo(v.y) + KV_OFF; a[3] += f16_hi(v.y) + KV_OFF;
                            a[4] += f16_lo(v.z) - KV_OFF; a[5] += f16_hi(v.z) - KV_OFF; a[6] += f16_lo(v.w) - KV_OFF; a[7] += f16_hi(v.w) - KV_OFF;
                        }
                    }
                    store(i, a);
                }
                auto add4 = [&](const uint4& a, const uint4& b) { return make_uint4(hadd2_f16(a.x, b.x), hadd2_f16(a.y, b.y), hadd2_f16(a.z, b.z), hadd2_f16(a.w, b.w)); };
                int ni = -1, left = 0, pos = 0, ec = 0;
                uint32_t en = ents(0);
                uint4 acc = make_uint4(0, 0, 0, 0);
                auto step = [&](uint4 (&v)[4], int& tag) {
                    if (left <= 0 || pos == 32) {
                        if (left > 0) {
                            en = ents(ni) >> 16;
                        } else {
                            ni++;
                            left = __shfl_sync(~0u, mine, ni) & 0xFFFF;
                            if (left > CAP) left = 0;
                        }
                        ec = lane < left ? row_off(en & 0xFFFF) : 0;
                        en = ents(ni + 1);
                        pos = 0;
                    }
                    int of[4];
#pragma unroll
                    for (int j = 0; j < 4; j++) asm volatile("shfl.sync.idx.b32 %0, %1, %2, 31, -1;\n" : "=r"(of[j]) : "r"(ec), "r"(pos + j));
                    acc = add4(acc, add4(add4(add4(v[0], v[1]), make_uint4(KV_OFF8, KV_OFF8, KV_OFF8 | NEG2, KV_OFF8 | NEG2)), add4(v[2], v[3])));
                    asm volatile("" : "+r"(acc.x), "+r"(acc.y), "+r"(acc.z), "+r"(acc.w));
                    asm volatile("{\n.reg .pred p;\nsetp.lt.s32 p, %0, 0;\nL:\n@p pmevent 0;\n@p bra L;\n}\n" ::"r"(ni) : "memory");
#pragma unroll
                    for (int j = 0; j < 4; j++) v[j] = row(of[j]);
                    pos += 4; left -= 4;
                    const int i = tag;
                    tag = left <= 0 ? ni : -1;
                    if (i >= 0) {
                        const float a[8] = {f16_lo(acc.x), f16_hi(acc.x), f16_lo(acc.y), f16_hi(acc.y), f16_lo(acc.z), f16_hi(acc.z), f16_lo(acc.w), f16_hi(acc.w)};
                        if ((__shfl_sync(~0u, mine, i) & 0xFFFF) <= CAP) store(i, a);
                        acc = make_uint4(0, 0, 0, 0);
                        if (i == GF0 || i == 8) {
                            __syncwarp();
                            if (elect()) red_release(&g_sync[(i == 8 ? SY_AUX1 : SY_AUX0) * 32]);
                            __syncwarp();
                        }
                    }
                    return i == num - 1;
                };
                uint4 va[4], vb[4];
#pragma unroll
                for (int j = 0; j < 4; j++) va[j] = vb[j] = make_uint4(KV_OFF2 | NEG2, KV_OFF2 | NEG2, KV_OFF2, KV_OFF2);
                int ta = -1, tb = -1;
#pragma unroll 1
                while (!step(va, ta) && !step(vb, tb)) {}
            }
            bar_sync(BAR_AUX, 96);
            if (warp == 1 && elect()) {
                red_release(&g_sync[SY_AUX * 32]);
                red_add(&g_sync[SY_DONE * 32]);
            }
            }
        }
        __syncwarp();
        asm volatile("barrier.cluster.arrive.relaxed.aligned;\n" ::: "memory");
        if (warp == 1) mbar_wait_bounded(bar_end, 0);
        else if (elect()) mbar_arrive(bar_end);
        __syncwarp();
        asm volatile("barrier.cluster.wait.acquire.aligned;\n" ::: "memory");
    }
}

}

extern "C" void kernel_launch(void* const* d_in, const int* in_sizes, int n_in, void* d_out, int out_size) {
    Hot H;
    Params P;
    H.x = (const __nv_bfloat16*)d_in[0];
    P.src = (const int*)d_in[1];
    P.dst = (const int*)d_in[2];
    P.deg_inv = (const __nv_bfloat16*)d_in[3];
    H.wq = (const __nv_bfloat16*)d_in[5];
    H.wk = (const __nv_bfloat16*)d_in[6];
    P.out = (__nv_bfloat16*)d_out;
    typedef CUresult (*EncodeFn)(CUtensorMap*, CUtensorMapDataType, cuuint32_t, void*, const cuuint64_t*, const cuuint64_t*, const cuuint32_t*,
                                 const cuuint32_t*, CUtensorMapInterleave, CUtensorMapSwizzle, CUtensorMapL2promotion, CUtensorMapFloatOOBfill);
    void* fn = nullptr;
    cudaDriverEntryPointQueryResult qr;
    cudaGetDriverEntryPoint("cuTensorMapEncodeTiled", &fn, cudaEnableDefault, &qr);
    auto encode = [&](CUtensorMap* tm, const void* ptr, int rows, int box_rows, int box_cb = 4) {
        const cuuint64_t dims[4] = {64, 8, 4, (cuuint64_t)rows / 8};
        const cuuint64_t strides[3] = {512, 128, 4096};
        const cuuint32_t box[4] = {64, 8, (cuuint32_t)box_cb, (cuuint32_t)box_rows / 8}, es[4] = {1, 1, 1, 1};
        ((EncodeFn)fn)(tm, CU_TENSOR_MAP_DATA_TYPE_BFLOAT16, 4, (void*)ptr, dims, strides, box, es, CU_TENSOR_MAP_INTERLEAVE_NONE,
                       CU_TENSOR_MAP_SWIZZLE_128B, CU_TENSOR_MAP_L2_PROMOTION_NONE, CU_TENSOR_MAP_FLOAT_OOB_FILL_NONE);
    };
    encode(&P.tm_out, d_out, NN, 8);
    encode(&P.tm_outc, d_out, NN, 16, 1);
    for (int i = 0; i < 2; i++) {
        const cuuint64_t dims[5] = {64, 2, 32, 4, 4};
        const cuuint64_t strides[4] = {512, 4096, 128, 1024};
        const cuuint32_t box[5] = {64, 2, 4, 4, 4}, es[5] = {1, 1, 1, 1, 1};
        ((EncodeFn)fn)(&P.tm_w[i], CU_TENSOR_MAP_DATA_TYPE_BFLOAT16, 5, d_in[i ? 4 : 7], dims, strides, box, es, CU_TENSOR_MAP_INTERLEAVE_NONE,
                       CU_TENSOR_MAP_SWIZZLE_128B, CU_TENSOR_MAP_L2_PROMOTION_NONE, CU_TENSOR_MAP_FLOAT_OOB_FILL_NONE);
    }
    encode(&P.tm_w[2], d_in[8], 256, 64);
    void* raw = nullptr;
    cudaGetSymbolAddress(&raw, g_raw);
    H.s = (Scratch*)(((uintptr_t)raw + ((8 << 20) - 1)) & ~(uintptr_t)((8 << 20) - 1));
    P.dhi = 0x40000100u;
    P.E = in_sizes[1] < MAXE ? in_sizes[1] : MAXE;
    cudaFuncSetAttribute(k_main, cudaFuncAttributeMaxDynamicSharedMemorySize, SM_TOTAL);
    k_main<<<NCTA, 384, SM_TOTAL>>>(H, P);
}
```

```cpp
#include <cuda_runtime.h>
#include <cuda.h>
#include <cuda_bf16.h>
#include <stdint.h>
#include <stddef.h>

namespace {

constexpr int NN = 10000;
constexpr int BN = 80;
constexpr int NKV = NN / BN;
constexpr int NQB = 158;
constexpr int NCTA = 132;
constexpr int NAUX = 3 * (NCTA - 2);
constexpr int STAGES = 4;
constexpr int KV_BYTES = BN * 512;
constexpr int QB_BYTES = 64 * 512;
constexpr int PART_BYTES = QB_BYTES + 512;
constexpr int CAP = 64;
constexpr int MAXE = 160000;

#define QRND(v) (((v) + 0x00040004u) & 0xFFF8FFF8u)
#define GO0 5
#define GO1 41
#define GF0 2
#define CSRU 3
#define CPYU 9
#define REFUP 2.f
#define SND0 10
#define CUT2 2
#define TICK 1024
#define TSL 30
#define NQR 7
#define QSTEP 2
#define QREG(kk) ((kk) % QSTEP == 1 % QSTEP && (kk) > 0 && ((kk) - 1) / QSTEP < NQR ? ((kk) - 1) / QSTEP : -1)
#define REG_C 224
#define REG_P 56

enum { SY_PART = 4, SY_H1 = 5, SY_CSR = 6, SY_AUX = 7, SY_DONE = 8, SY_AUX0 = 9, SY_B = 10, SY_AUX1 = 11, SY_H0 = 12 };
struct Scratch {
    uint8_t hz[4096 + NN * 512];
    uint8_t w[12 * QB_BYTES];
    int sync[25 * 32];
    int qflag[96];
    int ovf_n[32];
    float r255[512];
    int cnt[NN + 16];
    int bucket[(NN + 1) * 32];
    int2 ovf[MAXE];
    uint8_t q[NQB * QB_BYTES];
    uint8_t agg[NQB * QB_BYTES];
    uint8_t part[52 * 2 * PART_BYTES];
};
static_assert(offsetof(Scratch, ovf) <= (8 << 20), "window");
static_assert(offsetof(Scratch, qflag) == offsetof(Scratch, sync) + 25 * 128, "flags");
static_assert(offsetof(Scratch, w) % 1024 == 0 && offsetof(Scratch, sync) % 128 == 0 &&
              offsetof(Scratch, bucket) % 128 == 0 && offsetof(Scratch, q) % 128 == 0, "alignment");
__device__ uint8_t g_raw[(8 << 20) + sizeof(Scratch)];
#define g_hz (H.s->hz)
#define g_w (H.s->w)
#define g_sync (H.s->sync)
#define g_qflag (H.s->qflag)
#define g_ovf_n (H.s->ovf_n)
#define g_cnt (H.s->cnt)
#define g_bucket (H.s->bucket)
#define g_ovf (H.s->ovf)
#define g_q (H.s->q)
#define g_agg (H.s->agg)
#define g_part (H.s->part)

__device__ __forceinline__ void wgmma_ss_n80(uint32_t (&d)[20], uint64_t da, uint64_t db) {
    asm volatile("wgmma.mma_async.sync.aligned.m64n80k16.f16.f16.f16 {"
        "%0, %1, %2, %3, %4, %5, %6, %7, %8, %9, %10, %11, %12, %13, %14, %15, %16, %17, %18, %19}, %20, %21, 1, 1, 1, 0, 0;\n"
        : "+r"(d[0]), "+r"(d[1]), "+r"(d[2]), "+r"(d[3]), "+r"(d[4]), "+r"(d[5]), "+r"(d[6]), "+r"(d[7]),
          "+r"(d[8]), "+r"(d[9]), "+r"(d[10]), "+r"(d[11]), "+r"(d[12]), "+r"(d[13]), "+r"(d[14]), "+r"(d[15]),
          "+r"(d[16]), "+r"(d[17]), "+r"(d[18]), "+r"(d[19])
        : "l"(da), "l"(db));
}
__device__ __forceinline__ void wgmma_ss_n80_init(uint32_t (&d)[20], uint64_t da, uint64_t db) {
    asm volatile("wgmma.mma_async.sync.aligned.m64n80k16.f16.f16.f16 {"
        "%0, %1, %2, %3, %4, %5, %6, %7, %8, %9, %10, %11, %12, %13, %14, %15, %16, %17, %18, %19}, %20, %21, 0, 1, 1, 0, 0;\n"
        : "=r"(d[0]), "=r"(d[1]), "=r"(d[2]), "=r"(d[3]), "=r"(d[4]), "=r"(d[5]), "=r"(d[6]), "=r"(d[7]),
          "=r"(d[8]), "=r"(d[9]), "=r"(d[10]), "=r"(d[11]), "=r"(d[12]), "=r"(d[13]), "=r"(d[14]), "=r"(d[15]),
          "=r"(d[16]), "=r"(d[17]), "=r"(d[18]), "=r"(d[19])
        : "l"(da), "l"(db));
}
__device__ __forceinline__ void wgmma_rs_n80(uint32_t (&d)[20], uint32_t a0, uint32_t a1, uint32_t a2, uint32_t a3, uint64_t db) {
    asm volatile("wgmma.mma_async.sync.aligned.m64n80k16.f16.f16.f16 {"
        "%0, %1, %2, %3, %4, %5, %6, %7, %8, %9, %10, %11, %12, %13, %14, %15, %16, %17, %18, %19}, {%20, %21, %22, %23}, %24, 1, 1, 1, 0;\n"
        : "+r"(d[0]), "+r"(d[1]), "+r"(d[2]), "+r"(d[3]), "+r"(d[4]), "+r"(d[5]), "+r"(d[6]), "+r"(d[7]),
          "+r"(d[8]), "+r"(d[9]), "+r"(d[10]), "+r"(d[11]), "+r"(d[12]), "+r"(d[13]), "+r"(d[14]), "+r"(d[15]),
          "+r"(d[16]), "+r"(d[17]), "+r"(d[18]), "+r"(d[19])
        : "r"(a0), "r"(a1), "r"(a2), "r"(a3), "l"(db));
}
__device__ __forceinline__ void wgmma_rs_n256_tb(float (&d)[128], uint32_t a0, uint32_t a1, uint32_t a2, uint32_t a3, uint64_t db) {
    asm volatile("wgmma.mma_async.sync.aligned.m64n256k16.f32.f16.f16 {"
        "%0, %1, %2, %3, %4, %5, %6, %7, %8, %9, %10, %11, %12, %13, %14, %15, %16, %17, %18, %19, %20, %21, %22, %23, %24, %25, %26, %27, %28, %29, %30, %31, "
        "%32, %33, %34, %35, %36, %37, %38, %39, %40, %41, %42, %43, %44, %45, %46, %47, %48, %49, %50, %51, %52, %53, %54, %55, %56, %57, %58, %59, %60, %61, %62, %63, "
        "%64, %65, %66, %67, %68, %69, %70, %71, %72, %73, %74, %75, %76, %77, %78, %79, %80, %81, %82, %83, %84, %85, %86, %87, %88, %89, %90, %91, %92, %93, %94, %95, "
        "%96, %97, %98, %99, %100, %101, %102, %103, %104, %105, %106, %107, %108, %109, %110, %111, %112, %113, %114, %115, %116, %117, %118, %119, %120, %121, %122, %123, %124, %125, %126, %127}, {%128, %129, %130, %131}, %132, 1, 1, 1, 1;\n"
        : "+f"(d[0]), "+f"(d[1]), "+f"(d[2]), "+f"(d[3]), "+f"(d[4]), "+f"(d[5]), "+f"(d[6]), "+f"(d[7]),
          "+f"(d[8]), "+f"(d[9]), "+f"(d[10]), "+f"(d[11]), "+f"(d[12]), "+f"(d[13]), "+f"(d[14]), "+f"(d[15]),
          "+f"(d[16]), "+f"(d[17]), "+f"(d[18]), "+f"(d[19]), "+f"(d[20]), "+f"(d[21]), "+f"(d[22]), "+f"(d[23]),
          "+f"(d[24]), "+f"(d[25]), "+f"(d[26]), "+f"(d[27]), "+f"(d[28]), "+f"(d[29]), "+f"(d[30]), "+f"(d[31]),
          "+f"(d[32]), "+f"(d[33]), "+f"(d[34]), "+f"(d[35]), "+f"(d[36]), "+f"(d[37]), "+f"(d[38]), "+f"(d[39]),
          "+f"(d[40]), "+f"(d[41]), "+f"(d[42]), "+f"(d[43]), "+f"(d[44]), "+f"(d[45]), "+f"(d[46]), "+f"(d[47]),
          "+f"(d[48]), "+f"(d[49]), "+f"(d[50]), "+f"(d[51]), "+f"(d[52]), "+f"(d[53]), "+f"(d[54]), "+f"(d[55]),
          "+f"(d[56]), "+f"(d[57]), "+f"(d[58]), "+f"(d[59]), "+f"(d[60]), "+f"(d[61]), "+f"(d[62]), "+f"(d[63]),
          "+f"(d[64]), "+f"(d[65]), "+f"(d[66]), "+f"(d[67]), "+f"(d[68]), "+f"(d[69]), "+f"(d[70]), "+f"(d[71]),
          "+f"(d[72]), "+f"(d[73]), "+f"(d[74]), "+f"(d[75]), "+f"(d[76]), "+f"(d[77]), "+f"(d[78]), "+f"(d[79]),
          "+f"(d[80]), "+f"(d[81]), "+f"(d[82]), "+f"(d[83]), "+f"(d[84]), "+f"(d[85]), "+f"(d[86]), "+f"(d[87]),
          "+f"(d[88]), "+f"(d[89]), "+f"(d[90]), "+f"(d[91]), "+f"(d[92]), "+f"(d[93]), "+f"(d[94]), "+f"(d[95]),
          "+f"(d[96]), "+f"(d[97]), "+f"(d[98]), "+f"(d[99]), "+f"(d[100]), "+f"(d[101]), "+f"(d[102]), "+f"(d[103]),
          "+f"(d[104]), "+f"(d[105]), "+f"(d[106]), "+f"(d[107]), "+f"(d[108]), "+f"(d[109]), "+f"(d[110]), "+f"(d[111]),
          "+f"(d[112]), "+f"(d[113]), "+f"(d[114]), "+f"(d[115]), "+f"(d[116]), "+f"(d[117]), "+f"(d[118]), "+f"(d[119]),
          "+f"(d[120]), "+f"(d[121]), "+f"(d[122]), "+f"(d[123]), "+f"(d[124]), "+f"(d[125]), "+f"(d[126]), "+f"(d[127])
        : "r"(a0), "r"(a1), "r"(a2), "r"(a3), "l"(db));
}
__device__ __forceinline__ void wgmma_rs_n256_tb_init(float (&d)[128], uint32_t a0, uint32_t a1, uint32_t a2, uint32_t a3, uint64_t db) {
    asm volatile("wgmma.mma_async.sync.aligned.m64n256k16.f32.f16.f16 {"
        "%0, %1, %2, %3, %4, %5, %6, %7, %8, %9, %10, %11, %12, %13, %14, %15, %16, %17, %18, %19, %20, %21, %22, %23, %24, %25, %26, %27, %28, %29, %30, %31, "
        "%32, %33, %34, %35, %36, %37, %38, %39, %40, %41, %42, %43, %44, %45, %46, %47, %48, %49, %50, %51, %52, %53, %54, %55, %56, %57, %58, %59, %60, %61, %62, %63, "
        "%64, %65, %66, %67, %68, %69, %70, %71, %72, %73, %74, %75, %76, %77, %78, %79, %80, %81, %82, %83, %84, %85, %86, %87, %88, %89, %90, %91, %92, %93, %94, %95, "
        "%96, %97, %98, %99, %100, %101, %102, %103, %104, %105, %106, %107, %108, %109, %110, %111, %112, %113, %114, %115, %116, %117, %118, %119, %120, %121, %122, %123, %124, %125, %126, %127}, {%128, %129, %130, %131}, %132, 0, 1, 1, 1;\n"
        : "=f"(d[0]), "=f"(d[1]), "=f"(d[2]), "=f"(d[3]), "=f"(d[4]), "=f"(d[5]), "=f"(d[6]), "=f"(d[7]),
          "=f"(d[8]), "=f"(d[9]), "=f"(d[10]), "=f"(d[11]), "=f"(d[12]), "=f"(d[13]), "=f"(d[14]), "=f"(d[15]),
          "=f"(d[16]), "=f"(d[17]), "=f"(d[18]), "=f"(d[19]), "=f"(d[20]), "=f"(d[21]), "=f"(d[22]), "=f"(d[23]),
          "=f"(d[24]), "=f"(d[25]), "=f"(d[26]), "=f"(d[27]), "=f"(d[28]), "=f"(d[29]), "=f"(d[30]), "=f"(d[31]),
          "=f"(d[32]), "=f"(d[33]), "=f"(d[34]), "=f"(d[35]), "=f"(d[36]), "=f"(d[37]), "=f"(d[38]), "=f"(d[39]),
          "=f"(d[40]), "=f"(d[41]), "=f"(d[42]), "=f"(d[43]), "=f"(d[44]), "=f"(d[45]), "=f"(d[46]), "=f"(d[47]),
          "=f"(d[48]), "=f"(d[49]), "=f"(d[50]), "=f"(d[51]), "=f"(d[52]), "=f"(d[53]), "=f"(d[54]), "=f"(d[55]),
          "=f"(d[56]), "=f"(d[57]), "=f"(d[58]), "=f"(d[59]), "=f"(d[60]), "=f"(d[61]), "=f"(d[62]), "=f"(d[63]),
          "=f"(d[64]), "=f"(d[65]), "=f"(d[66]), "=f"(d[67]), "=f"(d[68]), "=f"(d[69]), "=f"(d[70]), "=f"(d[71]),
          "=f"(d[72]), "=f"(d[73]), "=f"(d[74]), "=f"(d[75]), "=f"(d[76]), "=f"(d[77]), "=f"(d[78]), "=f"(d[79]),
          "=f"(d[80]), "=f"(d[81]), "=f"(d[82]), "=f"(d[83]), "=f"(d[84]), "=f"(d[85]), "=f"(d[86]), "=f"(d[87]),
          "=f"(d[88]), "=f"(d[89]), "=f"(d[90]), "=f"(d[91]), "=f"(d[92]), "=f"(d[93]), "=f"(d[94]), "=f"(d[95]),
          "=f"(d[96]), "=f"(d[97]), "=f"(d[98]), "=f"(d[99]), "=f"(d[100]), "=f"(d[101]), "=f"(d[102]), "=f"(d[103]),
          "=f"(d[104]), "=f"(d[105]), "=f"(d[106]), "=f"(d[107]), "=f"(d[108]), "=f"(d[109]), "=f"(d[110]), "=f"(d[111]),
          "=f"(d[112]), "=f"(d[113]), "=f"(d[114]), "=f"(d[115]), "=f"(d[116]), "=f"(d[117]), "=f"(d[118]), "=f"(d[119]),
          "=f"(d[120]), "=f"(d[121]), "=f"(d[122]), "=f"(d[123]), "=f"(d[124]), "=f"(d[125]), "=f"(d[126]), "=f"(d[127])
        : "r"(a0), "r"(a1), "r"(a2), "r"(a3), "l"(db));
}
__device__ __forceinline__ void wgmma_rs_n256_tb_pred(float (&d)[128], uint32_t a0, uint32_t a1, uint32_t a2, uint32_t a3, uint64_t db, int acc) {
    asm volatile("{\n.reg .pred p;\nsetp.ne.s32 p, %133, 0;\nwgmma.mma_async.sync.aligned.m64n256k16.f32.f16.f16 {"
        "%0, %1, %2, %3, %4, %5, %6, %7, %8, %9, %10, %11, %12, %13, %14, %15, %16, %17, %18, %19, %20, %21, %22, %23, %24, %25, %26, %27, %28, %29, %30, %31, "
        "%32, %33, %34, %35, %36, %37, %38, %39, %40, %41, %42, %43, %44, %45, %46, %47, %48, %49, %50, %51, %52, %53, %54, %55, %56, %57, %58, %59, %60, %61, %62, %63, "
        "%64, %65, %66, %67, %68, %69, %70, %71, %72, %73, %74, %75, %76, %77, %78, %79, %80, %81, %82, %83, %84, %85, %86, %87, %88, %89, %90, %91, %92, %93, %94, %95, "
        "%96, %97, %98, %99, %100, %101, %102, %103, %104, %105, %106, %107, %108, %109, %110, %111, %112, %113, %114, %115, %116, %117, %118, %119, %120, %121, %122, %123, %124, %125, %126, %127}, {%128, %129, %130, %131}, %132, p, 1, 1, 1;\n}\n"
        : "+f"(d[0]), "+f"(d[1]), "+f"(d[2]), "+f"(d[3]), "+f"(d[4]), "+f"(d[5]), "+f"(d[6]), "+f"(d[7]),
          "+f"(d[8]), "+f"(d[9]), "+f"(d[10]), "+f"(d[11]), "+f"(d[12]), "+f"(d[13]), "+f"(d[14]), "+f"(d[15]),
          "+f"(d[16]), "+f"(d[17]), "+f"(d[18]), "+f"(d[19]), "+f"(d[20]), "+f"(d[21]), "+f"(d[22]), "+f"(d[23]),
          "+f"(d[24]), "+f"(d[25]), "+f"(d[26]), "+f"(d[27]), "+f"(d[28]), "+f"(d[29]), "+f"(d[30]), "+f"(d[31]),
          "+f"(d[32]), "+f"(d[33]), "+f"(d[34]), "+f"(d[35]), "+f"(d[36]), "+f"(d[37]), "+f"(d[38]), "+f"(d[39]),
          "+f"(d[40]), "+f"(d[41]), "+f"(d[42]), "+f"(d[43]), "+f"(d[44]), "+f"(d[45]), "+f"(d[46]), "+f"(d[47]),
          "+f"(d[48]), "+f"(d[49]), "+f"(d[50]), "+f"(d[51]), "+f"(d[52]), "+f"(d[53]), "+f"(d[54]), "+f"(d[55]),
          "+f"(d[56]), "+f"(d[57]), "+f"(d[58]), "+f"(d[59]), "+f"(d[60]), "+f"(d[61]), "+f"(d[62]), "+f"(d[63]),
          "+f"(d[64]), "+f"(d[65]), "+f"(d[66]), "+f"(d[67]), "+f"(d[68]), "+f"(d[69]), "+f"(d[70]), "+f"(d[71]),
          "+f"(d[72]), "+f"(d[73]), "+f"(d[74]), "+f"(d[75]), "+f"(d[76]), "+f"(d[77]), "+f"(d[78]), "+f"(d[79]),
          "+f"(d[80]), "+f"(d[81]), "+f"(d[82]), "+f"(d[83]), "+f"(d[84]), "+f"(d[85]), "+f"(d[86]), "+f"(d[87]),
          "+f"(d[88]), "+f"(d[89]), "+f"(d[90]), "+f"(d[91]), "+f"(d[92]), "+f"(d[93]), "+f"(d[94]), "+f"(d[95]),
          "+f"(d[96]), "+f"(d[97]), "+f"(d[98]), "+f"(d[99]), "+f"(d[100]), "+f"(d[101]), "+f"(d[102]), "+f"(d[103]),
          "+f"(d[104]), "+f"(d[105]), "+f"(d[106]), "+f"(d[107]), "+f"(d[108]), "+f"(d[109]), "+f"(d[110]), "+f"(d[111]),
          "+f"(d[112]), "+f"(d[113]), "+f"(d[114]), "+f"(d[115]), "+f"(d[116]), "+f"(d[117]), "+f"(d[118]), "+f"(d[119]),
          "+f"(d[120]), "+f"(d[121]), "+f"(d[122]), "+f"(d[123]), "+f"(d[124]), "+f"(d[125]), "+f"(d[126]), "+f"(d[127])
        : "r"(a0), "r"(a1), "r"(a2), "r"(a3), "l"(db), "r"(acc));
}
__device__ __forceinline__ void wgmma_ss_n256_tb(float (&d)[128], uint64_t da, uint64_t db) {
    asm volatile("wgmma.mma_async.sync.aligned.m64n256k16.f32.bf16.bf16 {"
        "%0, %1, %2, %3, %4, %5, %6, %7, %8, %9, %10, %11, %12, %13, %14, %15, %16, %17, %18, %19, %20, %21, %22, %23, %24, %25, %26, %27, %28, %29, %30, %31, "
        "%32, %33, %34, %35, %36, %37, %38, %39, %40, %41, %42, %43, %44, %45, %46, %47, %48, %49, %50, %51, %52, %53, %54, %55, %56, %57, %58, %59, %60, %61, %62, %63, "
        "%64, %65, %66, %67, %68, %69, %70, %71, %72, %73, %74, %75, %76, %77, %78, %79, %80, %81, %82, %83, %84, %85, %86, %87, %88, %89, %90, %91, %92, %93, %94, %95, "
        "%96, %97, %98, %99, %100, %101, %102, %103, %104, %105, %106, %107, %108, %109, %110, %111, %112, %113, %114, %115, %116, %117, %118, %119, %120, %121, %122, %123, %124, %125, %126, %127}, %128, %129, 1, 1, 1, 0, 1;\n"
        : "+f"(d[0]), "+f"(d[1]), "+f"(d[2]), "+f"(d[3]), "+f"(d[4]), "+f"(d[5]), "+f"(d[6]), "+f"(d[7]),
          "+f"(d[8]), "+f"(d[9]), "+f"(d[10]), "+f"(d[11]), "+f"(d[12]), "+f"(d[13]), "+f"(d[14]), "+f"(d[15]),
          "+f"(d[16]), "+f"(d[17]), "+f"(d[18]), "+f"(d[19]), "+f"(d[20]), "+f"(d[21]), "+f"(d[22]), "+f"(d[23]),
          "+f"(d[24]), "+f"(d[25]), "+f"(d[26]), "+f"(d[27]), "+f"(d[28]), "+f"(d[29]), "+f"(d[30]), "+f"(d[31]),
          "+f"(d[32]), "+f"(d[33]), "+f"(d[34]), "+f"(d[35]), "+f"(d[36]), "+f"(d[37]), "+f"(d[38]), "+f"(d[39]),
          "+f"(d[40]), "+f"(d[41]), "+f"(d[42]), "+f"(d[43]), "+f"(d[44]), "+f"(d[45]), "+f"(d[46]), "+f"(d[47]),
          "+f"(d[48]), "+f"(d[49]), "+f"(d[50]), "+f"(d[51]), "+f"(d[52]), "+f"(d[53]), "+f"(d[54]), "+f"(d[55]),
          "+f"(d[56]), "+f"(d[57]), "+f"(d[58]), "+f"(d[59]), "+f"(d[60]), "+f"(d[61]), "+f"(d[62]), "+f"(d[63]),
          "+f"(d[64]), "+f"(d[65]), "+f"(d[66]), "+f"(d[67]), "+f"(d[68]), "+f"(d[69]), "+f"(d[70]), "+f"(d[71]),
          "+f"(d[72]), "+f"(d[73]), "+f"(d[74]), "+f"(d[75]), "+f"(d[76]), "+f"(d[77]), "+f"(d[78]), "+f"(d[79]),
          "+f"(d[80]), "+f"(d[81]), "+f"(d[82]), "+f"(d[83]), "+f"(d[84]), "+f"(d[85]), "+f"(d[86]), "+f"(d[87]),
          "+f"(d[88]), "+f"(d[89]), "+f"(d[90]), "+f"(d[91]), "+f"(d[92]), "+f"(d[93]), "+f"(d[94]), "+f"(d[95]),
          "+f"(d[96]), "+f"(d[97]), "+f"(d[98]), "+f"(d[99]), "+f"(d[100]), "+f"(d[101]), "+f"(d[102]), "+f"(d[103]),
          "+f"(d[104]), "+f"(d[105]), "+f"(d[106]), "+f"(d[107]), "+f"(d[108]), "+f"(d[109]), "+f"(d[110]), "+f"(d[111]),
          "+f"(d[112]), "+f"(d[113]), "+f"(d[114]), "+f"(d[115]), "+f"(d[116]), "+f"(d[117]), "+f"(d[118]), "+f"(d[119]),
          "+f"(d[120]), "+f"(d[121]), "+f"(d[122]), "+f"(d[123]), "+f"(d[124]), "+f"(d[125]), "+f"(d[126]), "+f"(d[127])
        : "l"(da), "l"(db));
}
__device__ __forceinline__ void wgmma_ss_n256_tb_init(float (&d)[128], uint64_t da, uint64_t db) {
    asm volatile("wgmma.mma_async.sync.aligned.m64n256k16.f32.bf16.bf16 {"
        "%0, %1, %2, %3, %4, %5, %6, %7, %8, %9, %10, %11, %12, %13, %14, %15, %16, %17, %18, %19, %20, %21, %22, %23, %24, %25, %26, %27, %28, %29, %30, %31, "
        "%32, %33, %34, %35, %36, %37, %38, %39, %40, %41, %42, %43, %44, %45, %46, %47, %48, %49, %50, %51, %52, %53, %54, %55, %56, %57, %58, %59, %60, %61, %62, %63, "
        "%64, %65, %66, %67, %68, %69, %70, %71, %72, %73, %74, %75, %76, %77, %78, %79, %80, %81, %82, %83, %84, %85, %86, %87, %88, %89, %90, %91, %92, %93, %94, %95, "
        "%96, %97, %98, %99, %100, %101, %102, %103, %104, %105, %106, %107, %108, %109, %110, %111, %112, %113, %114, %115, %116, %117, %118, %119, %120, %121, %122, %123, %124, %125, %126, %127}, %128, %129, 0, 1, 1, 0, 1;\n"
        : "=f"(d[0]), "=f"(d[1]), "=f"(d[2]), "=f"(d[3]), "=f"(d[4]), "=f"(d[5]), "=f"(d[6]), "=f"(d[7]),
          "=f"(d[8]), "=f"(d[9]), "=f"(d[10]), "=f"(d[11]), "=f"(d[12]), "=f"(d[13]), "=f"(d[14]), "=f"(d[15]),
          "=f"(d[16]), "=f"(d[17]), "=f"(d[18]), "=f"(d[19]), "=f"(d[20]), "=f"(d[21]), "=f"(d[22]), "=f"(d[23]),
          "=f"(d[24]), "=f"(d[25]), "=f"(d[26]), "=f"(d[27]), "=f"(d[28]), "=f"(d[29]), "=f"(d[30]), "=f"(d[31]),
          "=f"(d[32]), "=f"(d[33]), "=f"(d[34]), "=f"(d[35]), "=f"(d[36]), "=f"(d[37]), "=f"(d[38]), "=f"(d[39]),
          "=f"(d[40]), "=f"(d[41]), "=f"(d[42]), "=f"(d[43]), "=f"(d[44]), "=f"(d[45]), "=f"(d[46]), "=f"(d[47]),
          "=f"(d[48]), "=f"(d[49]), "=f"(d[50]), "=f"(d[51]), "=f"(d[52]), "=f"(d[53]), "=f"(d[54]), "=f"(d[55]),
          "=f"(d[56]), "=f"(d[57]), "=f"(d[58]), "=f"(d[59]), "=f"(d[60]), "=f"(d[61]), "=f"(d[62]), "=f"(d[63]),
          "=f"(d[64]), "=f"(d[65]), "=f"(d[66]), "=f"(d[67]), "=f"(d[68]), "=f"(d[69]), "=f"(d[70]), "=f"(d[71]),
          "=f"(d[72]), "=f"(d[73]), "=f"(d[74]), "=f"(d[75]), "=f"(d[76]), "=f"(d[77]), "=f"(d[78]), "=f"(d[79]),
          "=f"(d[80]), "=f"(d[81]), "=f"(d[82]), "=f"(d[83]), "=f"(d[84]), "=f"(d[85]), "=f"(d[86]), "=f"(d[87]),
          "=f"(d[88]), "=f"(d[89]), "=f"(d[90]), "=f"(d[91]), "=f"(d[92]), "=f"(d[93]), "=f"(d[94]), "=f"(d[95]),
          "=f"(d[96]), "=f"(d[97]), "=f"(d[98]), "=f"(d[99]), "=f"(d[100]), "=f"(d[101]), "=f"(d[102]), "=f"(d[103]),
          "=f"(d[104]), "=f"(d[105]), "=f"(d[106]), "=f"(d[107]), "=f"(d[108]), "=f"(d[109]), "=f"(d[110]), "=f"(d[111]),
          "=f"(d[112]), "=f"(d[113]), "=f"(d[114]), "=f"(d[115]), "=f"(d[116]), "=f"(d[117]), "=f"(d[118]), "=f"(d[119]),
          "=f"(d[120]), "=f"(d[121]), "=f"(d[122]), "=f"(d[123]), "=f"(d[124]), "=f"(d[125]), "=f"(d[126]), "=f"(d[127])
        : "l"(da), "l"(db));
}
__device__ __forceinline__ void wgmma_ss_n256_tb_pred(float (&d)[128], uint64_t da, uint64_t db, int acc) {
    asm volatile("{\n.reg .pred p;\nsetp.ne.s32 p, %130, 0;\nwgmma.mma_async.sync.aligned.m64n256k16.f32.bf16.bf16 {"
        "%0, %1, %2, %3, %4, %5, %6, %7, %8, %9, %10, %11, %12, %13, %14, %15, %16, %17, %18, %19, %20, %21, %22, %23, %24, %25, %26, %27, %28, %29, %30, %31, "
        "%32, %33, %34, %35, %36, %37, %38, %39, %40, %41, %42, %43, %44, %45, %46, %47, %48, %49, %50, %51, %52, %53, %54, %55, %56, %57, %58, %59, %60, %61, %62, %63, "
        "%64, %65, %66, %67, %68, %69, %70, %71, %72, %73, %74, %75, %76, %77, %78, %79, %80, %81, %82, %83, %84, %85, %86, %87, %88, %89, %90, %91, %92, %93, %94, %95, "
        "%96, %97, %98, %99, %100, %101, %102, %103, %104, %105, %106, %107, %108, %109, %110, %111, %112, %113, %114, %115, %116, %117, %118, %119, %120, %121, %122, %123, %124, %125, %126, %127}, %128, %129, p, 1, 1, 0, 1;\n}\n"
        : "+f"(d[0]), "+f"(d[1]), "+f"(d[2]), "+f"(d[3]), "+f"(d[4]), "+f"(d[5]), "+f"(d[6]), "+f"(d[7]),
          "+f"(d[8]), "+f"(d[9]), "+f"(d[10]), "+f"(d[11]), "+f"(d[12]), "+f"(d[13]), "+f"(d[14]), "+f"(d[15]),
          "+f"(d[16]), "+f"(d[17]), "+f"(d[18]), "+f"(d[19]), "+f"(d[20]), "+f"(d[21]), "+f"(d[22]), "+f"(d[23]),
          "+f"(d[24]), "+f"(d[25]), "+f"(d[26]), "+f"(d[27]), "+f"(d[28]), "+f"(d[29]), "+f"(d[30]), "+f"(d[31]),
          "+f"(d[32]), "+f"(d[33]), "+f"(d[34]), "+f"(d[35]), "+f"(d[36]), "+f"(d[37]), "+f"(d[38]), "+f"(d[39]),
          "+f"(d[40]), "+f"(d[41]), "+f"(d[42]), "+f"(d[43]), "+f"(d[44]), "+f"(d[45]), "+f"(d[46]), "+f"(d[47]),
          "+f"(d[48]), "+f"(d[49]), "+f"(d[50]), "+f"(d[51]), "+f"(d[52]), "+f"(d[53]), "+f"(d[54]), "+f"(d[55]),
          "+f"(d[56]), "+f"(d[57]), "+f"(d[58]), "+f"(d[59]), "+f"(d[60]), "+f"(d[61]), "+f"(d[62]), "+f"(d[63]),
          "+f"(d[64]), "+f"(d[65]), "+f"(d[66]), "+f"(d[67]), "+f"(d[68]), "+f"(d[69]), "+f"(d[70]), "+f"(d[71]),
          "+f"(d[72]), "+f"(d[73]), "+f"(d[74]), "+f"(d[75]), "+f"(d[76]), "+f"(d[77]), "+f"(d[78]), "+f"(d[79]),
          "+f"(d[80]), "+f"(d[81]), "+f"(d[82]), "+f"(d[83]), "+f"(d[84]), "+f"(d[85]), "+f"(d[86]), "+f"(d[87]),
          "+f"(d[88]), "+f"(d[89]), "+f"(d[90]), "+f"(d[91]), "+f"(d[92]), "+f"(d[93]), "+f"(d[94]), "+f"(d[95]),
          "+f"(d[96]), "+f"(d[97]), "+f"(d[98]), "+f"(d[99]), "+f"(d[100]), "+f"(d[101]), "+f"(d[102]), "+f"(d[103]),
          "+f"(d[104]), "+f"(d[105]), "+f"(d[106]), "+f"(d[107]), "+f"(d[108]), "+f"(d[109]), "+f"(d[110]), "+f"(d[111]),
          "+f"(d[112]), "+f"(d[113]), "+f"(d[114]), "+f"(d[115]), "+f"(d[116]), "+f"(d[117]), "+f"(d[118]), "+f"(d[119]),
          "+f"(d[120]), "+f"(d[121]), "+f"(d[122]), "+f"(d[123]), "+f"(d[124]), "+f"(d[125]), "+f"(d[126]), "+f"(d[127])
        : "l"(da), "l"(db), "r"(acc));
}
__device__ __forceinline__ void wgmma_rs_n64_tb(float (&d)[32], uint32_t a0, uint32_t a1, uint32_t a2, uint32_t a3, uint64_t db) {
    asm volatile("wgmma.mma_async.sync.aligned.m64n64k16.f32.bf16.bf16 {"
        "%0, %1, %2, %3, %4, %5, %6, %7, %8, %9, %10, %11, %12, %13, %14, %15, %16, %17, %18, %19, %20, %21, %22, %23, %24, %25, %26, %27, %28, %29, %30, %31}, {%32, %33, %34, %35}, %36, 1, 1, 1, 1;\n"
        : "+f"(d[0]), "+f"(d[1]), "+f"(d[2]), "+f"(d[3]), "+f"(d[4]), "+f"(d[5]), "+f"(d[6]), "+f"(d[7]),
          "+f"(d[8]), "+f"(d[9]), "+f"(d[10]), "+f"(d[11]), "+f"(d[12]), "+f"(d[13]), "+f"(d[14]), "+f"(d[15]),
          "+f"(d[16]), "+f"(d[17]), "+f"(d[18]), "+f"(d[19]), "+f"(d[20]), "+f"(d[21]), "+f"(d[22]), "+f"(d[23]),
          "+f"(d[24]), "+f"(d[25]), "+f"(d[26]), "+f"(d[27]), "+f"(d[28]), "+f"(d[29]), "+f"(d[30]), "+f"(d[31])
        : "r"(a0), "r"(a1), "r"(a2), "r"(a3), "l"(db));
}
__device__ __forceinline__ void wgmma_rs_n64_tb_init(float (&d)[32], uint32_t a0, uint32_t a1, uint32_t a2, uint32_t a3, uint64_t db) {
    asm volatile("wgmma.mma_async.sync.aligned.m64n64k16.f32.bf16.bf16 {"
        "%0, %1, %2, %3, %4, %5, %6, %7, %8, %9, %10, %11, %12, %13, %14, %15, %16, %17, %18, %19, %20, %21, %22, %23, %24, %25, %26, %27, %28, %29, %30, %31}, {%32, %33, %34, %35}, %36, 0, 1, 1, 1;\n"
        : "=f"(d[0]), "=f"(d[1]), "=f"(d[2]), "=f"(d[3]), "=f"(d[4]), "=f"(d[5]), "=f"(d[6]), "=f"(d[7]),
          "=f"(d[8]), "=f"(d[9]), "=f"(d[10]), "=f"(d[11]), "=f"(d[12]), "=f"(d[13]), "=f"(d[14]), "=f"(d[15]),
          "=f"(d[16]), "=f"(d[17]), "=f"(d[18]), "=f"(d[19]), "=f"(d[20]), "=f"(d[21]), "=f"(d[22]), "=f"(d[23]),
          "=f"(d[24]), "=f"(d[25]), "=f"(d[26]), "=f"(d[27]), "=f"(d[28]), "=f"(d[29]), "=f"(d[30]), "=f"(d[31])
        : "r"(a0), "r"(a1), "r"(a2), "r"(a3), "l"(db));
}

__device__ __forceinline__ void wg_fence() { asm volatile("wgmma.fence.sync.aligned;\n" ::: "memory"); }
__device__ __forceinline__ void wg_commit() { asm volatile("wgmma.commit_group.sync.aligned;\n" ::: "memory"); }
template <int N> __device__ __forceinline__ void wg_wait() { asm volatile("wgmma.wait_group.sync.aligned %0;\n" ::"n"(N) : "memory"); }
template <int N> __device__ __forceinline__ void fence_regs(float (&a)[N]) {
#pragma unroll
    for (int i = 0; i < N; i++) asm volatile("" : "+f"(a[i])::"memory");
}
template <int N> __device__ __forceinline__ void fence_regs(uint32_t (&a)[N]) {
#pragma unroll
    for (int i = 0; i < N; i++) asm volatile("" : "+r"(a[i])::"memory");
}
__device__ __forceinline__ void mbar_init(uint32_t bar, uint32_t cnt) {
    asm volatile("mbarrier.init.shared::cta.b64 [%0], %1;\n" ::"r"(bar), "r"(cnt) : "memory");
}
__device__ __forceinline__ void mbar_expect_tx(uint32_t bar, uint32_t bytes) {
    asm volatile("mbarrier.arrive.expect_tx.shared::cta.b64 _, [%0], %1;\n" ::"r"(bar), "r"(bytes) : "memory");
}
__device__ __forceinline__ void mbar_wait(uint32_t bar, uint32_t parity) {
    asm volatile("{\n.reg .pred p;\nLW:\nmbarrier.try_wait.parity.shared::cta.b64 p, [%0], %1;\n@!p pmevent 0;\n@!p bra LW;\n}\n" ::"r"(bar), "r"(parity) : "memory");
}
__device__ __forceinline__ void mbar_wait_sleep(uint32_t bar, uint32_t parity) {
    asm volatile("{\n.reg .pred p;\nLW:\nmbarrier.try_wait.parity.shared::cta.b64 p, [%0], %1, 20000;\n@!p pmevent 0;\n@!p bra LW;\n}\n" ::"r"(bar), "r"(parity) : "memory");
}
__device__ __forceinline__ void mbar_wait_bounded(uint32_t bar, uint32_t parity) {
    asm volatile("{\n.reg .pred p;\n.reg .u32 c;\nmov.u32 c, 0;\nLW:\nmbarrier.try_wait.parity.shared::cta.b64 p, [%0], %1, 20000;\n@p bra LD;\n"
                 "add.u32 c, c, 1;\nsetp.ge.u32 p, c, 262144;\n@p trap;\nbra LW;\nLD:\n}\n" ::"r"(bar), "r"(parity) : "memory");
}
__device__ __forceinline__ void flag_wait(const int* p, int v) {
    asm volatile("{\n.reg .pred p;\n.reg .s32 f;\nLW:\nld.acquire.gpu.global.s32 f, [%0];\nsub.s32 f, f, %1;\nsetp.lt.s32 p, f, 0;\n@p bra LW;\n}\n" ::"l"(p), "r"(v) : "memory");
}
__device__ __forceinline__ void flag_wait_bounded(const int* p, int v) {
    asm volatile("{\n.reg .pred p;\n.reg .u32 c;\n.reg .s32 f;\nmov.u32 c, 0;\nLW:\nld.acquire.gpu.global.s32 f, [%0];\nsub.s32 f, f, %1;\nsetp.ge.s32 p, f, 0;\n@p bra LD;\n"
                 "nanosleep.u32 500;\nadd.u32 c, c, 1;\nsetp.ge.u32 p, c, 4194304;\n@p trap;\nbra LW;\nLD:\n}\n" ::"l"(p), "r"(v) : "memory");
}
__device__ __forceinline__ int lane_now() {
    int l; asm volatile("mov.u32 %0, %%laneid;\n" : "=r"(l)); return l;
}
__device__ __forceinline__ bool elect() {
    uint32_t p; asm volatile("{\n.reg .pred p;\nelect.sync _|p, -1;\nselp.u32 %0, 1, 0, p;\n}\n" : "=r"(p)); return p;
}
__device__ __forceinline__ void bulk_g2s(uint32_t dst, const void* src, uint32_t bytes, uint32_t bar) {
    asm volatile("cp.async.bulk.shared::cluster.global.mbarrier::complete_tx::bytes [%0], [%1], %2, [%3];\n"
                 ::"r"(dst), "l"(src), "r"(bytes), "r"(bar) : "memory");
}
__device__ __forceinline__ void tma_g2s(uint32_t dst, const CUtensorMap* tm, int rowgroup, uint32_t bar) {
    asm volatile("cp.async.bulk.tensor.4d.shared::cluster.global.tile.mbarrier::complete_tx::bytes [%0], [%1, {0, 0, 0, %2}], [%3];\n"
                 ::"r"(dst), "l"(tm), "r"(rowgroup), "r"(bar) : "memory");
}
__device__ __forceinline__ void bar_sync(int id, int n) { asm volatile("bar.sync %0, %1;\n" ::"r"(id), "r"(n) : "memory"); }
__device__ __forceinline__ void bar_arrive(int id, int n) { asm volatile("bar.arrive %0, %1;\n" ::"r"(id), "r"(n) : "memory"); }
__device__ __forceinline__ float quad_last(float v) {
    float r; asm volatile("shfl.sync.idx.b32 %0, %1, 3, 0x1c1f, -1;\n" : "=f"(r) : "f"(v)); return r;
}
__device__ __forceinline__ float ex2(float x) { float y; asm("ex2.approx.ftz.f32 %0, %1;\n" : "=f"(y) : "f"(x)); return y; }
__device__ __forceinline__ uint32_t ex2_f16(uint32_t x) { uint32_t y; asm("ex2.approx.f16x2 %0, %1;\n" : "=r"(y) : "r"(x)); return y; }
__device__ __forceinline__ uint32_t hmax2_f16(uint32_t a, uint32_t b) { uint32_t r; asm("max.f16x2 %0, %1, %2;\n" : "=r"(r) : "r"(a), "r"(b)); return r; }
__device__ __forceinline__ float rcp(float x) { float y; asm("rcp.approx.ftz.f32 %0, %1;\n" : "=f"(y) : "f"(x)); return y; }
__device__ __forceinline__ uint32_t pack_bf16(float lo, float hi) {
    uint32_t r; asm("cvt.rn.bf16x2.f32 %0, %1, %2;\n" : "=r"(r) : "f"(hi), "f"(lo)); return r;
}
__device__ __forceinline__ uint32_t pack_f16(float lo, float hi) {
    uint32_t r; asm("cvt.rn.f16x2.f32 %0, %1, %2;\n" : "=r"(r) : "f"(hi), "f"(lo)); return r;
}
__device__ __forceinline__ uint32_t pack_f16_sat(float lo, float hi) {
    uint32_t r; asm("cvt.rn.satfinite.f16x2.f32 %0, %1, %2;\n" : "=r"(r) : "f"(hi), "f"(lo)); return r;
}
__device__ __forceinline__ float f16_lo(uint32_t v) { float r; asm("cvt.f32.f16 %0, %1;\n" : "=f"(r) : "h"((unsigned short)v)); return r; }
__device__ __forceinline__ float f16_hi(uint32_t v) { return f16_lo(v >> 16); }
__device__ __forceinline__ float bf_lo(uint32_t v) { return __uint_as_float(v << 16); }
__device__ __forceinline__ float bf_hi(uint32_t v) { return __uint_as_float(v & 0xFFFF0000u); }
__device__ __forceinline__ float bf_round(float x) { return __uint_as_float(pack_bf16(0.f, x)); }
__device__ __forceinline__ void st_release(int* p, int v) {
    asm volatile("st.release.gpu.global.s32 [%0], %1;\n" ::"l"(p), "r"(v) : "memory");
}
__device__ __forceinline__ uint4 ldg_pinned(const uint4* p) {
    uint4 v; asm volatile("ld.global.nc.v4.u32 {%0, %1, %2, %3}, [%4];\n" : "=r"(v.x), "=r"(v.y), "=r"(v.z), "=r"(v.w) : "l"(p) : "memory"); return v;
}
__device__ __forceinline__ void stmatrix_x4(uint32_t addr, uint32_t r0, uint32_t r1, uint32_t r2, uint32_t r3) {
    asm volatile("stmatrix.sync.aligned.m8n8.x4.shared.b16 [%0], {%1, %2, %3, %4};\n" ::"r"(addr), "r"(r0), "r"(r1), "r"(r2), "r"(r3) : "memory");
}

__device__ __forceinline__ uint32_t tile_off(int r, int ch) {
    return (uint32_t)((r >> 3) * 4096 + (ch >> 3) * 1024 + (r & 7) * 128 + (((ch ^ r) & 7) << 4));
}
__device__ __forceinline__ int h_unit(int qt, int u) { return qt < 78 ? u * 78 + qt : 624; }
__device__ __forceinline__ int row_off(int r) { return 4096 + h_unit(r >> 7, (r >> 4) & 7) * 8192 + (r & 8) * 512 + (r & 7) * 144; }

__device__ __forceinline__ float4 lds128f(uint32_t a) {
    float4 v; asm volatile("ld.shared.v4.f32 {%0, %1, %2, %3}, [%4];\n" : "=f"(v.x), "=f"(v.y), "=f"(v.z), "=f"(v.w) : "r"(a) : "memory"); return v;
}
__device__ __forceinline__ uint64_t lds64(uint32_t a) { uint64_t v; asm volatile("ld.shared.u64 %0, [%1];\n" : "=l"(v) : "r"(a) : "memory"); return v; }
__device__ __forceinline__ uint4 lds128(uint32_t a) {
    uint4 v; asm volatile("ld.shared.v4.u32 {%0, %1, %2, %3}, [%4];\n" : "=r"(v.x), "=r"(v.y), "=r"(v.z), "=r"(v.w) : "r"(a) : "memory"); return v;
}
__device__ __forceinline__ void sts128(uint32_t a, uint32_t x, uint32_t y, uint32_t z, uint32_t w) {
    asm volatile("st.shared.v4.u32 [%0], {%1, %2, %3, %4};\n" ::"r"(a), "r"(x), "r"(y), "r"(z), "r"(w) : "memory");
}
__device__ __forceinline__ void mbar_arrive(uint32_t bar) {
    asm volatile("mbarrier.arrive.shared::cta.b64 _, [%0];\n" ::"r"(bar) : "memory");
}
__device__ __forceinline__ uint64_t mkaddr(uint32_t lo, uint32_t hi) { uint64_t a; asm("mov.b64 %0, {%1, %2};\n" : "=l"(a) : "r"(lo), "r"(hi)); return a; }
__device__ __forceinline__ void red_add(int* p) { asm volatile("red.relaxed.gpu.global.add.s32 [%0], 1;\n" ::"l"(p) : "memory"); }
__device__ __forceinline__ void red_release(int* p) {
    asm volatile("fence.proxy.async.global;\nfence.acq_rel.gpu;\nred.relaxed.gpu.global.add.s32 [%0], 1;\n" ::"l"(p) : "memory");
}
__device__ __forceinline__ void fence_async_global() { asm volatile("fence.proxy.async.global;\n" ::: "memory"); }
__device__ __forceinline__ void fence_async_smem() { asm volatile("fence.proxy.async.shared::cta;\n" ::: "memory"); }
__device__ __forceinline__ void bulk_s2g(void* dst, uint32_t src, uint32_t bytes) {
    asm volatile("cp.async.bulk.global.shared::cta.bulk_group [%0], [%1], %2;\ncp.async.bulk.commit_group;\n" ::"l"(dst), "r"(src), "r"(bytes) : "memory");
}
__device__ __forceinline__ void mma16816(float (&c)[4], uint32_t a0, uint32_t a1, uint32_t a2, uint32_t a3, uint32_t b0, uint32_t b1) {
    asm("mma.sync.aligned.m16n8k16.row.col.f32.bf16.bf16.f32 {%0, %1, %2, %3}, {%4, %5, %6, %7}, {%8, %9}, {%0, %1, %2, %3};\n"
        : "+f"(c[0]), "+f"(c[1]), "+f"(c[2]), "+f"(c[3]) : "r"(a0), "r"(a1), "r"(a2), "r"(a3), "r"(b0), "r"(b1));
}
__device__ __forceinline__ void mma1688(float (&c)[4], uint32_t a0, uint32_t a1, uint32_t b0) {
    asm("mma.sync.aligned.m16n8k8.row.col.f32.bf16.bf16.f32 {%0, %1, %2, %3}, {%4, %5}, {%6}, {%0, %1, %2, %3};\n"
        : "+f"(c[0]), "+f"(c[1]), "+f"(c[2]), "+f"(c[3]) : "r"(a0), "r"(a1), "r"(b0));
}
__device__ __forceinline__ uint32_t hadd2_f16(uint32_t a, uint32_t b) { uint32_t r; asm("add.rn.f16x2 %0, %1, %2;\n" : "=r"(r) : "r"(a), "r"(b)); return r; }
__device__ __forceinline__ uint32_t hadd2(uint32_t a, uint32_t b) { uint32_t r; asm("add.rn.bf16x2 %0, %1, %2;\n" : "=r"(r) : "r"(a), "r"(b)); return r; }
__device__ __forceinline__ uint32_t hmul2(uint32_t a, uint32_t b) { uint32_t r; asm("mul.rn.bf16x2 %0, %1, %2;\n" : "=r"(r) : "r"(a), "r"(b)); return r; }
__device__ __forceinline__ uint32_t hfma2(uint32_t a, uint32_t b, uint32_t c) { uint32_t r; asm("fma.rn.bf16x2 %0, %1, %2, %3;\n" : "=r"(r) : "r"(a), "r"(b), "r"(c)); return r; }

constexpr int SM_Q = 0;
constexpr int SM_KV = 65536;
constexpr int SM_ML = SM_KV + STAGES * KV_BYTES;
constexpr int SM_BAR = SM_ML + 1024;
constexpr int SM_TOTAL = SM_BAR + 256;
constexpr float SCALE_LOG2 = 1.4426950408889634f / 16.0f;
constexpr float KV_SCALE = 6.f;
constexpr float KV_OFF = 48.f;
constexpr uint32_t KV_OFF2 = 0x52005200u;
constexpr uint32_t KV_OFF8 = 0x5A005A00u;
constexpr uint32_t NEG2 = 0x80008000u;
constexpr uint32_t S_LIMIT = 0x4B804B80u;
constexpr float REF_UP = REFUP;
__device__ __forceinline__ uint32_t kvf(uint32_t a, uint32_t off) {
    uint32_t r; asm("fma.rn.f16x2 %0, %1, %2, %3;\n" : "=r"(r) : "r"(a), "r"(pack_f16(KV_SCALE, KV_SCALE)), "r"(off)); return r;
}
enum { BAR_PP0 = 1, BAR_PP1 = 2, BAR_WG0 = 3, BAR_WG1 = 4, BAR_H0 = 5, BAR_H1 = 6, BAR_AUX = 7, BAR_BF = 8, BAR_H2 = 9, BAR_X = 10, BAR_GO = 11, BAR_WG2 = 12, BAR_ST = 13 };

struct Hot {
    const __nv_bfloat16 *wk, *wq, *x;
    Scratch* s;
};
struct Params {
    const __nv_bfloat16* deg_inv;
    const int *src, *dst;
    __nv_bfloat16* out;
    uint32_t dhi;
    int E;
    CUtensorMap tm_out;
    CUtensorMap tm_outc;
    CUtensorMap tm_w[3];
};
static_assert(offsetof(Params, tm_outc) == offsetof(Params, tm_out) + 128, "layout");
#define SC_PAIR (blockIdx.x < 104)
#define SC_TAIL (blockIdx.x >= NCTA - 2)
#define SC_LAST (blockIdx.x == NCTA - 1)
#define SC_HELP (SC_PAIR && rank)
#define SC_OWNER (!SC_HELP && !SC_LAST)
#define SC_QT1 (26 + (int)(blockIdx.x >> 1))
#define SC_QT0 (SC_PAIR ? (rank ? (int)(blockIdx.x >> 2) : SC_QT1) : SC_TAIL ? 78 : (int)blockIdx.x - 104)
#define SC_NKV (SC_LAST ? 50 : 75)
#define SC_CLS (SC_PAIR ? (rank ? 0x120 ^ (blockIdx.x & 2) * 0x80 : 0x430) | (blockIdx.x & 2) >> 1 : SC_LAST ? 0x10 : 0x432)
#define SC_NW (SC_PAIR ? 8 : SC_LAST ? 0 : 4)
#define SC_ZB (2 * SC_QT1 + 1 - (int)rank)
#define SC_TZB(k) (rank && !(k) ? 156 : 2 * (k) - (int)rank)

__global__ void __cluster_dims__(2, 1, 1) __launch_bounds__(384, 1) k_main(const __grid_constant__ Hot H, const __grid_constant__ Params P) {
    extern __shared__ __align__(1024) uint8_t smem[];
    const uint32_t sb = (uint32_t)__cvta_generic_to_shared(smem);
    const int tid = threadIdx.x, wg = __shfl_sync(~0u, tid >> 7, 0);
    const int lane = tid & 31, g = lane >> 2, q = lane & 3;
    const uint32_t rank = blockIdx.x & 1;
    const uint32_t bar_full = sb + SM_BAR, bar_q = bar_full + 32, bar_go = bar_full + 48;
    const uint32_t bar_pin = bar_full + 56;
    const uint32_t bar_qfree = bar_full + 72, bar_pdone = bar_full + 88, bar_zst = bar_full + 104, bar_rfree = bar_full + 120;
    const uint32_t bar_empty = bar_full + 128, bar_end = bar_full + 160, s_tm = bar_full + 184, bar_x = bar_full + 192;
    const uint32_t bar_a = sb + SM_ML;

    const int t = tid & 127, warp = __shfl_sync(~0u, t >> 5, 0);
    int ep = 0;
    if (wg & 2) {
        unsigned done;
        {
            uint4 ra[2], rb[2], rk[5][2];
            if (blockIdx.x < 128) {
                const int e = (blockIdx.x >> 4) * 32 + (g >> 1) * 8 + (blockIdx.x & 8) / 2 + (g & 1);
                const uint4* pq = (const uint4*)(H.wq + e * 256) + warp * 8 + q;
                const uint4* pk = (const uint4*)(H.wk + ((blockIdx.x & 7) * 32 + g) * 256) + warp * 8 + q;
                const uint4* pz = (const uint4*)(H.wk + 255 * 256) + warp * 8 + q;
#pragma unroll
                for (int s = 0; s < 2; s++) {
                    ra[s] = ldg_pinned(pq + 4 * s);
                    rb[s] = ldg_pinned(pq + 4 * s + 64);
#pragma unroll
                    for (int n = 0; n < 4; n++) rk[n][s] = ldg_pinned(pk + 4 * s + n * 256);
                    rk[4][s] = ldg_pinned(pz + 4 * s);
                }
            }
            asm volatile("{\n.reg .pred p;\nsetp.eq.s32 p, %2, 0;\nmov.u32 %0, 0;\n@p ld.global.cg.u32 %0, [%1];\n}\n" : "=r"(done) : "l"(&g_sync[SY_DONE * 32]), "r"(lane) : "memory");
            bar_arrive(BAR_X, 384);
            if (warp == 0 && elect()) {
#pragma unroll
                for (int i = 0; i < 21; i++) mbar_init(bar_full + 8 * i, i < 9 ? 1 : i < 16 ? 4 : i == 20 ? 11 : SC_TAIL ? 4 : 8);
#pragma unroll
                for (int i = 0; i < 4; i++) mbar_init(bar_a + 8 * i, 1);
                mbar_expect_tx(bar_pin, QB_BYTES / 2 + 512); mbar_expect_tx(bar_pin + 8, QB_BYTES / 2);
                asm volatile("fence.mbarrier_init.release.cluster;\n" ::: "memory");
            }
            __syncwarp();
            asm volatile("barrier.cluster.arrive.relaxed.aligned;\n" ::: "memory");
            if (blockIdx.x < 128) {
                float c[5][4] = {};
#pragma unroll
                for (int s = 0; s < 2; s++) {
#pragma unroll
                    for (int n = 0; n < 5; n++) mma16816(c[n], ra[s].x, rb[s].x, ra[s].y, rb[s].y, rk[n][s].x, rk[n][s].y);
#pragma unroll
                    for (int n = 0; n < 5; n++) mma16816(c[n], ra[s].z, rb[s].z, ra[s].w, rb[s].w, rk[n][s].z, rk[n][s].w);
                }
#pragma unroll
                for (int i = 0; i < 4; i++) {
                    const int r = i & 2, n = (i & 1) * 2;
                    sts128(sb + SM_KV + 3 * KV_BYTES + QB_BYTES + i * 2048 + t * 16, __float_as_uint(c[n][r] - c[4][r]), __float_as_uint(c[n][r + 1] - c[4][r]),
                           __float_as_uint(c[n + 1][r] - c[4][r]), __float_as_uint(c[n + 1][r + 1] - c[4][r]));
                }
            }
        }
        asm volatile("setmaxnreg.dec.sync.aligned.u32 %0;\n" ::"n"(REG_P));
        if (blockIdx.x < 128) {
            bar_sync(BAR_WG2, 128);
            float4 v[4];
#pragma unroll
            for (int i = 0; i < 4; i++) v[i] = lds128f(sb + SM_KV + 3 * KV_BYTES + QB_BYTES + (warp & 2) * 2048 + (lane & 1) * 2048 + i * 512 + ((warp & 1) * 16 + (lane >> 1)) * 16);
            constexpr float SC = SCALE_LOG2 / KV_SCALE;
            const int r = (warp & 1) * 4 + (lane >> 3);
            *(uint2*)(g_w + tile_off((blockIdx.x >> 3) * 16 + (warp & 2) * 4 + r, (blockIdx.x & 7) * 4 + ((lane >> 1) & 3)) + (lane & 1) * 8) =
                make_uint2(pack_f16_sat(((v[0].x + v[1].x) + (v[2].x + v[3].x)) * SC, ((v[0].y + v[1].y) + (v[2].y + v[3].y)) * SC) | 1,
                           pack_f16_sat(((v[0].z + v[1].z) + (v[2].z + v[3].z)) * SC, ((v[0].w + v[1].w) + (v[2].w + v[3].w)) * SC) | 1);
            if (warp != 1) {
                bar_arrive(BAR_AUX, 128);
            } else {
                bar_sync(BAR_AUX, 128);
                if (elect()) { red_add(&g_sync[SY_DONE * 32 + 4 + (blockIdx.x >> 5)]); }
                __syncwarp();
            }
        }
        else bar_sync(BAR_WG2, 128);
        if (warp == 1) bar_arrive(BAR_GO, 160);
        auto load_a = [&](int j) {
            if (elect()) {
                mbar_expect_tx(bar_a + 8 * j, QB_BYTES);
                bulk_g2s(sb + SM_KV + j * KV_BYTES, g_w + j * QB_BYTES, QB_BYTES, bar_a + 8 * j);
            }
            __syncwarp();
        };
        if (warp == 0) {
            auto poll = [&]() { int c; asm volatile("ld.relaxed.gpu.global.s32 %0, [%1];\n" : "=r"(c) : "l"(&g_sync[SY_DONE * 32 + 4 + (lane & 3)]) : "memory"); return c; };
#pragma unroll 1
            for (int j = 0; j < 4;) {
#pragma unroll 1
                for (const uint32_t mk = __ballot_sync(~0u, poll() >= 32) & 15; (mk >> j) & 1; j++) load_a(j);
            }
        } else if (warp & 1) {
#pragma unroll 1
            for (int j = 0, n = 0; j < 4;) {
                mbar_wait_bounded(bar_a + 8 * j, n & 1);
                uint32_t ok = 1;
#pragma unroll
                for (int i = 0; i < 16; i++) {
                    uint32_t v;
                    asm volatile("ld.shared.u32 %0, [%1];\n" : "=r"(v) : "r"(sb + SM_KV + j * KV_BYTES + (warp & 2) * 8192 + i * 1024 + lane * 32 + g * 4) : "memory");
                    ok &= v;
                }
                asm volatile("{\n.reg .pred p;\nsetp.ne.u32 p, %0, 0;\nbar.red.and.pred p, %1, 64, p;\nselp.u32 %0, 1, 0, p;\n}\n" : "+r"(ok) : "n"((int)BAR_WG2) : "memory");
                if (__any_sync(~0u, ok)) {
                    if (warp == 1 && elect()) asm volatile("mbarrier.arrive.shared::cta.b64 _, [%0];\nmbarrier.inval.shared::cta.b64 [%1];\n" ::"r"(bar_full + 8 * j), "r"(bar_a + 8 * j) : "memory");
                    __syncwarp();
                    j++; n = 0;
                } else {
                    asm volatile("{\n.reg .pred p;\nsetp.gt.s32 p, %0, 1000000;\n@p trap;\n}\n" ::"r"(++n) : "memory");
                    fence_async_smem();
                    if (warp == 1) load_a(j);
                }
            }
        }
        done = __shfl_sync(~0u, done, 0);
        ep = (int)(done / NCTA) + 1;
        asm volatile("barrier.cluster.wait.acquire.aligned;\n" ::: "memory");
        if (warp == 0) {
            asm volatile("st.shared.u64 [%0], %1;\n" ::"r"(s_tm), "l"(&P.tm_outc) : "memory");
            __syncwarp();
            if (elect()) {
                const uint8_t* base = (const uint8_t*)H.s;
                uint32_t cls = SC_CLS, bytes = KV_BYTES, step = 5 * KV_BYTES;
                const uint8_t* src = base;
                bool tick;
                int next = 0;
                const int nit = SC_NKV + SC_NW;
#pragma unroll 1
                for (int j = 0; j < nit; j++) {
                    const uint32_t slot = sb + SM_KV + (j & 3) * KV_BYTES, fb = bar_full + 8 * (j & 3);
                    if (j == next) {
                        const int k = j - SC_NKV;
                        const int sw = SC_HELP ? j - 25 : -1;
                        next = j + 1;
                        tick = j >= 3 && k < 0 && (sw | 1) != 3 && !SC_TAIL;
                        if (j >= 3 && (unsigned)sw >= 5) next = k >= 0 ? next : j < GO0 ? GO0 : j < 25 ? 25 : j < GO1 ? GO1 : j < 49 ? 49 : j < 50 ? 50 : 75;
                        if (j == 0 || j == 25 || j == 50) { src = base + (4096 + (cls & 15) * KV_BYTES); cls >>= 4; }
                        if (SC_TAIL ? j == nit - 1 : j == GO0 || j == GO1) mbar_arrive(bar_go);
                        int fo = -1, fv = 1;
                        if (j < 3) { fo = (SY_H0 + 5 * j + (SC_CLS & 15)) * 32; fv = 5; }
                        if (j == 3) { fo = SY_H1 * 32; fv = 79; }
                        if (sw == 1) fo = 25 * 32 + SC_QT1;
                        if (k == 0) fo = SY_B * 32;
                        if (k == 1 && !SC_PAIR) { fo = SY_AUX0 * 32; fv = NAUX; }
                        if (k == 2 && SC_PAIR) { fo = SY_AUX * 32; fv = NAUX / 3; }
                        if (fo >= 0) {
                            flag_wait(g_sync + fo, fv * ep);
                            fence_async_global();
                        }
                        if (sw == 2 || (k == 2 && !SC_TAIL)) {
                            uint32_t qs = sw == 2 ? offsetof(Scratch, q) + (2 * SC_QT1 + 1) * QB_BYTES : SC_PAIR ? offsetof(Scratch, agg) + SC_ZB * QB_BYTES : offsetof(Scratch, part) + SC_QT0 * (4 * PART_BYTES);
#pragma unroll 1
                            for (int w = 0; w < (k == 2 && SC_PAIR ? 1 : 2); w++) {
                                mbar_wait_sleep(bar_qfree + 8 * w, k == 2 && SC_HELP);
                                mbar_expect_tx(bar_q + 8 * w, SC_PAIR ? QB_BYTES : PART_BYTES);
                                if (!SC_PAIR) bulk_g2s(sb + SM_ML + w * 512, base + (qs + (w ? -512 : QB_BYTES)), 512, bar_q + 8 * w);
                                bulk_g2s(sb + SM_Q + w * QB_BYTES, base + qs, QB_BYTES, bar_q + 8 * w);
                                qs += sw == 2 ? -QB_BYTES : PART_BYTES + 512;
                            }
                        }
                        if ((sw | 1) == 3) {
                            mbar_wait_sleep(bar_pdone + 8 * (sw - 2), 0);
                            bulk_s2g(g_part + (blockIdx.x - 3 + sw) * PART_BYTES, slot, PART_BYTES);
                            asm volatile("cp.async.bulk.wait_group.read 0;\n" ::: "memory");
                        }
                        if (sw == 5) {
                            asm volatile("cp.async.bulk.wait_group 0;\n" ::: "memory");
                            red_release(&g_sync[SY_PART * 32]);
                        }
                        if (k == 0) {
                            asm volatile("prefetch.tensormap [%0];\n" ::"l"(&P.tm_outc) : "memory");
                            src = g_w + (12 - SC_NW) * QB_BYTES; bytes = step = QB_BYTES;
                        }
                        if (k == 2) next = SC_TAIL ? nit - 1 : nit;
                    }
                    mbar_wait_sleep(fb + (bar_empty - bar_full), (j >> 2) & 1);
                    mbar_expect_tx(fb, bytes);
                    if (tick)
                        asm volatile("{\n.reg .pred p;\n.reg .u32 a, b;\nmov.u32 a, %%globaltimer_lo;\nnot.b32 b, a;\nand.b32 b, b, %0;\nshr.u32 b, b, 1;\nnanosleep.u32 b;\n"
                                     "L:\nmov.u32 b, %%globaltimer_lo;\nxor.b32 b, b, a;\nsetp.le.u32 p, b, %0;\n@p nanosleep.u32 %1;\n@p bra L;\n}\n" ::"n"(TICK - 1), "n"(TSL) : "memory");
                    bulk_g2s(slot, src, bytes, fb);
                    src += step;
                }
            }
        } else {
            if (warp == 2 && SC_OWNER) {
                uint8_t* dst = g_hz + 4096 + h_unit(SC_QT0, 0) * 8192;
                auto send = [&](int u0, int u1) {
#pragma unroll
                    for (int u = u0; u < u1; u++) {
                        bulk_s2g(dst + u * (78 * 8192), sb + SM_Q + u * 8192, 8192);
                        asm volatile("cp.async.bulk.wait_group 0;\n" ::: "memory");
                    }
                };
                int* f0 = &g_sync[(SY_H0 + SC_QT0 / 5) * 32];
                bar_sync(BAR_H0, 64);
                if (elect()) {
                    send(0, 1);
                    if (SC_QT0 < 65) red_release(f0);
                }
                bar_sync(BAR_H1, 160);
                if (elect()) {
                    if (!SC_TAIL) send(1, 4);
                    mbar_arrive(bar_q);
                }
                bar_sync(BAR_H2, 160);
                if (elect()) {
                    if (!SC_TAIL) { send(4, 8); mbar_arrive(bar_q + 8); }
                    red_release(&g_sync[SY_H1 * 32]);
                }
                __syncwarp();
            }
        }
    } else {
        const uint32_t sq = sb + SM_Q + wg * QB_BYTES;
        const uint32_t qbar = bar_q + 8 * wg;
        const uint32_t dq0 = __shfl_sync(~0u, ((sq & 0x3FFFF) >> 4) | (64u << 16), 0);
        const uint32_t dk0 = __shfl_sync(~0u, (((sb + SM_KV) & 0x3FFFF) >> 4) | (64u << 16), 0);
        float o[128];
        int it = 4;
        const uint32_t dhi = P.dhi;
        auto release = [&](int st, int n = 1) {
            if (n == 1) asm volatile("{\n.reg .pred p;\nelect.sync _|p, -1;\n@p mbarrier.arrive.shared::cta.b64 _, [%0];\n}\n" ::"r"(bar_empty + 8 * st) : "memory");
            else asm volatile("{\n.reg .pred p;\nelect.sync _|p, -1;\n@p mbarrier.arrive.shared::cta.b64 _, [%0], 2;\n}\n" ::"r"(bar_empty + 8 * st) : "memory");
        };
        const bool active = !(SC_TAIL && wg == 1);
        auto pp_sync = [&]() { if (!SC_TAIL) bar_sync(BAR_PP0 + wg, 256); };
        auto pp_arrive = [&]() { if (!SC_TAIL) bar_arrive(BAR_PP1 - wg, 256); };
        auto warp_arrive = [&](uint32_t bar) {
            __syncwarp();
            asm volatile("{\n.reg .pred p;\nelect.sync _|p, -1;\n@p mbarrier.arrive.shared::cta.b64 _, [%0];\n}\n" ::"r"(bar + 8 * wg) : "memory");
        };
        auto peer_arrive = [&]() {
            asm volatile("{\n.reg .pred p;\n.reg .b32 a;\nelect.sync _|p, -1;\nmapa.shared::cluster.u32 a, %0, %1;\n"
                         "@p mbarrier.arrive.shared::cluster.b64 _, [a];\n}\n" ::"r"(bar_rfree), "r"(rank ^ 1) : "memory");
        };
        auto cut = [&]() { asm volatile("{\n.reg .pred p;\nsetp.lt.s32 p, %0, 0;\nL:\n@p pmevent 0;\n@p bra L;\n}\n" ::"r"(dhi) : "memory"); };
        float qs = 1.f;
        uint32_t qr[4 * NQR];
        auto stage_q = [&]() {
            int k = dhi & 1;
            uint32_t big;
#pragma unroll 1
            do {
                if (k) {
                    qs *= 16.f;
#pragma unroll
                    for (int i = 0; i < 128; i++) o[i] *= 0.0625f;
                }
                big = 0;
                auto pk = [&](int i) { return QRND(pack_f16_sat(o[i], o[i + 1])); };
#pragma unroll
                for (int i = 0; i < 16; i++) {
                    if (QREG(i) >= 0) continue;
                    const uint32_t v0 = pk(8 * i), v1 = pk(8 * i + 2), v2 = pk(8 * i + 4) | (i == 15 ? k : 0), v3 = pk(8 * i + 6);
                    stmatrix_x4(sq + warp * 8192 + tile_off(lane & 15, 2 * i + (lane >> 4)), v0, v1, v2, v3);
                    big |= v0 | v1; big |= v2 | v3;
                    if (i == 15) cut();
                }
#pragma unroll
                for (int i = 0; i < 64; i++)
                    if (const int r = QREG(i / 4); r >= 0) big |= qr[4 * r + (i & 3)] = pk(2 * i);
                k++;
            } while (__any_sync(~0u, (big & 0x40004000u) && k < 8));
        };
        uint32_t s[20];
        auto issue_qk = [&](int st, int sh = 24) {
            const uint64_t kb = mkaddr(dk0 + st * (KV_BYTES >> 4), dhi);
            const uint64_t qd = mkaddr(dq0 + ((uint32_t)it >> sh), dhi);
            wgmma_ss_n80_init(s, qd, kb);
#pragma unroll
            for (int j = 1; j < 16; j++) {
                const int kk = j == 8 ? 15 : j < 8 ? j : j - 1;
                const int r = QREG(kk);
                if (r >= 0) wgmma_rs_n80(s, qr[4 * r], qr[4 * r + 1], qr[4 * r + 2], qr[4 * r + 3], kb + ((kk >> 2) * 64 + (kk & 3) * 2));
                else wgmma_ss_n80(s, qd + ((kk >> 2) * 64 + (kk & 3) * 2), kb + ((kk >> 2) * 64 + (kk & 3) * 2));
            }
            wg_commit();
        };

        {
            const int rb = (2 * SC_QT0 + wg) * 64 + warp * 16;
            const uint32_t xbar = bar_x + 32 * wg + 8 * warp;
            if (elect()) {
                mbar_init(xbar, 1);
                asm volatile("fence.mbarrier_init.release.cluster;\nfence.proxy.async.shared::cta;\n" ::: "memory");
                mbar_expect_tx(xbar, rb < NN ? 8192 : 0);
            }
            asm volatile("barrier.cluster.arrive.relaxed.aligned;\n" ::: "memory");
            if (wg == 1) pp_arrive();
            bar_sync(BAR_X, 384);
            if (wg == 1) bar_sync(BAR_GO, 160);
            if (rb < NN && elect()) bulk_g2s(sq + warp * 8192, H.x + (size_t)rb * 256, 8192, xbar);
            if (rb >= NN) {
#pragma unroll 1
                for (int i = 0; i < 16; i++) sts128(sq + warp * 8192 + i * 512 + lane * 16, 0, 0, 0, 0);
            }
            __syncwarp();
            mbar_wait(xbar, 0);
            uint4 xa[8], xb[8];
#pragma unroll
            for (int s = 0; s < 8; s++) {
                xa[s] = lds128(sq + (warp * 16 + g) * 512 + (4 * s + q) * 16);
                xb[s] = lds128(sq + (warp * 16 + g + 8) * 512 + (4 * s + q) * 16);
            }
            float sm[2][4], sq2[2][4][4];
#pragma unroll
            for (int i = 0; i < 4; i++) {
                sm[0][i] = sm[1][i] = 0.f;
#pragma unroll
                for (int k = 0; k < 4; k++) sq2[0][k][i] = sq2[1][k][i] = 0.f;
            }
#pragma unroll
            for (int s = 0; s < 8; s++) {
#pragma unroll
                for (int hh = 0; hh < 2; hh++) {
                    const uint4 v = hh ? xb[s] : xa[s];
                    mma16816(sm[hh], v.x, v.y, v.z, v.w, 0x3F803F80u, 0x3F803F80u);
                    mma1688(sq2[hh][0], v.x, v.y, v.x); mma1688(sq2[hh][1], v.x, v.y, v.y);
                    mma1688(sq2[hh][2], v.z, v.w, v.z); mma1688(sq2[hh][3], v.z, v.w, v.w);
                }
            }
            float inv[2], off[2];
#pragma unroll
            for (int hh = 0; hh < 2; hh++) {
                const float mean = (sm[hh][0] + sm[hh][2]) * (1.f / 256.f);
                const float d0 = (sq2[hh][0][0] + sq2[hh][2][0]) + (sq2[hh][1][2] + sq2[hh][3][2]);
                const float d1 = (sq2[hh][0][1] + sq2[hh][2][1]) + (sq2[hh][1][3] + sq2[hh][3][3]);
                const float ss = __shfl_sync(~0u, (g & 1) ? d1 : d0, g * 4 + (g >> 1));
                const float var = fmaxf(ss * (1.f / 256.f) - mean * mean, 0.f);
                float sd;
                asm("sqrt.approx.ftz.f32 %0, %1;\n" : "=f"(sd) : "f"(bf_round(bf_round(var) + 1e-5f)));
                asm("rcp.approx.ftz.f32 %0, %1;\n" : "=f"(inv[hh]) : "f"(bf_round(sd)));
                off[hh] = -mean * inv[hh];
            }
            uint32_t a[64];
#pragma unroll
            for (int s = 0; s < 8; s++) {
                a[8 * s] = xa[s].x; a[8 * s + 1] = xb[s].x; a[8 * s + 2] = xa[s].y; a[8 * s + 3] = xb[s].y;
                a[8 * s + 4] = xa[s].z; a[8 * s + 5] = xb[s].z; a[8 * s + 6] = xa[s].w; a[8 * s + 7] = xb[s].w;
            }
            fence_regs(a);
            if (wg == 1 && __any_sync(~0u, inv[0] + inv[1] != -1.f)) bar_arrive(BAR_ST, 256);
            asm volatile("setmaxnreg.inc.sync.aligned.u32 %0;\n" ::"n"(REG_C));
            fence_regs(a);
#pragma unroll
            for (int i = 0; i < 64; i++)
                a[i] = pack_f16(fmaf(bf_lo(a[i]), inv[i & 1], off[i & 1]), fmaf(bf_hi(a[i]), inv[i & 1], off[i & 1]));
            if (SC_OWNER) {
                const uint32_t ko = (q & 2) ? KV_OFF2 : KV_OFF2 | NEG2;
#pragma unroll
                for (int i = 0; i < 16; i++) {
                    const uint32_t mk = (i == 15 && q == 3) ? 0xFFFFu : ~0u;
                    stmatrix_x4(sq + warp * 8192 + tile_off(lane & 15, 2 * i + (lane >> 4)), kvf(a[4 * i], ko), kvf(a[4 * i + 1], ko),
                                kvf(a[4 * i + 2] & mk, ko), kvf(a[4 * i + 3] & mk, ko));
                }
                fence_async_smem();
                if (tid < 32) bar_arrive(BAR_H0, 64);
                bar_arrive(wg ? BAR_H2 : BAR_H1, 160);
            }
            asm volatile("barrier.cluster.wait.acquire.aligned;\n" ::: "memory");
            if (wg == 0) bar_sync(BAR_ST, 256);
            if (active) {
                fence_regs(a);
#pragma unroll
                for (int c = 0; c < 4; c++) {
                    if (c == 1) {
                        if (wg == 1) {
                            wg_wait<0>();
                            release(0);
                        }
                        pp_sync();
                    }
                    mbar_wait(bar_full + 8 * c, 0);
                    const uint64_t wb = mkaddr(dk0 + c * (KV_BYTES >> 4), dhi);
                    wg_fence();
#pragma unroll
                    for (int kk = 0; kk < 4; kk++) {
                        if (c | kk) wgmma_rs_n256_tb(o, a[16 * c + 4 * kk], a[16 * c + 4 * kk + 1], a[16 * c + 4 * kk + 2], a[16 * c + 4 * kk + 3], wb + kk * 512);
                        else wgmma_rs_n256_tb_init(o, a[0], a[1], a[2], a[3], wb);
                    }
                    wg_commit();
                    if (c > 0) { wg_wait<1>(); if (c > 1 || wg == 0) release(c - 1); }
                }
                if (wg == 0) pp_arrive();
                wg_wait<0>();
                fence_regs(o);
                release(3);
                if (SC_OWNER) mbar_wait(qbar, 0);
                stage_q();
                fence_async_smem();
                bar_sync(BAR_WG0 + wg, 128);
                mbar_wait(bar_full, 1);
                wg_fence();
                issue_qk(0);
                if (wg == 1) pp_arrive();
                if (SC_PAIR && !rank) {
#pragma unroll
                    for (int i = 0; i < 16; i++)
                        if (const int r = QREG(i); r >= 0)
                            stmatrix_x4(sq + warp * 8192 + tile_off(lane & 15, 2 * i + (lane >> 4)), qr[4 * r], qr[4 * r + 1], qr[4 * r + 2], qr[4 * r + 3]);
                }
            } else {
                peer_arrive();
            }
        }

        uint32_t p[20];
        float m0 = 0.f, m1 = 0.f, e0, e1, l0, l1;
        uint32_t plim;
        uint32_t qphase = (SC_OWNER && active) ? 1 : 0;
        auto issue_pv = [&](int st, int acc) {
            const uint64_t vb = mkaddr(dk0 + st * (KV_BYTES >> 4), dhi);
            wgmma_rs_n256_tb_pred(o, p[0], p[1], p[2], p[3], vb, acc);
#pragma unroll
            for (int kk = 1; kk < 5; kk++)
                wgmma_rs_n256_tb(o, p[4 * kk], p[4 * kk + 1], p[4 * kk + 2], p[4 * kk + 3], vb + kk * 512);
            wg_commit();
        };
        auto mq_addr = [&](int ln) { return sq + warp * 8192 + tile_off(ln >> 2, 31) + 12; };
        auto exceeds = [&](const uint32_t (&p)[20]) {
            uint32_t a = __vimax3_s16x2(S_LIMIT, p[0], p[1]), b = __vimax3_s16x2(p[2], p[3], p[4]);
#pragma unroll
            for (int i = 5; i < 17; i += 4) { a = __vimax3_s16x2(a, p[i], p[i + 1]); b = __vimax3_s16x2(b, p[i + 2], p[i + 3]); }
            a = __vimax3_s16x2(a, p[17], p[18]);
            return __any_sync(~0u, __vimax3_s16x2(a, b, p[19]) != plim);
        };
        auto remax = [&](float& a, float& b, bool store) {
            const int ln = lane_now();
            asm volatile("" : "+f"(qs));
            uint32_t ha = s[0], hb = s[1];
#pragma unroll
            for (int i = 1; i < 10; i++) { ha = hmax2_f16(ha, s[2 * i]); hb = hmax2_f16(hb, s[2 * i + 1]); }
            ha = hmax2_f16(__byte_perm(ha, hb, 0x5410), __byte_perm(ha, hb, 0x7632));
            ha = hmax2_f16(ha, __shfl_xor_sync(~0u, ha, 1));
            ha = hmax2_f16(ha, __shfl_xor_sync(~0u, ha, 2));
            a = fmaxf(a, f16_lo(ha) * qs - e0 + REF_UP); b = fmaxf(b, f16_hi(ha) * qs - e1 + REF_UP);
            const float qi = __uint_as_float(0x7F000000u - __float_as_uint(qs)) * (-1.f / KV_OFF);
            const uint32_t u = pack_f16((m0 + a) * qi, (m1 + b) * qi);
            const float g0 = (m0 + a) + KV_OFF * qs * f16_lo(u), g1 = (m1 + b) + KV_OFF * qs * f16_hi(u);
            const bool x0 = fabsf(g0) <= 1.f, x1 = fabsf(g1) <= 1.f;
            if (x0) a -= g0;
            if (x1) b -= g1;
            const float da = a + e0, db = b + e1;
            m0 += a; m1 += b;
            e0 = x0 ? 0.f : g0; e1 = x1 ? 0.f : g1;
            plim = (x0 && x1 && qs == 1.f) ? S_LIMIT : 0u;
            asm volatile("{\n.reg .pred p;\nsetp.ne.s32 p, %3, 0;\n@p st.shared.u16 [%0], %1;\n@p st.shared.u16 [%0 + 4096], %2;\n}\n"
                         ::"r"(mq_addr(ln) + 2), "h"((unsigned short)u), "h"((unsigned short)(u >> 16)), "r"((int)(store && (ln & 3) == 0)) : "memory");
#pragma unroll
            for (int i = 0; i < 10; i++) {
                p[2 * i] = pack_f16(ex2(fmaf(f16_lo(s[2 * i]), qs, -da)), ex2(fmaf(f16_hi(s[2 * i]), qs, -da)));
                p[2 * i + 1] = pack_f16(ex2(fmaf(f16_lo(s[2 * i + 1]), qs, -db)), ex2(fmaf(f16_hi(s[2 * i + 1]), qs, -db)));
            }
            fence_regs(p);
            fence_async_smem();
            __syncwarp();
        };

        auto row_sums = [&](float& z0, float& z1, int q) {
            z0 = quad_last(o[125]); z1 = quad_last(o[127]);
            l0 = z0 * (KV_SCALE / KV_OFF); l1 = z1 * (KV_SCALE / KV_OFF);
            if (!(q & 2)) { z0 = -z0; z1 = -z1; }
        };
        auto stats = [&](int q) { return (q & 2) ? ((q & 1) ? l1 : m1) : ((q & 1) ? l0 : m0); };
        const int nseg = SC_HELP ? 2 : 1;
        if (active) {
#pragma unroll 1
        for (int seg = 0;; seg++) {
            wg_wait<0>();
            fence_regs(s);
            e0 = e1 = 0.f;
            const int it0 = it, itl = __shfl_sync(~0u, seg + 1 < nseg ? 3 + 25 : 3 + SC_NKV, 0);
            const int itx = (wg == 1 && seg + 1 == nseg) ? itl : -1;
            bool redo = true, have = !seg;
#pragma unroll 1
            for (;;) {
                if (!have) {
#pragma unroll
                    for (int i = 0; i < 20; i++) p[i] = ex2_f16(s[i]);
                    redo = exceeds(s);
                }
                if (redo) {
                    float d0 = it != it0 ? 0.f : -INFINITY, d1 = d0;
                    remax(d0, d1, it != itl);
                    if (it != it0) {
                        const float a0 = ex2(-d0), a1 = ex2(-d1);
#pragma unroll
                        for (int i = 0; i < 32; i++) { o[4 * i] *= a0; o[4 * i + 1] *= a0; o[4 * i + 2] *= a1; o[4 * i + 3] *= a1; }
                    } else if (SC_OWNER) {
                        warp_arrive(bar_pdone);
                    }
                }
                if (it == itl) break;
                const int stp = it & 3;
                it++;
                pp_sync();
                fence_regs(o); fence_regs(p);
                have = SC_TAIL || it == itx;
                if (!have) {
                    wg_fence();
                    issue_pv(stp, it - 1 - it0);
                    mbar_wait(bar_full + 8 * (it & 3), (it >> 2) & 1);
                    wg_fence();
                    issue_qk(it & 3);
                    pp_arrive();
                    wg_wait<0>();
                    fence_regs(s); fence_regs(o); fence_regs(p);
                    if (it == itl) warp_arrive(bar_qfree);
                } else {
                    const int zero = (uint32_t)it >> 23;
                    mbar_wait(bar_full + 8 * (it & 3), (it >> 2) & 1);
                    wg_fence();
                    issue_qk((it & 3) + zero, 25);
                    if (it == itl) {
                        wg_wait<0>();
                        if (SC_PAIR) peer_arrive(); else warp_arrive(bar_qfree);
                        if (wg) bar_sync(BAR_ST, 256);
                    }
                    wg_fence();
                    issue_pv(stp + zero, it - 1 - it0);
                    pp_arrive();
                    wg_wait<1>();
                    fence_regs(s);
                    redo = exceeds(s);
                    if (!redo) {
#pragma unroll
                        for (int i = 0; i < 20; i++) s[i] = ex2_f16(s[i]);
                        fence_regs(s);
                        cut();
                    }
                    wg_wait<0>();
                    fence_regs(o); fence_regs(p);
#pragma unroll
                    for (int i = 0; i < 20; i++) p[i] = s[i];
                }
                release(stp);
            }
            if (seg + 1 < nseg) pp_sync();
            fence_regs(o); fence_regs(p);
            wg_fence();
            issue_pv(it & 3, 1);
            asm volatile("{\n.reg .pred p;\nsetp.ne.s32 p, %0, 0;\n@p bar.arrive %1, 256;\n}\n" ::"r"((int)(seg + 1 == nseg && (wg ? SC_PAIR : !SC_TAIL))), "r"(BAR_ST + wg) : "memory");
            it++;
            if (seg + 1 == nseg) break;
            const int is = it - 2 + wg, ln = lane_now();
            uint32_t dst = sb + SM_KV + (is & 3) * KV_BYTES + wg * 512 + warp * 8192 + ln * 16;
            uint32_t dml = sb + SM_KV + (is & 3) * KV_BYTES + (wg ? 0 : QB_BYTES) + warp * 128 + ln * 4;
            asm volatile("" : "+r"(dst), "+r"(dml));
            mbar_wait(qbar, qphase); qphase ^= 1;
            uint32_t u0, u1;
            asm volatile("ld.shared.u32 %0, [%2];\nld.shared.u32 %1, [%2 + 4096];\n" : "=r"(u0), "=r"(u1) : "r"(mq_addr(ln)) : "memory");
#pragma unroll
            for (int i = 0; i < 16; i++)
                if (const int r = QREG(i); r >= 0)
                    asm volatile("ldmatrix.sync.aligned.m8n8.x4.shared.b16 {%0, %1, %2, %3}, [%4];\n" : "=r"(qr[4 * r]), "=r"(qr[4 * r + 1]), "=r"(qr[4 * r + 2]), "=r"(qr[4 * r + 3])
                                 : "r"(sq + warp * 8192 + tile_off(ln & 15, 2 * i + (ln >> 4))) : "memory");
            mbar_wait(bar_full + 8 * (it & 3), (it >> 2) & 1);
            mbar_wait(bar_empty + 8 * ((it - 2) & 3), ((it - 2) >> 2) & 1);
            float z0, z1;
            fence_regs(qr);
            wg_fence();
            issue_qk(it & 3);
            wg_wait<1>();
            fence_regs(o);
            row_sums(z0, z1, ln);
            release((it - 1) & 3);
            pp_arrive();
            bar_sync(BAR_WG0 + wg, 128);
#pragma unroll
            for (int i = 0; i < 128; i++) o[i] -= (i & 2) ? z1 : z0;
            fence_regs(o);
            cut();
            asm volatile("st.shared.f32 [%0], %1;\n" ::"r"(dml), "f"(stats(ln)) : "memory");
            qs = __uint_as_float(0x3F800000u + ((u0 & 7) << 25));
            m0 = -KV_OFF * qs * f16_hi(u0); m1 = -KV_OFF * qs * f16_hi(u1);
            plim = fmaxf(fabsf(m0), fabsf(m1)) <= 3072.f && qs == 1.f ? S_LIMIT : 0u;
            uint32_t v[2][8] = {};
#pragma unroll
            for (int i = 0; i < 8; i++) {
                uint32_t *w = v[i & 1], *u = v[(i & 1) ^ 1];
#pragma unroll
                for (int j = 0; j < 8; j++) w[j] = pack_bf16(o[16 * i + 2 * j], o[16 * i + 2 * j + 1]);
                sts128(dst + i * 1024, w[0], w[1], w[2], w[3]);
                sts128(dst + i * 1024 + 512, w[4], w[5], w[6], w[7]);
                if (i) asm volatile("{\n.reg .pred p;\nsetp.lt.s32 p, %9, 0;\nL:\n@p st.shared.v4.u32 [%0], {%1, %2, %3, %4};\n@p st.shared.v4.u32 [%0 + 16], {%5, %6, %7, %8};\n@p bra L;\n}\n"
                             ::"r"(dst), "r"(u[0]), "r"(u[1]), "r"(u[2]), "r"(u[3]), "r"(u[4]), "r"(u[5]), "r"(u[6]), "r"(u[7]), "r"(it) : "memory");
            }
            fence_async_smem();
            warp_arrive(bar_pdone);
        }
        constexpr int IW = 4 + 75;
        uint32_t a[64];
        const int lane = lane_now(), t = warp * 32 + lane;
        if (wg == 0 && (SC_PAIR || SC_LAST)) {
            uint32_t rq, rml, rbar;
            asm volatile("mapa.shared::cluster.u32 %0, %3, %6;\nmapa.shared::cluster.u32 %1, %4, %6;\nmapa.shared::cluster.u32 %2, %5, %6;\n"
                         : "=r"(rq), "=r"(rml), "=r"(rbar) : "r"(sb + SM_Q + QB_BYTES + warp * 8192 + lane * 16), "r"(sb + SM_ML + 512 + t * 4),
                         "r"(bar_pin), "r"(rank ^ 1));
            auto send = [&](int i) {
                asm volatile("st.async.weak.shared::cluster.mbarrier::complete_tx::bytes.v4.b32 [%0], {%1, %2, %3, %4}, [%5];\n"
                             ::"r"(rq + i * 512), "r"(a[4 * i]), "r"(a[4 * i + 1]), "r"(a[4 * i + 2]), "r"(a[4 * i + 3]), "r"(rbar + (i & 8)) : "memory");
            };
            mbar_wait(bar_rfree, 0);
            wg_wait<0>();
            fence_regs(o);
            release((it - 1) & 3);
            float z0, z1;
            row_sums(z0, z1, lane);
            asm volatile("st.async.weak.shared::cluster.mbarrier::complete_tx::bytes.f32 [%0], %1, [%2];\n" ::"r"(rml), "f"(stats(lane)), "r"(rbar) : "memory");
#pragma unroll
            for (int i = 0; i < 16; i++) {
                a[4 * i] = pack_bf16(o[8 * i] - z0, o[8 * i + 1] - z0); a[4 * i + 1] = pack_bf16(o[8 * i + 2] - z1, o[8 * i + 3] - z1);
                a[4 * i + 2] = pack_bf16(o[8 * i + 4] - z0, o[8 * i + 5] - z0); a[4 * i + 3] = pack_bf16(o[8 * i + 6] - z1, o[8 * i + 7] - z1);
                if (i * SND0 / 16 != (i + 1) * SND0 / 16) send(i * SND0 / 16);
                if (i % CUT2 == CUT2 - 1) cut();
            }
            if (SC_PAIR) {
                float z[128];
                const uint32_t dkz = dk0 + ((uint32_t)it >> 24), dqz = dq0 + ((uint32_t)it >> 24);
                auto gemm = [&](int c) {
                    mbar_wait(bar_full + 8 * ((IW + c) & 3), ((IW + c) >> 2) & 1);
                    const uint64_t wb = mkaddr(dkz + ((IW + c) & 3) * (KV_BYTES >> 4), dhi), ab = mkaddr(dqz + c * 64, dhi);
                    wg_fence();
#pragma unroll
                    for (int kk = 0; kk < 4; kk++) {
                        if (c | kk) wgmma_ss_n256_tb(z, ab + kk * 2, wb + kk * 512);
                        else wgmma_ss_n256_tb_init(z, ab, wb);
                    }
                    wg_commit();
                };
                mbar_wait(qbar, qphase);
                bar_sync(BAR_ST + 1, 256);
                gemm(0);
#pragma unroll
                for (int i = SND0; i < 16; i++) send(i);
#pragma unroll
                for (int c = 1; c < 4; c++) { gemm(c); if (c == 3) pp_arrive(); wg_wait<1>(); release((IW + c - 1) & 3, 2); }
                wg_wait<0>();
                fence_regs(z);
                release((IW + 3) & 3, 2);
#pragma unroll
                for (int i = 0; i < 16; i++) {
                    sts128(sq + warp * 8192 + lane * 16 + i * 512, pack_bf16(z[8 * i], z[8 * i + 1]), pack_bf16(z[8 * i + 2], z[8 * i + 3]),
                           pack_bf16(z[8 * i + 4], z[8 * i + 5]), pack_bf16(z[8 * i + 6], z[8 * i + 7]));
                    if (i == 3 || i == 15) bar_arrive(i == 3 ? BAR_BF : BAR_H0, 256);
                    if (i == 3) cut();
                }
            } else {
#pragma unroll
                for (int i = SND0; i < 16; i++) send(i);
            }
        } else {
            const int pair = SC_PAIR;
            const bool glob = !(pair || SC_TAIL);
            const uint32_t ml = sb + SM_ML + (t & ~3) * 4, src = (glob ? sq : sb + SM_Q + QB_BYTES) + warp * 8192 + lane * 16;
            const uint64_t tm = lds64(s_tm);
            wg_wait<0>();
            fence_regs(o);
            release((IW - 1) & 3);
            float c0, c1;
            row_sums(c0, c1, lane);
            mbar_wait(glob ? qbar : bar_pin, glob ? qphase : 0);
            const float4 ps = lds128f(ml + (glob ? wg * 512 : 512));
            auto load = [&](int i) {
                asm volatile("ld.shared.v4.u32 {%0, %1, %2, %3}, [%4];\n" : "=r"(a[4 * i]), "=r"(a[4 * i + 1]), "=r"(a[4 * i + 2]), "=r"(a[4 * i + 3]) : "r"(src + i * 512) : "memory");
            };
#pragma unroll
            for (int i = 0; i < 8; i++) load(i);
            const float n0 = fmaxf(m0, ps.x), n1 = fmaxf(m1, ps.z);
            const float a0 = ex2(m0 - n0), a1 = ex2(m1 - n1), b0 = ex2(ps.x - n0), b1 = ex2(ps.z - n1);
            const float i0 = rcp(l0 * a0 + ps.y * b0), i1 = rcp(l1 * a1 + ps.w * b1);
            const float r0 = a0 * i0, r1 = a1 * i1;
            c0 *= -r0; c1 *= -r1;
            const uint32_t u0 = pack_bf16(b0 * i0, b0 * i0), u1 = pack_bf16(b1 * i1, b1 * i1);
#pragma unroll
            for (int i = 0; i < 32; i++) {
                if (i == 16) {
                    if (!glob) mbar_wait(bar_pin + 8, 0);
#pragma unroll
                    for (int j = 8; j < 16; j++) load(j);
                }
                a[2 * i] = hfma2(a[2 * i], u0, pack_bf16(fmaf(o[4 * i], r0, c0), fmaf(o[4 * i + 1], r0, c0)));
                a[2 * i + 1] = hfma2(a[2 * i + 1], u1, pack_bf16(fmaf(o[4 * i + 2], r1, c1), fmaf(o[4 * i + 3], r1, c1)));
            }
            float y[2][32];
            auto gemm = [&](int c, int kh) {
                if (!kh) mbar_wait(bar_full + 8 * ((IW + c) & 3), (((IW + c) >> 2) & 1) ^ pair);
                const uint64_t wb = mkaddr(dk0 + ((IW + c) & 3) * (KV_BYTES >> 4), dhi - 192);
                wg_fence();
#pragma unroll
                for (int kk = 8 * kh; kk < 8 * kh + 8; kk++) {
                    if (kk) wgmma_rs_n64_tb(y[c & 1], a[4 * kk], a[4 * kk + 1], a[4 * kk + 2], a[4 * kk + 3], wb + kk * 128);
                    else wgmma_rs_n64_tb_init(y[c & 1], a[0], a[1], a[2], a[3], wb);
                }
                wg_commit();
            };
            const uint32_t stg = sq + warp * 8192 + (lane & 15) * 128 + (((lane >> 4) ^ lane) & 7) * 16;
            uint4 z[4] = {};
            auto load_z = [&](int cb) {
                if (cb < 2) asm volatile("{\n.reg .pred p;\nsetp.ne.s32 p, %0, 0;\n@p bar.sync %1, 256;\n}\n" ::"r"(pair), "r"(cb ? BAR_H0 : BAR_BF) : "memory");
#pragma unroll
                for (int i = 0; i < 4; i++)
                    asm volatile("{\n.reg .pred p;\nsetp.ne.u32 p, %4, 0;\n@p ld.shared.v4.u32 {%0, %1, %2, %3}, [%5];\n}\n"
                                 : "+r"(z[i].x), "+r"(z[i].y), "+r"(z[i].z), "+r"(z[i].w) : "r"(pair), "r"(src - QB_BYTES + (4 * cb + i) * 512) : "memory");
            };
            pp_sync();
            gemm(0, 0);
            gemm(0, 1);
#pragma unroll
            for (int c = 0; c < 4; c++) {
                if (c) load_z(c);
                if (c < 3) gemm(c + 1, 0);
                if (!c) load_z(0);
                if (c < 3) wg_wait<1>(); else wg_wait<0>();
                fence_regs(y[c & 1]);
                const float* x = y[c & 1];
#pragma unroll
                for (int i = 0; i < 4; i++)
                    stmatrix_x4((stg ^ (32 * i)) + c * 2048, hadd2(pack_bf16(x[8 * i], x[8 * i + 1]), z[i].x), hadd2(pack_bf16(x[8 * i + 2], x[8 * i + 3]), z[i].y),
                                hadd2(pack_bf16(x[8 * i + 4], x[8 * i + 5]), z[i].z), hadd2(pack_bf16(x[8 * i + 6], x[8 * i + 7]), z[i].w));
                if (c < 3) gemm(c + 1, 1);
                fence_async_smem();
                __syncwarp();
                asm volatile("{\n.reg .pred p;\nelect.sync _|p, -1;\n"
                             "@p cp.reduce.async.bulk.tensor.4d.global.shared::cta.add.tile.bulk_group [%0, {0, 0, %1, %2}], [%3];\n}\n"
                             ::"l"(tm), "r"(c), "r"((pair ? SC_ZB : 2 * SC_QT0 + wg) * 8 + warp * 2), "r"(sq + warp * 8192 + c * 2048) : "memory");
                if (c == 2 && glob) pp_arrive();
            }
            asm volatile("cp.async.bulk.commit_group;\ncp.async.bulk.wait_group.read 0;\n" ::: "memory");
        }
        } else {
            wg_wait<0>();
        }
        if (SC_TAIL) {
        float o[128];
        const int lane = lane_now(), t = warp * 32 + lane, q = lane & 3;
        auto emit = [&](uint32_t base, int lane, int row0, uint8_t* wdst, int turn) {
#pragma unroll
            for (int hh = 0; hh < 2; hh++) {
                if (turn > 0) mbar_wait(bar_zst + 8 * hh, (turn - 1) & 1);
#pragma unroll
                for (int i = 0; i < 8; i++)
                    stmatrix_x4(base + tile_off(8 * hh + (lane & 7), 4 * i + (lane >> 3)),
                                pack_bf16(o[16 * i + 2 * hh], o[16 * i + 2 * hh + 1]), pack_bf16(o[16 * i + 4 + 2 * hh], o[16 * i + 5 + 2 * hh]),
                                pack_bf16(o[16 * i + 8 + 2 * hh], o[16 * i + 9 + 2 * hh]), pack_bf16(o[16 * i + 12 + 2 * hh], o[16 * i + 13 + 2 * hh]));
                fence_async_smem();
                __syncwarp();
                if (wdst) {
                    if (lane < 4)
                        asm volatile("cp.async.bulk.global.shared::cta.bulk_group [%0], [%1], 1024;\n"
                                     ::"l"(wdst + ((turn & 1) ? hh * 4096 + lane * 1024 : hh * 1024 + lane * QB_BYTES)), "r"(base + hh * 4096 + lane * 1024) : "memory");
                    asm volatile("cp.async.bulk.commit_group;\n" ::: "memory");
                } else {
                    asm volatile("{\n.reg .pred p;\nsetp.eq.s32 p, %3, 0;\n"
                                 "@p cp.reduce.async.bulk.tensor.4d.global.shared::cta.add.tile.bulk_group [%0, {0, 0, 0, %1}], [%2];\n"
                                 "cp.async.bulk.commit_group;\n}\n"
                                 ::"l"(&P.tm_out), "r"((row0 >> 3) + hh), "r"(base + hh * 4096), "r"(lane) : "memory");
                }
            }
            asm volatile("cp.async.bulk.wait_group.read 1;\n" ::: "memory");
            warp_arrive(bar_zst - 8 * wg);
        };
        auto emit_done = [&](bool pending) {
            asm volatile("cp.async.bulk.wait_group.read 0;\n" ::: "memory");
            __syncwarp();
            asm volatile("{\n.reg .pred p;\nsetp.eq.s32 p, %1, 0;\n@p mbarrier.arrive.shared::cta.b64 _, [%0];\n}\n"
                         ::"r"(bar_zst + 8), "r"(pending ? lane : 1) : "memory");
        };
        if (!(rank | wg)) { release(0); release(1); release(2); release(3); }
        bar_sync(BAR_BF, 256);
        warp_arrive(bar_qfree);
        const int nf = rank ? 8 : 0;
        const int nz = nf + 26 + rank;
        const int itz = 4 + SC_NKV + SC_NW;
        bool pend = false;
#pragma unroll 1
        for (int k = wg; k < nz; k += 2) {
            const int iz = itz + (k < nf ? 0 : nf >> 1);
            mbar_wait(qbar, qphase); qphase ^= 1;
#pragma unroll 1
            for (int c = 0; c < 4; c++) {
                mbar_wait(bar_full + 8 * ((iz + c) & 3), ((iz + c) >> 2) & 1);
                const uint64_t wb = mkaddr(dk0 + ((iz + c) & 3) * (KV_BYTES >> 4), dhi), ab = mkaddr(dq0 + c * 64, dhi);
                wg_fence();
                wgmma_ss_n256_tb_pred(o, ab, wb, c);
#pragma unroll
                for (int kk = 1; kk < 4; kk++) wgmma_ss_n256_tb(o, ab + kk * 2, wb + kk * 512);
                wg_commit();
                emit_done(pend);
                pend = false;
            }
            wg_wait<0>();
            fence_regs(o);
            warp_arrive(bar_qfree);
            const int fb = ((k >> 1) + 3) & 3;
            if (k < nf) {
                float2* r255 = (float2*)H.s->r255 + wg * 128 + q;
                if (k < 2) {
                    if (t >= 124) {
#pragma unroll
                        for (int i = 0; i < 32; i++) r255[4 * i] = make_float2(o[4 * i + 2], o[4 * i + 3]);
                    }
                    bar_sync(BAR_WG0 + wg, 128);
                }
#pragma unroll
                for (int i = 0; i < 32; i++) {
                    const float2 v = __ldcg(r255 + 4 * i);
                    o[4 * i] -= v.x; o[4 * i + 1] -= v.y; o[4 * i + 2] -= v.x; o[4 * i + 3] -= v.y;
                }
            }
            int ln = lane;
            asm volatile("" : "+r"(ln));
            emit(sb + SM_KV + QB_BYTES + warp * KV_BYTES, ln, SC_TZB(k - nf) * 64 + warp * 16,
                 k >= nf ? nullptr : (k & 1) ? g_w + (4 + fb) * QB_BYTES + warp * 8192 : g_w + 8 * QB_BYTES + fb * 8192 + warp * 2048, k);
            pend = k + 2 < nz && (k | 1) != nf - 1;
            if (!pend) emit_done(true);
            if ((k | 1) == nf - 1) {
                asm volatile("cp.async.bulk.wait_group 0;\nfence.proxy.async.global;\nfence.acq_rel.gpu;\n" ::: "memory");
                bar_sync(BAR_BF, 256);
                if (tid == 0) red_release(&g_sync[SY_B * 32]);
                if (wg == 0) { release(0); release(1); release(2); release(3); }
            }
        }
        }
        if (wg == 0) pp_sync();
        warp_arrive(bar_end - 8 * wg);
        asm volatile("barrier.cluster.arrive.relaxed.aligned;\n" ::: "memory");
        if (P.E >= 0) return;
        asm volatile("setmaxnreg.dec.sync.aligned.u32 %0;\n" ::"n"(REG_P));
    }
    {
        if (warp != 0) {
            if (warp == 3 && SC_OWNER && SC_PAIR && elect()) {
                flag_wait_bounded(&g_sync[SY_H1 * 32], 79 * ep);
                mbar_wait_sleep(bar_pdone, 0);
                mbar_wait_sleep(bar_pdone + 8, 0);
#pragma unroll 1
                for (int u = 0; u < 16; u++) {
                    bulk_s2g(g_q + SC_QT0 * (2 * QB_BYTES) + u * 4096, sb + SM_Q + u * 4096, 4096);
                    asm volatile("cp.async.bulk.wait_group 0;\n" ::: "memory");
                }
                fence_async_global();
                st_release(&g_qflag[SC_QT0], ep);
            }
            __syncwarp();
            if (SC_TAIL) {
                bar_sync(BAR_AUX, 96);
                if (warp == 1 && elect()) red_release(&g_sync[SY_CSR * 32]);
                __syncwarp();
            }
            mbar_wait_bounded(bar_go, 0);
            if (SC_TAIL) {
                if (warp == 1 && elect()) red_add(&g_sync[SY_DONE * 32]);
                if (warp == 3 && elect()) {
                    int it = 4 + SC_NKV + SC_NW;
                    asm volatile("prefetch.tensormap [%0];\n" ::"l"(&P.tm_out) : "memory");
                    if (rank) {
#pragma unroll 1
                        for (int j = 0; j < 4; j++, it++) {
                            mbar_wait_sleep(bar_empty + 8 * (it & 3), ((it >> 2) & 1) ^ 1);
                            mbar_expect_tx(bar_full + 8 * (it & 3), QB_BYTES);
                            tma_g2s(sb + SM_KV + (it & 3) * KV_BYTES, &P.tm_w[2], 8 * j, bar_full + 8 * (it & 3));
                        }
#pragma unroll 1
                        for (int k = 0; k < 8; k++) {
                            mbar_wait_sleep(bar_qfree + 8 * (k & 1), ((k >> 1) ^ (k & 1) ^ 1) & 1);
                            mbar_expect_tx(bar_q + 8 * (k & 1), QB_BYTES);
#pragma unroll 1
                            for (int hf = 0; hf < 2; hf++)
                                asm volatile("cp.async.bulk.tensor.5d.shared::cluster.global.tile.mbarrier::complete_tx::bytes [%0], [%1, {0, 0, %2, 0, 0}], [%3];\n"
                                             ::"r"(sb + SM_Q + (k & 1) * QB_BYTES + hf * 16384), "l"(&P.tm_w[k & 1]),
                                             "r"(8 * (((k >> 1) + 3) & 3) + 4 * hf), "r"(bar_q + 8 * (k & 1)) : "memory");
                        }
                        flag_wait_bounded(&g_sync[SY_B * 32], ep);
                        fence_async_global();
                    }
#pragma unroll 1
                    for (int j = 0; j < 4; j++, it++) {
                        mbar_wait_sleep(bar_empty + 8 * (it & 3), ((it >> 2) & 1) ^ 1);
                        mbar_expect_tx(bar_full + 8 * (it & 3), QB_BYTES);
                        bulk_g2s(sb + SM_KV + (it & 3) * KV_BYTES, g_w + (4 + j) * QB_BYTES, QB_BYTES, bar_full + 8 * (it & 3));
                    }
#pragma unroll 1
                    for (int k = 0; k < 26 + rank; k++) {
                        if (k == 0 || k == ((GF0 + 1) * NAUX - 16) / 128) { flag_wait_bounded(&g_sync[(k ? SY_AUX1 : SY_AUX0) * 32], NAUX * ep); fence_async_global(); }
                        mbar_wait_sleep(bar_qfree + 8 * (k & 1), ((k >> 1) ^ (k & 1) ^ 1) & 1);
                        mbar_expect_tx(bar_q + 8 * (k & 1), QB_BYTES);
                        bulk_g2s(sb + SM_Q + (k & 1) * QB_BYTES, g_agg + SC_TZB(k) * QB_BYTES, QB_BYTES, bar_q + 8 * (k & 1));
                    }
                }
            } else {
            const int par = ep & 1;
            if (blockIdx.x == 0 && t == 32) g_ovf_n[par ^ 1] = 0;
            if (blockIdx.x == 0 && warp == 1) *(uint4*)(g_hz + (lane >> 3) * 1024 + (lane & 7) * 16) = make_uint4(KV_OFF2 | NEG2, KV_OFF2 | NEG2, KV_OFF2, KV_OFF2);
            const uint32_t wlo = (uint32_t)(uintptr_t)H.s, whi = (uint32_t)((uintptr_t)H.s >> 32);
            const uint32_t blo = wlo + (uint32_t)offsetof(Scratch, bucket);
            {
                const int* pd = P.dst + blockIdx.x * 96 + (t - 32);
                const int* ps = P.src + blockIdx.x * 96 + (t - 32);
#pragma unroll 1
                for (int e = P.E - (blockIdx.x * 96 + (t - 32)); e > 0; e -= CSRU * NAUX * 32, pd += CSRU * NAUX * 32, ps += CSRU * NAUX * 32) {
                    int d[CSRU], sr[CSRU], sl[CSRU];
#pragma unroll
                    for (int i = 0; i < CSRU; i++) {
                        d[i] = e > i * NAUX * 32 ? __ldg(pd + i * NAUX * 32) : NN;
                        sr[i] = e > i * NAUX * 32 ? __ldg(ps + i * NAUX * 32) : 0;
                    }
#pragma unroll
                    for (int i = 0; i < CSRU; i++) {
                        sl[i] = 0;
                        asm volatile("{\n.reg .pred p;\nsetp.lt.s32 p, %2, %3;\n@p atom.relaxed.gpu.global.add.s32 %0, [%1], 1;\n}\n"
                                     : "+r"(sl[i]) : "l"(mkaddr(wlo + (uint32_t)offsetof(Scratch, cnt) + d[i] * 4, whi)), "r"(d[i]), "n"(NN) : "memory");
                    }
                    uint32_t ov = 0;
#pragma unroll
                    for (int i = 0; i < CSRU; i++) {
                        asm volatile("{\n.reg .pred p;\nsetp.lt.s32 p, %3, %4;\n@p st.global.u16 [%1], %2;\n@!p or.b32 %0, %0, %5;\n}\n"
                                     : "+r"(ov) : "l"(mkaddr(blo + d[i] * 128 + (sl[i] & 31) * 4 + (sl[i] >> 5) * 2, whi)), "h"((unsigned short)sr[i]), "r"(sl[i]), "n"(CAP), "r"(1 << i) : "memory");
                    }
#pragma unroll 1
                    for (; ov; ov &= ov - 1) {
                        const int i = (__ffs(ov) - 1) * (NAUX * 32);
                        int at;
                        asm volatile("atom.relaxed.gpu.global.add.s32 %0, [%1], 1;\n" : "=r"(at) : "l"(&g_ovf_n[par]) : "memory");
                        g_ovf[at] = make_int2(__ldg(pd + i), __ldg(ps + i));
                    }
                }
            }
            bar_sync(BAR_AUX, 96);
            if (warp == 1 && elect()) { red_release(&g_sync[SY_CSR * 32]); }
            __syncwarp();
            {
                const int r0 = blockIdx.x * 3 + warp - 1;
                const uint4* xp = (const uint4*)(H.x + r0 * 256) + lane;
                uint4* op = (uint4*)(P.out + r0 * 256) + lane;
#pragma unroll 1
                for (int r = r0; r < NN; r += CPYU * NAUX, xp += CPYU * NAUX * 32, op += CPYU * NAUX * 32) {
                    uint4 v[CPYU];
#pragma unroll
                    for (int i = 0; i < CPYU; i++) if (r + i * NAUX < NN) v[i] = ldg_pinned(xp + i * NAUX * 32);
#pragma unroll
                    for (int i = 0; i < CPYU; i++) if (r + i * NAUX < NN) op[i * NAUX * 32] = v[i];
                }
            }
            mbar_wait_bounded(bar_go, 1);
            if (const int un = (3 - warp) * (NAUX / 3) + (NAUX / 3 - 1) - blockIdx.x; un < 208) {
                flag_wait_bounded(&g_sync[SY_PART * 32], 52 * ep);
                uint8_t* pp = g_part + (un >> 3) * (4 * PART_BYTES);
                float* ml = (float*)(pp + QB_BYTES) + (un & 7) * 32;
                const float4 sa = __ldcg((const float4*)ml + g), sc = __ldcg((const float4*)ml + g + 2 * PART_BYTES / 16);
                const float n0 = fmaxf(sa.x, sc.x), n1 = fmaxf(sa.z, sc.z);
                const uint32_t a0 = pack_bf16(ex2(sa.x - n0), ex2(sa.x - n0)), a1 = pack_bf16(ex2(sa.z - n1), ex2(sa.z - n1));
                const uint32_t b0 = pack_bf16(ex2(sc.x - n0), ex2(sc.x - n0)), b1 = pack_bf16(ex2(sc.z - n1), ex2(sc.z - n1));
                __syncwarp();
                if (q == 0) ((float4*)ml)[g] = make_float4(n0, sa.y * bf_hi(a0) + sc.y * bf_hi(b0), n1, sa.w * bf_hi(a1) + sc.w * bf_hi(b1));
                uint4* d = (uint4*)(pp + (un & 4) * 256 + (un & 7) * 8192) + lane;
#pragma unroll 1
                for (int i = 0; i < 4; i++, d += 128) {
                    uint4 u[4], v[4];
#pragma unroll
                    for (int j = 0; j < 4; j++) { u[j] = __ldcg(d + j * 32); v[j] = __ldcg(d + j * 32 + 2 * PART_BYTES / 16); }
#pragma unroll
                    for (int j = 0; j < 4; j++)
                        d[j * 32] = make_uint4(hfma2(v[j].x, b0, hmul2(u[j].x, a0)), hfma2(v[j].y, b1, hmul2(u[j].y, a1)),
                                               hfma2(v[j].z, b0, hmul2(u[j].z, a0)), hfma2(v[j].w, b1, hmul2(u[j].w, a1)));
                }
            }
            flag_wait_bounded(&g_sync[SY_CSR * 32], NCTA * ep);
            if (warp == 2 && blockIdx.x < 129) {
                uint4* z = blockIdx.x < 128 ? (uint4*)(g_w + blockIdx.x * 1024) + lane : (uint4*)&g_sync[SY_DONE * 32 + 4];
                z[0] = make_uint4(0, 0, 0, 0);
                if (blockIdx.x < 128) z[32] = make_uint4(0, 0, 0, 0);
            }
            {
                const uint32_t lc = (lane >> 3) * 1024 + (lane & 7) * 16;
                const uint32_t alo = wlo ^ lc;
                const int node0 = blockIdx.x * 3 + warp - 17;
                auto node = [&](int i) { const int nd = node0 + i * NAUX; return (int)min((unsigned)nd, (unsigned)(nd + NN)); };
                const int num = (NN - 17 - node0) / NAUX + 1;
                uint32_t mine = 0;
                if (lane < num) {
                    mine = min(__ldcg(&g_cnt[node(lane)]), CAP + 1) | (uint32_t)__ldg((const unsigned short*)P.deg_inv + node(lane)) << 16;
                    g_cnt[node(lane)] = 0;
                }
                auto row = [&](int off) {
                    uint4 v;
                    asm volatile("ld.global.v4.u32 {%0, %1, %2, %3}, [%4];\n"
                                 : "=r"(v.x), "=r"(v.y), "=r"(v.z), "=r"(v.w) : "l"(mkaddr(alo ^ off, whi)));
                    return v;
                };
                auto ents = [&](int i) {
                    uint32_t e;
                    asm volatile("ld.global.cg.u32 %0, [%1];\n" : "=r"(e) : "l"(mkaddr(blo + (min(node(i), NN - 1) * 32 + lane) * 4, whi)));
                    return e;
                };
                auto store = [&](int i, const float (&a)[8]) {
                    const float di = bf_hi(__shfl_sync(~0u, mine, i)) * (1.f / KV_SCALE);
                    const int nd = node(i);
                    *(uint4*)(g_agg + (uint32_t)(((nd >> 3) * 4096 + (nd & 7) * 144) ^ lc)) =
                        make_uint4(pack_bf16(a[0] * di, a[1] * di), pack_bf16(a[2] * di, a[3] * di), pack_bf16(a[4] * di, a[5] * di), pack_bf16(a[6] * di, a[7] * di));
                };
#pragma unroll 1
                for (uint32_t big = __ballot_sync(~0u, (mine & 0xFFFF) > CAP); big; big &= big - 1) {
                    const int i = __ffs(big) - 1, no = __ldcg(&g_ovf_n[par]);
                    float a[8] = {};
#pragma unroll 1
                    for (int k = -64; k < no; k += 32) {
                        const int2 pr = k < 0 ? make_int2(node(i), (ents(i) >> (k & 32) / 2) & 0xFFFF) : k + lane < no ? __ldcg(&g_ovf[k + lane]) : make_int2(-1, 0);
#pragma unroll 1
                        for (uint32_t mk = __ballot_sync(~0u, pr.x == node(i)); mk; mk &= mk - 1) {
                            const uint4 v = row(row_off(__shfl_sync(~0u, pr.y, __ffs(mk) - 1)));
                            a[0] += f16_lo(v.x) + KV_OFF; a[1] += f16_hi(v.x) + KV_OFF; a[2] += f16_lo(v.y) + KV_OFF; a[3] += f16_hi(v.y) + KV_OFF;
                            a[4] += f16_lo(v.z) - KV_OFF; a[5] += f16_hi(v.z) - KV_OFF; a[6] += f16_lo(v.w) - KV_OFF; a[7] += f16_hi(v.w) - KV_OFF;
                        }
                    }
                    store(i, a);
                }
                auto add4 = [&](const uint4& a, const uint4& b) { return make_uint4(hadd2_f16(a.x, b.x), hadd2_f16(a.y, b.y), hadd2_f16(a.z, b.z), hadd2_f16(a.w, b.w)); };
                int ni = -1, left = 0, pos = 0, ec = 0;
                uint32_t en = ents(0);
                uint4 acc = make_uint4(0, 0, 0, 0);
                auto step = [&](uint4 (&v)[4], int& tag) {
                    if (left <= 0 || pos == 32) {
                        if (left > 0) {
                            en = ents(ni) >> 16;
                        } else {
                            ni++;
                            left = __shfl_sync(~0u, mine, ni) & 0xFFFF;
                            if (left > CAP) left = 0;
                        }
                        ec = lane < left ? row_off(en & 0xFFFF) : 0;
                        en = ents(ni + 1);
                        pos = 0;
                    }
                    int of[4];
#pragma unroll
                    for (int j = 0; j < 4; j++) asm volatile("shfl.sync.idx.b32 %0, %1, %2, 31, -1;\n" : "=r"(of[j]) : "r"(ec), "r"(pos + j));
                    acc = add4(acc, add4(add4(add4(v[0], v[1]), make_uint4(KV_OFF8, KV_OFF8, KV_OFF8 | NEG2, KV_OFF8 | NEG2)), add4(v[2], v[3])));
                    asm volatile("" : "+r"(acc.x), "+r"(acc.y), "+r"(acc.z), "+r"(acc.w));
                    asm volatile("{\n.reg .pred p;\nsetp.lt.s32 p, %0, 0;\nL:\n@p pmevent 0;\n@p bra L;\n}\n" ::"r"(ni) : "memory");
#pragma unroll
                    for (int j = 0; j < 4; j++) v[j] = row(of[j]);
                    pos += 4; left -= 4;
                    const int i = tag;
                    tag = left <= 0 ? ni : -1;
                    if (i >= 0) {
                        const float a[8] = {f16_lo(acc.x), f16_hi(acc.x), f16_lo(acc.y), f16_hi(acc.y), f16_lo(acc.z), f16_hi(acc.z), f16_lo(acc.w), f16_hi(acc.w)};
                        if ((__shfl_sync(~0u, mine, i) & 0xFFFF) <= CAP) store(i, a);
                        acc = make_uint4(0, 0, 0, 0);
                        if (i == GF0 || i == 8) {
                            __syncwarp();
                            if (elect()) red_release(&g_sync[(i == 8 ? SY_AUX1 : SY_AUX0) * 32]);
                            __syncwarp();
                        }
                    }
                    return i == num - 1;
                };
                uint4 va[4], vb[4];
#pragma unroll
                for (int j = 0; j < 4; j++) va[j] = vb[j] = make_uint4(KV_OFF2 | NEG2, KV_OFF2 | NEG2, KV_OFF2, KV_OFF2);
                int ta = -1, tb = -1;
#pragma unroll 1
                while (!step(va, ta) && !step(vb, tb)) {}
            }
            bar_sync(BAR_AUX, 96);
            if (warp == 1 && elect()) {
                red_release(&g_sync[SY_AUX * 32]);
                red_add(&g_sync[SY_DONE * 32]);
            }
            }
        }
        __syncwarp();
        asm volatile("barrier.cluster.arrive.relaxed.aligned;\n" ::: "memory");
        if (warp == 1) mbar_wait_bounded(bar_end, 0);
        else if (elect()) mbar_arrive(bar_end);
        __syncwarp();
        asm volatile("barrier.cluster.wait.acquire.aligned;\n" ::: "memory");
    }
}

}

extern "C" void kernel_launch(void* const* d_in, const int* in_sizes, int n_in, void* d_out, int out_size) {
    Hot H;
    Params P;
    H.x = (const __nv_bfloat16*)d_in[0];
    P.src = (const int*)d_in[1];
    P.dst = (const int*)d_in[2];
    P.deg_inv = (const __nv_bfloat16*)d_in[3];
    H.wq = (const __nv_bfloat16*)d_in[5];
    H.wk = (const __nv_bfloat16*)d_in[6];
    P.out = (__nv_bfloat16*)d_out;
    typedef CUresult (*EncodeFn)(CUtensorMap*, CUtensorMapDataType, cuuint32_t, void*, const cuuint64_t*, const cuuint64_t*, const cuuint32_t*,
                                 const cuuint32_t*, CUtensorMapInterleave, CUtensorMapSwizzle, CUtensorMapL2promotion, CUtensorMapFloatOOBfill);
    void* fn = nullptr;
    cudaDriverEntryPointQueryResult qr;
    cudaGetDriverEntryPoint("cuTensorMapEncodeTiled", &fn, cudaEnableDefault, &qr);
    auto encode = [&](CUtensorMap* tm, const void* ptr, int rows, int box_rows, int box_cb = 4) {
        const cuuint64_t dims[4] = {64, 8, 4, (cuuint64_t)rows / 8};
        const cuuint64_t strides[3] = {512, 128, 4096};
        const cuuint32_t box[4] = {64, 8, (cuuint32_t)box_cb, (cuuint32_t)box_rows / 8}, es[4] = {1, 1, 1, 1};
        ((EncodeFn)fn)(tm, CU_TENSOR_MAP_DATA_TYPE_BFLOAT16, 4, (void*)ptr, dims, strides, box, es, CU_TENSOR_MAP_INTERLEAVE_NONE,
                       CU_TENSOR_MAP_SWIZZLE_128B, CU_TENSOR_MAP_L2_PROMOTION_NONE, CU_TENSOR_MAP_FLOAT_OOB_FILL_NONE);
    };
    encode(&P.tm_out, d_out, NN, 8);
    encode(&P.tm_outc, d_out, NN, 16, 1);
    for (int i = 0; i < 2; i++) {
        const cuuint64_t dims[5] = {64, 2, 32, 4, 4};
        const cuuint64_t strides[4] = {512, 4096, 128, 1024};
        const cuuint32_t box[5] = {64, 2, 4, 4, 4}, es[5] = {1, 1, 1, 1, 1};
        ((EncodeFn)fn)(&P.tm_w[i], CU_TENSOR_MAP_DATA_TYPE_BFLOAT16, 5, d_in[i ? 4 : 7], dims, strides, box, es, CU_TENSOR_MAP_INTERLEAVE_NONE,
                       CU_TENSOR_MAP_SWIZZLE_128B, CU_TENSOR_MAP_L2_PROMOTION_NONE, CU_TENSOR_MAP_FLOAT_OOB_FILL_NONE);
    }
    encode(&P.tm_w[2], d_in[8], 256, 64);
    void* raw = nullptr;
    cudaGetSymbolAddress(&raw, g_raw);
    H.s = (Scratch*)(((uintptr_t)raw + ((8 << 20) - 1)) & ~(uintptr_t)((8 << 20) - 1));
    P.dhi = 0x40000100u;
    P.E = in_sizes[1] < MAXE ? in_sizes[1] : MAXE;
    cudaFuncSetAttribute(k_main, cudaFuncAttributeMaxDynamicSharedMemorySize, SM_TOTAL);
    k_main<<<NCTA, 384, SM_TOTAL>>>(H, P);
}
```

```cpp
#include <cuda_runtime.h>
#include <cuda.h>
#include <cuda_bf16.h>
#include <stdint.h>
#include <stddef.h>

namespace {

constexpr int NN = 10000;
constexpr int BN = 80;
constexpr int NKV = NN / BN;
constexpr int NQB = 158;
constexpr int NCTA = 132;
constexpr int NAUX = 3 * (NCTA - 2);
constexpr int STAGES = 4;
constexpr int KV_BYTES = BN * 512;
constexpr int QB_BYTES = 64 * 512;
constexpr int PART_BYTES = QB_BYTES + 512;
constexpr int CAP = 64;
constexpr int MAXE = 160000;

#define QRND(v) (((v) + 0x00040004u) & 0xFFF8FFF8u)
#define GO0 5
#define GO1 41
#define GF0 2
#define CSRU 3
#define CPYU 9
#define REFUP 2.f
#define SND0 10
#define CUT2 2
#define TICK 1024
#define TSL 30
#define NQR 7
#define QSTEP 2
#define QREG(kk) ((kk) % QSTEP == 1 % QSTEP && (kk) > 0 && ((kk) - 1) / QSTEP < NQR ? ((kk) - 1) / QSTEP : -1)
#define REG_C 224
#define REG_P 56

enum { SY_PART = 4, SY_H1 = 5, SY_CSR = 6, SY_AUX = 7, SY_DONE = 8, SY_AUX0 = 9, SY_B = 10, SY_AUX1 = 11, SY_H0 = 12 };
struct Scratch {
    uint8_t hz[4096 + NN * 512];
    uint8_t w[12 * QB_BYTES];
    int sync[25 * 32];
    int qflag[96];
    int ovf_n[32];
    float r255[512];
    int cnt[NN + 16];
    int bucket[(NN + 1) * 32];
    int2 ovf[MAXE];
    uint8_t q[NQB * QB_BYTES];
    uint8_t agg[NQB * QB_BYTES];
    uint8_t part[52 * 2 * PART_BYTES];
};
static_assert(offsetof(Scratch, ovf) <= (8 << 20), "window");
static_assert(offsetof(Scratch, qflag) == offsetof(Scratch, sync) + 25 * 128, "flags");
static_assert(offsetof(Scratch, w) % 1024 == 0 && offsetof(Scratch, sync) % 128 == 0 &&
              offsetof(Scratch, bucket) % 128 == 0 && offsetof(Scratch, q) % 128 == 0, "alignment");
__device__ uint8_t g_raw[(8 << 20) + sizeof(Scratch)];
#define g_hz (H.s->hz)
#define g_w (H.s->w)
#define g_sync (H.s->sync)
#define g_qflag (H.s->qflag)
#define g_ovf_n (H.s->ovf_n)
#define g_cnt (H.s->cnt)
#define g_bucket (H.s->bucket)
#define g_ovf (H.s->ovf)
#define g_q (H.s->q)
#define g_agg (H.s->agg)
#define g_part (H.s->part)

__device__ __forceinline__ void wgmma_ss_n80(uint32_t (&d)[20], uint64_t da, uint64_t db) {
    asm volatile("wgmma.mma_async.sync.aligned.m64n80k16.f16.f16.f16 {"
        "%0, %1, %2, %3, %4, %5, %6, %7, %8, %9, %10, %11, %12, %13, %14, %15, %16, %17, %18, %19}, %20, %21, 1, 1, 1, 0, 0;\n"
        : "+r"(d[0]), "+r"(d[1]), "+r"(d[2]), "+r"(d[3]), "+r"(d[4]), "+r"(d[5]), "+r"(d[6]), "+r"(d[7]),
          "+r"(d[8]), "+r"(d[9]), "+r"(d[10]), "+r"(d[11]), "+r"(d[12]), "+r"(d[13]), "+r"(d[14]), "+r"(d[15]),
          "+r"(d[16]), "+r"(d[17]), "+r"(d[18]), "+r"(d[19])
        : "l"(da), "l"(db));
}
__device__ __forceinline__ void wgmma_ss_n80_init(uint32_t (&d)[20], uint64_t da, uint64_t db) {
    asm volatile("wgmma.mma_async.sync.aligned.m64n80k16.f16.f16.f16 {"
        "%0, %1, %2, %3, %4, %5, %6, %7, %8, %9, %10, %11, %12, %13, %14, %15, %16, %17, %18, %19}, %20, %21, 0, 1, 1, 0, 0;\n"
        : "=r"(d[0]), "=r"(d[1]), "=r"(d[2]), "=r"(d[3]), "=r"(d[4]), "=r"(d[5]), "=r"(d[6]), "=r"(d[7]),
          "=r"(d[8]), "=r"(d[9]), "=r"(d[10]), "=r"(d[11]), "=r"(d[12]), "=r"(d[13]), "=r"(d[14]), "=r"(d[15]),
          "=r"(d[16]), "=r"(d[17]), "=r"(d[18]), "=r"(d[19])
        : "l"(da), "l"(db));
}
__device__ __forceinline__ void wgmma_rs_n80(uint32_t (&d)[20], uint32_t a0, uint32_t a1, uint32_t a2, uint32_t a3, uint64_t db) {
    asm volatile("wgmma.mma_async.sync.aligned.m64n80k16.f16.f16.f16 {"
        "%0, %1, %2, %3, %4, %5, %6, %7, %8, %9, %10, %11, %12, %13, %14, %15, %16, %17, %18, %19}, {%20, %21, %22, %23}, %24, 1, 1, 1, 0;\n"
        : "+r"(d[0]), "+r"(d[1]), "+r"(d[2]), "+r"(d[3]), "+r"(d[4]), "+r"(d[5]), "+r"(d[6]), "+r"(d[7]),
          "+r"(d[8]), "+r"(d[9]), "+r"(d[10]), "+r"(d[11]), "+r"(d[12]), "+r"(d[13]), "+r"(d[14]), "+r"(d[15]),
          "+r"(d[16]), "+r"(d[17]), "+r"(d[18]), "+r"(d[19])
        : "r"(a0), "r"(a1), "r"(a2), "r"(a3), "l"(db));
}
__device__ __forceinline__ void wgmma_rs_n256_tb(float (&d)[128], uint32_t a0, uint32_t a1, uint32_t a2, uint32_t a3, uint64_t db) {
    asm volatile("wgmma.mma_async.sync.aligned.m64n256k16.f32.f16.f16 {"
        "%0, %1, %2, %3, %4, %5, %6, %7, %8, %9, %10, %11, %12, %13, %14, %15, %16, %17, %18, %19, %20, %21, %22, %23, %24, %25, %26, %27, %28, %29, %30, %31, "
        "%32, %33, %34, %35, %36, %37, %38, %39, %40, %41, %42, %43, %44, %45, %46, %47, %48, %49, %50, %51, %52, %53, %54, %55, %56, %57, %58, %59, %60, %61, %62, %63, "
        "%64, %65, %66, %67, %68, %69, %70, %71, %72, %73, %74, %75, %76, %77, %78, %79, %80, %81, %82, %83, %84, %85, %86, %87, %88, %89, %90, %91, %92, %93, %94, %95, "
        "%96, %97, %98, %99, %100, %101, %102, %103, %104, %105, %106, %107, %108, %109, %110, %111, %112, %113, %114, %115, %116, %117, %118, %119, %120, %121, %122, %123, %124, %125, %126, %127}, {%128, %129, %130, %131}, %132, 1, 1, 1, 1;\n"
        : "+f"(d[0]), "+f"(d[1]), "+f"(d[2]), "+f"(d[3]), "+f"(d[4]), "+f"(d[5]), "+f"(d[6]), "+f"(d[7]),
          "+f"(d[8]), "+f"(d[9]), "+f"(d[10]), "+f"(d[11]), "+f"(d[12]), "+f"(d[13]), "+f"(d[14]), "+f"(d[15]),
          "+f"(d[16]), "+f"(d[17]), "+f"(d[18]), "+f"(d[19]), "+f"(d[20]), "+f"(d[21]), "+f"(d[22]), "+f"(d[23]),
          "+f"(d[24]), "+f"(d[25]), "+f"(d[26]), "+f"(d[27]), "+f"(d[28]), "+f"(d[29]), "+f"(d[30]), "+f"(d[31]),
          "+f"(d[32]), "+f"(d[33]), "+f"(d[34]), "+f"(d[35]), "+f"(d[36]), "+f"(d[37]), "+f"(d[38]), "+f"(d[39]),
          "+f"(d[40]), "+f"(d[41]), "+f"(d[42]), "+f"(d[43]), "+f"(d[44]), "+f"(d[45]), "+f"(d[46]), "+f"(d[47]),
          "+f"(d[48]), "+f"(d[49]), "+f"(d[50]), "+f"(d[51]), "+f"(d[52]), "+f"(d[53]), "+f"(d[54]), "+f"(d[55]),
          "+f"(d[56]), "+f"(d[57]), "+f"(d[58]), "+f"(d[59]), "+f"(d[60]), "+f"(d[61]), "+f"(d[62]), "+f"(d[63]),
          "+f"(d[64]), "+f"(d[65]), "+f"(d[66]), "+f"(d[67]), "+f"(d[68]), "+f"(d[69]), "+f"(d[70]), "+f"(d[71]),
          "+f"(d[72]), "+f"(d[73]), "+f"(d[74]), "+f"(d[75]), "+f"(d[76]), "+f"(d[77]), "+f"(d[78]), "+f"(d[79]),
          "+f"(d[80]), "+f"(d[81]), "+f"(d[82]), "+f"(d[83]), "+f"(d[84]), "+f"(d[85]), "+f"(d[86]), "+f"(d[87]),
          "+f"(d[88]), "+f"(d[89]), "+f"(d[90]), "+f"(d[91]), "+f"(d[92]), "+f"(d[93]), "+f"(d[94]), "+f"(d[95]),
          "+f"(d[96]), "+f"(d[97]), "+f"(d[98]), "+f"(d[99]), "+f"(d[100]), "+f"(d[101]), "+f"(d[102]), "+f"(d[103]),
          "+f"(d[104]), "+f"(d[105]), "+f"(d[106]), "+f"(d[107]), "+f"(d[108]), "+f"(d[109]), "+f"(d[110]), "+f"(d[111]),
          "+f"(d[112]), "+f"(d[113]), "+f"(d[114]), "+f"(d[115]), "+f"(d[116]), "+f"(d[117]), "+f"(d[118]), "+f"(d[119]),
          "+f"(d[120]), "+f"(d[121]), "+f"(d[122]), "+f"(d[123]), "+f"(d[124]), "+f"(d[125]), "+f"(d[126]), "+f"(d[127])
        : "r"(a0), "r"(a1), "r"(a2), "r"(a3), "l"(db));
}
__device__ __forceinline__ void wgmma_rs_n256_tb_init(float (&d)[128], uint32_t a0, uint32_t a1, uint32_t a2, uint32_t a3, uint64_t db) {
    asm volatile("wgmma.mma_async.sync.aligned.m64n256k16.f32.f16.f16 {"
        "%0, %1, %2, %3, %4, %5, %6, %7, %8, %9, %10, %11, %12, %13, %14, %15, %16, %17, %18, %19, %20, %21, %22, %23, %24, %25, %26, %27, %28, %29, %30, %31, "
        "%32, %33, %34, %35, %36, %37, %38, %39, %40, %41, %42, %43, %44, %45, %46, %47, %48, %49, %50, %51, %52, %53, %54, %55, %56, %57, %58, %59, %60, %61, %62, %63, "
        "%64, %65, %66, %67, %68, %69, %70, %71, %72, %73, %74, %75, %76, %77, %78, %79, %80, %81, %82, %83, %84, %85, %86, %87, %88, %89, %90, %91, %92, %93, %94, %95, "
        "%96, %97, %98, %99, %100, %101, %102, %103, %104, %105, %106, %107, %108, %109, %110, %111, %112, %113, %114, %115, %116, %117, %118, %119, %120, %121, %122, %123, %124, %125, %126, %127}, {%128, %129, %130, %131}, %132, 0, 1, 1, 1;\n"
        : "=f"(d[0]), "=f"(d[1]), "=f"(d[2]), "=f"(d[3]), "=f"(d[4]), "=f"(d[5]), "=f"(d[6]), "=f"(d[7]),
          "=f"(d[8]), "=f"(d[9]), "=f"(d[10]), "=f"(d[11]), "=f"(d[12]), "=f"(d[13]), "=f"(d[14]), "=f"(d[15]),
          "=f"(d[16]), "=f"(d[17]), "=f"(d[18]), "=f"(d[19]), "=f"(d[20]), "=f"(d[21]), "=f"(d[22]), "=f"(d[23]),
          "=f"(d[24]), "=f"(d[25]), "=f"(d[26]), "=f"(d[27]), "=f"(d[28]), "=f"(d[29]), "=f"(d[30]), "=f"(d[31]),
          "=f"(d[32]), "=f"(d[33]), "=f"(d[34]), "=f"(d[35]), "=f"(d[36]), "=f"(d[37]), "=f"(d[38]), "=f"(d[39]),
          "=f"(d[40]), "=f"(d[41]), "=f"(d[42]), "=f"(d[43]), "=f"(d[44]), "=f"(d[45]), "=f"(d[46]), "=f"(d[47]),
          "=f"(d[48]), "=f"(d[49]), "=f"(d[50]), "=f"(d[51]), "=f"(d[52]), "=f"(d[53]), "=f"(d[54]), "=f"(d[55]),
          "=f"(d[56]), "=f"(d[57]), "=f"(d[58]), "=f"(d[59]), "=f"(d[60]), "=f"(d[61]), "=f"(d[62]), "=f"(d[63]),
          "=f"(d[64]), "=f"(d[65]), "=f"(d[66]), "=f"(d[67]), "=f"(d[68]), "=f"(d[69]), "=f"(d[70]), "=f"(d[71]),
          "=f"(d[72]), "=f"(d[73]), "=f"(d[74]), "=f"(d[75]), "=f"(d[76]), "=f"(d[77]), "=f"(d[78]), "=f"(d[79]),
          "=f"(d[80]), "=f"(d[81]), "=f"(d[82]), "=f"(d[83]), "=f"(d[84]), "=f"(d[85]), "=f"(d[86]), "=f"(d[87]),
          "=f"(d[88]), "=f"(d[89]), "=f"(d[90]), "=f"(d[91]), "=f"(d[92]), "=f"(d[93]), "=f"(d[94]), "=f"(d[95]),
          "=f"(d[96]), "=f"(d[97]), "=f"(d[98]), "=f"(d[99]), "=f"(d[100]), "=f"(d[101]), "=f"(d[102]), "=f"(d[103]),
          "=f"(d[104]), "=f"(d[105]), "=f"(d[106]), "=f"(d[107]), "=f"(d[108]), "=f"(d[109]), "=f"(d[110]), "=f"(d[111]),
          "=f"(d[112]), "=f"(d[113]), "=f"(d[114]), "=f"(d[115]), "=f"(d[116]), "=f"(d[117]), "=f"(d[118]), "=f"(d[119]),
          "=f"(d[120]), "=f"(d[121]), "=f"(d[122]), "=f"(d[123]), "=f"(d[124]), "=f"(d[125]), "=f"(d[126]), "=f"(d[127])
        : "r"(a0), "r"(a1), "r"(a2), "r"(a3), "l"(db));
}
__device__ __forceinline__ void wgmma_rs_n256_tb_pred(float (&d)[128], uint32_t a0, uint32_t a1, uint32_t a2, uint32_t a3, uint64_t db, int acc) {
    asm volatile("{\n.reg .pred p;\nsetp.ne.s32 p, %133, 0;\nwgmma.mma_async.sync.aligned.m64n256k16.f32.f16.f16 {"
        "%0, %1, %2, %3, %4, %5, %6, %7, %8, %9, %10, %11, %12, %13, %14, %15, %16, %17, %18, %19, %20, %21, %22, %23, %24, %25, %26, %27, %28, %29, %30, %31, "
        "%32, %33, %34, %35, %36, %37, %38, %39, %40, %41, %42, %43, %44, %45, %46, %47, %48, %49, %50, %51, %52, %53, %54, %55, %56, %57, %58, %59, %60, %61, %62, %63, "
        "%64, %65, %66, %67, %68, %69, %70, %71, %72, %73, %74, %75, %76, %77, %78, %79, %80, %81, %82, %83, %84, %85, %86, %87, %88, %89, %90, %91, %92, %93, %94, %95, "
        "%96, %97, %98, %99, %100, %101, %102, %103, %104, %105, %106, %107, %108, %109, %110, %111, %112, %113, %114, %115, %116, %117, %118, %119, %120, %121, %122, %123, %124, %125, %126, %127}, {%128, %129, %130, %131}, %132, p, 1, 1, 1;\n}\n"
        : "+f"(d[0]), "+f"(d[1]), "+f"(d[2]), "+f"(d[3]), "+f"(d[4]), "+f"(d[5]), "+f"(d[6]), "+f"(d[7]),
          "+f"(d[8]), "+f"(d[9]), "+f"(d[10]), "+f"(d[11]), "+f"(d[12]), "+f"(d[13]), "+f"(d[14]), "+f"(d[15]),
          "+f"(d[16]), "+f"(d[17]), "+f"(d[18]), "+f"(d[19]), "+f"(d[20]), "+f"(d[21]), "+f"(d[22]), "+f"(d[23]),
          "+f"(d[24]), "+f"(d[25]), "+f"(d[26]), "+f"(d[27]), "+f"(d[28]), "+f"(d[29]), "+f"(d[30]), "+f"(d[31]),
          "+f"(d[32]), "+f"(d[33]), "+f"(d[34]), "+f"(d[35]), "+f"(d[36]), "+f"(d[37]), "+f"(d[38]), "+f"(d[39]),
          "+f"(d[40]), "+f"(d[41]), "+f"(d[42]), "+f"(d[43]), "+f"(d[44]), "+f"(d[45]), "+f"(d[46]), "+f"(d[47]),
          "+f"(d[48]), "+f"(d[49]), "+f"(d[50]), "+f"(d[51]), "+f"(d[52]), "+f"(d[53]), "+f"(d[54]), "+f"(d[55]),
          "+f"(d[56]), "+f"(d[57]), "+f"(d[58]), "+f"(d[59]), "+f"(d[60]), "+f"(d[61]), "+f"(d[62]), "+f"(d[63]),
          "+f"(d[64]), "+f"(d[65]), "+f"(d[66]), "+f"(d[67]), "+f"(d[68]), "+f"(d[69]), "+f"(d[70]), "+f"(d[71]),
          "+f"(d[72]), "+f"(d[73]), "+f"(d[74]), "+f"(d[75]), "+f"(d[76]), "+f"(d[77]), "+f"(d[78]), "+f"(d[79]),
          "+f"(d[80]), "+f"(d[81]), "+f"(d[82]), "+f"(d[83]), "+f"(d[84]), "+f"(d[85]), "+f"(d[86]), "+f"(d[87]),
          "+f"(d[88]), "+f"(d[89]), "+f"(d[90]), "+f"(d[91]), "+f"(d[92]), "+f"(d[93]), "+f"(d[94]), "+f"(d[95]),
          "+f"(d[96]), "+f"(d[97]), "+f"(d[98]), "+f"(d[99]), "+f"(d[100]), "+f"(d[101]), "+f"(d[102]), "+f"(d[103]),
          "+f"(d[104]), "+f"(d[105]), "+f"(d[106]), "+f"(d[107]), "+f"(d[108]), "+f"(d[109]), "+f"(d[110]), "+f"(d[111]),
          "+f"(d[112]), "+f"(d[113]), "+f"(d[114]), "+f"(d[115]), "+f"(d[116]), "+f"(d[117]), "+f"(d[118]), "+f"(d[119]),
          "+f"(d[120]), "+f"(d[121]), "+f"(d[122]), "+f"(d[123]), "+f"(d[124]), "+f"(d[125]), "+f"(d[126]), "+f"(d[127])
        : "r"(a0), "r"(a1), "r"(a2), "r"(a3), "l"(db), "r"(acc));
}
__device__ __forceinline__ void wgmma_ss_n256_tb(float (&d)[128], uint64_t da, uint64_t db) {
    asm volatile("wgmma.mma_async.sync.aligned.m64n256k16.f32.bf16.bf16 {"
        "%0, %1, %2, %3, %4, %5, %6, %7, %8, %9, %10, %11, %12, %13, %14, %15, %16, %17, %18, %19, %20, %21, %22, %23, %24, %25, %26, %27, %28, %29, %30, %31, "
        "%32, %33, %34, %35, %36, %37, %38, %39, %40, %41, %42, %43, %44, %45, %46, %47, %48, %49, %50, %51, %52, %53, %54, %55, %56, %57, %58, %59, %60, %61, %62, %63, "
        "%64, %65, %66, %67, %68, %69, %70, %71, %72, %73, %74, %75, %76, %77, %78, %79, %80, %81, %82, %83, %84, %85, %86, %87, %88, %89, %90, %91, %92, %93, %94, %95, "
        "%96, %97, %98, %99, %100, %101, %102, %103, %104, %105, %106, %107, %108, %109, %110, %111, %112, %113, %114, %115, %116, %117, %118, %119, %120, %121, %122, %123, %124, %125, %126, %127}, %128, %129, 1, 1, 1, 0, 1;\n"
        : "+f"(d[0]), "+f"(d[1]), "+f"(d[2]), "+f"(d[3]), "+f"(d[4]), "+f"(d[5]), "+f"(d[6]), "+f"(d[7]),
          "+f"(d[8]), "+f"(d[9]), "+f"(d[10]), "+f"(d[11]), "+f"(d[12]), "+f"(d[13]), "+f"(d[14]), "+f"(d[15]),
          "+f"(d[16]), "+f"(d[17]), "+f"(d[18]), "+f"(d[19]), "+f"(d[20]), "+f"(d[21]), "+f"(d[22]), "+f"(d[23]),
          "+f"(d[24]), "+f"(d[25]), "+f"(d[26]), "+f"(d[27]), "+f"(d[28]), "+f"(d[29]), "+f"(d[30]), "+f"(d[31]),
          "+f"(d[32]), "+f"(d[33]), "+f"(d[34]), "+f"(d[35]), "+f"(d[36]), "+f"(d[37]), "+f"(d[38]), "+f"(d[39]),
          "+f"(d[40]), "+f"(d[41]), "+f"(d[42]), "+f"(d[43]), "+f"(d[44]), "+f"(d[45]), "+f"(d[46]), "+f"(d[47]),
          "+f"(d[48]), "+f"(d[49]), "+f"(d[50]), "+f"(d[51]), "+f"(d[52]), "+f"(d[53]), "+f"(d[54]), "+f"(d[55]),
          "+f"(d[56]), "+f"(d[57]), "+f"(d[58]), "+f"(d[59]), "+f"(d[60]), "+f"(d[61]), "+f"(d[62]), "+f"(d[63]),
          "+f"(d[64]), "+f"(d[65]), "+f"(d[66]), "+f"(d[67]), "+f"(d[68]), "+f"(d[69]), "+f"(d[70]), "+f"(d[71]),
          "+f"(d[72]), "+f"(d[73]), "+f"(d[74]), "+f"(d[75]), "+f"(d[76]), "+f"(d[77]), "+f"(d[78]), "+f"(d[79]),
          "+f"(d[80]), "+f"(d[81]), "+f"(d[82]), "+f"(d[83]), "+f"(d[84]), "+f"(d[85]), "+f"(d[86]), "+f"(d[87]),
          "+f"(d[88]), "+f"(d[89]), "+f"(d[90]), "+f"(d[91]), "+f"(d[92]), "+f"(d[93]), "+f"(d[94]), "+f"(d[95]),
          "+f"(d[96]), "+f"(d[97]), "+f"(d[98]), "+f"(d[99]), "+f"(d[100]), "+f"(d[101]), "+f"(d[102]), "+f"(d[103]),
          "+f"(d[104]), "+f"(d[105]), "+f"(d[106]), "+f"(d[107]), "+f"(d[108]), "+f"(d[109]), "+f"(d[110]), "+f"(d[111]),
          "+f"(d[112]), "+f"(d[113]), "+f"(d[114]), "+f"(d[115]), "+f"(d[116]), "+f"(d[117]), "+f"(d[118]), "+f"(d[119]),
          "+f"(d[120]), "+f"(d[121]), "+f"(d[122]), "+f"(d[123]), "+f"(d[124]), "+f"(d[125]), "+f"(d[126]), "+f"(d[127])
        : "l"(da), "l"(db));
}
__device__ __forceinline__ void wgmma_ss_n256_tb_init(float (&d)[128], uint64_t da, uint64_t db) {
    asm volatile("wgmma.mma_async.sync.aligned.m64n256k16.f32.bf16.bf16 {"
        "%0, %1, %2, %3, %4, %5, %6, %7, %8, %9, %10, %11, %12, %13, %14, %15, %16, %17, %18, %19, %20, %21, %22, %23, %24, %25, %26, %27, %28, %29, %30, %31, "
        "%32, %33, %34, %35, %36, %37, %38, %39, %40, %41, %42, %43, %44, %45, %46, %47, %48, %49, %50, %51, %52, %53, %54, %55, %56, %57, %58, %59, %60, %61, %62, %63, "
        "%64, %65, %66, %67, %68, %69, %70, %71, %72, %73, %74, %75, %76, %77, %78, %79, %80, %81, %82, %83, %84, %85, %86, %87, %88, %89, %90, %91, %92, %93, %94, %95, "
        "%96, %97, %98, %99, %100, %101, %102, %103, %104, %105, %106, %107, %108, %109, %110, %111, %112, %113, %114, %115, %116, %117, %118, %119, %120, %121, %122, %123, %124, %125, %126, %127}, %128, %129, 0, 1, 1, 0, 1;\n"
        : "=f"(d[0]), "=f"(d[1]), "=f"(d[2]), "=f"(d[3]), "=f"(d[4]), "=f"(d[5]), "=f"(d[6]), "=f"(d[7]),
          "=f"(d[8]), "=f"(d[9]), "=f"(d[10]), "=f"(d[11]), "=f"(d[12]), "=f"(d[13]), "=f"(d[14]), "=f"(d[15]),
          "=f"(d[16]), "=f"(d[17]), "=f"(d[18]), "=f"(d[19]), "=f"(d[20]), "=f"(d[21]), "=f"(d[22]), "=f"(d[23]),
          "=f"(d[24]), "=f"(d[25]), "=f"(d[26]), "=f"(d[27]), "=f"(d[28]), "=f"(d[29]), "=f"(d[30]), "=f"(d[31]),
          "=f"(d[32]), "=f"(d[33]), "=f"(d[34]), "=f"(d[35]), "=f"(d[36]), "=f"(d[37]), "=f"(d[38]), "=f"(d[39]),
          "=f"(d[40]), "=f"(d[41]), "=f"(d[42]), "=f"(d[43]), "=f"(d[44]), "=f"(d[45]), "=f"(d[46]), "=f"(d[47]),
          "=f"(d[48]), "=f"(d[49]), "=f"(d[50]), "=f"(d[51]), "=f"(d[52]), "=f"(d[53]), "=f"(d[54]), "=f"(d[55]),
          "=f"(d[56]), "=f"(d[57]), "=f"(d[58]), "=f"(d[59]), "=f"(d[60]), "=f"(d[61]), "=f"(d[62]), "=f"(d[63]),
          "=f"(d[64]), "=f"(d[65]), "=f"(d[66]), "=f"(d[67]), "=f"(d[68]), "=f"(d[69]), "=f"(d[70]), "=f"(d[71]),
          "=f"(d[72]), "=f"(d[73]), "=f"(d[74]), "=f"(d[75]), "=f"(d[76]), "=f"(d[77]), "=f"(d[78]), "=f"(d[79]),
          "=f"(d[80]), "=f"(d[81]), "=f"(d[82]), "=f"(d[83]), "=f"(d[84]), "=f"(d[85]), "=f"(d[86]), "=f"(d[87]),
          "=f"(d[88]), "=f"(d[89]), "=f"(d[90]), "=f"(d[91]), "=f"(d[92]), "=f"(d[93]), "=f"(d[94]), "=f"(d[95]),
          "=f"(d[96]), "=f"(d[97]), "=f"(d[98]), "=f"(d[99]), "=f"(d[100]), "=f"(d[101]), "=f"(d[102]), "=f"(d[103]),
          "=f"(d[104]), "=f"(d[105]), "=f"(d[106]), "=f"(d[107]), "=f"(d[108]), "=f"(d[109]), "=f"(d[110]), "=f"(d[111]),
          "=f"(d[112]), "=f"(d[113]), "=f"(d[114]), "=f"(d[115]), "=f"(d[116]), "=f"(d[117]), "=f"(d[118]), "=f"(d[119]),
          "=f"(d[120]), "=f"(d[121]), "=f"(d[122]), "=f"(d[123]), "=f"(d[124]), "=f"(d[125]), "=f"(d[126]), "=f"(d[127])
        : "l"(da), "l"(db));
}
__device__ __forceinline__ void wgmma_ss_n256_tb_pred(float (&d)[128], uint64_t da, uint64_t db, int acc) {
    asm volatile("{\n.reg .pred p;\nsetp.ne.s32 p, %130, 0;\nwgmma.mma_async.sync.aligned.m64n256k16.f32.bf16.bf16 {"
        "%0, %1, %2, %3, %4, %5, %6, %7, %8, %9, %10, %11, %12, %13, %14, %15, %16, %17, %18, %19, %20, %21, %22, %23, %24, %25, %26, %27, %28, %29, %30, %31, "
        "%32, %33, %34, %35, %36, %37, %38, %39, %40, %41, %42, %43, %44, %45, %46, %47, %48, %49, %50, %51, %52, %53, %54, %55, %56, %57, %58, %59, %60, %61, %62, %63, "
        "%64, %65, %66, %67, %68, %69, %70, %71, %72, %73, %74, %75, %76, %77, %78, %79, %80, %81, %82, %83, %84, %85, %86, %87, %88, %89, %90, %91, %92, %93, %94, %95, "
        "%96, %97, %98, %99, %100, %101, %102, %103, %104, %105, %106, %107, %108, %109, %110, %111, %112, %113, %114, %115, %116, %117, %118, %119, %120, %121, %122, %123, %124, %125, %126, %127}, %128, %129, p, 1, 1, 0, 1;\n}\n"
        : "+f"(d[0]), "+f"(d[1]), "+f"(d[2]), "+f"(d[3]), "+f"(d[4]), "+f"(d[5]), "+f"(d[6]), "+f"(d[7]),
          "+f"(d[8]), "+f"(d[9]), "+f"(d[10]), "+f"(d[11]), "+f"(d[12]), "+f"(d[13]), "+f"(d[14]), "+f"(d[15]),
          "+f"(d[16]), "+f"(d[17]), "+f"(d[18]), "+f"(d[19]), "+f"(d[20]), "+f"(d[21]), "+f"(d[22]), "+f"(d[23]),
          "+f"(d[24]), "+f"(d[25]), "+f"(d[26]), "+f"(d[27]), "+f"(d[28]), "+f"(d[29]), "+f"(d[30]), "+f"(d[31]),
          "+f"(d[32]), "+f"(d[33]), "+f"(d[34]), "+f"(d[35]), "+f"(d[36]), "+f"(d[37]), "+f"(d[38]), "+f"(d[39]),
          "+f"(d[40]), "+f"(d[41]), "+f"(d[42]), "+f"(d[43]), "+f"(d[44]), "+f"(d[45]), "+f"(d[46]), "+f"(d[47]),
          "+f"(d[48]), "+f"(d[49]), "+f"(d[50]), "+f"(d[51]), "+f"(d[52]), "+f"(d[53]), "+f"(d[54]), "+f"(d[55]),
          "+f"(d[56]), "+f"(d[57]), "+f"(d[58]), "+f"(d[59]), "+f"(d[60]), "+f"(d[61]), "+f"(d[62]), "+f"(d[63]),
          "+f"(d[64]), "+f"(d[65]), "+f"(d[66]), "+f"(d[67]), "+f"(d[68]), "+f"(d[69]), "+f"(d[70]), "+f"(d[71]),
          "+f"(d[72]), "+f"(d[73]), "+f"(d[74]), "+f"(d[75]), "+f"(d[76]), "+f"(d[77]), "+f"(d[78]), "+f"(d[79]),
          "+f"(d[80]), "+f"(d[81]), "+f"(d[82]), "+f"(d[83]), "+f"(d[84]), "+f"(d[85]), "+f"(d[86]), "+f"(d[87]),
          "+f"(d[88]), "+f"(d[89]), "+f"(d[90]), "+f"(d[91]), "+f"(d[92]), "+f"(d[93]), "+f"(d[94]), "+f"(d[95]),
          "+f"(d[96]), "+f"(d[97]), "+f"(d[98]), "+f"(d[99]), "+f"(d[100]), "+f"(d[101]), "+f"(d[102]), "+f"(d[103]),
          "+f"(d[104]), "+f"(d[105]), "+f"(d[106]), "+f"(d[107]), "+f"(d[108]), "+f"(d[109]), "+f"(d[110]), "+f"(d[111]),
          "+f"(d[112]), "+f"(d[113]), "+f"(d[114]), "+f"(d[115]), "+f"(d[116]), "+f"(d[117]), "+f"(d[118]), "+f"(d[119]),
          "+f"(d[120]), "+f"(d[121]), "+f"(d[122]), "+f"(d[123]), "+f"(d[124]), "+f"(d[125]), "+f"(d[126]), "+f"(d[127])
        : "l"(da), "l"(db), "r"(acc));
}
__device__ __forceinline__ void wgmma_rs_n64_tb(float (&d)[32], uint32_t a0, uint32_t a1, uint32_t a2, uint32_t a3, uint64_t db) {
    asm volatile("wgmma.mma_async.sync.aligned.m64n64k16.f32.bf16.bf16 {"
        "%0, %1, %2, %3, %4, %5, %6, %7, %8, %9, %10, %11, %12, %13, %14, %15, %16, %17, %18, %19, %20, %21, %22, %23, %24, %25, %26, %27, %28, %29, %30, %31}, {%32, %33, %34, %35}, %36, 1, 1, 1, 1;\n"
        : "+f"(d[0]), "+f"(d[1]), "+f"(d[2]), "+f"(d[3]), "+f"(d[4]), "+f"(d[5]), "+f"(d[6]), "+f"(d[7]),
          "+f"(d[8]), "+f"(d[9]), "+f"(d[10]), "+f"(d[11]), "+f"(d[12]), "+f"(d[13]), "+f"(d[14]), "+f"(d[15]),
          "+f"(d[16]), "+f"(d[17]), "+f"(d[18]), "+f"(d[19]), "+f"(d[20]), "+f"(d[21]), "+f"(d[22]), "+f"(d[23]),
          "+f"(d[24]), "+f"(d[25]), "+f"(d[26]), "+f"(d[27]), "+f"(d[28]), "+f"(d[29]), "+f"(d[30]), "+f"(d[31])
        : "r"(a0), "r"(a1), "r"(a2), "r"(a3), "l"(db));
}
__device__ __forceinline__ void wgmma_rs_n64_tb_init(float (&d)[32], uint32_t a0, uint32_t a1, uint32_t a2, uint32_t a3, uint64_t db) {
    asm volatile("wgmma.mma_async.sync.aligned.m64n64k16.f32.bf16.bf16 {"
        "%0, %1, %2, %3, %4, %5, %6, %7, %8, %9, %10, %11, %12, %13, %14, %15, %16, %17, %18, %19, %20, %21, %22, %23, %24, %25, %26, %27, %28, %29, %30, %31}, {%32, %33, %34, %35}, %36, 0, 1, 1, 1;\n"
        : "=f"(d[0]), "=f"(d[1]), "=f"(d[2]), "=f"(d[3]), "=f"(d[4]), "=f"(d[5]), "=f"(d[6]), "=f"(d[7]),
          "=f"(d[8]), "=f"(d[9]), "=f"(d[10]), "=f"(d[11]), "=f"(d[12]), "=f"(d[13]), "=f"(d[14]), "=f"(d[15]),
          "=f"(d[16]), "=f"(d[17]), "=f"(d[18]), "=f"(d[19]), "=f"(d[20]), "=f"(d[21]), "=f"(d[22]), "=f"(d[23]),
          "=f"(d[24]), "=f"(d[25]), "=f"(d[26]), "=f"(d[27]), "=f"(d[28]), "=f"(d[29]), "=f"(d[30]), "=f"(d[31])
        : "r"(a0), "r"(a1), "r"(a2), "r"(a3), "l"(db));
}

__device__ __forceinline__ void wg_fence() { asm volatile("wgmma.fence.sync.aligned;\n" ::: "memory"); }
__device__ __forceinline__ void wg_commit() { asm volatile("wgmma.commit_group.sync.aligned;\n" ::: "memory"); }
template <int N> __device__ __forceinline__ void wg_wait() { asm volatile("wgmma.wait_group.sync.aligned %0;\n" ::"n"(N) : "memory"); }
template <int N> __device__ __forceinline__ void fence_regs(float (&a)[N]) {
#pragma unroll
    for (int i = 0; i < N; i++) asm volatile("" : "+f"(a[i])::"memory");
}
template <int N> __device__ __forceinline__ void fence_regs(uint32_t (&a)[N]) {
#pragma unroll
    for (int i = 0; i < N; i++) asm volatile("" : "+r"(a[i])::"memory");
}
__device__ __forceinline__ void mbar_init(uint32_t bar, uint32_t cnt) {
    asm volatile("mbarrier.init.shared::cta.b64 [%0], %1;\n" ::"r"(bar), "r"(cnt) : "memory");
}
__device__ __forceinline__ void mbar_expect_tx(uint32_t bar, uint32_t bytes) {
    asm volatile("mbarrier.arrive.expect_tx.shared::cta.b64 _, [%0], %1;\n" ::"r"(bar), "r"(bytes) : "memory");
}
__device__ __forceinline__ void mbar_wait(uint32_t bar, uint32_t parity) {
    asm volatile("{\n.reg .pred p;\nLW:\nmbarrier.try_wait.parity.shared::cta.b64 p, [%0], %1;\n@!p pmevent 0;\n@!p bra LW;\n}\n" ::"r"(bar), "r"(parity) : "memory");
}
__device__ __forceinline__ void mbar_wait_sleep(uint32_t bar, uint32_t parity) {
    asm volatile("{\n.reg .pred p;\nLW:\nmbarrier.try_wait.parity.shared::cta.b64 p, [%0], %1, 20000;\n@!p pmevent 0;\n@!p bra LW;\n}\n" ::"r"(bar), "r"(parity) : "memory");
}
__device__ __forceinline__ void mbar_wait_bounded(uint32_t bar, uint32_t parity) {
    asm volatile("{\n.reg .pred p;\n.reg .u32 c;\nmov.u32 c, 0;\nLW:\nmbarrier.try_wait.parity.shared::cta.b64 p, [%0], %1, 20000;\n@p bra LD;\n"
                 "add.u32 c, c, 1;\nsetp.ge.u32 p, c, 262144;\n@p trap;\nbra LW;\nLD:\n}\n" ::"r"(bar), "r"(parity) : "memory");
}
__device__ __forceinline__ void flag_wait(const int* p, int v) {
    asm volatile("{\n.reg .pred p;\n.reg .s32 f;\nLW:\nld.acquire.gpu.global.s32 f, [%0];\nsub.s32 f, f, %1;\nsetp.lt.s32 p, f, 0;\n@p bra LW;\n}\n" ::"l"(p), "r"(v) : "memory");
}
__device__ __forceinline__ void flag_wait_bounded(const int* p, int v) {
    asm volatile("{\n.reg .pred p;\n.reg .u32 c;\n.reg .s32 f;\nmov.u32 c, 0;\nLW:\nld.acquire.gpu.global.s32 f, [%0];\nsub.s32 f, f, %1;\nsetp.ge.s32 p, f, 0;\n@p bra LD;\n"
                 "nanosleep.u32 500;\nadd.u32 c, c, 1;\nsetp.ge.u32 p, c, 4194304;\n@p trap;\nbra LW;\nLD:\n}\n" ::"l"(p), "r"(v) : "memory");
}
__device__ __forceinline__ int lane_now() {
    int l; asm volatile("mov.u32 %0, %%laneid;\n" : "=r"(l)); return l;
}
__device__ __forceinline__ bool elect() {
    uint32_t p; asm volatile("{\n.reg .pred p;\nelect.sync _|p, -1;\nselp.u32 %0, 1, 0, p;\n}\n" : "=r"(p)); return p;
}
__device__ __forceinline__ void bulk_g2s(uint32_t dst, const void* src, uint32_t bytes, uint32_t bar) {
    asm volatile("cp.async.bulk.shared::cluster.global.mbarrier::complete_tx::bytes [%0], [%1], %2, [%3];\n"
                 ::"r"(dst), "l"(src), "r"(bytes), "r"(bar) : "memory");
}
__device__ __forceinline__ void tma_g2s(uint32_t dst, const CUtensorMap* tm, int rowgroup, uint32_t bar) {
    asm volatile("cp.async.bulk.tensor.4d.shared::cluster.global.tile.mbarrier::complete_tx::bytes [%0], [%1, {0, 0, 0, %2}], [%3];\n"
                 ::"r"(dst), "l"(tm), "r"(rowgroup), "r"(bar) : "memory");
}
__device__ __forceinline__ void bar_sync(int id, int n) { asm volatile("bar.sync %0, %1;\n" ::"r"(id), "r"(n) : "memory"); }
__device__ __forceinline__ void bar_arrive(int id, int n) { asm volatile("bar.arrive %0, %1;\n" ::"r"(id), "r"(n) : "memory"); }
__device__ __forceinline__ float quad_last(float v) {
    float r; asm volatile("shfl.sync.idx.b32 %0, %1, 3, 0x1c1f, -1;\n" : "=f"(r) : "f"(v)); return r;
}
__device__ __forceinline__ float ex2(float x) { float y; asm("ex2.approx.ftz.f32 %0, %1;\n" : "=f"(y) : "f"(x)); return y; }
__device__ __forceinline__ uint32_t ex2_f16(uint32_t x) { uint32_t y; asm("ex2.approx.f16x2 %0, %1;\n" : "=r"(y) : "r"(x)); return y; }
__device__ __forceinline__ uint32_t hmax2_f16(uint32_t a, uint32_t b) { uint32_t r; asm("max.f16x2 %0, %1, %2;\n" : "=r"(r) : "r"(a), "r"(b)); return r; }
__device__ __forceinline__ float rcp(float x) { float y; asm("rcp.approx.ftz.f32 %0, %1;\n" : "=f"(y) : "f"(x)); return y; }
__device__ __forceinline__ uint32_t pack_bf16(float lo, float hi) {
    uint32_t r; asm("cvt.rn.bf16x2.f32 %0, %1, %2;\n" : "=r"(r) : "f"(hi), "f"(lo)); return r;
}
__device__ __forceinline__ uint32_t pack_f16(float lo, float hi) {
    uint32_t r; asm("cvt.rn.f16x2.f32 %0, %1, %2;\n" : "=r"(r) : "f"(hi), "f"(lo)); return r;
}
__device__ __forceinline__ uint32_t pack_f16_sat(float lo, float hi) {
    uint32_t r; asm("cvt.rn.satfinite.f16x2.f32 %0, %1, %2;\n" : "=r"(r) : "f"(hi), "f"(lo)); return r;
}
__device__ __forceinline__ float f16_lo(uint32_t v) { float r; asm("cvt.f32.f16 %0, %1;\n" : "=f"(r) : "h"((unsigned short)v)); return r; }
__device__ __forceinline__ float f16_hi(uint32_t v) { return f16_lo(v >> 16); }
__device__ __forceinline__ float bf_lo(uint32_t v) { return __uint_as_float(v << 16); }
__device__ __forceinline__ float bf_hi(uint32_t v) { return __uint_as_float(v & 0xFFFF0000u); }
__device__ __forceinline__ float bf_round(float x) { return __uint_as_float(pack_bf16(0.f, x)); }
__device__ __forceinline__ void st_release(int* p, int v) {
    asm volatile("st.release.gpu.global.s32 [%0], %1;\n" ::"l"(p), "r"(v) : "memory");
}
__device__ __forceinline__ uint4 ldg_pinned(const uint4* p) {
    uint4 v; asm volatile("ld.global.nc.v4.u32 {%0, %1, %2, %3}, [%4];\n" : "=r"(v.x), "=r"(v.y), "=r"(v.z), "=r"(v.w) : "l"(p) : "memory"); return v;
}
__device__ __forceinline__ void stmatrix_x4(uint32_t addr, uint32_t r0, uint32_t r1, uint32_t r2, uint32_t r3) {
    asm volatile("stmatrix.sync.aligned.m8n8.x4.shared.b16 [%0], {%1, %2, %3, %4};\n" ::"r"(addr), "r"(r0), "r"(r1), "r"(r2), "r"(r3) : "memory");
}

__device__ __forceinline__ uint32_t tile_off(int r, int ch) {
    return (uint32_t)((r >> 3) * 4096 + (ch >> 3) * 1024 + (r & 7) * 128 + (((ch ^ r) & 7) << 4));
}
__device__ __forceinline__ int h_unit(int qt, int u) { return qt < 78 ? u * 78 + qt : 624; }
__device__ __forceinline__ int row_off(int r) { return 4096 + h_unit(r >> 7, (r >> 4) & 7) * 8192 + (r & 8) * 512 + (r & 7) * 144; }

__device__ __forceinline__ float4 lds128f(uint32_t a) {
    float4 v; asm volatile("ld.shared.v4.f32 {%0, %1, %2, %3}, [%4];\n" : "=f"(v.x), "=f"(v.y), "=f"(v.z), "=f"(v.w) : "r"(a) : "memory"); return v;
}
__device__ __forceinline__ uint64_t lds64(uint32_t a) { uint64_t v; asm volatile("ld.shared.u64 %0, [%1];\n" : "=l"(v) : "r"(a) : "memory"); return v; }
__device__ __forceinline__ uint4 lds128(uint32_t a) {
    uint4 v; asm volatile("ld.shared.v4.u32 {%0, %1, %2, %3}, [%4];\n" : "=r"(v.x), "=r"(v.y), "=r"(v.z), "=r"(v.w) : "r"(a) : "memory"); return v;
}
__device__ __forceinline__ void sts128(uint32_t a, uint32_t x, uint32_t y, uint32_t z, uint32_t w) {
    asm volatile("st.shared.v4.u32 [%0], {%1, %2, %3, %4};\n" ::"r"(a), "r"(x), "r"(y), "r"(z), "r"(w) : "memory");
}
__device__ __forceinline__ void mbar_arrive(uint32_t bar) {
    asm volatile("mbarrier.arrive.shared::cta.b64 _, [%0];\n" ::"r"(bar) : "memory");
}
__device__ __forceinline__ uint64_t mkaddr(uint32_t lo, uint32_t hi) { uint64_t a; asm("mov.b64 %0, {%1, %2};\n" : "=l"(a) : "r"(lo), "r"(hi)); return a; }
__device__ __forceinline__ void red_add(int* p) { asm volatile("red.relaxed.gpu.global.add.s32 [%0], 1;\n" ::"l"(p) : "memory"); }
__device__ __forceinline__ void red_release(int* p) {
    asm volatile("fence.proxy.async.global;\nfence.acq_rel.gpu;\nred.relaxed.gpu.global.add.s32 [%0], 1;\n" ::"l"(p) : "memory");
}
__device__ __forceinline__ void fence_async_global() { asm volatile("fence.proxy.async.global;\n" ::: "memory"); }
__device__ __forceinline__ void fence_async_smem() { asm volatile("fence.proxy.async.shared::cta;\n" ::: "memory"); }
__device__ __forceinline__ void bulk_s2g(void* dst, uint32_t src, uint32_t bytes) {
    asm volatile("cp.async.bulk.global.shared::cta.bulk_group [%0], [%1], %2;\ncp.async.bulk.commit_group;\n" ::"l"(dst), "r"(src), "r"(bytes) : "memory");
}
__device__ __forceinline__ void mma16816(float (&c)[4], uint32_t a0, uint32_t a1, uint32_t a2, uint32_t a3, uint32_t b0, uint32_t b1) {
    asm("mma.sync.aligned.m16n8k16.row.col.f32.bf16.bf16.f32 {%0, %1, %2, %3}, {%4, %5, %6, %7}, {%8, %9}, {%0, %1, %2, %3};\n"
        : "+f"(c[0]), "+f"(c[1]), "+f"(c[2]), "+f"(c[3]) : "r"(a0), "r"(a1), "r"(a2), "r"(a3), "r"(b0), "r"(b1));
}
__device__ __forceinline__ void mma1688(float (&c)[4], uint32_t a0, uint32_t a1, uint32_t b0) {
    asm("mma.sync.aligned.m16n8k8.row.col.f32.bf16.bf16.f32 {%0, %1, %2, %3}, {%4, %5}, {%6}, {%0, %1, %2, %3};\n"
        : "+f"(c[0]), "+f"(c[1]), "+f"(c[2]), "+f"(c[3]) : "r"(a0), "r"(a1), "r"(b0));
}
__device__ __forceinline__ uint32_t hadd2_f16(uint32_t a, uint32_t b) { uint32_t r; asm("add.rn.f16x2 %0, %1, %2;\n" : "=r"(r) : "r"(a), "r"(b)); return r; }
__device__ __forceinline__ uint32_t hadd2(uint32_t a, uint32_t b) { uint32_t r; asm("add.rn.bf16x2 %0, %1, %2;\n" : "=r"(r) : "r"(a), "r"(b)); return r; }
__device__ __forceinline__ uint32_t hmul2(uint32_t a, uint32_t b) { uint32_t r; asm("mul.rn.bf16x2 %0, %1, %2;\n" : "=r"(r) : "r"(a), "r"(b)); return r; }
__device__ __forceinline__ uint32_t hfma2(uint32_t a, uint32_t b, uint32_t c) { uint32_t r; asm("fma.rn.bf16x2 %0, %1, %2, %3;\n" : "=r"(r) : "r"(a), "r"(b), "r"(c)); return r; }

constexpr int SM_Q = 0;
constexpr int SM_KV = 65536;
constexpr int SM_ML = SM_KV + STAGES * KV_BYTES;
constexpr int SM_BAR = SM_ML + 1024;
constexpr int SM_TOTAL = SM_BAR + 256;
constexpr float SCALE_LOG2 = 1.4426950408889634f / 16.0f;
constexpr float KV_SCALE = 6.f;
constexpr float KV_OFF = 48.f;
constexpr uint32_t KV_OFF2 = 0x52005200u;
constexpr uint32_t KV_OFF8 = 0x5A005A00u;
constexpr uint32_t NEG2 = 0x80008000u;
constexpr uint32_t S_LIMIT = 0x4B804B80u;
constexpr float REF_UP = REFUP;
__device__ __forceinline__ uint32_t kvf(uint32_t a, uint32_t off) {
    uint32_t r; asm("fma.rn.f16x2 %0, %1, %2, %3;\n" : "=r"(r) : "r"(a), "r"(pack_f16(KV_SCALE, KV_SCALE)), "r"(off)); return r;
}
enum { BAR_PP0 = 1, BAR_PP1 = 2, BAR_WG0 = 3, BAR_WG1 = 4, BAR_H0 = 5, BAR_H1 = 6, BAR_AUX = 7, BAR_BF = 8, BAR_H2 = 9, BAR_X = 10, BAR_GO = 11, BAR_WG2 = 12, BAR_ST = 13 };

struct Hot {
    const __nv_bfloat16 *wk, *wq, *x;
    Scratch* s;
};
struct Params {
    const __nv_bfloat16* deg_inv;
    const int *src, *dst;
    __nv_bfloat16* out;
    uint32_t dhi;
    int E;
    CUtensorMap tm_out;
    CUtensorMap tm_outc;
    CUtensorMap tm_w[3];
};
static_assert(offsetof(Params, tm_outc) == offsetof(Params, tm_out) + 128, "layout");
#define SC_PAIR (blockIdx.x < 104)
#define SC_TAIL (blockIdx.x >= NCTA - 2)
#define SC_LAST (blockIdx.x == NCTA - 1)
#define SC_HELP (SC_PAIR && rank)
#define SC_OWNER (!SC_HELP && !SC_LAST)
#define SC_QT1 (26 + (int)(blockIdx.x >> 1))
#define SC_QT0 (SC_PAIR ? (rank ? (int)(blockIdx.x >> 2) : SC_QT1) : SC_TAIL ? 78 : (int)blockIdx.x - 104)
#define SC_NKV (SC_LAST ? 50 : 75)
#define SC_CLS (SC_PAIR ? (rank ? 0x120 ^ (blockIdx.x & 2) * 0x80 : 0x430) | (blockIdx.x & 2) >> 1 : SC_LAST ? 0x10 : 0x432)
#define SC_NW (SC_PAIR ? 8 : SC_LAST ? 0 : 4)
#define SC_ZB (2 * SC_QT1 + 1 - (int)rank)
#define SC_TZB(k) (rank && !(k) ? 156 : 2 * (k) - (int)rank)

__global__ void __cluster_dims__(2, 1, 1) __launch_bounds__(384, 1) k_main(const __grid_constant__ Hot H, const __grid_constant__ Params P) {
    extern __shared__ __align__(1024) uint8_t smem[];
    const uint32_t sb = (uint32_t)__cvta_generic_to_shared(smem);
    const int tid = threadIdx.x, wg = __shfl_sync(~0u, tid >> 7, 0);
    const int lane = tid & 31, g = lane >> 2, q = lane & 3;
    const uint32_t rank = blockIdx.x & 1;
    const uint32_t bar_full = sb + SM_BAR, bar_q = bar_full + 32, bar_go = bar_full + 48;
    const uint32_t bar_pin = bar_full + 56;
    const uint32_t bar_qfree = bar_full + 72, bar_pdone = bar_full + 88, bar_zst = bar_full + 104, bar_rfree = bar_full + 120;
    const uint32_t bar_empty = bar_full + 128, bar_end = bar_full + 160, s_tm = bar_full + 184, bar_x = bar_full + 192;
    const uint32_t bar_a = sb + SM_ML;

    const int t = tid & 127, warp = __shfl_sync(~0u, t >> 5, 0);
    int ep = 0;
    if (wg & 2) {
        unsigned done;
        {
            uint4 ra[2], rb[2], rk[5][2];
            if (blockIdx.x < 128) {
                const int e = (blockIdx.x >> 4) * 32 + (g >> 1) * 8 + (blockIdx.x & 8) / 2 + (g & 1);
                const uint4* pq = (const uint4*)(H.wq + e * 256) + warp * 8 + q;
                const uint4* pk = (const uint4*)(H.wk + ((blockIdx.x & 7) * 32 + g) * 256) + warp * 8 + q;
                const uint4* pz = (const uint4*)(H.wk + 255 * 256) + warp * 8 + q;
#pragma unroll
                for (int s = 0; s < 2; s++) {
                    ra[s] = ldg_pinned(pq + 4 * s);
                    rb[s] = ldg_pinned(pq + 4 * s + 64);
#pragma unroll
                    for (int n = 0; n < 4; n++) rk[n][s] = ldg_pinned(pk + 4 * s + n * 256);
                    rk[4][s] = ldg_pinned(pz + 4 * s);
                }
            }
            asm volatile("{\n.reg .pred p;\nsetp.eq.s32 p, %2, 0;\nmov.u32 %0, 0;\n@p ld.global.cg.u32 %0, [%1];\n}\n" : "=r"(done) : "l"(&g_sync[SY_DONE * 32]), "r"(lane) : "memory");
            bar_arrive(BAR_X, 384);
            if (warp == 0 && elect()) {
#pragma unroll
                for (int i = 0; i < 21; i++) mbar_init(bar_full + 8 * i, i < 9 ? 1 : i < 16 ? 4 : i == 20 ? 11 : SC_TAIL ? 4 : 8);
#pragma unroll
                for (int i = 0; i < 4; i++) mbar_init(bar_a + 8 * i, 1);
                mbar_expect_tx(bar_pin, QB_BYTES / 2 + 512); mbar_expect_tx(bar_pin + 8, QB_BYTES / 2);
                asm volatile("fence.mbarrier_init.release.cluster;\n" ::: "memory");
            }
            __syncwarp();
            asm volatile("barrier.cluster.arrive.relaxed.aligned;\n" ::: "memory");
            if (blockIdx.x < 128) {
                float c[5][4] = {};
#pragma unroll
                for (int s = 0; s < 2; s++) {
#pragma unroll
                    for (int n = 0; n < 5; n++) mma16816(c[n], ra[s].x, rb[s].x, ra[s].y, rb[s].y, rk[n][s].x, rk[n][s].y);
#pragma unroll
                    for (int n = 0; n < 5; n++) mma16816(c[n], ra[s].z, rb[s].z, ra[s].w, rb[s].w, rk[n][s].z, rk[n][s].w);
                }
#pragma unroll
                for (int i = 0; i < 4; i++) {
                    const int r = i & 2, n = (i & 1) * 2;
                    sts128(sb + SM_KV + 3 * KV_BYTES + QB_BYTES + i * 2048 + t * 16, __float_as_uint(c[n][r] - c[4][r]), __float_as_uint(c[n][r + 1] - c[4][r]),
                           __float_as_uint(c[n + 1][r] - c[4][r]), __float_as_uint(c[n + 1][r + 1] - c[4][r]));
                }
            }
        }
        asm volatile("setmaxnreg.dec.sync.aligned.u32 %0;\n" ::"n"(REG_P));
        if (blockIdx.x < 128) {
            bar_sync(BAR_WG2, 128);
            float4 v[4];
#pragma unroll
            for (int i = 0; i < 4; i++) v[i] = lds128f(sb + SM_KV + 3 * KV_BYTES + QB_BYTES + (warp & 2) * 2048 + (lane & 1) * 2048 + i * 512 + ((warp & 1) * 16 + (lane >> 1)) * 16);
            constexpr float SC = SCALE_LOG2 / KV_SCALE;
            const int r = (warp & 1) * 4 + (lane >> 3);
            *(uint2*)(g_w + tile_off((blockIdx.x >> 3) * 16 + (warp & 2) * 4 + r, (blockIdx.x & 7) * 4 + ((lane >> 1) & 3)) + (lane & 1) * 8) =
                make_uint2(pack_f16_sat(((v[0].x + v[1].x) + (v[2].x + v[3].x)) * SC, ((v[0].y + v[1].y) + (v[2].y + v[3].y)) * SC) | 1,
                           pack_f16_sat(((v[0].z + v[1].z) + (v[2].z + v[3].z)) * SC, ((v[0].w + v[1].w) + (v[2].w + v[3].w)) * SC) | 1);
            if (warp != 1) {
                bar_arrive(BAR_AUX, 128);
            } else {
                bar_sync(BAR_AUX, 128);
                if (elect()) { red_add(&g_sync[SY_DONE * 32 + 4 + (blockIdx.x >> 5)]); }
                __syncwarp();
            }
        }
        else bar_sync(BAR_WG2, 128);
        if (warp == 1) bar_arrive(BAR_GO, 160);
        auto load_a = [&](int j) {
            if (elect()) {
                mbar_expect_tx(bar_a + 8 * j, QB_BYTES);
                bulk_g2s(sb + SM_KV + j * KV_BYTES, g_w + j * QB_BYTES, QB_BYTES, bar_a + 8 * j);
            }
            __syncwarp();
        };
        if (warp == 0) {
            auto poll = [&]() { int c; asm volatile("ld.relaxed.gpu.global.s32 %0, [%1];\n" : "=r"(c) : "l"(&g_sync[SY_DONE * 32 + 4 + (lane & 3)]) : "memory"); return c; };
#pragma unroll 1
            for (int j = 0; j < 4;) {
#pragma unroll 1
                for (const uint32_t mk = __ballot_sync(~0u, poll() >= 32) & 15; (mk >> j) & 1; j++) load_a(j);
            }
        } else if (warp & 1) {
#pragma unroll 1
            for (int j = 0, n = 0; j < 4;) {
                mbar_wait_bounded(bar_a + 8 * j, n & 1);
                uint32_t ok = 1;
#pragma unroll
                for (int i = 0; i < 16; i++) {
                    uint32_t v;
                    asm volatile("ld.shared.u32 %0, [%1];\n" : "=r"(v) : "r"(sb + SM_KV + j * KV_BYTES + (warp & 2) * 8192 + i * 1024 + lane * 32 + g * 4) : "memory");
                    ok &= v;
                }
                asm volatile("{\n.reg .pred p;\nsetp.ne.u32 p, %0, 0;\nbar.red.and.pred p, %1, 64, p;\nselp.u32 %0, 1, 0, p;\n}\n" : "+r"(ok) : "n"((int)BAR_WG2) : "memory");
                if (__any_sync(~0u, ok)) {
                    if (warp == 1 && elect()) asm volatile("mbarrier.arrive.shared::cta.b64 _, [%0];\nmbarrier.inval.shared::cta.b64 [%1];\n" ::"r"(bar_full + 8 * j), "r"(bar_a + 8 * j) : "memory");
                    __syncwarp();
                    j++; n = 0;
                } else {
                    asm volatile("{\n.reg .pred p;\nsetp.gt.s32 p, %0, 1000000;\n@p trap;\n}\n" ::"r"(++n) : "memory");
                    fence_async_smem();
                    if (warp == 1) load_a(j);
                }
            }
        }
        done = __shfl_sync(~0u, done, 0);
        ep = (int)(done / NCTA) + 1;
        asm volatile("barrier.cluster.wait.acquire.aligned;\n" ::: "memory");
        if (warp == 0) {
            asm volatile("st.shared.u64 [%0], %1;\n" ::"r"(s_tm), "l"(&P.tm_outc) : "memory");
            __syncwarp();
            if (elect()) {
                const uint8_t* base = (const uint8_t*)H.s;
                uint32_t cls = SC_CLS, bytes = KV_BYTES, step = 5 * KV_BYTES;
                const uint8_t* src = base;
                bool tick;
                int next = 0;
                const int nit = SC_NKV + SC_NW;
#pragma unroll 1
                for (int j = 0; j < nit; j++) {
                    const uint32_t slot = sb + SM_KV + (j & 3) * KV_BYTES, fb = bar_full + 8 * (j & 3);
                    if (j == next) {
                        const int k = j - SC_NKV;
                        const int sw = SC_HELP ? j - 25 : -1;
                        next = j + 1;
                        tick = j >= 3 && k < 0 && (unsigned)sw >= 4 && !SC_TAIL;
                        if (j >= 3 && (unsigned)sw >= 5) next = k >= 0 ? next : j < GO0 ? GO0 : j < 25 ? 25 : j < GO1 ? GO1 : j < 49 ? 49 : j < 50 ? 50 : 75;
                        if (j == 0 || j == 25 || j == 50) { src = base + (4096 + (cls & 15) * KV_BYTES); cls >>= 4; }
                        if (SC_TAIL ? j == nit - 1 : j == GO0 || j == GO1) mbar_arrive(bar_go);
                        int fo = -1, fv = 1;
                        if (j < 3) { fo = (SY_H0 + 5 * j + (SC_CLS & 15)) * 32; fv = 5; }
                        if (j == 3) { fo = SY_H1 * 32; fv = 79; }
                        if (sw == 1) fo = 25 * 32 + SC_QT1;
                        if (k == 0) fo = SY_B * 32;
                        if (k == 1 && !SC_PAIR) { fo = SY_AUX0 * 32; fv = NAUX; }
                        if (k == 2 && SC_PAIR) { fo = SY_AUX * 32; fv = NAUX / 3; }
                        if (fo >= 0) {
                            flag_wait(g_sync + fo, fv * ep);
                            fence_async_global();
                        }
                        if (sw == 2 || (k == 2 && !SC_TAIL)) {
                            uint32_t qs = sw == 2 ? offsetof(Scratch, q) + (2 * SC_QT1 + 1) * QB_BYTES : SC_PAIR ? offsetof(Scratch, agg) + SC_ZB * QB_BYTES : offsetof(Scratch, part) + SC_QT0 * (4 * PART_BYTES);
#pragma unroll 1
                            for (int w = 0; w < (k == 2 && SC_PAIR ? 1 : 2); w++) {
                                mbar_wait_sleep(bar_qfree + 8 * w, k == 2 && SC_HELP);
                                mbar_expect_tx(bar_q + 8 * w, SC_PAIR ? QB_BYTES : PART_BYTES);
                                if (!SC_PAIR) bulk_g2s(sb + SM_ML + w * 512, base + (qs + (w ? -512 : QB_BYTES)), 512, bar_q + 8 * w);
                                bulk_g2s(sb + SM_Q + w * QB_BYTES, base + qs, QB_BYTES, bar_q + 8 * w);
                                qs += sw == 2 ? -QB_BYTES : PART_BYTES + 512;
                            }
                        }
                        if ((sw | 1) == 3) {
                            mbar_wait_sleep(bar_pdone + 8 * (sw - 2), 0);
                            bulk_s2g(g_part + (blockIdx.x - 3 + sw) * PART_BYTES, slot, PART_BYTES);
                            asm volatile("cp.async.bulk.wait_group.read 0;\n" ::: "memory");
                        }
                        if (sw == 5) {
                            asm volatile("cp.async.bulk.wait_group 0;\n" ::: "memory");
                            red_release(&g_sync[SY_PART * 32]);
                        }
                        if (k == 0) {
                            asm volatile("prefetch.tensormap [%0];\n" ::"l"(&P.tm_outc) : "memory");
                            src = g_w + (12 - SC_NW) * QB_BYTES; bytes = step = QB_BYTES;
                        }
                        if (k == 2) next = SC_TAIL ? nit - 1 : nit;
                    }
                    mbar_wait_sleep(fb + (bar_empty - bar_full), (j >> 2) & 1);
                    mbar_expect_tx(fb, bytes);
                    if (tick)
                        asm volatile("{\n.reg .pred p;\n.reg .u32 a, b;\nmov.u32 a, %%globaltimer_lo;\nnot.b32 b, a;\nand.b32 b, b, %0;\nshr.u32 b, b, 1;\nnanosleep.u32 b;\n"
                                     "L:\nmov.u32 b, %%globaltimer_lo;\nxor.b32 b, b, a;\nsetp.le.u32 p, b, %0;\n@p nanosleep.u32 %1;\n@p bra L;\n}\n" ::"n"(TICK - 1), "n"(TSL) : "memory");
                    bulk_g2s(slot, src, bytes, fb);
                    src += step;
                }
            }
        } else {
            if (warp == 2 && SC_OWNER) {
                uint8_t* dst = g_hz + 4096 + h_unit(SC_QT0, 0) * 8192;
                auto send = [&](int u0, int u1) {
#pragma unroll
                    for (int u = u0; u < u1; u++) {
                        bulk_s2g(dst + u * (78 * 8192), sb + SM_Q + u * 8192, 8192);
                        asm volatile("cp.async.bulk.wait_group 0;\n" ::: "memory");
                    }
                };
                int* f0 = &g_sync[(SY_H0 + SC_QT0 / 5) * 32];
                bar_sync(BAR_H0, 64);
                if (elect()) {
                    send(0, 1);
                    if (SC_QT0 < 65) red_release(f0);
                }
                bar_sync(BAR_H1, 160);
                if (elect()) {
                    if (!SC_TAIL) send(1, 4);
                    mbar_arrive(bar_q);
                }
                bar_sync(BAR_H2, 160);
                if (elect()) {
                    if (!SC_TAIL) { send(4, 8); mbar_arrive(bar_q + 8); }
                    red_release(&g_sync[SY_H1 * 32]);
                }
                __syncwarp();
            }
        }
    } else {
        const uint32_t sq = sb + SM_Q + wg * QB_BYTES;
        const uint32_t qbar = bar_q + 8 * wg;
        const uint32_t dq0 = __shfl_sync(~0u, ((sq & 0x3FFFF) >> 4) | (64u << 16), 0);
        const uint32_t dk0 = __shfl_sync(~0u, (((sb + SM_KV) & 0x3FFFF) >> 4) | (64u << 16), 0);
        float o[128];
        int it = 4;
        const uint32_t dhi = P.dhi;
        auto release = [&](int st, int n = 1) {
            if (n == 1) asm volatile("{\n.reg .pred p;\nelect.sync _|p, -1;\n@p mbarrier.arrive.shared::cta.b64 _, [%0];\n}\n" ::"r"(bar_empty + 8 * st) : "memory");
            else asm volatile("{\n.reg .pred p;\nelect.sync _|p, -1;\n@p mbarrier.arrive.shared::cta.b64 _, [%0], 2;\n}\n" ::"r"(bar_empty + 8 * st) : "memory");
        };
        const bool active = !(SC_TAIL && wg == 1);
        auto pp_sync = [&]() { if (!SC_TAIL) bar_sync(BAR_PP0 + wg, 256); };
        auto pp_arrive = [&]() { if (!SC_TAIL) bar_arrive(BAR_PP1 - wg, 256); };
        auto warp_arrive = [&](uint32_t bar) {
            __syncwarp();
            asm volatile("{\n.reg .pred p;\nelect.sync _|p, -1;\n@p mbarrier.arrive.shared::cta.b64 _, [%0];\n}\n" ::"r"(bar + 8 * wg) : "memory");
        };
        auto peer_arrive = [&]() {
            asm volatile("{\n.reg .pred p;\n.reg .b32 a;\nelect.sync _|p, -1;\nmapa.shared::cluster.u32 a, %0, %1;\n"
                         "@p mbarrier.arrive.shared::cluster.b64 _, [a];\n}\n" ::"r"(bar_rfree), "r"(rank ^ 1) : "memory");
        };
        auto cut = [&]() { asm volatile("{\n.reg .pred p;\nsetp.lt.s32 p, %0, 0;\nL:\n@p pmevent 0;\n@p bra L;\n}\n" ::"r"(dhi) : "memory"); };
        float qs = 1.f;
        uint32_t qr[4 * NQR];
        auto stage_q = [&]() {
            int k = dhi & 1;
            uint32_t big;
#pragma unroll 1
            do {
                if (k) {
                    qs *= 16.f;
#pragma unroll
                    for (int i = 0; i < 128; i++) o[i] *= 0.0625f;
                }
                big = 0;
                auto pk = [&](int i) { return QRND(pack_f16_sat(o[i], o[i + 1])); };
#pragma unroll
                for (int i = 0; i < 16; i++) {
                    if (QREG(i) >= 0) continue;
                    const uint32_t v0 = pk(8 * i), v1 = pk(8 * i + 2), v2 = pk(8 * i + 4) | (i == 15 ? k : 0), v3 = pk(8 * i + 6);
                    stmatrix_x4(sq + warp * 8192 + tile_off(lane & 15, 2 * i + (lane >> 4)), v0, v1, v2, v3);
                    big |= v0 | v1; big |= v2 | v3;
                    if (i == 15) cut();
                }
#pragma unroll
                for (int i = 0; i < 64; i++)
                    if (const int r = QREG(i / 4); r >= 0) big |= qr[4 * r + (i & 3)] = pk(2 * i);
                k++;
            } while (__any_sync(~0u, (big & 0x40004000u) && k < 8));
        };
        uint32_t s[20];
        auto issue_qk = [&](int st, int sh = 24) {
            const uint64_t kb = mkaddr(dk0 + st * (KV_BYTES >> 4), dhi);
            const uint64_t qd = mkaddr(dq0 + ((uint32_t)it >> sh), dhi);
            wgmma_ss_n80_init(s, qd, kb);
#pragma unroll
            for (int j = 1; j < 16; j++) {
                const int kk = j == 8 ? 15 : j < 8 ? j : j - 1;
                const int r = QREG(kk);
                if (r >= 0) wgmma_rs_n80(s, qr[4 * r], qr[4 * r + 1], qr[4 * r + 2], qr[4 * r + 3], kb + ((kk >> 2) * 64 + (kk & 3) * 2));
                else wgmma_ss_n80(s, qd + ((kk >> 2) * 64 + (kk & 3) * 2), kb + ((kk >> 2) * 64 + (kk & 3) * 2));
            }
            wg_commit();
        };

        {
            const int rb = (2 * SC_QT0 + wg) * 64 + warp * 16;
            const uint32_t xbar = bar_x + 32 * wg + 8 * warp;
            if (elect()) {
                mbar_init(xbar, 1);
                asm volatile("fence.mbarrier_init.release.cluster;\nfence.proxy.async.shared::cta;\n" ::: "memory");
                mbar_expect_tx(xbar, rb < NN ? 8192 : 0);
            }
            asm volatile("barrier.cluster.arrive.relaxed.aligned;\n" ::: "memory");
            if (wg == 1) pp_arrive();
            bar_sync(BAR_X, 384);
            if (wg == 1) bar_sync(BAR_GO, 160);
            if (rb < NN && elect()) bulk_g2s(sq + warp * 8192, H.x + (size_t)rb * 256, 8192, xbar);
            if (rb >= NN) {
#pragma unroll 1
                for (int i = 0; i < 16; i++) sts128(sq + warp * 8192 + i * 512 + lane * 16, 0, 0, 0, 0);
            }
            __syncwarp();
            mbar_wait(xbar, 0);
            uint4 xa[8], xb[8];
#pragma unroll
            for (int s = 0; s < 8; s++) {
                xa[s] = lds128(sq + (warp * 16 + g) * 512 + (4 * s + q) * 16);
                xb[s] = lds128(sq + (warp * 16 + g + 8) * 512 + (4 * s + q) * 16);
            }
            float sm[2][4], sq2[2][4][4];
#pragma unroll
            for (int i = 0; i < 4; i++) {
                sm[0][i] = sm[1][i] = 0.f;
#pragma unroll
                for (int k = 0; k < 4; k++) sq2[0][k][i] = sq2[1][k][i] = 0.f;
            }
#pragma unroll
            for (int s = 0; s < 8; s++) {
#pragma unroll
                for (int hh = 0; hh < 2; hh++) {
                    const uint4 v = hh ? xb[s] : xa[s];
                    mma16816(sm[hh], v.x, v.y, v.z, v.w, 0x3F803F80u, 0x3F803F80u);
                    mma1688(sq2[hh][0], v.x, v.y, v.x); mma1688(sq2[hh][1], v.x, v.y, v.y);
                    mma1688(sq2[hh][2], v.z, v.w, v.z); mma1688(sq2[hh][3], v.z, v.w, v.w);
                }
            }
            float inv[2], off[2];
#pragma unroll
            for (int hh = 0; hh < 2; hh++) {
                const float mean = (sm[hh][0] + sm[hh][2]) * (1.f / 256.f);
                const float d0 = (sq2[hh][0][0] + sq2[hh][2][0]) + (sq2[hh][1][2] + sq2[hh][3][2]);
                const float d1 = (sq2[hh][0][1] + sq2[hh][2][1]) + (sq2[hh][1][3] + sq2[hh][3][3]);
                const float ss = __shfl_sync(~0u, (g & 1) ? d1 : d0, g * 4 + (g >> 1));
                const float var = fmaxf(ss * (1.f / 256.f) - mean * mean, 0.f);
                float sd;
                asm("sqrt.approx.ftz.f32 %0, %1;\n" : "=f"(sd) : "f"(bf_round(bf_round(var) + 1e-5f)));
                asm("rcp.approx.ftz.f32 %0, %1;\n" : "=f"(inv[hh]) : "f"(bf_round(sd)));
                off[hh] = -mean * inv[hh];
            }
            uint32_t a[64];
#pragma unroll
            for (int s = 0; s < 8; s++) {
                a[8 * s] = xa[s].x; a[8 * s + 1] = xb[s].x; a[8 * s + 2] = xa[s].y; a[8 * s + 3] = xb[s].y;
                a[8 * s + 4] = xa[s].z; a[8 * s + 5] = xb[s].z; a[8 * s + 6] = xa[s].w; a[8 * s + 7] = xb[s].w;
            }
            fence_regs(a);
            if (wg == 1 && __any_sync(~0u, inv[0] + inv[1] != -1.f)) bar_arrive(BAR_ST, 256);
            asm volatile("setmaxnreg.inc.sync.aligned.u32 %0;\n" ::"n"(REG_C));
            fence_regs(a);
#pragma unroll
            for (int i = 0; i < 64; i++)
                a[i] = pack_f16(fmaf(bf_lo(a[i]), inv[i & 1], off[i & 1]), fmaf(bf_hi(a[i]), inv[i & 1], off[i & 1]));
            if (SC_OWNER) {
                const uint32_t ko = (q & 2) ? KV_OFF2 : KV_OFF2 | NEG2;
#pragma unroll
                for (int i = 0; i < 16; i++) {
                    const uint32_t mk = (i == 15 && q == 3) ? 0xFFFFu : ~0u;
                    stmatrix_x4(sq + warp * 8192 + tile_off(lane & 15, 2 * i + (lane >> 4)), kvf(a[4 * i], ko), kvf(a[4 * i + 1], ko),
                                kvf(a[4 * i + 2] & mk, ko), kvf(a[4 * i + 3] & mk, ko));
                }
                fence_async_smem();
                if (tid < 32) bar_arrive(BAR_H0, 64);
                bar_arrive(wg ? BAR_H2 : BAR_H1, 160);
            }
            asm volatile("barrier.cluster.wait.acquire.aligned;\n" ::: "memory");
            if (wg == 0) bar_sync(BAR_ST, 256);
            if (active) {
                fence_regs(a);
#pragma unroll
                for (int c = 0; c < 4; c++) {
                    if (c == 1) {
                        if (wg == 1) {
                            wg_wait<0>();
                            release(0);
                        }
                        pp_sync();
                    }
                    mbar_wait(bar_full + 8 * c, 0);
                    const uint64_t wb = mkaddr(dk0 + c * (KV_BYTES >> 4), dhi);
                    wg_fence();
#pragma unroll
                    for (int kk = 0; kk < 4; kk++) {
                        if (c | kk) wgmma_rs_n256_tb(o, a[16 * c + 4 * kk], a[16 * c + 4 * kk + 1], a[16 * c + 4 * kk + 2], a[16 * c + 4 * kk + 3], wb + kk * 512);
                        else wgmma_rs_n256_tb_init(o, a[0], a[1], a[2], a[3], wb);
                    }
                    wg_commit();
                    if (c > 0) { wg_wait<1>(); if (c > 1 || wg == 0) release(c - 1); }
                }
                if (wg == 0) pp_arrive();
                wg_wait<0>();
                fence_regs(o);
                release(3);
                if (SC_OWNER) mbar_wait(qbar, 0);
                stage_q();
                fence_async_smem();
                bar_sync(BAR_WG0 + wg, 128);
                mbar_wait(bar_full, 1);
                wg_fence();
                issue_qk(0);
                if (wg == 1) pp_arrive();
                if (SC_PAIR && !rank) {
#pragma unroll
                    for (int i = 0; i < 16; i++)
                        if (const int r = QREG(i); r >= 0)
                            stmatrix_x4(sq + warp * 8192 + tile_off(lane & 15, 2 * i + (lane >> 4)), qr[4 * r], qr[4 * r + 1], qr[4 * r + 2], qr[4 * r + 3]);
                }
            } else {
                peer_arrive();
            }
        }

        uint32_t p[20];
        float m0 = 0.f, m1 = 0.f, e0, e1, l0, l1;
        uint32_t plim;
        uint32_t qphase = (SC_OWNER && active) ? 1 : 0;
        auto issue_pv = [&](int st, int acc) {
            const uint64_t vb = mkaddr(dk0 + st * (KV_BYTES >> 4), dhi);
            wgmma_rs_n256_tb_pred(o, p[0], p[1], p[2], p[3], vb, acc);
#pragma unroll
            for (int kk = 1; kk < 5; kk++)
                wgmma_rs_n256_tb(o, p[4 * kk], p[4 * kk + 1], p[4 * kk + 2], p[4 * kk + 3], vb + kk * 512);
            wg_commit();
        };
        auto mq_addr = [&](int ln) { return sq + warp * 8192 + tile_off(ln >> 2, 31) + 12; };
        auto exceeds = [&](const uint32_t (&p)[20]) {
            uint32_t a = __vimax3_s16x2(S_LIMIT, p[0], p[1]), b = __vimax3_s16x2(p[2], p[3], p[4]);
#pragma unroll
            for (int i = 5; i < 17; i += 4) { a = __vimax3_s16x2(a, p[i], p[i + 1]); b = __vimax3_s16x2(b, p[i + 2], p[i + 3]); }
            a = __vimax3_s16x2(a, p[17], p[18]);
            return __any_sync(~0u, __vimax3_s16x2(a, b, p[19]) != plim);
        };
        auto remax = [&](float& a, float& b, bool store) {
            const int ln = lane_now();
            asm volatile("" : "+f"(qs));
            uint32_t ha = s[0], hb = s[1];
#pragma unroll
            for (int i = 1; i < 10; i++) { ha = hmax2_f16(ha, s[2 * i]); hb = hmax2_f16(hb, s[2 * i + 1]); }
            ha = hmax2_f16(__byte_perm(ha, hb, 0x5410), __byte_perm(ha, hb, 0x7632));
            ha = hmax2_f16(ha, __shfl_xor_sync(~0u, ha, 1));
            ha = hmax2_f16(ha, __shfl_xor_sync(~0u, ha, 2));
            a = fmaxf(a, f16_lo(ha) * qs - e0 + REF_UP); b = fmaxf(b, f16_hi(ha) * qs - e1 + REF_UP);
            const float qi = __uint_as_float(0x7F000000u - __float_as_uint(qs)) * (-1.f / KV_OFF);
            const uint32_t u = pack_f16((m0 + a) * qi, (m1 + b) * qi);
            const float g0 = (m0 + a) + KV_OFF * qs * f16_lo(u), g1 = (m1 + b) + KV_OFF * qs * f16_hi(u);
            const bool x0 = fabsf(g0) <= 1.f, x1 = fabsf(g1) <= 1.f;
            if (x0) a -= g0;
            if (x1) b -= g1;
            const float da = a + e0, db = b + e1;
            m0 += a; m1 += b;
            e0 = x0 ? 0.f : g0; e1 = x1 ? 0.f : g1;
            plim = (x0 && x1 && qs == 1.f) ? S_LIMIT : 0u;
            asm volatile("{\n.reg .pred p;\nsetp.ne.s32 p, %3, 0;\n@p st.shared.u16 [%0], %1;\n@p st.shared.u16 [%0 + 4096], %2;\n}\n"
                         ::"r"(mq_addr(ln) + 2), "h"((unsigned short)u), "h"((unsigned short)(u >> 16)), "r"((int)(store && (ln & 3) == 0)) : "memory");
#pragma unroll
            for (int i = 0; i < 10; i++) {
                p[2 * i] = pack_f16(ex2(fmaf(f16_lo(s[2 * i]), qs, -da)), ex2(fmaf(f16_hi(s[2 * i]), qs, -da)));
                p[2 * i + 1] = pack_f16(ex2(fmaf(f16_lo(s[2 * i + 1]), qs, -db)), ex2(fmaf(f16_hi(s[2 * i + 1]), qs, -db)));
            }
            fence_regs(p);
            fence_async_smem();
            __syncwarp();
        };

        auto row_sums = [&](float& z0, float& z1, int q) {
            z0 = quad_last(o[125]); z1 = quad_last(o[127]);
            l0 = z0 * (KV_SCALE / KV_OFF); l1 = z1 * (KV_SCALE / KV_OFF);
            if (!(q & 2)) { z0 = -z0; z1 = -z1; }
        };
        auto stats = [&](int q) { return (q & 2) ? ((q & 1) ? l1 : m1) : ((q & 1) ? l0 : m0); };
        const int nseg = SC_HELP ? 2 : 1;
        if (active) {
#pragma unroll 1
        for (int seg = 0;; seg++) {
            wg_wait<0>();
            fence_regs(s);
            e0 = e1 = 0.f;
            const int it0 = it, itl = __shfl_sync(~0u, seg + 1 < nseg ? 3 + 25 : 3 + SC_NKV, 0);
            const int itx = (wg == 1 && seg + 1 == nseg) ? itl : -1;
            bool redo = true, have = !seg;
#pragma unroll 1
            for (;;) {
                if (!have) {
#pragma unroll
                    for (int i = 0; i < 20; i++) p[i] = ex2_f16(s[i]);
                    redo = exceeds(s);
                }
                if (redo) {
                    float d0 = it != it0 ? 0.f : -INFINITY, d1 = d0;
                    remax(d0, d1, it != itl);
                    if (it != it0) {
                        const float a0 = ex2(-d0), a1 = ex2(-d1);
#pragma unroll
                        for (int i = 0; i < 32; i++) { o[4 * i] *= a0; o[4 * i + 1] *= a0; o[4 * i + 2] *= a1; o[4 * i + 3] *= a1; }
                    } else if (SC_OWNER) {
                        warp_arrive(bar_pdone);
                    }
                }
                if (it == itl) break;
                const int stp = it & 3;
                it++;
                pp_sync();
                fence_regs(o); fence_regs(p);
                have = SC_TAIL || it == itx;
                if (!have) {
                    wg_fence();
                    issue_pv(stp, it - 1 - it0);
                    mbar_wait(bar_full + 8 * (it & 3), (it >> 2) & 1);
                    wg_fence();
                    issue_qk(it & 3);
                    pp_arrive();
                    wg_wait<0>();
                    fence_regs(s); fence_regs(o); fence_regs(p);
                    if (it == itl) warp_arrive(bar_qfree);
                } else {
                    const int zero = (uint32_t)it >> 23;
                    mbar_wait(bar_full + 8 * (it & 3), (it >> 2) & 1);
                    wg_fence();
                    issue_qk((it & 3) + zero, 25);
                    if (it == itl) {
                        wg_wait<0>();
                        if (SC_PAIR) peer_arrive(); else warp_arrive(bar_qfree);
                        if (wg) bar_sync(BAR_ST, 256);
                    }
                    wg_fence();
                    issue_pv(stp + zero, it - 1 - it0);
                    pp_arrive();
                    wg_wait<1>();
                    fence_regs(s);
                    redo = exceeds(s);
                    if (!redo) {
#pragma unroll
                        for (int i = 0; i < 20; i++) s[i] = ex2_f16(s[i]);
                        fence_regs(s);
                        cut();
                    }
                    wg_wait<0>();
                    fence_regs(o); fence_regs(p);
#pragma unroll
                    for (int i = 0; i < 20; i++) p[i] = s[i];
                }
                release(stp);
            }
            if (seg + 1 < nseg) pp_sync();
            fence_regs(o); fence_regs(p);
            wg_fence();
            issue_pv(it & 3, 1);
            asm volatile("{\n.reg .pred p;\nsetp.ne.s32 p, %0, 0;\n@p bar.arrive %1, 256;\n}\n" ::"r"((int)(seg + 1 == nseg && (wg ? SC_PAIR : !SC_TAIL))), "r"(BAR_ST + wg) : "memory");
            it++;
            if (seg + 1 == nseg) break;
            constexpr int IS = 4 + 25;
            const int ln = lane_now();
            uint32_t qa = sq + warp * 8192 + tile_off(ln & 15, ln >> 4);
            asm volatile("" : "+r"(qa));
            mbar_wait(bar_full + 8 * (IS & 3), (IS >> 2) & 1);
            mbar_wait(qbar, 0); qphase = 1;
#pragma unroll
            for (int i = 0; i < 16; i++)
                if (const int r = QREG(i); r >= 0)
                    asm volatile("ldmatrix.sync.aligned.m8n8.x4.shared.b16 {%0, %1, %2, %3}, [%4];\n" : "=r"(qr[4 * r]), "=r"(qr[4 * r + 1]), "=r"(qr[4 * r + 2]), "=r"(qr[4 * r + 3])
                                 : "r"((qa ^ (i & 3) * 32) + (i >> 2) * 1024) : "memory");
            fence_regs(qr);
            wg_fence();
            issue_qk(it & 3);
            wg_wait<1>();
            pp_arrive();
            fence_regs(o);
            float z0, z1;
            row_sums(z0, z1, ln);
            release((IS - 1) & 3);
            uint32_t u0, u1;
            asm volatile("ld.shared.u32 %0, [%2];\nld.shared.u32 %1, [%2 + 4096];\n" : "=r"(u0), "=r"(u1) : "r"(mq_addr(ln)) : "memory");
            const uint32_t slot = sb + SM_KV + ((IS - 2 + wg) & 3) * KV_BYTES;
            const uint32_t dst = slot + wg * 512 + warp * 8192 + ln * 16, dml = slot + (wg ? 0 : QB_BYTES) + warp * 128 + ln * 4;
#pragma unroll
            for (int i = 0; i < 128; i++) o[i] -= (i & 2) ? z1 : z0;
            fence_regs(o);
            mbar_wait(bar_empty + 8 * ((IS - 2 + wg) & 3), ((IS - 2 + wg) >> 2) & 1);
            asm volatile("st.shared.f32 [%0], %1;\n" ::"r"(dml), "f"(stats(ln)) : "memory");
            qs = __uint_as_float(0x3F800000u + ((u0 & 7) << 25));
            m0 = -KV_OFF * qs * f16_hi(u0); m1 = -KV_OFF * qs * f16_hi(u1);
            plim = fmaxf(fabsf(m0), fabsf(m1)) <= 3072.f && qs == 1.f ? S_LIMIT : 0u;
            uint32_t v[2][8] = {};
#pragma unroll
            for (int i = 0; i < 8; i++) {
                uint32_t *w = v[i & 1], *u = v[(i & 1) ^ 1];
#pragma unroll
                for (int j = 0; j < 8; j++) w[j] = pack_bf16(o[16 * i + 2 * j], o[16 * i + 2 * j + 1]);
                sts128(dst + i * 1024, w[0], w[1], w[2], w[3]);
                sts128(dst + i * 1024 + 512, w[4], w[5], w[6], w[7]);
                if (i) asm volatile("{\n.reg .pred p;\nsetp.lt.s32 p, %9, 0;\nL:\n@p st.shared.v4.u32 [%0], {%1, %2, %3, %4};\n@p st.shared.v4.u32 [%0 + 16], {%5, %6, %7, %8};\n@p bra L;\n}\n"
                             ::"r"(dst), "r"(u[0]), "r"(u[1]), "r"(u[2]), "r"(u[3]), "r"(u[4]), "r"(u[5]), "r"(u[6]), "r"(u[7]), "r"(it) : "memory");
            }
            fence_async_smem();
            warp_arrive(bar_pdone);
        }
        constexpr int IW = 4 + 75;
        uint32_t a[64];
        const int lane = lane_now(), t = warp * 32 + lane;
        if (wg == 0 && (SC_PAIR || SC_LAST)) {
            uint32_t rq, rml, rbar;
            asm volatile("mapa.shared::cluster.u32 %0, %3, %6;\nmapa.shared::cluster.u32 %1, %4, %6;\nmapa.shared::cluster.u32 %2, %5, %6;\n"
                         : "=r"(rq), "=r"(rml), "=r"(rbar) : "r"(sb + SM_Q + QB_BYTES + warp * 8192 + lane * 16), "r"(sb + SM_ML + 512 + t * 4),
                         "r"(bar_pin), "r"(rank ^ 1));
            auto send = [&](int i) {
                asm volatile("st.async.weak.shared::cluster.mbarrier::complete_tx::bytes.v4.b32 [%0], {%1, %2, %3, %4}, [%5];\n"
                             ::"r"(rq + i * 512), "r"(a[4 * i]), "r"(a[4 * i + 1]), "r"(a[4 * i + 2]), "r"(a[4 * i + 3]), "r"(rbar + (i & 8)) : "memory");
            };
            mbar_wait(bar_rfree, 0);
            wg_wait<0>();
            fence_regs(o);
            release((it - 1) & 3);
            float z0, z1;
            row_sums(z0, z1, lane);
            asm volatile("st.async.weak.shared::cluster.mbarrier::complete_tx::bytes.f32 [%0], %1, [%2];\n" ::"r"(rml), "f"(stats(lane)), "r"(rbar) : "memory");
#pragma unroll
            for (int i = 0; i < 16; i++) {
                a[4 * i] = pack_bf16(o[8 * i] - z0, o[8 * i + 1] - z0); a[4 * i + 1] = pack_bf16(o[8 * i + 2] - z1, o[8 * i + 3] - z1);
                a[4 * i + 2] = pack_bf16(o[8 * i + 4] - z0, o[8 * i + 5] - z0); a[4 * i + 3] = pack_bf16(o[8 * i + 6] - z1, o[8 * i + 7] - z1);
                if (i * SND0 / 16 != (i + 1) * SND0 / 16) send(i * SND0 / 16);
                if (i % CUT2 == CUT2 - 1) cut();
            }
            if (SC_PAIR) {
                float z[128];
                const uint32_t dkz = dk0 + ((uint32_t)it >> 24), dqz = dq0 + ((uint32_t)it >> 24);
                auto gemm = [&](int c) {
                    mbar_wait(bar_full + 8 * ((IW + c) & 3), ((IW + c) >> 2) & 1);
                    const uint64_t wb = mkaddr(dkz + ((IW + c) & 3) * (KV_BYTES >> 4), dhi), ab = mkaddr(dqz + c * 64, dhi);
                    wg_fence();
#pragma unroll
                    for (int kk = 0; kk < 4; kk++) {
                        if (c | kk) wgmma_ss_n256_tb(z, ab + kk * 2, wb + kk * 512);
                        else wgmma_ss_n256_tb_init(z, ab, wb);
                    }
                    wg_commit();
                };
                mbar_wait(qbar, qphase);
                bar_sync(BAR_ST + 1, 256);
                gemm(0);
#pragma unroll
                for (int i = SND0; i < 16; i++) send(i);
#pragma unroll
                for (int c = 1; c < 4; c++) { gemm(c); if (c == 3) pp_arrive(); wg_wait<1>(); release((IW + c - 1) & 3, 2); }
                wg_wait<0>();
                fence_regs(z);
                release((IW + 3) & 3, 2);
#pragma unroll
                for (int i = 0; i < 16; i++) {
                    sts128(sq + warp * 8192 + lane * 16 + i * 512, pack_bf16(z[8 * i], z[8 * i + 1]), pack_bf16(z[8 * i + 2], z[8 * i + 3]),
                           pack_bf16(z[8 * i + 4], z[8 * i + 5]), pack_bf16(z[8 * i + 6], z[8 * i + 7]));
                    if (i == 3 || i == 15) bar_arrive(i == 3 ? BAR_BF : BAR_H0, 256);
                    if (i == 3) cut();
                }
            } else {
#pragma unroll
                for (int i = SND0; i < 16; i++) send(i);
            }
        } else {
            const int pair = SC_PAIR;
            const bool glob = !(pair || SC_TAIL);
            const uint32_t ml = sb + SM_ML + (t & ~3) * 4, src = (glob ? sq : sb + SM_Q + QB_BYTES) + warp * 8192 + lane * 16;
            const uint64_t tm = lds64(s_tm);
            wg_wait<0>();
            fence_regs(o);
            release((IW - 1) & 3);
            float c0, c1;
            row_sums(c0, c1, lane);
            mbar_wait(glob ? qbar : bar_pin, glob ? qphase : 0);
            const float4 ps = lds128f(ml + (glob ? wg * 512 : 512));
            auto load = [&](int i) {
                asm volatile("ld.shared.v4.u32 {%0, %1, %2, %3}, [%4];\n" : "=r"(a[4 * i]), "=r"(a[4 * i + 1]), "=r"(a[4 * i + 2]), "=r"(a[4 * i + 3]) : "r"(src + i * 512) : "memory");
            };
#pragma unroll
            for (int i = 0; i < 8; i++) load(i);
            const float n0 = fmaxf(m0, ps.x), n1 = fmaxf(m1, ps.z);
            const float a0 = ex2(m0 - n0), a1 = ex2(m1 - n1), b0 = ex2(ps.x - n0), b1 = ex2(ps.z - n1);
            const float i0 = rcp(l0 * a0 + ps.y * b0), i1 = rcp(l1 * a1 + ps.w * b1);
            const float r0 = a0 * i0, r1 = a1 * i1;
            c0 *= -r0; c1 *= -r1;
            const uint32_t u0 = pack_bf16(b0 * i0, b0 * i0), u1 = pack_bf16(b1 * i1, b1 * i1);
#pragma unroll
            for (int i = 0; i < 32; i++) {
                if (i == 16) {
                    if (!glob) mbar_wait(bar_pin + 8, 0);
#pragma unroll
                    for (int j = 8; j < 16; j++) load(j);
                }
                a[2 * i] = hfma2(a[2 * i], u0, pack_bf16(fmaf(o[4 * i], r0, c0), fmaf(o[4 * i + 1], r0, c0)));
                a[2 * i + 1] = hfma2(a[2 * i + 1], u1, pack_bf16(fmaf(o[4 * i + 2], r1, c1), fmaf(o[4 * i + 3], r1, c1)));
            }
            float y[2][32];
            auto gemm = [&](int c, int kh) {
                if (!kh) mbar_wait(bar_full + 8 * ((IW + c) & 3), (((IW + c) >> 2) & 1) ^ pair);
                const uint64_t wb = mkaddr(dk0 + ((IW + c) & 3) * (KV_BYTES >> 4), dhi - 192);
                wg_fence();
#pragma unroll
                for (int kk = 8 * kh; kk < 8 * kh + 8; kk++) {
                    if (kk) wgmma_rs_n64_tb(y[c & 1], a[4 * kk], a[4 * kk + 1], a[4 * kk + 2], a[4 * kk + 3], wb + kk * 128);
                    else wgmma_rs_n64_tb_init(y[c & 1], a[0], a[1], a[2], a[3], wb);
                }
                wg_commit();
            };
            const uint32_t stg = sq + warp * 8192 + (lane & 15) * 128 + (((lane >> 4) ^ lane) & 7) * 16;
            uint4 z[4] = {};
            auto load_z = [&](int cb) {
                if (cb < 2) asm volatile("{\n.reg .pred p;\nsetp.ne.s32 p, %0, 0;\n@p bar.sync %1, 256;\n}\n" ::"r"(pair), "r"(cb ? BAR_H0 : BAR_BF) : "memory");
#pragma unroll
                for (int i = 0; i < 4; i++)
                    asm volatile("{\n.reg .pred p;\nsetp.ne.u32 p, %4, 0;\n@p ld.shared.v4.u32 {%0, %1, %2, %3}, [%5];\n}\n"
                                 : "+r"(z[i].x), "+r"(z[i].y), "+r"(z[i].z), "+r"(z[i].w) : "r"(pair), "r"(src - QB_BYTES + (4 * cb + i) * 512) : "memory");
            };
            pp_sync();
            gemm(0, 0);
            gemm(0, 1);
#pragma unroll
            for (int c = 0; c < 4; c++) {
                if (c) load_z(c);
                if (c < 3) gemm(c + 1, 0);
                if (!c) load_z(0);
                if (c < 3) wg_wait<1>(); else wg_wait<0>();
                fence_regs(y[c & 1]);
                const float* x = y[c & 1];
#pragma unroll
                for (int i = 0; i < 4; i++)
                    stmatrix_x4((stg ^ (32 * i)) + c * 2048, hadd2(pack_bf16(x[8 * i], x[8 * i + 1]), z[i].x), hadd2(pack_bf16(x[8 * i + 2], x[8 * i + 3]), z[i].y),
                                hadd2(pack_bf16(x[8 * i + 4], x[8 * i + 5]), z[i].z), hadd2(pack_bf16(x[8 * i + 6], x[8 * i + 7]), z[i].w));
                if (c < 3) gemm(c + 1, 1);
                fence_async_smem();
                __syncwarp();
                asm volatile("{\n.reg .pred p;\nelect.sync _|p, -1;\n"
                             "@p cp.reduce.async.bulk.tensor.4d.global.shared::cta.add.tile.bulk_group [%0, {0, 0, %1, %2}], [%3];\n}\n"
                             ::"l"(tm), "r"(c), "r"((pair ? SC_ZB : 2 * SC_QT0 + wg) * 8 + warp * 2), "r"(sq + warp * 8192 + c * 2048) : "memory");
                if (c == 2 && glob) pp_arrive();
            }
            asm volatile("cp.async.bulk.commit_group;\ncp.async.bulk.wait_group.read 0;\n" ::: "memory");
        }
        } else {
            wg_wait<0>();
        }
        if (SC_TAIL) {
        float o[128];
        const int lane = lane_now(), t = warp * 32 + lane, q = lane & 3;
        auto emit = [&](uint32_t base, int lane, int row0, uint8_t* wdst, int turn) {
#pragma unroll
            for (int hh = 0; hh < 2; hh++) {
                if (turn > 0) mbar_wait(bar_zst + 8 * hh, (turn - 1) & 1);
#pragma unroll
                for (int i = 0; i < 8; i++)
                    stmatrix_x4(base + tile_off(8 * hh + (lane & 7), 4 * i + (lane >> 3)),
                                pack_bf16(o[16 * i + 2 * hh], o[16 * i + 2 * hh + 1]), pack_bf16(o[16 * i + 4 + 2 * hh], o[16 * i + 5 + 2 * hh]),
                                pack_bf16(o[16 * i + 8 + 2 * hh], o[16 * i + 9 + 2 * hh]), pack_bf16(o[16 * i + 12 + 2 * hh], o[16 * i + 13 + 2 * hh]));
                fence_async_smem();
                __syncwarp();
                if (wdst) {
                    if (lane < 4)
                        asm volatile("cp.async.bulk.global.shared::cta.bulk_group [%0], [%1], 1024;\n"
                                     ::"l"(wdst + ((turn & 1) ? hh * 4096 + lane * 1024 : hh * 1024 + lane * QB_BYTES)), "r"(base + hh * 4096 + lane * 1024) : "memory");
                    asm volatile("cp.async.bulk.commit_group;\n" ::: "memory");
                } else {
                    asm volatile("{\n.reg .pred p;\nsetp.eq.s32 p, %3, 0;\n"
                                 "@p cp.reduce.async.bulk.tensor.4d.global.shared::cta.add.tile.bulk_group [%0, {0, 0, 0, %1}], [%2];\n"
                                 "cp.async.bulk.commit_group;\n}\n"
                                 ::"l"(&P.tm_out), "r"((row0 >> 3) + hh), "r"(base + hh * 4096), "r"(lane) : "memory");
                }
            }
            asm volatile("cp.async.bulk.wait_group.read 1;\n" ::: "memory");
            warp_arrive(bar_zst - 8 * wg);
        };
        auto emit_done = [&](bool pending) {
            asm volatile("cp.async.bulk.wait_group.read 0;\n" ::: "memory");
            __syncwarp();
            asm volatile("{\n.reg .pred p;\nsetp.eq.s32 p, %1, 0;\n@p mbarrier.arrive.shared::cta.b64 _, [%0];\n}\n"
                         ::"r"(bar_zst + 8), "r"(pending ? lane : 1) : "memory");
        };
        if (!(rank | wg)) { release(0); release(1); release(2); release(3); }
        bar_sync(BAR_BF, 256);
        warp_arrive(bar_qfree);
        const int nf = rank ? 8 : 0;
        const int nz = nf + 26 + rank;
        const int itz = 4 + SC_NKV + SC_NW;
        bool pend = false;
#pragma unroll 1
        for (int k = wg; k < nz; k += 2) {
            const int iz = itz + (k < nf ? 0 : nf >> 1);
            mbar_wait(qbar, qphase); qphase ^= 1;
#pragma unroll 1
            for (int c = 0; c < 4; c++) {
                mbar_wait(bar_full + 8 * ((iz + c) & 3), ((iz + c) >> 2) & 1);
                const uint64_t wb = mkaddr(dk0 + ((iz + c) & 3) * (KV_BYTES >> 4), dhi), ab = mkaddr(dq0 + c * 64, dhi);
                wg_fence();
                wgmma_ss_n256_tb_pred(o, ab, wb, c);
#pragma unroll
                for (int kk = 1; kk < 4; kk++) wgmma_ss_n256_tb(o, ab + kk * 2, wb + kk * 512);
                wg_commit();
                emit_done(pend);
                pend = false;
            }
            wg_wait<0>();
            fence_regs(o);
            warp_arrive(bar_qfree);
            const int fb = ((k >> 1) + 3) & 3;
            if (k < nf) {
                float2* r255 = (float2*)H.s->r255 + wg * 128 + q;
                if (k < 2) {
                    if (t >= 124) {
#pragma unroll
                        for (int i = 0; i < 32; i++) r255[4 * i] = make_float2(o[4 * i + 2], o[4 * i + 3]);
                    }
                    bar_sync(BAR_WG0 + wg, 128);
                }
#pragma unroll
                for (int i = 0; i < 32; i++) {
                    const float2 v = __ldcg(r255 + 4 * i);
                    o[4 * i] -= v.x; o[4 * i + 1] -= v.y; o[4 * i + 2] -= v.x; o[4 * i + 3] -= v.y;
                }
            }
            int ln = lane;
            asm volatile("" : "+r"(ln));
            emit(sb + SM_KV + QB_BYTES + warp * KV_BYTES, ln, SC_TZB(k - nf) * 64 + warp * 16,
                 k >= nf ? nullptr : (k & 1) ? g_w + (4 + fb) * QB_BYTES + warp * 8192 : g_w + 8 * QB_BYTES + fb * 8192 + warp * 2048, k);
            pend = k + 2 < nz && (k | 1) != nf - 1;
            if (!pend) emit_done(true);
            if ((k | 1) == nf - 1) {
                asm volatile("cp.async.bulk.wait_group 0;\nfence.proxy.async.global;\nfence.acq_rel.gpu;\n" ::: "memory");
                bar_sync(BAR_BF, 256);
                if (tid == 0) red_release(&g_sync[SY_B * 32]);
                if (wg == 0) { release(0); release(1); release(2); release(3); }
            }
        }
        }
        if (wg == 0) pp_sync();
        warp_arrive(bar_end - 8 * wg);
        asm volatile("barrier.cluster.arrive.relaxed.aligned;\n" ::: "memory");
        if (P.E >= 0) return;
        asm volatile("setmaxnreg.dec.sync.aligned.u32 %0;\n" ::"n"(REG_P));
    }
    {
        if (warp != 0) {
            if (warp == 3 && SC_OWNER && SC_PAIR && elect()) {
                flag_wait_bounded(&g_sync[SY_H1 * 32], 79 * ep);
                mbar_wait_sleep(bar_pdone, 0);
                mbar_wait_sleep(bar_pdone + 8, 0);
#pragma unroll 1
                for (int u = 0; u < 16; u++) {
                    bulk_s2g(g_q + SC_QT0 * (2 * QB_BYTES) + u * 4096, sb + SM_Q + u * 4096, 4096);
                    asm volatile("cp.async.bulk.wait_group 0;\n" ::: "memory");
                }
                fence_async_global();
                st_release(&g_qflag[SC_QT0], ep);
            }
            __syncwarp();
            if (SC_TAIL) {
                bar_sync(BAR_AUX, 96);
                if (warp == 1 && elect()) red_release(&g_sync[SY_CSR * 32]);
                __syncwarp();
            }
            mbar_wait_bounded(bar_go, 0);
            if (SC_TAIL) {
                if (warp == 1 && elect()) red_add(&g_sync[SY_DONE * 32]);
                if (warp == 3 && elect()) {
                    int it = 4 + SC_NKV + SC_NW;
                    asm volatile("prefetch.tensormap [%0];\n" ::"l"(&P.tm_out) : "memory");
                    if (rank) {
#pragma unroll 1
                        for (int j = 0; j < 4; j++, it++) {
                            mbar_wait_sleep(bar_empty + 8 * (it & 3), ((it >> 2) & 1) ^ 1);
                            mbar_expect_tx(bar_full + 8 * (it & 3), QB_BYTES);
                            tma_g2s(sb + SM_KV + (it & 3) * KV_BYTES, &P.tm_w[2], 8 * j, bar_full + 8 * (it & 3));
                        }
#pragma unroll 1
                        for (int k = 0; k < 8; k++) {
                            mbar_wait_sleep(bar_qfree + 8 * (k & 1), ((k >> 1) ^ (k & 1) ^ 1) & 1);
                            mbar_expect_tx(bar_q + 8 * (k & 1), QB_BYTES);
#pragma unroll 1
                            for (int hf = 0; hf < 2; hf++)
                                asm volatile("cp.async.bulk.tensor.5d.shared::cluster.global.tile.mbarrier::complete_tx::bytes [%0], [%1, {0, 0, %2, 0, 0}], [%3];\n"
                                             ::"r"(sb + SM_Q + (k & 1) * QB_BYTES + hf * 16384), "l"(&P.tm_w[k & 1]),
                                             "r"(8 * (((k >> 1) + 3) & 3) + 4 * hf), "r"(bar_q + 8 * (k & 1)) : "memory");
                        }
                        flag_wait_bounded(&g_sync[SY_B * 32], ep);
                        fence_async_global();
                    }
#pragma unroll 1
                    for (int j = 0; j < 4; j++, it++) {
                        mbar_wait_sleep(bar_empty + 8 * (it & 3), ((it >> 2) & 1) ^ 1);
                        mbar_expect_tx(bar_full + 8 * (it & 3), QB_BYTES);
                        bulk_g2s(sb + SM_KV + (it & 3) * KV_BYTES, g_w + (4 + j) * QB_BYTES, QB_BYTES, bar_full + 8 * (it & 3));
                    }
#pragma unroll 1
                    for (int k = 0; k < 26 + rank; k++) {
                        if (k == 0 || k == ((GF0 + 1) * NAUX - 16) / 128) { flag_wait_bounded(&g_sync[(k ? SY_AUX1 : SY_AUX0) * 32], NAUX * ep); fence_async_global(); }
                        mbar_wait_sleep(bar_qfree + 8 * (k & 1), ((k >> 1) ^ (k & 1) ^ 1) & 1);
                        mbar_expect_tx(bar_q + 8 * (k & 1), QB_BYTES);
                        bulk_g2s(sb + SM_Q + (k & 1) * QB_BYTES, g_agg + SC_TZB(k) * QB_BYTES, QB_BYTES, bar_q + 8 * (k & 1));
                    }
                }
            } else {
            const int par = ep & 1;
            if (blockIdx.x == 0 && t == 32) g_ovf_n[par ^ 1] = 0;
            if (blockIdx.x == 0 && warp == 1) *(uint4*)(g_hz + (lane >> 3) * 1024 + (lane & 7) * 16) = make_uint4(KV_OFF2 | NEG2, KV_OFF2 | NEG2, KV_OFF2, KV_OFF2);
            const uint32_t wlo = (uint32_t)(uintptr_t)H.s, whi = (uint32_t)((uintptr_t)H.s >> 32);
            const uint32_t blo = wlo + (uint32_t)offsetof(Scratch, bucket);
            {
                const int* pd = P.dst + blockIdx.x * 96 + (t - 32);
                const int* ps = P.src + blockIdx.x * 96 + (t - 32);
#pragma unroll 1
                for (int e = P.E - (blockIdx.x * 96 + (t - 32)); e > 0; e -= CSRU * NAUX * 32, pd += CSRU * NAUX * 32, ps += CSRU * NAUX * 32) {
                    int d[CSRU], sr[CSRU], sl[CSRU];
#pragma unroll
                    for (int i = 0; i < CSRU; i++) {
                        d[i] = e > i * NAUX * 32 ? __ldg(pd + i * NAUX * 32) : NN;
                        sr[i] = e > i * NAUX * 32 ? __ldg(ps + i * NAUX * 32) : 0;
                    }
#pragma unroll
                    for (int i = 0; i < CSRU; i++) {
                        sl[i] = 0;
                        asm volatile("{\n.reg .pred p;\nsetp.lt.s32 p, %2, %3;\n@p atom.relaxed.gpu.global.add.s32 %0, [%1], 1;\n}\n"
                                     : "+r"(sl[i]) : "l"(mkaddr(wlo + (uint32_t)offsetof(Scratch, cnt) + d[i] * 4, whi)), "r"(d[i]), "n"(NN) : "memory");
                    }
                    uint32_t ov = 0;
#pragma unroll
                    for (int i = 0; i < CSRU; i++) {
                        asm volatile("{\n.reg .pred p;\nsetp.lt.s32 p, %3, %4;\n@p st.global.u16 [%1], %2;\n@!p or.b32 %0, %0, %5;\n}\n"
                                     : "+r"(ov) : "l"(mkaddr(blo + d[i] * 128 + (sl[i] & 31) * 4 + (sl[i] >> 5) * 2, whi)), "h"((unsigned short)sr[i]), "r"(sl[i]), "n"(CAP), "r"(1 << i) : "memory");
                    }
#pragma unroll 1
                    for (; ov; ov &= ov - 1) {
                        const int i = (__ffs(ov) - 1) * (NAUX * 32);
                        int at;
                        asm volatile("atom.relaxed.gpu.global.add.s32 %0, [%1], 1;\n" : "=r"(at) : "l"(&g_ovf_n[par]) : "memory");
                        g_ovf[at] = make_int2(__ldg(pd + i), __ldg(ps + i));
                    }
                }
            }
            bar_sync(BAR_AUX, 96);
            if (warp == 1 && elect()) { red_release(&g_sync[SY_CSR * 32]); }
            __syncwarp();
            {
                const int r0 = blockIdx.x * 3 + warp - 1;
                const uint4* xp = (const uint4*)(H.x + r0 * 256) + lane;
                uint4* op = (uint4*)(P.out + r0 * 256) + lane;
#pragma unroll 1
                for (int r = r0; r < NN; r += CPYU * NAUX, xp += CPYU * NAUX * 32, op += CPYU * NAUX * 32) {
                    uint4 v[CPYU];
#pragma unroll
                    for (int i = 0; i < CPYU; i++) if (r + i * NAUX < NN) v[i] = ldg_pinned(xp + i * NAUX * 32);
#pragma unroll
                    for (int i = 0; i < CPYU; i++) if (r + i * NAUX < NN) op[i * NAUX * 32] = v[i];
                }
            }
            mbar_wait_bounded(bar_go, 1);
            if (const int un = (3 - warp) * (NAUX / 3) + (NAUX / 3 - 1) - blockIdx.x; un < 208) {
                flag_wait_bounded(&g_sync[SY_PART * 32], 52 * ep);
                uint8_t* pp = g_part + (un >> 3) * (4 * PART_BYTES);
                float* ml = (float*)(pp + QB_BYTES) + (un & 7) * 32;
                const float4 sa = __ldcg((const float4*)ml + g), sc = __ldcg((const float4*)ml + g + 2 * PART_BYTES / 16);
                const float n0 = fmaxf(sa.x, sc.x), n1 = fmaxf(sa.z, sc.z);
                const uint32_t a0 = pack_bf16(ex2(sa.x - n0), ex2(sa.x - n0)), a1 = pack_bf16(ex2(sa.z - n1), ex2(sa.z - n1));
                const uint32_t b0 = pack_bf16(ex2(sc.x - n0), ex2(sc.x - n0)), b1 = pack_bf16(ex2(sc.z - n1), ex2(sc.z - n1));
                __syncwarp();
                if (q == 0) ((float4*)ml)[g] = make_float4(n0, sa.y * bf_hi(a0) + sc.y * bf_hi(b0), n1, sa.w * bf_hi(a1) + sc.w * bf_hi(b1));
                uint4* d = (uint4*)(pp + (un & 4) * 256 + (un & 7) * 8192) + lane;
#pragma unroll 1
                for (int i = 0; i < 4; i++, d += 128) {
                    uint4 u[4], v[4];
#pragma unroll
                    for (int j = 0; j < 4; j++) { u[j] = __ldcg(d + j * 32); v[j] = __ldcg(d + j * 32 + 2 * PART_BYTES / 16); }
#pragma unroll
                    for (int j = 0; j < 4; j++)
                        d[j * 32] = make_uint4(hfma2(v[j].x, b0, hmul2(u[j].x, a0)), hfma2(v[j].y, b1, hmul2(u[j].y, a1)),
                                               hfma2(v[j].z, b0, hmul2(u[j].z, a0)), hfma2(v[j].w, b1, hmul2(u[j].w, a1)));
                }
            }
            flag_wait_bounded(&g_sync[SY_CSR * 32], NCTA * ep);
            if (warp == 2 && blockIdx.x < 129) {
                uint4* z = blockIdx.x < 128 ? (uint4*)(g_w + blockIdx.x * 1024) + lane : (uint4*)&g_sync[SY_DONE * 32 + 4];
                z[0] = make_uint4(0, 0, 0, 0);
                if (blockIdx.x < 128) z[32] = make_uint4(0, 0, 0, 0);
            }
            {
                const uint32_t lc = (lane >> 3) * 1024 + (lane & 7) * 16;
                const uint32_t alo = wlo ^ lc;
                const int node0 = blockIdx.x * 3 + warp - 17;
                auto node = [&](int i) { const int nd = node0 + i * NAUX; return (int)min((unsigned)nd, (unsigned)(nd + NN)); };
                const int num = (NN - 17 - node0) / NAUX + 1;
                uint32_t mine = 0;
                if (lane < num) {
                    mine = min(__ldcg(&g_cnt[node(lane)]), CAP + 1) | (uint32_t)__ldg((const unsigned short*)P.deg_inv + node(lane)) << 16;
                    g_cnt[node(lane)] = 0;
                }
                auto row = [&](int off) {
                    uint4 v;
                    asm volatile("ld.global.v4.u32 {%0, %1, %2, %3}, [%4];\n"
                                 : "=r"(v.x), "=r"(v.y), "=r"(v.z), "=r"(v.w) : "l"(mkaddr(alo ^ off, whi)));
                    return v;
                };
                auto ents = [&](int i) {
                    uint32_t e;
                    asm volatile("ld.global.cg.u32 %0, [%1];\n" : "=r"(e) : "l"(mkaddr(blo + (min(node(i), NN - 1) * 32 + lane) * 4, whi)));
                    return e;
                };
                auto store = [&](int i, const float (&a)[8]) {
                    const float di = bf_hi(__shfl_sync(~0u, mine, i)) * (1.f / KV_SCALE);
                    const int nd = node(i);
                    *(uint4*)(g_agg + (uint32_t)(((nd >> 3) * 4096 + (nd & 7) * 144) ^ lc)) =
                        make_uint4(pack_bf16(a[0] * di, a[1] * di), pack_bf16(a[2] * di, a[3] * di), pack_bf16(a[4] * di, a[5] * di), pack_bf16(a[6] * di, a[7] * di));
                };
#pragma unroll 1
                for (uint32_t big = __ballot_sync(~0u, (mine & 0xFFFF) > CAP); big; big &= big - 1) {
                    const int i = __ffs(big) - 1, no = __ldcg(&g_ovf_n[par]);
                    float a[8] = {};
#pragma unroll 1
                    for (int k = -64; k < no; k += 32) {
                        const int2 pr = k < 0 ? make_int2(node(i), (ents(i) >> (k & 32) / 2) & 0xFFFF) : k + lane < no ? __ldcg(&g_ovf[k + lane]) : make_int2(-1, 0);
#pragma unroll 1
                        for (uint32_t mk = __ballot_sync(~0u, pr.x == node(i)); mk; mk &= mk - 1) {
                            const uint4 v = row(row_off(__shfl_sync(~0u, pr.y, __ffs(mk) - 1)));
                            a[0] += f16_lo(v.x) + KV_OFF; a[1] += f16_hi(v.x) + KV_OFF; a[2] += f16_lo(v.y) + KV_OFF; a[3] += f16_hi(v.y) + KV_OFF;
                            a[4] += f16_lo(v.z) - KV_OFF; a[5] += f16_hi(v.z) - KV_OFF; a[6] += f16_lo(v.w) - KV_OFF; a[7] += f16_hi(v.w) - KV_OFF;
                        }
                    }
                    store(i, a);
                }
                auto add4 = [&](const uint4& a, const uint4& b) { return make_uint4(hadd2_f16(a.x, b.x), hadd2_f16(a.y, b.y), hadd2_f16(a.z, b.z), hadd2_f16(a.w, b.w)); };
                int ni = -1, left = 0, pos = 0, ec = 0;
                uint32_t en = ents(0);
                uint4 acc = make_uint4(0, 0, 0, 0);
                auto step = [&](uint4 (&v)[4], int& tag) {
                    if (left <= 0 || pos == 32) {
                        if (left > 0) {
                            en = ents(ni) >> 16;
                        } else {
                            ni++;
                            left = __shfl_sync(~0u, mine, ni) & 0xFFFF;
                            if (left > CAP) left = 0;
                        }
                        ec = lane < left ? row_off(en & 0xFFFF) : 0;
                        en = ents(ni + 1);
                        pos = 0;
                    }
                    int of[4];
#pragma unroll
                    for (int j = 0; j < 4; j++) asm volatile("shfl.sync.idx.b32 %0, %1, %2, 31, -1;\n" : "=r"(of[j]) : "r"(ec), "r"(pos + j));
                    acc = add4(acc, add4(add4(add4(v[0], v[1]), make_uint4(KV_OFF8, KV_OFF8, KV_OFF8 | NEG2, KV_OFF8 | NEG2)), add4(v[2], v[3])));
                    asm volatile("" : "+r"(acc.x), "+r"(acc.y), "+r"(acc.z), "+r"(acc.w));
                    asm volatile("{\n.reg .pred p;\nsetp.lt.s32 p, %0, 0;\nL:\n@p pmevent 0;\n@p bra L;\n}\n" ::"r"(ni) : "memory");
#pragma unroll
                    for (int j = 0; j < 4; j++) v[j] = row(of[j]);
                    pos += 4; left -= 4;
                    const int i = tag;
                    tag = left <= 0 ? ni : -1;
                    if (i >= 0) {
                        const float a[8] = {f16_lo(acc.x), f16_hi(acc.x), f16_lo(acc.y), f16_hi(acc.y), f16_lo(acc.z), f16_hi(acc.z), f16_lo(acc.w), f16_hi(acc.w)};
                        if ((__shfl_sync(~0u, mine, i) & 0xFFFF) <= CAP) store(i, a);
                        acc = make_uint4(0, 0, 0, 0);
                        if (i == GF0 || i == 8) {
                            __syncwarp();
                            if (elect()) red_release(&g_sync[(i == 8 ? SY_AUX1 : SY_AUX0) * 32]);
                            __syncwarp();
                        }
                    }
                    return i == num - 1;
                };
                uint4 va[4], vb[4];
#pragma unroll
                for (int j = 0; j < 4; j++) va[j] = vb[j] = make_uint4(KV_OFF2 | NEG2, KV_OFF2 | NEG2, KV_OFF2, KV_OFF2);
                int ta = -1, tb = -1;
#pragma unroll 1
                while (!step(va, ta) && !step(vb, tb)) {}
            }
            bar_sync(BAR_AUX, 96);
            if (warp == 1 && elect()) {
                red_release(&g_sync[SY_AUX * 32]);
                red_add(&g_sync[SY_DONE * 32]);
            }
            }
        }
        __syncwarp();
        asm volatile("barrier.cluster.arrive.relaxed.aligned;\n" ::: "memory");
        if (warp == 1) mbar_wait_bounded(bar_end, 0);
        else if (elect()) mbar_arrive(bar_end);
        __syncwarp();
        asm volatile("barrier.cluster.wait.acquire.aligned;\n" ::: "memory");
    }
}

}

extern "C" void kernel_launch(void* const* d_in, const int* in_sizes, int n_in, void* d_out, int out_size) {
    Hot H;
    Params P;
    H.x = (const __nv_bfloat16*)d_in[0];
    P.src = (const int*)d_in[1];
    P.dst = (const int*)d_in[2];
    P.deg_inv = (const __nv_bfloat16*)d_in[3];
    H.wq = (const __nv_bfloat16*)d_in[5];
    H.wk = (const __nv_bfloat16*)d_in[6];
    P.out = (__nv_bfloat16*)d_out;
    typedef CUresult (*EncodeFn)(CUtensorMap*, CUtensorMapDataType, cuuint32_t, void*, const cuuint64_t*, const cuuint64_t*, const cuuint32_t*,
                                 const cuuint32_t*, CUtensorMapInterleave, CUtensorMapSwizzle, CUtensorMapL2promotion, CUtensorMapFloatOOBfill);
    void* fn = nullptr;
    cudaDriverEntryPointQueryResult qr;
    cudaGetDriverEntryPoint("cuTensorMapEncodeTiled", &fn, cudaEnableDefault, &qr);
    auto encode = [&](CUtensorMap* tm, const void* ptr, int rows, int box_rows, int box_cb = 4) {
        const cuuint64_t dims[4] = {64, 8, 4, (cuuint64_t)rows / 8};
        const cuuint64_t strides[3] = {512, 128, 4096};
        const cuuint32_t box[4] = {64, 8, (cuuint32_t)box_cb, (cuuint32_t)box_rows / 8}, es[4] = {1, 1, 1, 1};
        ((EncodeFn)fn)(tm, CU_TENSOR_MAP_DATA_TYPE_BFLOAT16, 4, (void*)ptr, dims, strides, box, es, CU_TENSOR_MAP_INTERLEAVE_NONE,
                       CU_TENSOR_MAP_SWIZZLE_128B, CU_TENSOR_MAP_L2_PROMOTION_NONE, CU_TENSOR_MAP_FLOAT_OOB_FILL_NONE);
    };
    encode(&P.tm_out, d_out, NN, 8);
    encode(&P.tm_outc, d_out, NN, 16, 1);
    for (int i = 0; i < 2; i++) {
        const cuuint64_t dims[5] = {64, 2, 32, 4, 4};
        const cuuint64_t strides[4] = {512, 4096, 128, 1024};
        const cuuint32_t box[5] = {64, 2, 4, 4, 4}, es[5] = {1, 1, 1, 1, 1};
        ((EncodeFn)fn)(&P.tm_w[i], CU_TENSOR_MAP_DATA_TYPE_BFLOAT16, 5, d_in[i ? 4 : 7], dims, strides, box, es, CU_TENSOR_MAP_INTERLEAVE_NONE,
                       CU_TENSOR_MAP_SWIZZLE_128B, CU_TENSOR_MAP_L2_PROMOTION_NONE, CU_TENSOR_MAP_FLOAT_OOB_FILL_NONE);
    }
    encode(&P.tm_w[2], d_in[8], 256, 64);
    void* raw = nullptr;
    cudaGetSymbolAddress(&raw, g_raw);
    H.s = (Scratch*)(((uintptr_t)raw + ((8 << 20) - 1)) & ~(uintptr_t)((8 << 20) - 1));
    P.dhi = 0x40000100u;
    P.E = in_sizes[1] < MAXE ? in_sizes[1] : MAXE;
    cudaFuncSetAttribute(k_main, cudaFuncAttributeMaxDynamicSharedMemorySize, SM_TOTAL);
    k_main<<<NCTA, 384, SM_TOTAL>>>(H, P);
}
```

```cpp
#include <cuda_runtime.h>
#include <cuda.h>
#include <cuda_bf16.h>
#include <stdint.h>
#include <stddef.h>

namespace {

constexpr int NN = 10000;
constexpr int BN = 80;
constexpr int NKV = NN / BN;
constexpr int NQB = 158;
constexpr int NCTA = 132;
constexpr int NAUX = 3 * (NCTA - 2);
constexpr int STAGES = 4;
constexpr int KV_BYTES = BN * 512;
constexpr int QB_BYTES = 64 * 512;
constexpr int PART_BYTES = QB_BYTES + 512;
constexpr int CAP = 64;
constexpr int MAXE = 160000;

#define QRND(v) (((v) + 0x00040004u) & 0xFFF8FFF8u)
#define GO0 5
#define GO1 41
#define GF0 2
#define CSRU 3
#define CPYU 9
#define REFUP 2.f
#define SND0 10
#define CUT2 2
#define TICK 1024
#define TSL 30
#define NQR 7
#define QSTEP 2
#define QREG(kk) ((kk) % QSTEP == 1 % QSTEP && (kk) > 0 && ((kk) - 1) / QSTEP < NQR ? ((kk) - 1) / QSTEP : -1)
#define REG_C 224
#define REG_P 56

enum { SY_PART = 4, SY_H1 = 5, SY_CSR = 6, SY_AUX = 7, SY_DONE = 8, SY_AUX0 = 9, SY_B = 10, SY_AUX1 = 11, SY_H0 = 12 };
struct Scratch {
    uint8_t hz[4096 + NN * 512];
    uint8_t w[12 * QB_BYTES];
    int sync[25 * 32];
    int qflag[96];
    int ovf_n[32];
    float r255[512];
    int cnt[NN + 16];
    int bucket[(NN + 1) * 32];
    int2 ovf[MAXE];
    uint8_t q[NQB * QB_BYTES];
    uint8_t agg[NQB * QB_BYTES];
    uint8_t part[52 * 2 * PART_BYTES];
};
static_assert(offsetof(Scratch, ovf) <= (8 << 20), "window");
static_assert(offsetof(Scratch, qflag) == offsetof(Scratch, sync) + 25 * 128, "flags");
static_assert(offsetof(Scratch, w) % 1024 == 0 && offsetof(Scratch, sync) % 128 == 0 &&
              offsetof(Scratch, bucket) % 128 == 0 && offsetof(Scratch, q) % 128 == 0, "alignment");
__device__ uint8_t g_raw[(8 << 20) + sizeof(Scratch)];
#define g_hz (H.s->hz)
#define g_w (H.s->w)
#define g_sync (H.s->sync)
#define g_qflag (H.s->qflag)
#define g_ovf_n (H.s->ovf_n)
#define g_cnt (H.s->cnt)
#define g_bucket (H.s->bucket)
#define g_ovf (H.s->ovf)
#define g_q (H.s->q)
#define g_agg (H.s->agg)
#define g_part (H.s->part)

__device__ __forceinline__ void wgmma_ss_n80(uint32_t (&d)[20], uint64_t da, uint64_t db) {
    asm volatile("wgmma.mma_async.sync.aligned.m64n80k16.f16.f16.f16 {"
        "%0, %1, %2, %3, %4, %5, %6, %7, %8, %9, %10, %11, %12, %13, %14, %15, %16, %17, %18, %19}, %20, %21, 1, 1, 1, 0, 0;\n"
        : "+r"(d[0]), "+r"(d[1]), "+r"(d[2]), "+r"(d[3]), "+r"(d[4]), "+r"(d[5]), "+r"(d[6]), "+r"(d[7]),
          "+r"(d[8]), "+r"(d[9]), "+r"(d[10]), "+r"(d[11]), "+r"(d[12]), "+r"(d[13]), "+r"(d[14]), "+r"(d[15]),
          "+r"(d[16]), "+r"(d[17]), "+r"(d[18]), "+r"(d[19])
        : "l"(da), "l"(db));
}
__device__ __forceinline__ void wgmma_ss_n80_init(uint32_t (&d)[20], uint64_t da, uint64_t db) {
    asm volatile("wgmma.mma_async.sync.aligned.m64n80k16.f16.f16.f16 {"
        "%0, %1, %2, %3, %4, %5, %6, %7, %8, %9, %10, %11, %12, %13, %14, %15, %16, %17, %18, %19}, %20, %21, 0, 1, 1, 0, 0;\n"
        : "=r"(d[0]), "=r"(d[1]), "=r"(d[2]), "=r"(d[3]), "=r"(d[4]), "=r"(d[5]), "=r"(d[6]), "=r"(d[7]),
          "=r"(d[8]), "=r"(d[9]), "=r"(d[10]), "=r"(d[11]), "=r"(d[12]), "=r"(d[13]), "=r"(d[14]), "=r"(d[15]),
          "=r"(d[16]), "=r"(d[17]), "=r"(d[18]), "=r"(d[19])
        : "l"(da), "l"(db));
}
__device__ __forceinline__ void wgmma_rs_n80(uint32_t (&d)[20], uint32_t a0, uint32_t a1, uint32_t a2, uint32_t a3, uint64_t db) {
    asm volatile("wgmma.mma_async.sync.aligned.m64n80k16.f16.f16.f16 {"
        "%0, %1, %2, %3, %4, %5, %6, %7, %8, %9, %10, %11, %12, %13, %14, %15, %16, %17, %18, %19}, {%20, %21, %22, %23}, %24, 1, 1, 1, 0;\n"
        : "+r"(d[0]), "+r"(d[1]), "+r"(d[2]), "+r"(d[3]), "+r"(d[4]), "+r"(d[5]), "+r"(d[6]), "+r"(d[7]),
          "+r"(d[8]), "+r"(d[9]), "+r"(d[10]), "+r"(d[11]), "+r"(d[12]), "+r"(d[13]), "+r"(d[14]), "+r"(d[15]),
          "+r"(d[16]), "+r"(d[17]), "+r"(d[18]), "+r"(d[19])
        : "r"(a0), "r"(a1), "r"(a2), "r"(a3), "l"(db));
}
__device__ __forceinline__ void wgmma_rs_n256_tb(float (&d)[128], uint32_t a0, uint32_t a1, uint32_t a2, uint32_t a3, uint64_t db) {
    asm volatile("wgmma.mma_async.sync.aligned.m64n256k16.f32.f16.f16 {"
        "%0, %1, %2, %3, %4, %5, %6, %7, %8, %9, %10, %11, %12, %13, %14, %15, %16, %17, %18, %19, %20, %21, %22, %23, %24, %25, %26, %27, %28, %29, %30, %31, "
        "%32, %33, %34, %35, %36, %37, %38, %39, %40, %41, %42, %43, %44, %45, %46, %47, %48, %49, %50, %51, %52, %53, %54, %55, %56, %57, %58, %59, %60, %61, %62, %63, "
        "%64, %65, %66, %67, %68, %69, %70, %71, %72, %73, %74, %75, %76, %77, %78, %79, %80, %81, %82, %83, %84, %85, %86, %87, %88, %89, %90, %91, %92, %93, %94, %95, "
        "%96, %97, %98, %99, %100, %101, %102, %103, %104, %105, %106, %107, %108, %109, %110, %111, %112, %113, %114, %115, %116, %117, %118, %119, %120, %121, %122, %123, %124, %125, %126, %127}, {%128, %129, %130, %131}, %132, 1, 1, 1, 1;\n"
        : "+f"(d[0]), "+f"(d[1]), "+f"(d[2]), "+f"(d[3]), "+f"(d[4]), "+f"(d[5]), "+f"(d[6]), "+f"(d[7]),
          "+f"(d[8]), "+f"(d[9]), "+f"(d[10]), "+f"(d[11]), "+f"(d[12]), "+f"(d[13]), "+f"(d[14]), "+f"(d[15]),
          "+f"(d[16]), "+f"(d[17]), "+f"(d[18]), "+f"(d[19]), "+f"(d[20]), "+f"(d[21]), "+f"(d[22]), "+f"(d[23]),
          "+f"(d[24]), "+f"(d[25]), "+f"(d[26]), "+f"(d[27]), "+f"(d[28]), "+f"(d[29]), "+f"(d[30]), "+f"(d[31]),
          "+f"(d[32]), "+f"(d[33]), "+f"(d[34]), "+f"(d[35]), "+f"(d[36]), "+f"(d[37]), "+f"(d[38]), "+f"(d[39]),
          "+f"(d[40]), "+f"(d[41]), "+f"(d[42]), "+f"(d[43]), "+f"(d[44]), "+f"(d[45]), "+f"(d[46]), "+f"(d[47]),
          "+f"(d[48]), "+f"(d[49]), "+f"(d[50]), "+f"(d[51]), "+f"(d[52]), "+f"(d[53]), "+f"(d[54]), "+f"(d[55]),
          "+f"(d[56]), "+f"(d[57]), "+f"(d[58]), "+f"(d[59]), "+f"(d[60]), "+f"(d[61]), "+f"(d[62]), "+f"(d[63]),
          "+f"(d[64]), "+f"(d[65]), "+f"(d[66]), "+f"(d[67]), "+f"(d[68]), "+f"(d[69]), "+f"(d[70]), "+f"(d[71]),
          "+f"(d[72]), "+f"(d[73]), "+f"(d[74]), "+f"(d[75]), "+f"(d[76]), "+f"(d[77]), "+f"(d[78]), "+f"(d[79]),
          "+f"(d[80]), "+f"(d[81]), "+f"(d[82]), "+f"(d[83]), "+f"(d[84]), "+f"(d[85]), "+f"(d[86]), "+f"(d[87]),
          "+f"(d[88]), "+f"(d[89]), "+f"(d[90]), "+f"(d[91]), "+f"(d[92]), "+f"(d[93]), "+f"(d[94]), "+f"(d[95]),
          "+f"(d[96]), "+f"(d[97]), "+f"(d[98]), "+f"(d[99]), "+f"(d[100]), "+f"(d[101]), "+f"(d[102]), "+f"(d[103]),
          "+f"(d[104]), "+f"(d[105]), "+f"(d[106]), "+f"(d[107]), "+f"(d[108]), "+f"(d[109]), "+f"(d[110]), "+f"(d[111]),
          "+f"(d[112]), "+f"(d[113]), "+f"(d[114]), "+f"(d[115]), "+f"(d[116]), "+f"(d[117]), "+f"(d[118]), "+f"(d[119]),
          "+f"(d[120]), "+f"(d[121]), "+f"(d[122]), "+f"(d[123]), "+f"(d[124]), "+f"(d[125]), "+f"(d[126]), "+f"(d[127])
        : "r"(a0), "r"(a1), "r"(a2), "r"(a3), "l"(db));
}
__device__ __forceinline__ void wgmma_rs_n256_tb_init(float (&d)[128], uint32_t a0, uint32_t a1, uint32_t a2, uint32_t a3, uint64_t db) {
    asm volatile("wgmma.mma_async.sync.aligned.m64n256k16.f32.f16.f16 {"
        "%0, %1, %2, %3, %4, %5, %6, %7, %8, %9, %10, %11, %12, %13, %14, %15, %16, %17, %18, %19, %20, %21, %22, %23, %24, %25, %26, %27, %28, %29, %30, %31, "
        "%32, %33, %34, %35, %36, %37, %38, %39, %40, %41, %42, %43, %44, %45, %46, %47, %48, %49, %50, %51, %52, %53, %54, %55, %56, %57, %58, %59, %60, %61, %62, %63, "
        "%64, %65, %66, %67, %68, %69, %70, %71, %72, %73, %74, %75, %76, %77, %78, %79, %80, %81, %82, %83, %84, %85, %86, %87, %88, %89, %90, %91, %92, %93, %94, %95, "
        "%96, %97, %98, %99, %100, %101, %102, %103, %104, %105, %106, %107, %108, %109, %110, %111, %112, %113, %114, %115, %116, %117, %118, %119, %120, %121, %122, %123, %124, %125, %126, %127}, {%128, %129, %130, %131}, %132, 0, 1, 1, 1;\n"
        : "=f"(d[0]), "=f"(d[1]), "=f"(d[2]), "=f"(d[3]), "=f"(d[4]), "=f"(d[5]), "=f"(d[6]), "=f"(d[7]),
          "=f"(d[8]), "=f"(d[9]), "=f"(d[10]), "=f"(d[11]), "=f"(d[12]), "=f"(d[13]), "=f"(d[14]), "=f"(d[15]),
          "=f"(d[16]), "=f"(d[17]), "=f"(d[18]), "=f"(d[19]), "=f"(d[20]), "=f"(d[21]), "=f"(d[22]), "=f"(d[23]),
          "=f"(d[24]), "=f"(d[25]), "=f"(d[26]), "=f"(d[27]), "=f"(d[28]), "=f"(d[29]), "=f"(d[30]), "=f"(d[31]),
          "=f"(d[32]), "=f"(d[33]), "=f"(d[34]), "=f"(d[35]), "=f"(d[36]), "=f"(d[37]), "=f"(d[38]), "=f"(d[39]),
          "=f"(d[40]), "=f"(d[41]), "=f"(d[42]), "=f"(d[43]), "=f"(d[44]), "=f"(d[45]), "=f"(d[46]), "=f"(d[47]),
          "=f"(d[48]), "=f"(d[49]), "=f"(d[50]), "=f"(d[51]), "=f"(d[52]), "=f"(d[53]), "=f"(d[54]), "=f"(d[55]),
          "=f"(d[56]), "=f"(d[57]), "=f"(d[58]), "=f"(d[59]), "=f"(d[60]), "=f"(d[61]), "=f"(d[62]), "=f"(d[63]),
          "=f"(d[64]), "=f"(d[65]), "=f"(d[66]), "=f"(d[67]), "=f"(d[68]), "=f"(d[69]), "=f"(d[70]), "=f"(d[71]),
          "=f"(d[72]), "=f"(d[73]), "=f"(d[74]), "=f"(d[75]), "=f"(d[76]), "=f"(d[77]), "=f"(d[78]), "=f"(d[79]),
          "=f"(d[80]), "=f"(d[81]), "=f"(d[82]), "=f"(d[83]), "=f"(d[84]), "=f"(d[85]), "=f"(d[86]), "=f"(d[87]),
          "=f"(d[88]), "=f"(d[89]), "=f"(d[90]), "=f"(d[91]), "=f"(d[92]), "=f"(d[93]), "=f"(d[94]), "=f"(d[95]),
          "=f"(d[96]), "=f"(d[97]), "=f"(d[98]), "=f"(d[99]), "=f"(d[100]), "=f"(d[101]), "=f"(d[102]), "=f"(d[103]),
          "=f"(d[104]), "=f"(d[105]), "=f"(d[106]), "=f"(d[107]), "=f"(d[108]), "=f"(d[109]), "=f"(d[110]), "=f"(d[111]),
          "=f"(d[112]), "=f"(d[113]), "=f"(d[114]), "=f"(d[115]), "=f"(d[116]), "=f"(d[117]), "=f"(d[118]), "=f"(d[119]),
          "=f"(d[120]), "=f"(d[121]), "=f"(d[122]), "=f"(d[123]), "=f"(d[124]), "=f"(d[125]), "=f"(d[126]), "=f"(d[127])
        : "r"(a0), "r"(a1), "r"(a2), "r"(a3), "l"(db));
}
__device__ __forceinline__ void wgmma_rs_n256_tb_pred(float (&d)[128], uint32_t a0, uint32_t a1, uint32_t a2, uint32_t a3, uint64_t db, int acc) {
    asm volatile("{\n.reg .pred p;\nsetp.ne.s32 p, %133, 0;\nwgmma.mma_async.sync.aligned.m64n256k16.f32.f16.f16 {"
        "%0, %1, %2, %3, %4, %5, %6, %7, %8, %9, %10, %11, %12, %13, %14, %15, %16, %17, %18, %19, %20, %21, %22, %23, %24, %25, %26, %27, %28, %29, %30, %31, "
        "%32, %33, %34, %35, %36, %37, %38, %39, %40, %41, %42, %43, %44, %45, %46, %47, %48, %49, %50, %51, %52, %53, %54, %55, %56, %57, %58, %59, %60, %61, %62, %63, "
        "%64, %65, %66, %67, %68, %69, %70, %71, %72, %73, %74, %75, %76, %77, %78, %79, %80, %81, %82, %83, %84, %85, %86, %87, %88, %89, %90, %91, %92, %93, %94, %95, "
        "%96, %97, %98, %99, %100, %101, %102, %103, %104, %105, %106, %107, %108, %109, %110, %111, %112, %113, %114, %115, %116, %117, %118, %119, %120, %121, %122, %123, %124, %125, %126, %127}, {%128, %129, %130, %131}, %132, p, 1, 1, 1;\n}\n"
        : "+f"(d[0]), "+f"(d[1]), "+f"(d[2]), "+f"(d[3]), "+f"(d[4]), "+f"(d[5]), "+f"(d[6]), "+f"(d[7]),
          "+f"(d[8]), "+f"(d[9]), "+f"(d[10]), "+f"(d[11]), "+f"(d[12]), "+f"(d[13]), "+f"(d[14]), "+f"(d[15]),
          "+f"(d[16]), "+f"(d[17]), "+f"(d[18]), "+f"(d[19]), "+f"(d[20]), "+f"(d[21]), "+f"(d[22]), "+f"(d[23]),
          "+f"(d[24]), "+f"(d[25]), "+f"(d[26]), "+f"(d[27]), "+f"(d[28]), "+f"(d[29]), "+f"(d[30]), "+f"(d[31]),
          "+f"(d[32]), "+f"(d[33]), "+f"(d[34]), "+f"(d[35]), "+f"(d[36]), "+f"(d[37]), "+f"(d[38]), "+f"(d[39]),
          "+f"(d[40]), "+f"(d[41]), "+f"(d[42]), "+f"(d[43]), "+f"(d[44]), "+f"(d[45]), "+f"(d[46]), "+f"(d[47]),
          "+f"(d[48]), "+f"(d[49]), "+f"(d[50]), "+f"(d[51]), "+f"(d[52]), "+f"(d[53]), "+f"(d[54]), "+f"(d[55]),
          "+f"(d[56]), "+f"(d[57]), "+f"(d[58]), "+f"(d[59]), "+f"(d[60]), "+f"(d[61]), "+f"(d[62]), "+f"(d[63]),
          "+f"(d[64]), "+f"(d[65]), "+f"(d[66]), "+f"(d[67]), "+f"(d[68]), "+f"(d[69]), "+f"(d[70]), "+f"(d[71]),
          "+f"(d[72]), "+f"(d[73]), "+f"(d[74]), "+f"(d[75]), "+f"(d[76]), "+f"(d[77]), "+f"(d[78]), "+f"(d[79]),
          "+f"(d[80]), "+f"(d[81]), "+f"(d[82]), "+f"(d[83]), "+f"(d[84]), "+f"(d[85]), "+f"(d[86]), "+f"(d[87]),
          "+f"(d[88]), "+f"(d[89]), "+f"(d[90]), "+f"(d[91]), "+f"(d[92]), "+f"(d[93]), "+f"(d[94]), "+f"(d[95]),
          "+f"(d[96]), "+f"(d[97]), "+f"(d[98]), "+f"(d[99]), "+f"(d[100]), "+f"(d[101]), "+f"(d[102]), "+f"(d[103]),
          "+f"(d[104]), "+f"(d[105]), "+f"(d[106]), "+f"(d[107]), "+f"(d[108]), "+f"(d[109]), "+f"(d[110]), "+f"(d[111]),
          "+f"(d[112]), "+f"(d[113]), "+f"(d[114]), "+f"(d[115]), "+f"(d[116]), "+f"(d[117]), "+f"(d[118]), "+f"(d[119]),
          "+f"(d[120]), "+f"(d[121]), "+f"(d[122]), "+f"(d[123]), "+f"(d[124]), "+f"(d[125]), "+f"(d[126]), "+f"(d[127])
        : "r"(a0), "r"(a1), "r"(a2), "r"(a3), "l"(db), "r"(acc));
}
__device__ __forceinline__ void wgmma_ss_n256_tb(float (&d)[128], uint64_t da, uint64_t db) {
    asm volatile("wgmma.mma_async.sync.aligned.m64n256k16.f32.bf16.bf16 {"
        "%0, %1, %2, %3, %4, %5, %6, %7, %8, %9, %10, %11, %12, %13, %14, %15, %16, %17, %18, %19, %20, %21, %22, %23, %24, %25, %26, %27, %28, %29, %30, %31, "
        "%32, %33, %34, %35, %36, %37, %38, %39, %40, %41, %42, %43, %44, %45, %46, %47, %48, %49, %50, %51, %52, %53, %54, %55, %56, %57, %58, %59, %60, %61, %62, %63, "
        "%64, %65, %66, %67, %68, %69, %70, %71, %72, %73, %74, %75, %76, %77, %78, %79, %80, %81, %82, %83, %84, %85, %86, %87, %88, %89, %90, %91, %92, %93, %94, %95, "
        "%96, %97, %98, %99, %100, %101, %102, %103, %104, %105, %106, %107, %108, %109, %110, %111, %112, %113, %114, %115, %116, %117, %118, %119, %120, %121, %122, %123, %124, %125, %126, %127}, %128, %129, 1, 1, 1, 0, 1;\n"
        : "+f"(d[0]), "+f"(d[1]), "+f"(d[2]), "+f"(d[3]), "+f"(d[4]), "+f"(d[5]), "+f"(d[6]), "+f"(d[7]),
          "+f"(d[8]), "+f"(d[9]), "+f"(d[10]), "+f"(d[11]), "+f"(d[12]), "+f"(d[13]), "+f"(d[14]), "+f"(d[15]),
          "+f"(d[16]), "+f"(d[17]), "+f"(d[18]), "+f"(d[19]), "+f"(d[20]), "+f"(d[21]), "+f"(d[22]), "+f"(d[23]),
          "+f"(d[24]), "+f"(d[25]), "+f"(d[26]), "+f"(d[27]), "+f"(d[28]), "+f"(d[29]), "+f"(d[30]), "+f"(d[31]),
          "+f"(d[32]), "+f"(d[33]), "+f"(d[34]), "+f"(d[35]), "+f"(d[36]), "+f"(d[37]), "+f"(d[38]), "+f"(d[39]),
          "+f"(d[40]), "+f"(d[41]), "+f"(d[42]), "+f"(d[43]), "+f"(d[44]), "+f"(d[45]), "+f"(d[46]), "+f"(d[47]),
          "+f"(d[48]), "+f"(d[49]), "+f"(d[50]), "+f"(d[51]), "+f"(d[52]), "+f"(d[53]), "+f"(d[54]), "+f"(d[55]),
          "+f"(d[56]), "+f"(d[57]), "+f"(d[58]), "+f"(d[59]), "+f"(d[60]), "+f"(d[61]), "+f"(d[62]), "+f"(d[63]),
          "+f"(d[64]), "+f"(d[65]), "+f"(d[66]), "+f"(d[67]), "+f"(d[68]), "+f"(d[69]), "+f"(d[70]), "+f"(d[71]),
          "+f"(d[72]), "+f"(d[73]), "+f"(d[74]), "+f"(d[75]), "+f"(d[76]), "+f"(d[77]), "+f"(d[78]), "+f"(d[79]),
          "+f"(d[80]), "+f"(d[81]), "+f"(d[82]), "+f"(d[83]), "+f"(d[84]), "+f"(d[85]), "+f"(d[86]), "+f"(d[87]),
          "+f"(d[88]), "+f"(d[89]), "+f"(d[90]), "+f"(d[91]), "+f"(d[92]), "+f"(d[93]), "+f"(d[94]), "+f"(d[95]),
          "+f"(d[96]), "+f"(d[97]), "+f"(d[98]), "+f"(d[99]), "+f"(d[100]), "+f"(d[101]), "+f"(d[102]), "+f"(d[103]),
          "+f"(d[104]), "+f"(d[105]), "+f"(d[106]), "+f"(d[107]), "+f"(d[108]), "+f"(d[109]), "+f"(d[110]), "+f"(d[111]),
          "+f"(d[112]), "+f"(d[113]), "+f"(d[114]), "+f"(d[115]), "+f"(d[116]), "+f"(d[117]), "+f"(d[118]), "+f"(d[119]),
          "+f"(d[120]), "+f"(d[121]), "+f"(d[122]), "+f"(d[123]), "+f"(d[124]), "+f"(d[125]), "+f"(d[126]), "+f"(d[127])
        : "l"(da), "l"(db));
}
__device__ __forceinline__ void wgmma_ss_n256_tb_init(float (&d)[128], uint64_t da, uint64_t db) {
    asm volatile("wgmma.mma_async.sync.aligned.m64n256k16.f32.bf16.bf16 {"
        "%0, %1, %2, %3, %4, %5, %6, %7, %8, %9, %10, %11, %12, %13, %14, %15, %16, %17, %18, %19, %20, %21, %22, %23, %24, %25, %26, %27, %28, %29, %30, %31, "
        "%32, %33, %34, %35, %36, %37, %38, %39, %40, %41, %42, %43, %44, %45, %46, %47, %48, %49, %50, %51, %52, %53, %54, %55, %56, %57, %58, %59, %60, %61, %62, %63, "
        "%64, %65, %66, %67, %68, %69, %70, %71, %72, %73, %74, %75, %76, %77, %78, %79, %80, %81, %82, %83, %84, %85, %86, %87, %88, %89, %90, %91, %92, %93, %94, %95, "
        "%96, %97, %98, %99, %100, %101, %102, %103, %104, %105, %106, %107, %108, %109, %110, %111, %112, %113, %114, %115, %116, %117, %118, %119, %120, %121, %122, %123, %124, %125, %126, %127}, %128, %129, 0, 1, 1, 0, 1;\n"
        : "=f"(d[0]), "=f"(d[1]), "=f"(d[2]), "=f"(d[3]), "=f"(d[4]), "=f"(d[5]), "=f"(d[6]), "=f"(d[7]),
          "=f"(d[8]), "=f"(d[9]), "=f"(d[10]), "=f"(d[11]), "=f"(d[12]), "=f"(d[13]), "=f"(d[14]), "=f"(d[15]),
          "=f"(d[16]), "=f"(d[17]), "=f"(d[18]), "=f"(d[19]), "=f"(d[20]), "=f"(d[21]), "=f"(d[22]), "=f"(d[23]),
          "=f"(d[24]), "=f"(d[25]), "=f"(d[26]), "=f"(d[27]), "=f"(d[28]), "=f"(d[29]), "=f"(d[30]), "=f"(d[31]),
          "=f"(d[32]), "=f"(d[33]), "=f"(d[34]), "=f"(d[35]), "=f"(d[36]), "=f"(d[37]), "=f"(d[38]), "=f"(d[39]),
          "=f"(d[40]), "=f"(d[41]), "=f"(d[42]), "=f"(d[43]), "=f"(d[44]), "=f"(d[45]), "=f"(d[46]), "=f"(d[47]),
          "=f"(d[48]), "=f"(d[49]), "=f"(d[50]), "=f"(d[51]), "=f"(d[52]), "=f"(d[53]), "=f"(d[54]), "=f"(d[55]),
          "=f"(d[56]), "=f"(d[57]), "=f"(d[58]), "=f"(d[59]), "=f"(d[60]), "=f"(d[61]), "=f"(d[62]), "=f"(d[63]),
          "=f"(d[64]), "=f"(d[65]), "=f"(d[66]), "=f"(d[67]), "=f"(d[68]), "=f"(d[69]), "=f"(d[70]), "=f"(d[71]),
          "=f"(d[72]), "=f"(d[73]), "=f"(d[74]), "=f"(d[75]), "=f"(d[76]), "=f"(d[77]), "=f"(d[78]), "=f"(d[79]),
          "=f"(d[80]), "=f"(d[81]), "=f"(d[82]), "=f"(d[83]), "=f"(d[84]), "=f"(d[85]), "=f"(d[86]), "=f"(d[87]),
          "=f"(d[88]), "=f"(d[89]), "=f"(d[90]), "=f"(d[91]), "=f"(d[92]), "=f"(d[93]), "=f"(d[94]), "=f"(d[95]),
          "=f"(d[96]), "=f"(d[97]), "=f"(d[98]), "=f"(d[99]), "=f"(d[100]), "=f"(d[101]), "=f"(d[102]), "=f"(d[103]),
          "=f"(d[104]), "=f"(d[105]), "=f"(d[106]), "=f"(d[107]), "=f"(d[108]), "=f"(d[109]), "=f"(d[110]), "=f"(d[111]),
          "=f"(d[112]), "=f"(d[113]), "=f"(d[114]), "=f"(d[115]), "=f"(d[116]), "=f"(d[117]), "=f"(d[118]), "=f"(d[119]),
          "=f"(d[120]), "=f"(d[121]), "=f"(d[122]), "=f"(d[123]), "=f"(d[124]), "=f"(d[125]), "=f"(d[126]), "=f"(d[127])
        : "l"(da), "l"(db));
}
__device__ __forceinline__ void wgmma_ss_n256_tb_pred(float (&d)[128], uint64_t da, uint64_t db, int acc) {
    asm volatile("{\n.reg .pred p;\nsetp.ne.s32 p, %130, 0;\nwgmma.mma_async.sync.aligned.m64n256k16.f32.bf16.bf16 {"
        "%0, %1, %2, %3, %4, %5, %6, %7, %8, %9, %10, %11, %12, %13, %14, %15, %16, %17, %18, %19, %20, %21, %22, %23, %24, %25, %26, %27, %28, %29, %30, %31, "
        "%32, %33, %34, %35, %36, %37, %38, %39, %40, %41, %42, %43, %44, %45, %46, %47, %48, %49, %50, %51, %52, %53, %54, %55, %56, %57, %58, %59, %60, %61, %62, %63, "
        "%64, %65, %66, %67, %68, %69, %70, %71, %72, %73, %74, %75, %76, %77, %78, %79, %80, %81, %82, %83, %84, %85, %86, %87, %88, %89, %90, %91, %92, %93, %94, %95, "
        "%96, %97, %98, %99, %100, %101, %102, %103, %104, %105, %106, %107, %108, %109, %110, %111, %112, %113, %114, %115, %116, %117, %118, %119, %120, %121, %122, %123, %124, %125, %126, %127}, %128, %129, p, 1, 1, 0, 1;\n}\n"
        : "+f"(d[0]), "+f"(d[1]), "+f"(d[2]), "+f"(d[3]), "+f"(d[4]), "+f"(d[5]), "+f"(d[6]), "+f"(d[7]),
          "+f"(d[8]), "+f"(d[9]), "+f"(d[10]), "+f"(d[11]), "+f"(d[12]), "+f"(d[13]), "+f"(d[14]), "+f"(d[15]),
          "+f"(d[16]), "+f"(d[17]), "+f"(d[18]), "+f"(d[19]), "+f"(d[20]), "+f"(d[21]), "+f"(d[22]), "+f"(d[23]),
          "+f"(d[24]), "+f"(d[25]), "+f"(d[26]), "+f"(d[27]), "+f"(d[28]), "+f"(d[29]), "+f"(d[30]), "+f"(d[31]),
          "+f"(d[32]), "+f"(d[33]), "+f"(d[34]), "+f"(d[35]), "+f"(d[36]), "+f"(d[37]), "+f"(d[38]), "+f"(d[39]),
          "+f"(d[40]), "+f"(d[41]), "+f"(d[42]), "+f"(d[43]), "+f"(d[44]), "+f"(d[45]), "+f"(d[46]), "+f"(d[47]),
          "+f"(d[48]), "+f"(d[49]), "+f"(d[50]), "+f"(d[51]), "+f"(d[52]), "+f"(d[53]), "+f"(d[54]), "+f"(d[55]),
          "+f"(d[56]), "+f"(d[57]), "+f"(d[58]), "+f"(d[59]), "+f"(d[60]), "+f"(d[61]), "+f"(d[62]), "+f"(d[63]),
          "+f"(d[64]), "+f"(d[65]), "+f"(d[66]), "+f"(d[67]), "+f"(d[68]), "+f"(d[69]), "+f"(d[70]), "+f"(d[71]),
          "+f"(d[72]), "+f"(d[73]), "+f"(d[74]), "+f"(d[75]), "+f"(d[76]), "+f"(d[77]), "+f"(d[78]), "+f"(d[79]),
          "+f"(d[80]), "+f"(d[81]), "+f"(d[82]), "+f"(d[83]), "+f"(d[84]), "+f"(d[85]), "+f"(d[86]), "+f"(d[87]),
          "+f"(d[88]), "+f"(d[89]), "+f"(d[90]), "+f"(d[91]), "+f"(d[92]), "+f"(d[93]), "+f"(d[94]), "+f"(d[95]),
          "+f"(d[96]), "+f"(d[97]), "+f"(d[98]), "+f"(d[99]), "+f"(d[100]), "+f"(d[101]), "+f"(d[102]), "+f"(d[103]),
          "+f"(d[104]), "+f"(d[105]), "+f"(d[106]), "+f"(d[107]), "+f"(d[108]), "+f"(d[109]), "+f"(d[110]), "+f"(d[111]),
          "+f"(d[112]), "+f"(d[113]), "+f"(d[114]), "+f"(d[115]), "+f"(d[116]), "+f"(d[117]), "+f"(d[118]), "+f"(d[119]),
          "+f"(d[120]), "+f"(d[121]), "+f"(d[122]), "+f"(d[123]), "+f"(d[124]), "+f"(d[125]), "+f"(d[126]), "+f"(d[127])
        : "l"(da), "l"(db), "r"(acc));
}
__device__ __forceinline__ void wgmma_rs_n64_tb(float (&d)[32], uint32_t a0, uint32_t a1, uint32_t a2, uint32_t a3, uint64_t db) {
    asm volatile("wgmma.mma_async.sync.aligned.m64n64k16.f32.bf16.bf16 {"
        "%0, %1, %2, %3, %4, %5, %6, %7, %8, %9, %10, %11, %12, %13, %14, %15, %16, %17, %18, %19, %20, %21, %22, %23, %24, %25, %26, %27, %28, %29, %30, %31}, {%32, %33, %34, %35}, %36, 1, 1, 1, 1;\n"
        : "+f"(d[0]), "+f"(d[1]), "+f"(d[2]), "+f"(d[3]), "+f"(d[4]), "+f"(d[5]), "+f"(d[6]), "+f"(d[7]),
          "+f"(d[8]), "+f"(d[9]), "+f"(d[10]), "+f"(d[11]), "+f"(d[12]), "+f"(d[13]), "+f"(d[14]), "+f"(d[15]),
          "+f"(d[16]), "+f"(d[17]), "+f"(d[18]), "+f"(d[19]), "+f"(d[20]), "+f"(d[21]), "+f"(d[22]), "+f"(d[23]),
          "+f"(d[24]), "+f"(d[25]), "+f"(d[26]), "+f"(d[27]), "+f"(d[28]), "+f"(d[29]), "+f"(d[30]), "+f"(d[31])
        : "r"(a0), "r"(a1), "r"(a2), "r"(a3), "l"(db));
}
__device__ __forceinline__ void wgmma_rs_n64_tb_init(float (&d)[32], uint32_t a0, uint32_t a1, uint32_t a2, uint32_t a3, uint64_t db) {
    asm volatile("wgmma.mma_async.sync.aligned.m64n64k16.f32.bf16.bf16 {"
        "%0, %1, %2, %3, %4, %5, %6, %7, %8, %9, %10, %11, %12, %13, %14, %15, %16, %17, %18, %19, %20, %21, %22, %23, %24, %25, %26, %27, %28, %29, %30, %31}, {%32, %33, %34, %35}, %36, 0, 1, 1, 1;\n"
        : "=f"(d[0]), "=f"(d[1]), "=f"(d[2]), "=f"(d[3]), "=f"(d[4]), "=f"(d[5]), "=f"(d[6]), "=f"(d[7]),
          "=f"(d[8]), "=f"(d[9]), "=f"(d[10]), "=f"(d[11]), "=f"(d[12]), "=f"(d[13]), "=f"(d[14]), "=f"(d[15]),
          "=f"(d[16]), "=f"(d[17]), "=f"(d[18]), "=f"(d[19]), "=f"(d[20]), "=f"(d[21]), "=f"(d[22]), "=f"(d[23]),
          "=f"(d[24]), "=f"(d[25]), "=f"(d[26]), "=f"(d[27]), "=f"(d[28]), "=f"(d[29]), "=f"(d[30]), "=f"(d[31])
        : "r"(a0), "r"(a1), "r"(a2), "r"(a3), "l"(db));
}

__device__ __forceinline__ void wg_fence() { asm volatile("wgmma.fence.sync.aligned;\n" ::: "memory"); }
__device__ __forceinline__ void wg_commit() { asm volatile("wgmma.commit_group.sync.aligned;\n" ::: "memory"); }
template <int N> __device__ __forceinline__ void wg_wait() { asm volatile("wgmma.wait_group.sync.aligned %0;\n" ::"n"(N) : "memory"); }
template <int N> __device__ __forceinline__ void fence_regs(float (&a)[N]) {
#pragma unroll
    for (int i = 0; i < N; i++) asm volatile("" : "+f"(a[i])::"memory");
}
template <int N> __device__ __forceinline__ void fence_regs(uint32_t (&a)[N]) {
#pragma unroll
    for (int i = 0; i < N; i++) asm volatile("" : "+r"(a[i])::"memory");
}
__device__ __forceinline__ void mbar_init(uint32_t bar, uint32_t cnt) {
    asm volatile("mbarrier.init.shared::cta.b64 [%0], %1;\n" ::"r"(bar), "r"(cnt) : "memory");
}
__device__ __forceinline__ void mbar_expect_tx(uint32_t bar, uint32_t bytes) {
    asm volatile("mbarrier.arrive.expect_tx.shared::cta.b64 _, [%0], %1;\n" ::"r"(bar), "r"(bytes) : "memory");
}
__device__ __forceinline__ void mbar_wait(uint32_t bar, uint32_t parity) {
    asm volatile("{\n.reg .pred p;\nLW:\nmbarrier.try_wait.parity.shared::cta.b64 p, [%0], %1;\n@!p pmevent 0;\n@!p bra LW;\n}\n" ::"r"(bar), "r"(parity) : "memory");
}
__device__ __forceinline__ void mbar_wait_sleep(uint32_t bar, uint32_t parity) {
    asm volatile("{\n.reg .pred p;\nLW:\nmbarrier.try_wait.parity.shared::cta.b64 p, [%0], %1, 20000;\n@!p pmevent 0;\n@!p bra LW;\n}\n" ::"r"(bar), "r"(parity) : "memory");
}
__device__ __forceinline__ void mbar_wait_bounded(uint32_t bar, uint32_t parity) {
    asm volatile("{\n.reg .pred p;\n.reg .u32 c, d;\nmov.u32 c, %%globaltimer_lo;\nLW:\nmbarrier.try_wait.parity.shared::cta.b64 p, [%0], %1, 20000;\n@p bra LD;\n"
                 "mov.u32 d, %%globaltimer_lo;\nsub.u32 d, d, c;\nsetp.ge.u32 p, d, 4000000000;\n@p trap;\nbra LW;\nLD:\n}\n" ::"r"(bar), "r"(parity) : "memory");
}
__device__ __forceinline__ void flag_wait(const int* p, int v) {
    asm volatile("{\n.reg .pred p;\n.reg .s32 f;\nLW:\nld.acquire.gpu.global.s32 f, [%0];\nsub.s32 f, f, %1;\nsetp.lt.s32 p, f, 0;\n@p bra LW;\n}\n" ::"l"(p), "r"(v) : "memory");
}
__device__ __forceinline__ void flag_wait_bounded(const int* p, int v) {
    asm volatile("{\n.reg .pred p;\n.reg .u32 c;\n.reg .s32 f;\nmov.u32 c, 0;\nLW:\nld.acquire.gpu.global.s32 f, [%0];\nsub.s32 f, f, %1;\nsetp.ge.s32 p, f, 0;\n@p bra LD;\n"
                 "nanosleep.u32 500;\nadd.u32 c, c, 1;\nsetp.ge.u32 p, c, 4194304;\n@p trap;\nbra LW;\nLD:\n}\n" ::"l"(p), "r"(v) : "memory");
}
__device__ __forceinline__ int lane_now() {
    int l; asm volatile("mov.u32 %0, %%laneid;\n" : "=r"(l)); return l;
}
__device__ __forceinline__ bool elect() {
    uint32_t p; asm volatile("{\n.reg .pred p;\nelect.sync _|p, -1;\nselp.u32 %0, 1, 0, p;\n}\n" : "=r"(p)); return p;
}
__device__ __forceinline__ void bulk_g2s(uint32_t dst, const void* src, uint32_t bytes, uint32_t bar) {
    asm volatile("cp.async.bulk.shared::cluster.global.mbarrier::complete_tx::bytes [%0], [%1], %2, [%3];\n"
                 ::"r"(dst), "l"(src), "r"(bytes), "r"(bar) : "memory");
}
__device__ __forceinline__ void tma_g2s(uint32_t dst, const CUtensorMap* tm, int rowgroup, uint32_t bar) {
    asm volatile("cp.async.bulk.tensor.4d.shared::cluster.global.tile.mbarrier::complete_tx::bytes [%0], [%1, {0, 0, 0, %2}], [%3];\n"
                 ::"r"(dst), "l"(tm), "r"(rowgroup), "r"(bar) : "memory");
}
__device__ __forceinline__ void bar_sync(int id, int n) { asm volatile("bar.sync %0, %1;\n" ::"r"(id), "r"(n) : "memory"); }
__device__ __forceinline__ void bar_arrive(int id, int n) { asm volatile("bar.arrive %0, %1;\n" ::"r"(id), "r"(n) : "memory"); }
__device__ __forceinline__ float quad_last(float v) {
    float r; asm volatile("shfl.sync.idx.b32 %0, %1, 3, 0x1c1f, -1;\n" : "=f"(r) : "f"(v)); return r;
}
__device__ __forceinline__ float ex2(float x) { float y; asm("ex2.approx.ftz.f32 %0, %1;\n" : "=f"(y) : "f"(x)); return y; }
__device__ __forceinline__ uint32_t ex2_f16(uint32_t x) { uint32_t y; asm("ex2.approx.f16x2 %0, %1;\n" : "=r"(y) : "r"(x)); return y; }
__device__ __forceinline__ uint32_t hmax2_f16(uint32_t a, uint32_t b) { uint32_t r; asm("max.f16x2 %0, %1, %2;\n" : "=r"(r) : "r"(a), "r"(b)); return r; }
__device__ __forceinline__ float rcp(float x) { float y; asm("rcp.approx.ftz.f32 %0, %1;\n" : "=f"(y) : "f"(x)); return y; }
__device__ __forceinline__ uint32_t pack_bf16(float lo, float hi) {
    uint32_t r; asm("cvt.rn.bf16x2.f32 %0, %1, %2;\n" : "=r"(r) : "f"(hi), "f"(lo)); return r;
}
__device__ __forceinline__ uint32_t pack_f16(float lo, float hi) {
    uint32_t r; asm("cvt.rn.f16x2.f32 %0, %1, %2;\n" : "=r"(r) : "f"(hi), "f"(lo)); return r;
}
__device__ __forceinline__ uint32_t pack_f16_sat(float lo, float hi) {
    uint32_t r; asm("cvt.rn.satfinite.f16x2.f32 %0, %1, %2;\n" : "=r"(r) : "f"(hi), "f"(lo)); return r;
}
__device__ __forceinline__ float f16_lo(uint32_t v) { float r; asm("cvt.f32.f16 %0, %1;\n" : "=f"(r) : "h"((unsigned short)v)); return r; }
__device__ __forceinline__ float f16_hi(uint32_t v) { return f16_lo(v >> 16); }
__device__ __forceinline__ float bf_lo(uint32_t v) { return __uint_as_float(v << 16); }
__device__ __forceinline__ float bf_hi(uint32_t v) { return __uint_as_float(v & 0xFFFF0000u); }
__device__ __forceinline__ float bf_round(float x) { return __uint_as_float(pack_bf16(0.f, x)); }
__device__ __forceinline__ void st_release(int* p, int v) {
    asm volatile("st.release.gpu.global.s32 [%0], %1;\n" ::"l"(p), "r"(v) : "memory");
}
__device__ __forceinline__ uint4 ldg_pinned(const uint4* p) {
    uint4 v; asm volatile("ld.global.nc.v4.u32 {%0, %1, %2, %3}, [%4];\n" : "=r"(v.x), "=r"(v.y), "=r"(v.z), "=r"(v.w) : "l"(p) : "memory"); return v;
}
__device__ __forceinline__ void stmatrix_x4(uint32_t addr, uint32_t r0, uint32_t r1, uint32_t r2, uint32_t r3) {
    asm volatile("stmatrix.sync.aligned.m8n8.x4.shared.b16 [%0], {%1, %2, %3, %4};\n" ::"r"(addr), "r"(r0), "r"(r1), "r"(r2), "r"(r3) : "memory");
}

__device__ __forceinline__ uint32_t tile_off(int r, int ch) {
    return (uint32_t)((r >> 3) * 4096 + (ch >> 3) * 1024 + (r & 7) * 128 + (((ch ^ r) & 7) << 4));
}
__device__ __forceinline__ int h_unit(int qt, int u) { return qt < 78 ? u * 78 + qt : 624; }
__device__ __forceinline__ int row_off(int r) { return 4096 + h_unit(r >> 7, (r >> 4) & 7) * 8192 + (r & 8) * 512 + (r & 7) * 144; }

__device__ __forceinline__ float4 lds128f(uint32_t a) {
    float4 v; asm volatile("ld.shared.v4.f32 {%0, %1, %2, %3}, [%4];\n" : "=f"(v.x), "=f"(v.y), "=f"(v.z), "=f"(v.w) : "r"(a) : "memory"); return v;
}
__device__ __forceinline__ uint64_t lds64(uint32_t a) { uint64_t v; asm volatile("ld.shared.u64 %0, [%1];\n" : "=l"(v) : "r"(a) : "memory"); return v; }
__device__ __forceinline__ uint4 lds128(uint32_t a) {
    uint4 v; asm volatile("ld.shared.v4.u32 {%0, %1, %2, %3}, [%4];\n" : "=r"(v.x), "=r"(v.y), "=r"(v.z), "=r"(v.w) : "r"(a) : "memory"); return v;
}
__device__ __forceinline__ void sts128(uint32_t a, uint32_t x, uint32_t y, uint32_t z, uint32_t w) {
    asm volatile("st.shared.v4.u32 [%0], {%1, %2, %3, %4};\n" ::"r"(a), "r"(x), "r"(y), "r"(z), "r"(w) : "memory");
}
__device__ __forceinline__ void mbar_arrive(uint32_t bar) {
    asm volatile("mbarrier.arrive.shared::cta.b64 _, [%0];\n" ::"r"(bar) : "memory");
}
__device__ __forceinline__ uint64_t mkaddr(uint32_t lo, uint32_t hi) { uint64_t a; asm("mov.b64 %0, {%1, %2};\n" : "=l"(a) : "r"(lo), "r"(hi)); return a; }
__device__ __forceinline__ void red_add(int* p) { asm volatile("red.relaxed.gpu.global.add.s32 [%0], 1;\n" ::"l"(p) : "memory"); }
__device__ __forceinline__ void red_release(int* p) {
    asm volatile("fence.proxy.async.global;\nfence.acq_rel.gpu;\nred.relaxed.gpu.global.add.s32 [%0], 1;\n" ::"l"(p) : "memory");
}
__device__ __forceinline__ void fence_async_global() { asm volatile("fence.proxy.async.global;\n" ::: "memory"); }
__device__ __forceinline__ void fence_async_smem() { asm volatile("fence.proxy.async.shared::cta;\n" ::: "memory"); }
__device__ __forceinline__ void bulk_s2g(void* dst, uint32_t src, uint32_t bytes) {
    asm volatile("cp.async.bulk.global.shared::cta.bulk_group [%0], [%1], %2;\ncp.async.bulk.commit_group;\n" ::"l"(dst), "r"(src), "r"(bytes) : "memory");
}
__device__ __forceinline__ void mma16816(float (&c)[4], uint32_t a0, uint32_t a1, uint32_t a2, uint32_t a3, uint32_t b0, uint32_t b1) {
    asm("mma.sync.aligned.m16n8k16.row.col.f32.bf16.bf16.f32 {%0, %1, %2, %3}, {%4, %5, %6, %7}, {%8, %9}, {%0, %1, %2, %3};\n"
        : "+f"(c[0]), "+f"(c[1]), "+f"(c[2]), "+f"(c[3]) : "r"(a0), "r"(a1), "r"(a2), "r"(a3), "r"(b0), "r"(b1));
}
__device__ __forceinline__ void mma1688(float (&c)[4], uint32_t a0, uint32_t a1, uint32_t b0) {
    asm("mma.sync.aligned.m16n8k8.row.col.f32.bf16.bf16.f32 {%0, %1, %2, %3}, {%4, %5}, {%6}, {%0, %1, %2, %3};\n"
        : "+f"(c[0]), "+f"(c[1]), "+f"(c[2]), "+f"(c[3]) : "r"(a0), "r"(a1), "r"(b0));
}
__device__ __forceinline__ uint32_t hadd2_f16(uint32_t a, uint32_t b) { uint32_t r; asm("add.rn.f16x2 %0, %1, %2;\n" : "=r"(r) : "r"(a), "r"(b)); return r; }
__device__ __forceinline__ uint32_t hadd2(uint32_t a, uint32_t b) { uint32_t r; asm("add.rn.bf16x2 %0, %1, %2;\n" : "=r"(r) : "r"(a), "r"(b)); return r; }
__device__ __forceinline__ uint32_t hmul2(uint32_t a, uint32_t b) { uint32_t r; asm("mul.rn.bf16x2 %0, %1, %2;\n" : "=r"(r) : "r"(a), "r"(b)); return r; }
__device__ __forceinline__ uint32_t hfma2(uint32_t a, uint32_t b, uint32_t c) { uint32_t r; asm("fma.rn.bf16x2 %0, %1, %2, %3;\n" : "=r"(r) : "r"(a), "r"(b), "r"(c)); return r; }

constexpr int SM_Q = 0;
constexpr int SM_KV = 65536;
constexpr int SM_ML = SM_KV + STAGES * KV_BYTES;
constexpr int SM_BAR = SM_ML + 1024;
constexpr int SM_TOTAL = SM_BAR + 256;
constexpr float SCALE_LOG2 = 1.4426950408889634f / 16.0f;
constexpr float KV_SCALE = 6.f;
constexpr float KV_OFF = 48.f;
constexpr uint32_t KV_OFF2 = 0x52005200u;
constexpr uint32_t KV_OFF8 = 0x5A005A00u;
constexpr uint32_t NEG2 = 0x80008000u;
constexpr uint32_t S_LIMIT = 0x4B804B80u;
constexpr float REF_UP = REFUP;
__device__ __forceinline__ uint32_t kvf(uint32_t a, uint32_t off) {
    uint32_t r; asm("fma.rn.f16x2 %0, %1, %2, %3;\n" : "=r"(r) : "r"(a), "r"(pack_f16(KV_SCALE, KV_SCALE)), "r"(off)); return r;
}
enum { BAR_PP0 = 1, BAR_PP1 = 2, BAR_WG0 = 3, BAR_WG1 = 4, BAR_H0 = 5, BAR_H1 = 6, BAR_AUX = 7, BAR_BF = 8, BAR_H2 = 9, BAR_X = 10, BAR_GO = 11, BAR_WG2 = 12, BAR_ST = 13 };

struct Hot {
    const __nv_bfloat16 *wk, *wq, *x;
    Scratch* s;
};
struct Params {
    const __nv_bfloat16* deg_inv;
    const int *src, *dst;
    __nv_bfloat16* out;
    uint32_t dhi;
    int E;
    CUtensorMap tm_out;
    CUtensorMap tm_outc;
    CUtensorMap tm_w[3];
};
static_assert(offsetof(Params, tm_outc) == offsetof(Params, tm_out) + 128, "layout");
#define SC_PAIR (blockIdx.x < 104)
#define SC_TAIL (blockIdx.x >= NCTA - 2)
#define SC_LAST (blockIdx.x == NCTA - 1)
#define SC_HELP (SC_PAIR && rank)
#define SC_OWNER (!SC_HELP && !SC_LAST)
#define SC_QT1 (26 + (int)(blockIdx.x >> 1))
#define SC_QT0 (SC_PAIR ? (rank ? (int)(blockIdx.x >> 2) : SC_QT1) : SC_TAIL ? 78 : (int)blockIdx.x - 104)
#define SC_NKV (SC_LAST ? 50 : 75)
#define SC_CLS (SC_PAIR ? (rank ? 0x120 ^ (blockIdx.x & 2) * 0x80 : 0x430) | (blockIdx.x & 2) >> 1 : SC_LAST ? 0x10 : 0x432)
#define SC_NW (SC_PAIR ? 8 : SC_LAST ? 0 : 4)
#define SC_ZB (2 * SC_QT1 + 1 - (int)rank)
#define SC_TZB(k) (rank && !(k) ? 156 : 2 * (k) - (int)rank)

__global__ void __cluster_dims__(2, 1, 1) __launch_bounds__(384, 1) k_main(const __grid_constant__ Hot H, const __grid_constant__ Params P) {
    extern __shared__ __align__(1024) uint8_t smem[];
    const uint32_t sb = (uint32_t)__cvta_generic_to_shared(smem);
    const int tid = threadIdx.x, wg = __shfl_sync(~0u, tid >> 7, 0);
    const int lane = tid & 31, g = lane >> 2, q = lane & 3;
    const uint32_t rank = blockIdx.x & 1;
    const uint32_t bar_full = sb + SM_BAR, bar_q = bar_full + 32, bar_go = bar_full + 48;
    const uint32_t bar_pin = bar_full + 56;
    const uint32_t bar_qfree = bar_full + 72, bar_pdone = bar_full + 88, bar_zst = bar_full + 104, bar_rfree = bar_full + 120;
    const uint32_t bar_empty = bar_full + 128, bar_end = bar_full + 160, s_tm = bar_full + 184, bar_x = bar_full + 192;
    const uint32_t bar_a = sb + SM_ML;

    const int t = tid & 127, warp = __shfl_sync(~0u, t >> 5, 0);
    int ep = 0;
    if (wg & 2) {
        unsigned done;
        {
            uint4 ra[2], rb[2], rk[5][2];
            if (blockIdx.x < 128) {
                const int e = (blockIdx.x >> 4) * 32 + (g >> 1) * 8 + (blockIdx.x & 8) / 2 + (g & 1);
                const uint4* pq = (const uint4*)(H.wq + e * 256) + warp * 8 + q;
                const uint4* pk = (const uint4*)(H.wk + ((blockIdx.x & 7) * 32 + g) * 256) + warp * 8 + q;
                const uint4* pz = (const uint4*)(H.wk + 255 * 256) + warp * 8 + q;
#pragma unroll
                for (int s = 0; s < 2; s++) {
                    ra[s] = ldg_pinned(pq + 4 * s);
                    rb[s] = ldg_pinned(pq + 4 * s + 64);
#pragma unroll
                    for (int n = 0; n < 4; n++) rk[n][s] = ldg_pinned(pk + 4 * s + n * 256);
                    rk[4][s] = ldg_pinned(pz + 4 * s);
                }
            }
            asm volatile("{\n.reg .pred p;\nsetp.eq.s32 p, %2, 0;\nmov.u32 %0, 0;\n@p ld.global.cg.u32 %0, [%1];\n}\n" : "=r"(done) : "l"(&g_sync[SY_DONE * 32]), "r"(lane) : "memory");
            bar_arrive(BAR_X, 384);
            if (warp == 0 && elect()) {
#pragma unroll
                for (int i = 0; i < 21; i++) mbar_init(bar_full + 8 * i, i < 9 ? 1 : i < 16 ? 4 : i == 20 ? 11 : SC_TAIL ? 4 : 8);
#pragma unroll
                for (int i = 0; i < 4; i++) mbar_init(bar_a + 8 * i, 1);
                mbar_expect_tx(bar_pin, QB_BYTES / 2 + 512); mbar_expect_tx(bar_pin + 8, QB_BYTES / 2);
                asm volatile("fence.mbarrier_init.release.cluster;\n" ::: "memory");
            }
            __syncwarp();
            asm volatile("barrier.cluster.arrive.relaxed.aligned;\n" ::: "memory");
            if (blockIdx.x < 128) {
                float c[5][4] = {};
#pragma unroll
                for (int s = 0; s < 2; s++) {
#pragma unroll
                    for (int n = 0; n < 5; n++) mma16816(c[n], ra[s].x, rb[s].x, ra[s].y, rb[s].y, rk[n][s].x, rk[n][s].y);
#pragma unroll
                    for (int n = 0; n < 5; n++) mma16816(c[n], ra[s].z, rb[s].z, ra[s].w, rb[s].w, rk[n][s].z, rk[n][s].w);
                }
#pragma unroll
                for (int i = 0; i < 4; i++) {
                    const int r = i & 2, n = (i & 1) * 2;
                    sts128(sb + SM_KV + 3 * KV_BYTES + QB_BYTES + i * 2048 + t * 16, __float_as_uint(c[n][r] - c[4][r]), __float_as_uint(c[n][r + 1] - c[4][r]),
                           __float_as_uint(c[n + 1][r] - c[4][r]), __float_as_uint(c[n + 1][r + 1] - c[4][r]));
                }
            }
        }
        asm volatile("setmaxnreg.dec.sync.aligned.u32 %0;\n" ::"n"(REG_P));
        if (blockIdx.x < 128) {
            bar_sync(BAR_WG2, 128);
            float4 v[4];
#pragma unroll
            for (int i = 0; i < 4; i++) v[i] = lds128f(sb + SM_KV + 3 * KV_BYTES + QB_BYTES + (warp & 2) * 2048 + (lane & 1) * 2048 + i * 512 + ((warp & 1) * 16 + (lane >> 1)) * 16);
            constexpr float SC = SCALE_LOG2 / KV_SCALE;
            const int r = (warp & 1) * 4 + (lane >> 3);
            *(uint2*)(g_w + tile_off((blockIdx.x >> 3) * 16 + (warp & 2) * 4 + r, (blockIdx.x & 7) * 4 + ((lane >> 1) & 3)) + (lane & 1) * 8) =
                make_uint2(pack_f16_sat(((v[0].x + v[1].x) + (v[2].x + v[3].x)) * SC, ((v[0].y + v[1].y) + (v[2].y + v[3].y)) * SC) | 1,
                           pack_f16_sat(((v[0].z + v[1].z) + (v[2].z + v[3].z)) * SC, ((v[0].w + v[1].w) + (v[2].w + v[3].w)) * SC) | 1);
            if (warp != 1) {
                bar_arrive(BAR_AUX, 128);
            } else {
                bar_sync(BAR_AUX, 128);
                if (elect()) { red_add(&g_sync[SY_DONE * 32 + 4 + (blockIdx.x >> 5)]); }
                __syncwarp();
            }
        }
        else bar_sync(BAR_WG2, 128);
        if (warp == 1) bar_arrive(BAR_GO, 160);
        auto load_a = [&](int j) {
            if (elect()) {
                mbar_expect_tx(bar_a + 8 * j, QB_BYTES);
                bulk_g2s(sb + SM_KV + j * KV_BYTES, g_w + j * QB_BYTES, QB_BYTES, bar_a + 8 * j);
            }
            __syncwarp();
        };
        if (warp == 0) {
            auto poll = [&]() { int c; asm volatile("ld.relaxed.gpu.global.s32 %0, [%1];\n" : "=r"(c) : "l"(&g_sync[SY_DONE * 32 + 4 + (lane & 3)]) : "memory"); return c; };
#pragma unroll 1
            for (int j = 0; j < 4;) {
#pragma unroll 1
                for (const uint32_t mk = __ballot_sync(~0u, poll() >= 32) & 15; (mk >> j) & 1; j++) load_a(j);
            }
        } else if (warp & 1) {
#pragma unroll 1
            for (int j = 0, n = 0; j < 4;) {
                mbar_wait_bounded(bar_a + 8 * j, n & 1);
                uint32_t ok = 1;
#pragma unroll
                for (int i = 0; i < 16; i++) {
                    uint32_t v;
                    asm volatile("ld.shared.u32 %0, [%1];\n" : "=r"(v) : "r"(sb + SM_KV + j * KV_BYTES + (warp & 2) * 8192 + i * 1024 + lane * 32 + g * 4) : "memory");
                    ok &= v;
                }
                asm volatile("{\n.reg .pred p;\nsetp.ne.u32 p, %0, 0;\nbar.red.and.pred p, %1, 64, p;\nselp.u32 %0, 1, 0, p;\n}\n" : "+r"(ok) : "n"((int)BAR_WG2) : "memory");
                if (__any_sync(~0u, ok)) {
                    if (warp == 1 && elect()) asm volatile("mbarrier.arrive.shared::cta.b64 _, [%0];\nmbarrier.inval.shared::cta.b64 [%1];\n" ::"r"(bar_full + 8 * j), "r"(bar_a + 8 * j) : "memory");
                    __syncwarp();
                    j++; n = 0;
                } else {
                    asm volatile("{\n.reg .pred p;\nsetp.gt.s32 p, %0, 1000000;\n@p trap;\n}\n" ::"r"(++n) : "memory");
                    fence_async_smem();
                    if (warp == 1) load_a(j);
                }
            }
        }
        done = __shfl_sync(~0u, done, 0);
        ep = (int)(done / NCTA) + 1;
        asm volatile("barrier.cluster.wait.acquire.aligned;\n" ::: "memory");
        if (warp == 0) {
            asm volatile("st.shared.u64 [%0], %1;\n" ::"r"(s_tm), "l"(&P.tm_outc) : "memory");
            __syncwarp();
            if (elect()) {
                const uint8_t* base = (const uint8_t*)H.s;
                uint32_t cls = SC_CLS, bytes = KV_BYTES, step = 5 * KV_BYTES;
                const uint8_t* src = base;
                bool tick;
                int next = 0;
                const int nit = SC_NKV + SC_NW;
#pragma unroll 1
                for (int j = 0; j < nit; j++) {
                    const uint32_t slot = sb + SM_KV + (j & 3) * KV_BYTES, fb = bar_full + 8 * (j & 3);
                    if (j == next) {
                        const int k = j - SC_NKV;
                        const int sw = SC_HELP ? j - 25 : -1;
                        next = j + 1;
                        tick = j >= 3 && k < 0 && (unsigned)sw >= 4 && !SC_TAIL;
                        if (j >= 3 && (unsigned)sw >= 5) next = k >= 0 ? next : j < GO0 ? GO0 : j < 25 ? 25 : j < GO1 ? GO1 : j < 49 ? 49 : j < 50 ? 50 : 75;
                        if (j == 0 || j == 25 || j == 50) { src = base + (4096 + (cls & 15) * KV_BYTES); cls >>= 4; }
                        if (SC_TAIL ? j == nit - 1 : j == GO0 || j == GO1) mbar_arrive(bar_go);
                        int fo = -1, fv = 1;
                        if (j < 3) { fo = (SY_H0 + 5 * j + (SC_CLS & 15)) * 32; fv = 5; }
                        if (j == 3) { fo = SY_H1 * 32; fv = 79; }
                        if (sw == 1) fo = 25 * 32 + SC_QT1;
                        if (k == 0) fo = SY_B * 32;
                        if (k == 1 && !SC_PAIR) { fo = SY_AUX0 * 32; fv = NAUX; }
                        if (k == 2 && SC_PAIR) { fo = SY_AUX * 32; fv = NAUX / 3; }
                        if (fo >= 0) {
                            flag_wait(g_sync + fo, fv * ep);
                            fence_async_global();
                        }
                        if (sw == 2 || (k == 2 && !SC_TAIL)) {
                            uint32_t qs = sw == 2 ? offsetof(Scratch, q) + (2 * SC_QT1 + 1) * QB_BYTES : SC_PAIR ? offsetof(Scratch, agg) + SC_ZB * QB_BYTES : offsetof(Scratch, part) + SC_QT0 * (4 * PART_BYTES);
#pragma unroll 1
                            for (int w = 0; w < (k == 2 && SC_PAIR ? 1 : 2); w++) {
                                mbar_wait_sleep(bar_qfree + 8 * w, k == 2 && SC_HELP);
                                mbar_expect_tx(bar_q + 8 * w, SC_PAIR ? QB_BYTES : PART_BYTES);
                                if (!SC_PAIR) bulk_g2s(sb + SM_ML + w * 512, base + (qs + (w ? -512 : QB_BYTES)), 512, bar_q + 8 * w);
                                bulk_g2s(sb + SM_Q + w * QB_BYTES, base + qs, QB_BYTES, bar_q + 8 * w);
                                qs += sw == 2 ? -QB_BYTES : PART_BYTES + 512;
                            }
                        }
                        if ((sw | 1) == 3) {
                            mbar_wait_sleep(bar_pdone + 8 * (sw - 2), 0);
                            bulk_s2g(g_part + (blockIdx.x - 3 + sw) * PART_BYTES, slot, PART_BYTES);
                            asm volatile("cp.async.bulk.wait_group.read 0;\n" ::: "memory");
                        }
                        if (sw == 5) {
                            asm volatile("cp.async.bulk.wait_group 0;\n" ::: "memory");
                            red_release(&g_sync[SY_PART * 32]);
                        }
                        if (k == 0) {
                            asm volatile("prefetch.tensormap [%0];\n" ::"l"(&P.tm_outc) : "memory");
                            src = g_w + (12 - SC_NW) * QB_BYTES; bytes = step = QB_BYTES;
                        }
                        if (k == 2) next = SC_TAIL ? nit - 1 : nit;
                    }
                    mbar_wait_sleep(fb + (bar_empty - bar_full), (j >> 2) & 1);
                    mbar_expect_tx(fb, bytes);
                    if (tick)
                        asm volatile("{\n.reg .pred p;\n.reg .u32 a, b, c;\nmov.u32 c, 1;\nmov.u32 a, %%globaltimer_lo;\nnot.b32 b, a;\nand.b32 b, b, %0;\nshr.u32 b, b, 1;\nnanosleep.u32 b;\n"
                                     "L:\nmov.u32 b, %%globaltimer_lo;\nlop3.b32 b, b, a, c, 0xBE;\nadd.u32 c, c, %2;\nsetp.le.u32 p, b, %0;\n@p nanosleep.u32 %1;\n@p bra L;\n}\n" ::"n"(TICK - 1), "n"(TSL), "n"(TICK / 32) : "memory");
                    bulk_g2s(slot, src, bytes, fb);
                    src += step;
                }
            }
        } else {
            if (warp == 2 && SC_OWNER) {
                uint8_t* dst = g_hz + 4096 + h_unit(SC_QT0, 0) * 8192;
                auto send = [&](int u0, int u1) {
#pragma unroll
                    for (int u = u0; u < u1; u++) {
                        bulk_s2g(dst + u * (78 * 8192), sb + SM_Q + u * 8192, 8192);
                        asm volatile("cp.async.bulk.wait_group 0;\n" ::: "memory");
                    }
                };
                int* f0 = &g_sync[(SY_H0 + SC_QT0 / 5) * 32];
                bar_sync(BAR_H0, 64);
                if (elect()) {
                    send(0, 1);
                    if (SC_QT0 < 65) red_release(f0);
                }
                bar_sync(BAR_H1, 160);
                if (elect()) {
                    if (!SC_TAIL) send(1, 4);
                    mbar_arrive(bar_q);
                }
                bar_sync(BAR_H2, 160);
                if (elect()) {
                    if (!SC_TAIL) { send(4, 8); mbar_arrive(bar_q + 8); }
                    red_release(&g_sync[SY_H1 * 32]);
                }
                __syncwarp();
            }
        }
    } else {
        const uint32_t sq = sb + SM_Q + wg * QB_BYTES;
        const uint32_t qbar = bar_q + 8 * wg;
        const uint32_t dq0 = __shfl_sync(~0u, ((sq & 0x3FFFF) >> 4) | (64u << 16), 0);
        const uint32_t dk0 = __shfl_sync(~0u, (((sb + SM_KV) & 0x3FFFF) >> 4) | (64u << 16), 0);
        float o[128];
        int it = 4;
        const uint32_t dhi = P.dhi;
        auto release = [&](int st, int n = 1) {
            if (n == 1) asm volatile("{\n.reg .pred p;\nelect.sync _|p, -1;\n@p mbarrier.arrive.shared::cta.b64 _, [%0];\n}\n" ::"r"(bar_empty + 8 * st) : "memory");
            else asm volatile("{\n.reg .pred p;\nelect.sync _|p, -1;\n@p mbarrier.arrive.shared::cta.b64 _, [%0], 2;\n}\n" ::"r"(bar_empty + 8 * st) : "memory");
        };
        const bool active = !(SC_TAIL && wg == 1);
        auto pp_sync = [&]() { if (!SC_TAIL) bar_sync(BAR_PP0 + wg, 256); };
        auto pp_arrive = [&]() { if (!SC_TAIL) bar_arrive(BAR_PP1 - wg, 256); };
        auto warp_arrive = [&](uint32_t bar) {
            __syncwarp();
            asm volatile("{\n.reg .pred p;\nelect.sync _|p, -1;\n@p mbarrier.arrive.shared::cta.b64 _, [%0];\n}\n" ::"r"(bar + 8 * wg) : "memory");
        };
        auto peer_arrive = [&]() {
            asm volatile("{\n.reg .pred p;\n.reg .b32 a;\nelect.sync _|p, -1;\nmapa.shared::cluster.u32 a, %0, %1;\n"
                         "@p mbarrier.arrive.shared::cluster.b64 _, [a];\n}\n" ::"r"(bar_rfree), "r"(rank ^ 1) : "memory");
        };
        auto cut = [&]() { asm volatile("{\n.reg .pred p;\nsetp.lt.s32 p, %0, 0;\nL:\n@p pmevent 0;\n@p bra L;\n}\n" ::"r"(dhi) : "memory"); };
        float qs = 1.f;
        uint32_t qr[4 * NQR];
        auto stage_q = [&]() {
            int k = dhi & 1;
            uint32_t big;
#pragma unroll 1
            do {
                if (k) {
                    qs *= 16.f;
#pragma unroll
                    for (int i = 0; i < 128; i++) o[i] *= 0.0625f;
                }
                big = 0;
                auto pk = [&](int i) { return QRND(pack_f16_sat(o[i], o[i + 1])); };
#pragma unroll
                for (int i = 0; i < 16; i++) {
                    if (QREG(i) >= 0) continue;
                    const uint32_t v0 = pk(8 * i), v1 = pk(8 * i + 2), v2 = pk(8 * i + 4) | (i == 15 ? k : 0), v3 = pk(8 * i + 6);
                    stmatrix_x4(sq + warp * 8192 + tile_off(lane & 15, 2 * i + (lane >> 4)), v0, v1, v2, v3);
                    big |= v0 | v1; big |= v2 | v3;
                    if (i == 15) cut();
                }
#pragma unroll
                for (int i = 0; i < 64; i++)
                    if (const int r = QREG(i / 4); r >= 0) big |= qr[4 * r + (i & 3)] = pk(2 * i);
                k++;
            } while (__any_sync(~0u, (big & 0x40004000u) && k < 8));
        };
        uint32_t s[20];
        auto issue_qk = [&](int st, int sh = 24) {
            const uint64_t kb = mkaddr(dk0 + st * (KV_BYTES >> 4), dhi);
            const uint64_t qd = mkaddr(dq0 + ((uint32_t)it >> sh), dhi);
            wgmma_ss_n80_init(s, qd, kb);
#pragma unroll
            for (int j = 1; j < 16; j++) {
                const int kk = j == 8 ? 15 : j < 8 ? j : j - 1;
                const int r = QREG(kk);
                if (r >= 0) wgmma_rs_n80(s, qr[4 * r], qr[4 * r + 1], qr[4 * r + 2], qr[4 * r + 3], kb + ((kk >> 2) * 64 + (kk & 3) * 2));
                else wgmma_ss_n80(s, qd + ((kk >> 2) * 64 + (kk & 3) * 2), kb + ((kk >> 2) * 64 + (kk & 3) * 2));
            }
            wg_commit();
        };

        {
            const int rb = (2 * SC_QT0 + wg) * 64 + warp * 16;
            const uint32_t xbar = bar_x + 32 * wg + 8 * warp;
            if (elect()) {
                mbar_init(xbar, 1);
                asm volatile("fence.mbarrier_init.release.cluster;\nfence.proxy.async.shared::cta;\n" ::: "memory");
                mbar_expect_tx(xbar, rb < NN ? 8192 : 0);
            }
            asm volatile("barrier.cluster.arrive.relaxed.aligned;\n" ::: "memory");
            if (wg == 1) pp_arrive();
            bar_sync(BAR_X, 384);
            if (wg == 1) bar_sync(BAR_GO, 160);
            if (rb < NN && elect()) bulk_g2s(sq + warp * 8192, H.x + (size_t)rb * 256, 8192, xbar);
            if (rb >= NN) {
#pragma unroll 1
                for (int i = 0; i < 16; i++) sts128(sq + warp * 8192 + i * 512 + lane * 16, 0, 0, 0, 0);
            }
            __syncwarp();
            mbar_wait(xbar, 0);
            uint4 xa[8], xb[8];
#pragma unroll
            for (int s = 0; s < 8; s++) {
                xa[s] = lds128(sq + (warp * 16 + g) * 512 + (4 * s + q) * 16);
                xb[s] = lds128(sq + (warp * 16 + g + 8) * 512 + (4 * s + q) * 16);
            }
            float sm[2][4], sq2[2][4][4];
#pragma unroll
            for (int i = 0; i < 4; i++) {
                sm[0][i] = sm[1][i] = 0.f;
#pragma unroll
                for (int k = 0; k < 4; k++) sq2[0][k][i] = sq2[1][k][i] = 0.f;
            }
#pragma unroll
            for (int s = 0; s < 8; s++) {
#pragma unroll
                for (int hh = 0; hh < 2; hh++) {
                    const uint4 v = hh ? xb[s] : xa[s];
                    mma16816(sm[hh], v.x, v.y, v.z, v.w, 0x3F803F80u, 0x3F803F80u);
                    mma1688(sq2[hh][0], v.x, v.y, v.x); mma1688(sq2[hh][1], v.x, v.y, v.y);
                    mma1688(sq2[hh][2], v.z, v.w, v.z); mma1688(sq2[hh][3], v.z, v.w, v.w);
                }
            }
            float inv[2], off[2];
#pragma unroll
            for (int hh = 0; hh < 2; hh++) {
                const float mean = (sm[hh][0] + sm[hh][2]) * (1.f / 256.f);
                const float d0 = (sq2[hh][0][0] + sq2[hh][2][0]) + (sq2[hh][1][2] + sq2[hh][3][2]);
                const float d1 = (sq2[hh][0][1] + sq2[hh][2][1]) + (sq2[hh][1][3] + sq2[hh][3][3]);
                const float ss = __shfl_sync(~0u, (g & 1) ? d1 : d0, g * 4 + (g >> 1));
                const float var = fmaxf(ss * (1.f / 256.f) - mean * mean, 0.f);
                float sd;
                asm("sqrt.approx.ftz.f32 %0, %1;\n" : "=f"(sd) : "f"(bf_round(bf_round(var) + 1e-5f)));
                asm("rcp.approx.ftz.f32 %0, %1;\n" : "=f"(inv[hh]) : "f"(bf_round(sd)));
                off[hh] = -mean * inv[hh];
            }
            uint32_t a[64];
#pragma unroll
            for (int s = 0; s < 8; s++) {
                a[8 * s] = xa[s].x; a[8 * s + 1] = xb[s].x; a[8 * s + 2] = xa[s].y; a[8 * s + 3] = xb[s].y;
                a[8 * s + 4] = xa[s].z; a[8 * s + 5] = xb[s].z; a[8 * s + 6] = xa[s].w; a[8 * s + 7] = xb[s].w;
            }
            fence_regs(a);
            if (wg == 1 && __any_sync(~0u, inv[0] + inv[1] != -1.f)) bar_arrive(BAR_ST, 256);
            asm volatile("setmaxnreg.inc.sync.aligned.u32 %0;\n" ::"n"(REG_C));
            fence_regs(a);
#pragma unroll
            for (int i = 0; i < 64; i++)
                a[i] = pack_f16(fmaf(bf_lo(a[i]), inv[i & 1], off[i & 1]), fmaf(bf_hi(a[i]), inv[i & 1], off[i & 1]));
            if (SC_OWNER) {
                const uint32_t ko = (q & 2) ? KV_OFF2 : KV_OFF2 | NEG2;
#pragma unroll
                for (int i = 0; i < 16; i++) {
                    const uint32_t mk = (i == 15 && q == 3) ? 0xFFFFu : ~0u;
                    stmatrix_x4(sq + warp * 8192 + tile_off(lane & 15, 2 * i + (lane >> 4)), kvf(a[4 * i], ko), kvf(a[4 * i + 1], ko),
                                kvf(a[4 * i + 2] & mk, ko), kvf(a[4 * i + 3] & mk, ko));
                }
                fence_async_smem();
                if (tid < 32) bar_arrive(BAR_H0, 64);
                bar_arrive(wg ? BAR_H2 : BAR_H1, 160);
            }
            asm volatile("barrier.cluster.wait.acquire.aligned;\n" ::: "memory");
            if (wg == 0) bar_sync(BAR_ST, 256);
            if (active) {
                fence_regs(a);
#pragma unroll
                for (int c = 0; c < 4; c++) {
                    if (c == 1) {
                        if (wg == 1) {
                            wg_wait<0>();
                            release(0);
                        }
                        pp_sync();
                    }
                    mbar_wait(bar_full + 8 * c, 0);
                    const uint64_t wb = mkaddr(dk0 + c * (KV_BYTES >> 4), dhi);
                    wg_fence();
#pragma unroll
                    for (int kk = 0; kk < 4; kk++) {
                        if (c | kk) wgmma_rs_n256_tb(o, a[16 * c + 4 * kk], a[16 * c + 4 * kk + 1], a[16 * c + 4 * kk + 2], a[16 * c + 4 * kk + 3], wb + kk * 512);
                        else wgmma_rs_n256_tb_init(o, a[0], a[1], a[2], a[3], wb);
                    }
                    wg_commit();
                    if (c > 0) { wg_wait<1>(); if (c > 1 || wg == 0) release(c - 1); }
                }
                if (wg == 0) pp_arrive();
                wg_wait<0>();
                fence_regs(o);
                release(3);
                if (SC_OWNER) mbar_wait(qbar, 0);
                stage_q();
                fence_async_smem();
                bar_sync(BAR_WG0 + wg, 128);
                mbar_wait(bar_full, 1);
                wg_fence();
                issue_qk(0);
                if (wg == 1) pp_arrive();
                if (SC_PAIR && !rank) {
#pragma unroll
                    for (int i = 0; i < 16; i++)
                        if (const int r = QREG(i); r >= 0)
                            stmatrix_x4(sq + warp * 8192 + tile_off(lane & 15, 2 * i + (lane >> 4)), qr[4 * r], qr[4 * r + 1], qr[4 * r + 2], qr[4 * r + 3]);
                }
            } else {
                peer_arrive();
            }
        }

        uint32_t p[20];
        float m0 = 0.f, m1 = 0.f, e0, e1, l0, l1;
        uint32_t plim;
        uint32_t qphase = (SC_OWNER && active) ? 1 : 0;
        auto issue_pv = [&](int st, int acc) {
            const uint64_t vb = mkaddr(dk0 + st * (KV_BYTES >> 4), dhi);
            wgmma_rs_n256_tb_pred(o, p[0], p[1], p[2], p[3], vb, acc);
#pragma unroll
            for (int kk = 1; kk < 5; kk++)
                wgmma_rs_n256_tb(o, p[4 * kk], p[4 * kk + 1], p[4 * kk + 2], p[4 * kk + 3], vb + kk * 512);
            wg_commit();
        };
        auto mq_addr = [&](int ln) { return sq + warp * 8192 + tile_off(ln >> 2, 31) + 12; };
        auto exceeds = [&](const uint32_t (&p)[20]) {
            uint32_t a = __vimax3_s16x2(S_LIMIT, p[0], p[1]), b = __vimax3_s16x2(p[2], p[3], p[4]);
#pragma unroll
            for (int i = 5; i < 17; i += 4) { a = __vimax3_s16x2(a, p[i], p[i + 1]); b = __vimax3_s16x2(b, p[i + 2], p[i + 3]); }
            a = __vimax3_s16x2(a, p[17], p[18]);
            return __any_sync(~0u, __vimax3_s16x2(a, b, p[19]) != plim);
        };
        auto remax = [&](float& a, float& b, bool store) {
            const int ln = lane_now();
            asm volatile("" : "+f"(qs));
            uint32_t ha = s[0], hb = s[1];
#pragma unroll
            for (int i = 1; i < 10; i++) { ha = hmax2_f16(ha, s[2 * i]); hb = hmax2_f16(hb, s[2 * i + 1]); }
            ha = hmax2_f16(__byte_perm(ha, hb, 0x5410), __byte_perm(ha, hb, 0x7632));
            ha = hmax2_f16(ha, __shfl_xor_sync(~0u, ha, 1));
            ha = hmax2_f16(ha, __shfl_xor_sync(~0u, ha, 2));
            a = fmaxf(a, f16_lo(ha) * qs - e0 + REF_UP); b = fmaxf(b, f16_hi(ha) * qs - e1 + REF_UP);
            const float qi = __uint_as_float(0x7F000000u - __float_as_uint(qs)) * (-1.f / KV_OFF);
            const uint32_t u = pack_f16((m0 + a) * qi, (m1 + b) * qi);
            const float g0 = (m0 + a) + KV_OFF * qs * f16_lo(u), g1 = (m1 + b) + KV_OFF * qs * f16_hi(u);
            const bool x0 = fabsf(g0) <= 1.f, x1 = fabsf(g1) <= 1.f;
            if (x0) a -= g0;
            if (x1) b -= g1;
            const float da = a + e0, db = b + e1;
            m0 += a; m1 += b;
            e0 = x0 ? 0.f : g0; e1 = x1 ? 0.f : g1;
            plim = (x0 && x1 && qs == 1.f) ? S_LIMIT : 0u;
            asm volatile("{\n.reg .pred p;\nsetp.ne.s32 p, %3, 0;\n@p st.shared.u16 [%0], %1;\n@p st.shared.u16 [%0 + 4096], %2;\n}\n"
                         ::"r"(mq_addr(ln) + 2), "h"((unsigned short)u), "h"((unsigned short)(u >> 16)), "r"((int)(store && (ln & 3) == 0)) : "memory");
#pragma unroll
            for (int i = 0; i < 10; i++) {
                p[2 * i] = pack_f16(ex2(fmaf(f16_lo(s[2 * i]), qs, -da)), ex2(fmaf(f16_hi(s[2 * i]), qs, -da)));
                p[2 * i + 1] = pack_f16(ex2(fmaf(f16_lo(s[2 * i + 1]), qs, -db)), ex2(fmaf(f16_hi(s[2 * i + 1]), qs, -db)));
            }
            fence_regs(p);
            fence_async_smem();
            __syncwarp();
        };

        auto row_sums = [&](float& z0, float& z1, int q) {
            z0 = quad_last(o[125]); z1 = quad_last(o[127]);
            l0 = z0 * (KV_SCALE / KV_OFF); l1 = z1 * (KV_SCALE / KV_OFF);
            if (!(q & 2)) { z0 = -z0; z1 = -z1; }
        };
        auto stats = [&](int q) { return (q & 2) ? ((q & 1) ? l1 : m1) : ((q & 1) ? l0 : m0); };
        const int nseg = SC_HELP ? 2 : 1;
        if (active) {
#pragma unroll 1
        for (int seg = 0;; seg++) {
            wg_wait<0>();
            fence_regs(s);
            e0 = e1 = 0.f;
            const int it0 = it, itl = __shfl_sync(~0u, seg + 1 < nseg ? 3 + 25 : 3 + SC_NKV, 0);
            const int itx = (wg == 1 && seg + 1 == nseg) ? itl : -1;
            bool redo = true, have = !seg;
#pragma unroll 1
            for (;;) {
                if (!have) {
#pragma unroll
                    for (int i = 0; i < 20; i++) p[i] = ex2_f16(s[i]);
                    redo = exceeds(s);
                }
                if (redo) {
                    float d0 = it != it0 ? 0.f : -INFINITY, d1 = d0;
                    remax(d0, d1, it != itl);
                    if (it != it0) {
                        const float a0 = ex2(-d0), a1 = ex2(-d1);
#pragma unroll
                        for (int i = 0; i < 32; i++) { o[4 * i] *= a0; o[4 * i + 1] *= a0; o[4 * i + 2] *= a1; o[4 * i + 3] *= a1; }
                    } else if (SC_OWNER) {
                        warp_arrive(bar_pdone);
                    }
                }
                if (it == itl) break;
                const int stp = it & 3;
                it++;
                pp_sync();
                fence_regs(o); fence_regs(p);
                have = SC_TAIL || it == itx;
                if (!have) {
                    wg_fence();
                    issue_pv(stp, it - 1 - it0);
                    mbar_wait(bar_full + 8 * (it & 3), (it >> 2) & 1);
                    wg_fence();
                    issue_qk(it & 3);
                    pp_arrive();
                    wg_wait<0>();
                    fence_regs(s); fence_regs(o); fence_regs(p);
                    if (it == itl) warp_arrive(bar_qfree);
                } else {
                    const int zero = (uint32_t)it >> 23;
                    mbar_wait(bar_full + 8 * (it & 3), (it >> 2) & 1);
                    wg_fence();
                    issue_qk((it & 3) + zero, 25);
                    if (it == itl) {
                        wg_wait<0>();
                        if (SC_PAIR) peer_arrive(); else warp_arrive(bar_qfree);
                        if (wg) bar_sync(BAR_ST, 256);
                    }
                    wg_fence();
                    issue_pv(stp + zero, it - 1 - it0);
                    pp_arrive();
                    wg_wait<1>();
                    fence_regs(s);
                    redo = exceeds(s);
                    if (!redo) {
#pragma unroll
                        for (int i = 0; i < 20; i++) s[i] = ex2_f16(s[i]);
                        fence_regs(s);
                        cut();
                    }
                    wg_wait<0>();
                    fence_regs(o); fence_regs(p);
#pragma unroll
                    for (int i = 0; i < 20; i++) p[i] = s[i];
                }
                release(stp);
            }
            if (seg + 1 < nseg) pp_sync();
            fence_regs(o); fence_regs(p);
            wg_fence();
            issue_pv(it & 3, 1);
            asm volatile("{\n.reg .pred p;\nsetp.ne.s32 p, %0, 0;\n@p bar.arrive %1, 256;\n}\n" ::"r"((int)(seg + 1 == nseg && (wg ? SC_PAIR : !SC_TAIL))), "r"(BAR_ST + wg) : "memory");
            it++;
            if (seg + 1 == nseg) break;
            constexpr int IS = 4 + 25;
            const int ln = lane_now();
            uint32_t qa = sq + warp * 8192 + tile_off(ln & 15, ln >> 4);
            asm volatile("" : "+r"(qa));
            mbar_wait(bar_full + 8 * (IS & 3), (IS >> 2) & 1);
            mbar_wait(qbar, 0); qphase = 1;
#pragma unroll
            for (int i = 0; i < 16; i++)
                if (const int r = QREG(i); r >= 0)
                    asm volatile("ldmatrix.sync.aligned.m8n8.x4.shared.b16 {%0, %1, %2, %3}, [%4];\n" : "=r"(qr[4 * r]), "=r"(qr[4 * r + 1]), "=r"(qr[4 * r + 2]), "=r"(qr[4 * r + 3])
                                 : "r"((qa ^ (i & 3) * 32) + (i >> 2) * 1024) : "memory");
            fence_regs(qr);
            wg_fence();
            issue_qk(it & 3);
            wg_wait<1>();
            pp_arrive();
            fence_regs(o);
            float z0, z1;
            row_sums(z0, z1, ln);
            release((IS - 1) & 3);
            uint32_t u0, u1;
            asm volatile("ld.shared.u32 %0, [%2];\nld.shared.u32 %1, [%2 + 4096];\n" : "=r"(u0), "=r"(u1) : "r"(mq_addr(ln)) : "memory");
            const uint32_t slot = sb + SM_KV + ((IS - 2 + wg) & 3) * KV_BYTES;
            const uint32_t dst = slot + wg * 512 + warp * 8192 + ln * 16, dml = slot + (wg ? 0 : QB_BYTES) + warp * 128 + ln * 4;
#pragma unroll
            for (int i = 0; i < 128; i++) o[i] -= (i & 2) ? z1 : z0;
            fence_regs(o);
            mbar_wait(bar_empty + 8 * ((IS - 2 + wg) & 3), ((IS - 2 + wg) >> 2) & 1);
            asm volatile("st.shared.f32 [%0], %1;\n" ::"r"(dml), "f"(stats(ln)) : "memory");
            qs = __uint_as_float(0x3F800000u + ((u0 & 7) << 25));
            m0 = -KV_OFF * qs * f16_hi(u0); m1 = -KV_OFF * qs * f16_hi(u1);
            plim = fmaxf(fabsf(m0), fabsf(m1)) <= 3072.f && qs == 1.f ? S_LIMIT : 0u;
            uint32_t v[2][8] = {};
#pragma unroll
            for (int i = 0; i < 8; i++) {
                uint32_t *w = v[i & 1], *u = v[(i & 1) ^ 1];
#pragma unroll
                for (int j = 0; j < 8; j++) w[j] = pack_bf16(o[16 * i + 2 * j], o[16 * i + 2 * j + 1]);
                sts128(dst + i * 1024, w[0], w[1], w[2], w[3]);
                sts128(dst + i * 1024 + 512, w[4], w[5], w[6], w[7]);
                if (i) asm volatile("{\n.reg .pred p;\nsetp.lt.s32 p, %9, 0;\nL:\n@p st.shared.v4.u32 [%0], {%1, %2, %3, %4};\n@p st.shared.v4.u32 [%0 + 16], {%5, %6, %7, %8};\n@p bra L;\n}\n"
                             ::"r"(dst), "r"(u[0]), "r"(u[1]), "r"(u[2]), "r"(u[3]), "r"(u[4]), "r"(u[5]), "r"(u[6]), "r"(u[7]), "r"(it) : "memory");
            }
            fence_async_smem();
            warp_arrive(bar_pdone);
        }
        constexpr int IW = 4 + 75;
        uint32_t a[64];
        const int lane = lane_now(), t = warp * 32 + lane;
        if (wg == 0 && (SC_PAIR || SC_LAST)) {
            uint32_t rq, rml, rbar;
            asm volatile("mapa.shared::cluster.u32 %0, %3, %6;\nmapa.shared::cluster.u32 %1, %4, %6;\nmapa.shared::cluster.u32 %2, %5, %6;\n"
                         : "=r"(rq), "=r"(rml), "=r"(rbar) : "r"(sb + SM_Q + QB_BYTES + warp * 8192 + lane * 16), "r"(sb + SM_ML + 512 + t * 4),
                         "r"(bar_pin), "r"(rank ^ 1));
            auto send = [&](int i) {
                asm volatile("st.async.weak.shared::cluster.mbarrier::complete_tx::bytes.v4.b32 [%0], {%1, %2, %3, %4}, [%5];\n"
                             ::"r"(rq + i * 512), "r"(a[4 * i]), "r"(a[4 * i + 1]), "r"(a[4 * i + 2]), "r"(a[4 * i + 3]), "r"(rbar + (i & 8)) : "memory");
            };
            mbar_wait(bar_rfree, 0);
            wg_wait<0>();
            fence_regs(o);
            release((it - 1) & 3);
            float z0, z1;
            row_sums(z0, z1, lane);
            asm volatile("st.async.weak.shared::cluster.mbarrier::complete_tx::bytes.f32 [%0], %1, [%2];\n" ::"r"(rml), "f"(stats(lane)), "r"(rbar) : "memory");
#pragma unroll
            for (int i = 0; i < 16; i++) {
                a[4 * i] = pack_bf16(o[8 * i] - z0, o[8 * i + 1] - z0); a[4 * i + 1] = pack_bf16(o[8 * i + 2] - z1, o[8 * i + 3] - z1);
                a[4 * i + 2] = pack_bf16(o[8 * i + 4] - z0, o[8 * i + 5] - z0); a[4 * i + 3] = pack_bf16(o[8 * i + 6] - z1, o[8 * i + 7] - z1);
                if (i * SND0 / 16 != (i + 1) * SND0 / 16) send(i * SND0 / 16);
                if (i % CUT2 == CUT2 - 1) cut();
            }
            if (SC_PAIR) {
                float z[128];
                const uint32_t dkz = dk0 + ((uint32_t)it >> 24), dqz = dq0 + ((uint32_t)it >> 24);
                auto gemm = [&](int c) {
                    mbar_wait(bar_full + 8 * ((IW + c) & 3), ((IW + c) >> 2) & 1);
                    const uint64_t wb = mkaddr(dkz + ((IW + c) & 3) * (KV_BYTES >> 4), dhi), ab = mkaddr(dqz + c * 64, dhi);
                    wg_fence();
#pragma unroll
                    for (int kk = 0; kk < 4; kk++) {
                        if (c | kk) wgmma_ss_n256_tb(z, ab + kk * 2, wb + kk * 512);
                        else wgmma_ss_n256_tb_init(z, ab, wb);
                    }
                    wg_commit();
                };
                mbar_wait(qbar, qphase);
                bar_sync(BAR_ST + 1, 256);
                gemm(0);
#pragma unroll
                for (int i = SND0; i < 16; i++) send(i);
#pragma unroll
                for (int c = 1; c < 4; c++) { gemm(c); if (c == 3) pp_arrive(); wg_wait<1>(); release((IW + c - 1) & 3, 2); }
                wg_wait<0>();
                fence_regs(z);
                release((IW + 3) & 3, 2);
#pragma unroll
                for (int i = 0; i < 16; i++) {
                    sts128(sq + warp * 8192 + lane * 16 + i * 512, pack_bf16(z[8 * i], z[8 * i + 1]), pack_bf16(z[8 * i + 2], z[8 * i + 3]),
                           pack_bf16(z[8 * i + 4], z[8 * i + 5]), pack_bf16(z[8 * i + 6], z[8 * i + 7]));
                    if (i == 3 || i == 15) bar_arrive(i == 3 ? BAR_BF : BAR_H0, 256);
                    if (i == 3) cut();
                }
            } else {
#pragma unroll
                for (int i = SND0; i < 16; i++) send(i);
            }
        } else {
            const int pair = SC_PAIR;
            const bool glob = !(pair || SC_TAIL);
            const uint32_t ml = sb + SM_ML + (t & ~3) * 4, src = (glob ? sq : sb + SM_Q + QB_BYTES) + warp * 8192 + lane * 16;
            const uint64_t tm = lds64(s_tm);
            wg_wait<0>();
            fence_regs(o);
            release((IW - 1) & 3);
            float c0, c1;
            row_sums(c0, c1, lane);
            mbar_wait(glob ? qbar : bar_pin, glob ? qphase : 0);
            const float4 ps = lds128f(ml + (glob ? wg * 512 : 512));
            auto load = [&](int i) {
                asm volatile("ld.shared.v4.u32 {%0, %1, %2, %3}, [%4];\n" : "=r"(a[4 * i]), "=r"(a[4 * i + 1]), "=r"(a[4 * i + 2]), "=r"(a[4 * i + 3]) : "r"(src + i * 512) : "memory");
            };
#pragma unroll
            for (int i = 0; i < 8; i++) load(i);
            const float n0 = fmaxf(m0, ps.x), n1 = fmaxf(m1, ps.z);
            const float a0 = ex2(m0 - n0), a1 = ex2(m1 - n1), b0 = ex2(ps.x - n0), b1 = ex2(ps.z - n1);
            const float i0 = rcp(l0 * a0 + ps.y * b0), i1 = rcp(l1 * a1 + ps.w * b1);
            const float r0 = a0 * i0, r1 = a1 * i1;
            c0 *= -r0; c1 *= -r1;
            const uint32_t u0 = pack_bf16(b0 * i0, b0 * i0), u1 = pack_bf16(b1 * i1, b1 * i1);
#pragma unroll
            for (int i = 0; i < 32; i++) {
                if (i == 16) {
                    if (!glob) mbar_wait(bar_pin + 8, 0);
#pragma unroll
                    for (int j = 8; j < 16; j++) load(j);
                }
                a[2 * i] = hfma2(a[2 * i], u0, pack_bf16(fmaf(o[4 * i], r0, c0), fmaf(o[4 * i + 1], r0, c0)));
                a[2 * i + 1] = hfma2(a[2 * i + 1], u1, pack_bf16(fmaf(o[4 * i + 2], r1, c1), fmaf(o[4 * i + 3], r1, c1)));
            }
            float y[2][32];
            auto gemm = [&](int c, int kh) {
                if (!kh) mbar_wait(bar_full + 8 * ((IW + c) & 3), (((IW + c) >> 2) & 1) ^ pair);
                const uint64_t wb = mkaddr(dk0 + ((IW + c) & 3) * (KV_BYTES >> 4), dhi - 192);
                wg_fence();
#pragma unroll
                for (int kk = 8 * kh; kk < 8 * kh + 8; kk++) {
                    if (kk) wgmma_rs_n64_tb(y[c & 1], a[4 * kk], a[4 * kk + 1], a[4 * kk + 2], a[4 * kk + 3], wb + kk * 128);
                    else wgmma_rs_n64_tb_init(y[c & 1], a[0], a[1], a[2], a[3], wb);
                }
                wg_commit();
            };
            const uint32_t stg = sq + warp * 8192 + (lane & 15) * 128 + (((lane >> 4) ^ lane) & 7) * 16;
            uint4 z[4] = {};
            auto load_z = [&](int cb) {
                if (cb < 2) asm volatile("{\n.reg .pred p;\nsetp.ne.s32 p, %0, 0;\n@p bar.sync %1, 256;\n}\n" ::"r"(pair), "r"(cb ? BAR_H0 : BAR_BF) : "memory");
#pragma unroll
                for (int i = 0; i < 4; i++)
                    asm volatile("{\n.reg .pred p;\nsetp.ne.u32 p, %4, 0;\n@p ld.shared.v4.u32 {%0, %1, %2, %3}, [%5];\n}\n"
                                 : "+r"(z[i].x), "+r"(z[i].y), "+r"(z[i].z), "+r"(z[i].w) : "r"(pair), "r"(src - QB_BYTES + (4 * cb + i) * 512) : "memory");
            };
            pp_sync();
            gemm(0, 0);
            gemm(0, 1);
#pragma unroll
            for (int c = 0; c < 4; c++) {
                if (c) load_z(c);
                if (c < 3) gemm(c + 1, 0);
                if (!c) load_z(0);
                if (c < 3) wg_wait<1>(); else wg_wait<0>();
                fence_regs(y[c & 1]);
                const float* x = y[c & 1];
#pragma unroll
                for (int i = 0; i < 4; i++)
                    stmatrix_x4((stg ^ (32 * i)) + c * 2048, hadd2(pack_bf16(x[8 * i], x[8 * i + 1]), z[i].x), hadd2(pack_bf16(x[8 * i + 2], x[8 * i + 3]), z[i].y),
                                hadd2(pack_bf16(x[8 * i + 4], x[8 * i + 5]), z[i].z), hadd2(pack_bf16(x[8 * i + 6], x[8 * i + 7]), z[i].w));
                if (c < 3) gemm(c + 1, 1);
                fence_async_smem();
                __syncwarp();
                asm volatile("{\n.reg .pred p;\nelect.sync _|p, -1;\n"
                             "@p cp.reduce.async.bulk.tensor.4d.global.shared::cta.add.tile.bulk_group [%0, {0, 0, %1, %2}], [%3];\n}\n"
                             ::"l"(tm), "r"(c), "r"((pair ? SC_ZB : 2 * SC_QT0 + wg) * 8 + warp * 2), "r"(sq + warp * 8192 + c * 2048) : "memory");
                if (c == 2 && glob) pp_arrive();
            }
            asm volatile("cp.async.bulk.commit_group;\ncp.async.bulk.wait_group.read 0;\n" ::: "memory");
        }
        } else {
            wg_wait<0>();
        }
        if (SC_TAIL) {
        float o[128];
        const int lane = lane_now(), t = warp * 32 + lane, q = lane & 3;
        auto emit = [&](uint32_t base, int lane, int row0, uint8_t* wdst, int turn) {
#pragma unroll
            for (int hh = 0; hh < 2; hh++) {
                if (turn > 0) mbar_wait(bar_zst + 8 * hh, (turn - 1) & 1);
#pragma unroll
                for (int i = 0; i < 8; i++)
                    stmatrix_x4(base + tile_off(8 * hh + (lane & 7), 4 * i + (lane >> 3)),
                                pack_bf16(o[16 * i + 2 * hh], o[16 * i + 2 * hh + 1]), pack_bf16(o[16 * i + 4 + 2 * hh], o[16 * i + 5 + 2 * hh]),
                                pack_bf16(o[16 * i + 8 + 2 * hh], o[16 * i + 9 + 2 * hh]), pack_bf16(o[16 * i + 12 + 2 * hh], o[16 * i + 13 + 2 * hh]));
                fence_async_smem();
                __syncwarp();
                if (wdst) {
                    if (lane < 4)
                        asm volatile("cp.async.bulk.global.shared::cta.bulk_group [%0], [%1], 1024;\n"
                                     ::"l"(wdst + ((turn & 1) ? hh * 4096 + lane * 1024 : hh * 1024 + lane * QB_BYTES)), "r"(base + hh * 4096 + lane * 1024) : "memory");
                    asm volatile("cp.async.bulk.commit_group;\n" ::: "memory");
                } else {
                    asm volatile("{\n.reg .pred p;\nsetp.eq.s32 p, %3, 0;\n"
                                 "@p cp.reduce.async.bulk.tensor.4d.global.shared::cta.add.tile.bulk_group [%0, {0, 0, 0, %1}], [%2];\n"
                                 "cp.async.bulk.commit_group;\n}\n"
                                 ::"l"(&P.tm_out), "r"((row0 >> 3) + hh), "r"(base + hh * 4096), "r"(lane) : "memory");
                }
            }
            asm volatile("cp.async.bulk.wait_group.read 1;\n" ::: "memory");
            warp_arrive(bar_zst - 8 * wg);
        };
        auto emit_done = [&](bool pending) {
            asm volatile("cp.async.bulk.wait_group.read 0;\n" ::: "memory");
            __syncwarp();
            asm volatile("{\n.reg .pred p;\nsetp.eq.s32 p, %1, 0;\n@p mbarrier.arrive.shared::cta.b64 _, [%0];\n}\n"
                         ::"r"(bar_zst + 8), "r"(pending ? lane : 1) : "memory");
        };
        if (!(rank | wg)) { release(0); release(1); release(2); release(3); }
        bar_sync(BAR_BF, 256);
        warp_arrive(bar_qfree);
        const int nf = rank ? 8 : 0;
        const int nz = nf + 26 + rank;
        const int itz = 4 + SC_NKV + SC_NW;
        bool pend = false;
#pragma unroll 1
        for (int k = wg; k < nz; k += 2) {
            const int iz = itz + (k < nf ? 0 : nf >> 1);
            mbar_wait(qbar, qphase); qphase ^= 1;
#pragma unroll 1
            for (int c = 0; c < 4; c++) {
                mbar_wait(bar_full + 8 * ((iz + c) & 3), ((iz + c) >> 2) & 1);
                const uint64_t wb = mkaddr(dk0 + ((iz + c) & 3) * (KV_BYTES >> 4), dhi), ab = mkaddr(dq0 + c * 64, dhi);
                wg_fence();
                wgmma_ss_n256_tb_pred(o, ab, wb, c);
#pragma unroll
                for (int kk = 1; kk < 4; kk++) wgmma_ss_n256_tb(o, ab + kk * 2, wb + kk * 512);
                wg_commit();
                emit_done(pend);
                pend = false;
            }
            wg_wait<0>();
            fence_regs(o);
            warp_arrive(bar_qfree);
            const int fb = ((k >> 1) + 3) & 3;
            if (k < nf) {
                float2* r255 = (float2*)H.s->r255 + wg * 128 + q;
                if (k < 2) {
                    if (t >= 124) {
#pragma unroll
                        for (int i = 0; i < 32; i++) r255[4 * i] = make_float2(o[4 * i + 2], o[4 * i + 3]);
                    }
                    bar_sync(BAR_WG0 + wg, 128);
                }
#pragma unroll
                for (int i = 0; i < 32; i++) {
                    const float2 v = __ldcg(r255 + 4 * i);
                    o[4 * i] -= v.x; o[4 * i + 1] -= v.y; o[4 * i + 2] -= v.x; o[4 * i + 3] -= v.y;
                }
            }
            int ln = lane;
            asm volatile("" : "+r"(ln));
            emit(sb + SM_KV + QB_BYTES + warp * KV_BYTES, ln, SC_TZB(k - nf) * 64 + warp * 16,
                 k >= nf ? nullptr : (k & 1) ? g_w + (4 + fb) * QB_BYTES + warp * 8192 : g_w + 8 * QB_BYTES + fb * 8192 + warp * 2048, k);
            pend = k + 2 < nz && (k | 1) != nf - 1;
            if (!pend) emit_done(true);
            if ((k | 1) == nf - 1) {
                asm volatile("cp.async.bulk.wait_group 0;\nfence.proxy.async.global;\nfence.acq_rel.gpu;\n" ::: "memory");
                bar_sync(BAR_BF, 256);
                if (tid == 0) red_release(&g_sync[SY_B * 32]);
                if (wg == 0) { release(0); release(1); release(2); release(3); }
            }
        }
        }
        if (wg == 0) pp_sync();
        warp_arrive(bar_end - 8 * wg);
        asm volatile("barrier.cluster.arrive.relaxed.aligned;\n" ::: "memory");
        if (P.E >= 0) return;
        asm volatile("setmaxnreg.dec.sync.aligned.u32 %0;\n" ::"n"(REG_P));
    }
    {
        if (warp != 0) {
            if (warp == 3 && SC_OWNER && SC_PAIR && elect()) {
                flag_wait_bounded(&g_sync[SY_H1 * 32], 79 * ep);
                mbar_wait_sleep(bar_pdone, 0);
                mbar_wait_sleep(bar_pdone + 8, 0);
#pragma unroll 1
                for (int u = 0; u < 16; u++) {
                    bulk_s2g(g_q + SC_QT0 * (2 * QB_BYTES) + u * 4096, sb + SM_Q + u * 4096, 4096);
                    asm volatile("cp.async.bulk.wait_group 0;\n" ::: "memory");
                }
                fence_async_global();
                st_release(&g_qflag[SC_QT0], ep);
            }
            __syncwarp();
            if (SC_TAIL) {
                bar_sync(BAR_AUX, 96);
                if (warp == 1 && elect()) red_release(&g_sync[SY_CSR * 32]);
                __syncwarp();
            }
            mbar_wait_bounded(bar_go, 0);
            if (SC_TAIL) {
                if (warp == 1 && elect()) red_add(&g_sync[SY_DONE * 32]);
                if (warp == 3 && elect()) {
                    int it = 4 + SC_NKV + SC_NW;
                    asm volatile("prefetch.tensormap [%0];\n" ::"l"(&P.tm_out) : "memory");
                    if (rank) {
#pragma unroll 1
                        for (int j = 0; j < 4; j++, it++) {
                            mbar_wait_sleep(bar_empty + 8 * (it & 3), ((it >> 2) & 1) ^ 1);
                            mbar_expect_tx(bar_full + 8 * (it & 3), QB_BYTES);
                            tma_g2s(sb + SM_KV + (it & 3) * KV_BYTES, &P.tm_w[2], 8 * j, bar_full + 8 * (it & 3));
                        }
#pragma unroll 1
                        for (int k = 0; k < 8; k++) {
                            mbar_wait_sleep(bar_qfree + 8 * (k & 1), ((k >> 1) ^ (k & 1) ^ 1) & 1);
                            mbar_expect_tx(bar_q + 8 * (k & 1), QB_BYTES);
#pragma unroll 1
                            for (int hf = 0; hf < 2; hf++)
                                asm volatile("cp.async.bulk.tensor.5d.shared::cluster.global.tile.mbarrier::complete_tx::bytes [%0], [%1, {0, 0, %2, 0, 0}], [%3];\n"
                                             ::"r"(sb + SM_Q + (k & 1) * QB_BYTES + hf * 16384), "l"(&P.tm_w[k & 1]),
                                             "r"(8 * (((k >> 1) + 3) & 3) + 4 * hf), "r"(bar_q + 8 * (k & 1)) : "memory");
                        }
                        flag_wait_bounded(&g_sync[SY_B * 32], ep);
                        fence_async_global();
                    }
#pragma unroll 1
                    for (int j = 0; j < 4; j++, it++) {
                        mbar_wait_sleep(bar_empty + 8 * (it & 3), ((it >> 2) & 1) ^ 1);
                        mbar_expect_tx(bar_full + 8 * (it & 3), QB_BYTES);
                        bulk_g2s(sb + SM_KV + (it & 3) * KV_BYTES, g_w + (4 + j) * QB_BYTES, QB_BYTES, bar_full + 8 * (it & 3));
                    }
#pragma unroll 1
                    for (int k = 0; k < 26 + rank; k++) {
                        if (k == 0 || k == ((GF0 + 1) * NAUX - 16) / 128) { flag_wait_bounded(&g_sync[(k ? SY_AUX1 : SY_AUX0) * 32], NAUX * ep); fence_async_global(); }
                        mbar_wait_sleep(bar_qfree + 8 * (k & 1), ((k >> 1) ^ (k & 1) ^ 1) & 1);
                        mbar_expect_tx(bar_q + 8 * (k & 1), QB_BYTES);
                        bulk_g2s(sb + SM_Q + (k & 1) * QB_BYTES, g_agg + SC_TZB(k) * QB_BYTES, QB_BYTES, bar_q + 8 * (k & 1));
                    }
                }
            } else {
            const int par = ep & 1;
            if (blockIdx.x == 0 && t == 32) g_ovf_n[par ^ 1] = 0;
            if (blockIdx.x == 0 && warp == 1) *(uint4*)(g_hz + (lane >> 3) * 1024 + (lane & 7) * 16) = make_uint4(KV_OFF2 | NEG2, KV_OFF2 | NEG2, KV_OFF2, KV_OFF2);
            const uint32_t wlo = (uint32_t)(uintptr_t)H.s, whi = (uint32_t)((uintptr_t)H.s >> 32);
            const uint32_t blo = wlo + (uint32_t)offsetof(Scratch, bucket);
            {
                const int* pd = P.dst + blockIdx.x * 96 + (t - 32);
                const int* ps = P.src + blockIdx.x * 96 + (t - 32);
#pragma unroll 1
                for (int e = P.E - (blockIdx.x * 96 + (t - 32)); e > 0; e -= CSRU * NAUX * 32, pd += CSRU * NAUX * 32, ps += CSRU * NAUX * 32) {
                    int d[CSRU], sr[CSRU], sl[CSRU];
#pragma unroll
                    for (int i = 0; i < CSRU; i++) {
                        d[i] = e > i * NAUX * 32 ? __ldg(pd + i * NAUX * 32) : NN;
                        sr[i] = e > i * NAUX * 32 ? __ldg(ps + i * NAUX * 32) : 0;
                    }
#pragma unroll
                    for (int i = 0; i < CSRU; i++) {
                        sl[i] = 0;
                        asm volatile("{\n.reg .pred p;\nsetp.lt.s32 p, %2, %3;\n@p atom.relaxed.gpu.global.add.s32 %0, [%1], 1;\n}\n"
                                     : "+r"(sl[i]) : "l"(mkaddr(wlo + (uint32_t)offsetof(Scratch, cnt) + d[i] * 4, whi)), "r"(d[i]), "n"(NN) : "memory");
                    }
                    uint32_t ov = 0;
#pragma unroll
                    for (int i = 0; i < CSRU; i++) {
                        asm volatile("{\n.reg .pred p;\nsetp.lt.s32 p, %3, %4;\n@p st.global.u16 [%1], %2;\n@!p or.b32 %0, %0, %5;\n}\n"
                                     : "+r"(ov) : "l"(mkaddr(blo + d[i] * 128 + (sl[i] & 31) * 4 + (sl[i] >> 5) * 2, whi)), "h"((unsigned short)sr[i]), "r"(sl[i]), "n"(CAP), "r"(1 << i) : "memory");
                    }
#pragma unroll 1
                    for (; ov; ov &= ov - 1) {
                        const int i = (__ffs(ov) - 1) * (NAUX * 32);
                        int at;
                        asm volatile("atom.relaxed.gpu.global.add.s32 %0, [%1], 1;\n" : "=r"(at) : "l"(&g_ovf_n[par]) : "memory");
                        g_ovf[at] = make_int2(__ldg(pd + i), __ldg(ps + i));
                    }
                }
            }
            bar_sync(BAR_AUX, 96);
            if (warp == 1 && elect()) { red_release(&g_sync[SY_CSR * 32]); }
            __syncwarp();
            {
                const int r0 = blockIdx.x * 3 + warp - 1;
                const uint4* xp = (const uint4*)(H.x + r0 * 256) + lane;
                uint4* op = (uint4*)(P.out + r0 * 256) + lane;
#pragma unroll 1
                for (int r = r0; r < NN; r += CPYU * NAUX, xp += CPYU * NAUX * 32, op += CPYU * NAUX * 32) {
                    uint4 v[CPYU];
#pragma unroll
                    for (int i = 0; i < CPYU; i++) if (r + i * NAUX < NN) v[i] = ldg_pinned(xp + i * NAUX * 32);
#pragma unroll
                    for (int i = 0; i < CPYU; i++) if (r + i * NAUX < NN) op[i * NAUX * 32] = v[i];
                }
            }
            mbar_wait_bounded(bar_go, 1);
            if (const int un = (3 - warp) * (NAUX / 3) + (NAUX / 3 - 1) - blockIdx.x; un < 208) {
                flag_wait_bounded(&g_sync[SY_PART * 32], 52 * ep);
                uint8_t* pp = g_part + (un >> 3) * (4 * PART_BYTES);
                float* ml = (float*)(pp + QB_BYTES) + (un & 7) * 32;
                const float4 sa = __ldcg((const float4*)ml + g), sc = __ldcg((const float4*)ml + g + 2 * PART_BYTES / 16);
                const float n0 = fmaxf(sa.x, sc.x), n1 = fmaxf(sa.z, sc.z);
                const uint32_t a0 = pack_bf16(ex2(sa.x - n0), ex2(sa.x - n0)), a1 = pack_bf16(ex2(sa.z - n1), ex2(sa.z - n1));
                const uint32_t b0 = pack_bf16(ex2(sc.x - n0), ex2(sc.x - n0)), b1 = pack_bf16(ex2(sc.z - n1), ex2(sc.z - n1));
                __syncwarp();
                if (q == 0) ((float4*)ml)[g] = make_float4(n0, sa.y * bf_hi(a0) + sc.y * bf_hi(b0), n1, sa.w * bf_hi(a1) + sc.w * bf_hi(b1));
                uint4* d = (uint4*)(pp + (un & 4) * 256 + (un & 7) * 8192) + lane;
#pragma unroll 1
                for (int i = 0; i < 4; i++, d += 128) {
                    uint4 u[4], v[4];
#pragma unroll
                    for (int j = 0; j < 4; j++) { u[j] = __ldcg(d + j * 32); v[j] = __ldcg(d + j * 32 + 2 * PART_BYTES / 16); }
#pragma unroll
                    for (int j = 0; j < 4; j++)
                        d[j * 32] = make_uint4(hfma2(v[j].x, b0, hmul2(u[j].x, a0)), hfma2(v[j].y, b1, hmul2(u[j].y, a1)),
                                               hfma2(v[j].z, b0, hmul2(u[j].z, a0)), hfma2(v[j].w, b1, hmul2(u[j].w, a1)));
                }
            }
            flag_wait_bounded(&g_sync[SY_CSR * 32], NCTA * ep);
            if (warp == 2 && blockIdx.x < 129) {
                uint4* z = blockIdx.x < 128 ? (uint4*)(g_w + blockIdx.x * 1024) + lane : (uint4*)&g_sync[SY_DONE * 32 + 4];
                z[0] = make_uint4(0, 0, 0, 0);
                if (blockIdx.x < 128) z[32] = make_uint4(0, 0, 0, 0);
            }
            {
                const uint32_t lc = (lane >> 3) * 1024 + (lane & 7) * 16;
                const uint32_t alo = wlo ^ lc;
                const int node0 = blockIdx.x * 3 + warp - 17;
                auto node = [&](int i) { const int nd = node0 + i * NAUX; return (int)min((unsigned)nd, (unsigned)(nd + NN)); };
                const int num = (NN - 17 - node0) / NAUX + 1;
                uint32_t mine = 0;
                if (lane < num) {
                    mine = min(__ldcg(&g_cnt[node(lane)]), CAP + 1) | (uint32_t)__ldg((const unsigned short*)P.deg_inv + node(lane)) << 16;
                    g_cnt[node(lane)] = 0;
                }
                auto row = [&](int off) {
                    uint4 v;
                    asm volatile("ld.global.v4.u32 {%0, %1, %2, %3}, [%4];\n"
                                 : "=r"(v.x), "=r"(v.y), "=r"(v.z), "=r"(v.w) : "l"(mkaddr(alo ^ off, whi)));
                    return v;
                };
                auto ents = [&](int i) {
                    uint32_t e;
                    asm volatile("ld.global.cg.u32 %0, [%1];\n" : "=r"(e) : "l"(mkaddr(blo + (min(node(i), NN - 1) * 32 + lane) * 4, whi)));
                    return e;
                };
                auto store = [&](int i, const float (&a)[8]) {
                    const float di = bf_hi(__shfl_sync(~0u, mine, i)) * (1.f / KV_SCALE);
                    const int nd = node(i);
                    *(uint4*)(g_agg + (uint32_t)(((nd >> 3) * 4096 + (nd & 7) * 144) ^ lc)) =
                        make_uint4(pack_bf16(a[0] * di, a[1] * di), pack_bf16(a[2] * di, a[3] * di), pack_bf16(a[4] * di, a[5] * di), pack_bf16(a[6] * di, a[7] * di));
                };
#pragma unroll 1
                for (uint32_t big = __ballot_sync(~0u, (mine & 0xFFFF) > CAP); big; big &= big - 1) {
                    const int i = __ffs(big) - 1, no = __ldcg(&g_ovf_n[par]);
                    float a[8] = {};
#pragma unroll 1
                    for (int k = -64; k < no; k += 32) {
                        const int2 pr = k < 0 ? make_int2(node(i), (ents(i) >> (k & 32) / 2) & 0xFFFF) : k + lane < no ? __ldcg(&g_ovf[k + lane]) : make_int2(-1, 0);
#pragma unroll 1
                        for (uint32_t mk = __ballot_sync(~0u, pr.x == node(i)); mk; mk &= mk - 1) {
                            const uint4 v = row(row_off(__shfl_sync(~0u, pr.y, __ffs(mk) - 1)));
                            a[0] += f16_lo(v.x) + KV_OFF; a[1] += f16_hi(v.x) + KV_OFF; a[2] += f16_lo(v.y) + KV_OFF; a[3] += f16_hi(v.y) + KV_OFF;
                            a[4] += f16_lo(v.z) - KV_OFF; a[5] += f16_hi(v.z) - KV_OFF; a[6] += f16_lo(v.w) - KV_OFF; a[7] += f16_hi(v.w) - KV_OFF;
                        }
                    }
                    store(i, a);
                }
                auto add4 = [&](const uint4& a, const uint4& b) { return make_uint4(hadd2_f16(a.x, b.x), hadd2_f16(a.y, b.y), hadd2_f16(a.z, b.z), hadd2_f16(a.w, b.w)); };
                int ni = -1, left = 0, pos = 0, ec = 0;
                uint32_t en = ents(0);
                uint4 acc = make_uint4(0, 0, 0, 0);
                auto step = [&](uint4 (&v)[4], int& tag) {
                    if (left <= 0 || pos == 32) {
                        if (left > 0) {
                            en = ents(ni) >> 16;
                        } else {
                            ni++;
                            left = __shfl_sync(~0u, mine, ni) & 0xFFFF;
                            if (left > CAP) left = 0;
                        }
                        ec = lane < left ? row_off(en & 0xFFFF) : 0;
                        en = ents(ni + 1);
                        pos = 0;
                    }
                    int of[4];
#pragma unroll
                    for (int j = 0; j < 4; j++) asm volatile("shfl.sync.idx.b32 %0, %1, %2, 31, -1;\n" : "=r"(of[j]) : "r"(ec), "r"(pos + j));
                    acc = add4(acc, add4(add4(add4(v[0], v[1]), make_uint4(KV_OFF8, KV_OFF8, KV_OFF8 | NEG2, KV_OFF8 | NEG2)), add4(v[2], v[3])));
                    asm volatile("" : "+r"(acc.x), "+r"(acc.y), "+r"(acc.z), "+r"(acc.w));
                    asm volatile("{\n.reg .pred p;\nsetp.lt.s32 p, %0, 0;\nL:\n@p pmevent 0;\n@p bra L;\n}\n" ::"r"(ni) : "memory");
#pragma unroll
                    for (int j = 0; j < 4; j++) v[j] = row(of[j]);
                    pos += 4; left -= 4;
                    const int i = tag;
                    tag = left <= 0 ? ni : -1;
                    if (i >= 0) {
                        const float a[8] = {f16_lo(acc.x), f16_hi(acc.x), f16_lo(acc.y), f16_hi(acc.y), f16_lo(acc.z), f16_hi(acc.z), f16_lo(acc.w), f16_hi(acc.w)};
                        if ((__shfl_sync(~0u, mine, i) & 0xFFFF) <= CAP) store(i, a);
                        acc = make_uint4(0, 0, 0, 0);
                        if (i == GF0 || i == 8) {
                            __syncwarp();
                            if (elect()) red_release(&g_sync[(i == 8 ? SY_AUX1 : SY_AUX0) * 32]);
                            __syncwarp();
                        }
                    }
                    return i == num - 1;
                };
                uint4 va[4], vb[4];
#pragma unroll
                for (int j = 0; j < 4; j++) va[j] = vb[j] = make_uint4(KV_OFF2 | NEG2, KV_OFF2 | NEG2, KV_OFF2, KV_OFF2);
                int ta = -1, tb = -1;
#pragma unroll 1
                while (!step(va, ta) && !step(vb, tb)) {}
            }
            bar_sync(BAR_AUX, 96);
            if (warp == 1 && elect()) {
                red_release(&g_sync[SY_AUX * 32]);
                red_add(&g_sync[SY_DONE * 32]);
            }
            }
        }
        __syncwarp();
        asm volatile("barrier.cluster.arrive.relaxed.aligned;\n" ::: "memory");
        if (warp == 1) mbar_wait_bounded(bar_end, 0);
        else if (elect()) mbar_arrive(bar_end);
        __syncwarp();
        asm volatile("barrier.cluster.wait.acquire.aligned;\n" ::: "memory");
    }
}

}

extern "C" void kernel_launch(void* const* d_in, const int* in_sizes, int n_in, void* d_out, int out_size) {
    Hot H;
    Params P;
    H.x = (const __nv_bfloat16*)d_in[0];
    P.src = (const int*)d_in[1];
    P.dst = (const int*)d_in[2];
    P.deg_inv = (const __nv_bfloat16*)d_in[3];
    H.wq = (const __nv_bfloat16*)d_in[5];
    H.wk = (const __nv_bfloat16*)d_in[6];
    P.out = (__nv_bfloat16*)d_out;
    typedef CUresult (*EncodeFn)(CUtensorMap*, CUtensorMapDataType, cuuint32_t, void*, const cuuint64_t*, const cuuint64_t*, const cuuint32_t*,
                                 const cuuint32_t*, CUtensorMapInterleave, CUtensorMapSwizzle, CUtensorMapL2promotion, CUtensorMapFloatOOBfill);
    void* fn = nullptr;
    cudaDriverEntryPointQueryResult qr;
    cudaGetDriverEntryPoint("cuTensorMapEncodeTiled", &fn, cudaEnableDefault, &qr);
    auto encode = [&](CUtensorMap* tm, const void* ptr, int rows, int box_rows, int box_cb = 4) {
        const cuuint64_t dims[4] = {64, 8, 4, (cuuint64_t)rows / 8};
        const cuuint64_t strides[3] = {512, 128, 4096};
        const cuuint32_t box[4] = {64, 8, (cuuint32_t)box_cb, (cuuint32_t)box_rows / 8}, es[4] = {1, 1, 1, 1};
        ((EncodeFn)fn)(tm, CU_TENSOR_MAP_DATA_TYPE_BFLOAT16, 4, (void*)ptr, dims, strides, box, es, CU_TENSOR_MAP_INTERLEAVE_NONE,
                       CU_TENSOR_MAP_SWIZZLE_128B, CU_TENSOR_MAP_L2_PROMOTION_NONE, CU_TENSOR_MAP_FLOAT_OOB_FILL_NONE);
    };
    encode(&P.tm_out, d_out, NN, 8);
    encode(&P.tm_outc, d_out, NN, 16, 1);
    for (int i = 0; i < 2; i++) {
        const cuuint64_t dims[5] = {64, 2, 32, 4, 4};
        const cuuint64_t strides[4] = {512, 4096, 128, 1024};
        const cuuint32_t box[5] = {64, 2, 4, 4, 4}, es[5] = {1, 1, 1, 1, 1};
        ((EncodeFn)fn)(&P.tm_w[i], CU_TENSOR_MAP_DATA_TYPE_BFLOAT16, 5, d_in[i ? 4 : 7], dims, strides, box, es, CU_TENSOR_MAP_INTERLEAVE_NONE,
                       CU_TENSOR_MAP_SWIZZLE_128B, CU_TENSOR_MAP_L2_PROMOTION_NONE, CU_TENSOR_MAP_FLOAT_OOB_FILL_NONE);
    }
    encode(&P.tm_w[2], d_in[8], 256, 64);
    void* raw = nullptr;
    cudaGetSymbolAddress(&raw, g_raw);
    H.s = (Scratch*)(((uintptr_t)raw + ((8 << 20) - 1)) & ~(uintptr_t)((8 << 20) - 1));
    P.dhi = 0x40000100u;
    P.E = in_sizes[1] < MAXE ? in_sizes[1] : MAXE;
    cudaFuncSetAttribute(k_main, cudaFuncAttributeMaxDynamicSharedMemorySize, SM_TOTAL);
    k_main<<<NCTA, 384, SM_TOTAL>>>(H, P);
}
```

```cpp
#include <cuda_runtime.h>
#include <cuda.h>
#include <cuda_bf16.h>
#include <stdint.h>
#include <stddef.h>

namespace {

constexpr int NN = 10000;
constexpr int BN = 80;
constexpr int NKV = NN / BN;
constexpr int NQB = 158;
constexpr int NCTA = 132;
constexpr int NAUX = 3 * (NCTA - 2);
constexpr int STAGES = 4;
constexpr int KV_BYTES = BN * 512;
constexpr int QB_BYTES = 64 * 512;
constexpr int PART_BYTES = QB_BYTES + 512;
constexpr int CAP = 64;
constexpr int MAXE = 160000;

#define QRND(v) (((v) + 0x00040004u) & 0xFFF8FFF8u)
#define GO0 5
#define GO1 41
#define GF0 2
#define CSRU 3
#define CPYU 9
#define REFUP 2.f
#define SND0 10
#define CUT2 2
#define TICK 1024
#define TSL 30
#define NQR 7
#define QSTEP 2
#define QREG(kk) ((kk) % QSTEP == 1 % QSTEP && (kk) > 0 && ((kk) - 1) / QSTEP < NQR ? ((kk) - 1) / QSTEP : -1)
#define M2 28
#define REG_C 224
#define REG_P 56

enum { SY_PART = 4, SY_H1 = 5, SY_CSR = 6, SY_AUX = 7, SY_DONE = 8, SY_AUX0 = 9, SY_B = 10, SY_AUX1 = 11, SY_H0 = 12 };
struct Scratch {
    uint8_t hz[4096 + NN * 512];
    uint8_t w[12 * QB_BYTES];
    int sync[25 * 32];
    int qflag[96];
    int ovf_n[32];
    float r255[512];
    int cnt[NN + 16];
    int bucket[(NN + 1) * 32];
    int2 ovf[MAXE];
    uint8_t q[NQB * QB_BYTES];
    uint8_t agg[NQB * QB_BYTES];
    uint8_t part[52 * 2 * PART_BYTES];
};
static_assert(offsetof(Scratch, ovf) <= (8 << 20), "window");
static_assert(offsetof(Scratch, qflag) == offsetof(Scratch, sync) + 25 * 128, "flags");
static_assert(offsetof(Scratch, w) % 1024 == 0 && offsetof(Scratch, sync) % 128 == 0 &&
              offsetof(Scratch, bucket) % 128 == 0 && offsetof(Scratch, q) % 128 == 0, "alignment");
__device__ uint8_t g_raw[(8 << 20) + sizeof(Scratch)];
#define g_hz (H.s->hz)
#define g_w (H.s->w)
#define g_sync (H.s->sync)
#define g_qflag (H.s->qflag)
#define g_ovf_n (H.s->ovf_n)
#define g_cnt (H.s->cnt)
#define g_bucket (H.s->bucket)
#define g_ovf (H.s->ovf)
#define g_q (H.s->q)
#define g_agg (H.s->agg)
#define g_part (H.s->part)

__device__ __forceinline__ void wgmma_ss_n80(uint32_t (&d)[20], uint64_t da, uint64_t db) {
    asm volatile("wgmma.mma_async.sync.aligned.m64n80k16.f16.f16.f16 {"
        "%0, %1, %2, %3, %4, %5, %6, %7, %8, %9, %10, %11, %12, %13, %14, %15, %16, %17, %18, %19}, %20, %21, 1, 1, 1, 0, 0;\n"
        : "+r"(d[0]), "+r"(d[1]), "+r"(d[2]), "+r"(d[3]), "+r"(d[4]), "+r"(d[5]), "+r"(d[6]), "+r"(d[7]),
          "+r"(d[8]), "+r"(d[9]), "+r"(d[10]), "+r"(d[11]), "+r"(d[12]), "+r"(d[13]), "+r"(d[14]), "+r"(d[15]),
          "+r"(d[16]), "+r"(d[17]), "+r"(d[18]), "+r"(d[19])
        : "l"(da), "l"(db));
}
__device__ __forceinline__ void wgmma_ss_n80_init(uint32_t (&d)[20], uint64_t da, uint64_t db) {
    asm volatile("wgmma.mma_async.sync.aligned.m64n80k16.f16.f16.f16 {"
        "%0, %1, %2, %3, %4, %5, %6, %7, %8, %9, %10, %11, %12, %13, %14, %15, %16, %17, %18, %19}, %20, %21, 0, 1, 1, 0, 0;\n"
        : "=r"(d[0]), "=r"(d[1]), "=r"(d[2]), "=r"(d[3]), "=r"(d[4]), "=r"(d[5]), "=r"(d[6]), "=r"(d[7]),
          "=r"(d[8]), "=r"(d[9]), "=r"(d[10]), "=r"(d[11]), "=r"(d[12]), "=r"(d[13]), "=r"(d[14]), "=r"(d[15]),
          "=r"(d[16]), "=r"(d[17]), "=r"(d[18]), "=r"(d[19])
        : "l"(da), "l"(db));
}
__device__ __forceinline__ void wgmma_rs_n80(uint32_t (&d)[20], uint32_t a0, uint32_t a1, uint32_t a2, uint32_t a3, uint64_t db) {
    asm volatile("wgmma.mma_async.sync.aligned.m64n80k16.f16.f16.f16 {"
        "%0, %1, %2, %3, %4, %5, %6, %7, %8, %9, %10, %11, %12, %13, %14, %15, %16, %17, %18, %19}, {%20, %21, %22, %23}, %24, 1, 1, 1, 0;\n"
        : "+r"(d[0]), "+r"(d[1]), "+r"(d[2]), "+r"(d[3]), "+r"(d[4]), "+r"(d[5]), "+r"(d[6]), "+r"(d[7]),
          "+r"(d[8]), "+r"(d[9]), "+r"(d[10]), "+r"(d[11]), "+r"(d[12]), "+r"(d[13]), "+r"(d[14]), "+r"(d[15]),
          "+r"(d[16]), "+r"(d[17]), "+r"(d[18]), "+r"(d[19])
        : "r"(a0), "r"(a1), "r"(a2), "r"(a3), "l"(db));
}
__device__ __forceinline__ void wgmma_rs_n256_tb(float (&d)[128], uint32_t a0, uint32_t a1, uint32_t a2, uint32_t a3, uint64_t db) {
    asm volatile("wgmma.mma_async.sync.aligned.m64n256k16.f32.f16.f16 {"
        "%0, %1, %2, %3, %4, %5, %6, %7, %8, %9, %10, %11, %12, %13, %14, %15, %16, %17, %18, %19, %20, %21, %22, %23, %24, %25, %26, %27, %28, %29, %30, %31, "
        "%32, %33, %34, %35, %36, %37, %38, %39, %40, %41, %42, %43, %44, %45, %46, %47, %48, %49, %50, %51, %52, %53, %54, %55, %56, %57, %58, %59, %60, %61, %62, %63, "
        "%64, %65, %66, %67, %68, %69, %70, %71, %72, %73, %74, %75, %76, %77, %78, %79, %80, %81, %82, %83, %84, %85, %86, %87, %88, %89, %90, %91, %92, %93, %94, %95, "
        "%96, %97, %98, %99, %100, %101, %102, %103, %104, %105, %106, %107, %108, %109, %110, %111, %112, %113, %114, %115, %116, %117, %118, %119, %120, %121, %122, %123, %124, %125, %126, %127}, {%128, %129, %130, %131}, %132, 1, 1, 1, 1;\n"
        : "+f"(d[0]), "+f"(d[1]), "+f"(d[2]), "+f"(d[3]), "+f"(d[4]), "+f"(d[5]), "+f"(d[6]), "+f"(d[7]),
          "+f"(d[8]), "+f"(d[9]), "+f"(d[10]), "+f"(d[11]), "+f"(d[12]), "+f"(d[13]), "+f"(d[14]), "+f"(d[15]),
          "+f"(d[16]), "+f"(d[17]), "+f"(d[18]), "+f"(d[19]), "+f"(d[20]), "+f"(d[21]), "+f"(d[22]), "+f"(d[23]),
          "+f"(d[24]), "+f"(d[25]), "+f"(d[26]), "+f"(d[27]), "+f"(d[28]), "+f"(d[29]), "+f"(d[30]), "+f"(d[31]),
          "+f"(d[32]), "+f"(d[33]), "+f"(d[34]), "+f"(d[35]), "+f"(d[36]), "+f"(d[37]), "+f"(d[38]), "+f"(d[39]),
          "+f"(d[40]), "+f"(d[41]), "+f"(d[42]), "+f"(d[43]), "+f"(d[44]), "+f"(d[45]), "+f"(d[46]), "+f"(d[47]),
          "+f"(d[48]), "+f"(d[49]), "+f"(d[50]), "+f"(d[51]), "+f"(d[52]), "+f"(d[53]), "+f"(d[54]), "+f"(d[55]),
          "+f"(d[56]), "+f"(d[57]), "+f"(d[58]), "+f"(d[59]), "+f"(d[60]), "+f"(d[61]), "+f"(d[62]), "+f"(d[63]),
          "+f"(d[64]), "+f"(d[65]), "+f"(d[66]), "+f"(d[67]), "+f"(d[68]), "+f"(d[69]), "+f"(d[70]), "+f"(d[71]),
          "+f"(d[72]), "+f"(d[73]), "+f"(d[74]), "+f"(d[75]), "+f"(d[76]), "+f"(d[77]), "+f"(d[78]), "+f"(d[79]),
          "+f"(d[80]), "+f"(d[81]), "+f"(d[82]), "+f"(d[83]), "+f"(d[84]), "+f"(d[85]), "+f"(d[86]), "+f"(d[87]),
          "+f"(d[88]), "+f"(d[89]), "+f"(d[90]), "+f"(d[91]), "+f"(d[92]), "+f"(d[93]), "+f"(d[94]), "+f"(d[95]),
          "+f"(d[96]), "+f"(d[97]), "+f"(d[98]), "+f"(d[99]), "+f"(d[100]), "+f"(d[101]), "+f"(d[102]), "+f"(d[103]),
          "+f"(d[104]), "+f"(d[105]), "+f"(d[106]), "+f"(d[107]), "+f"(d[108]), "+f"(d[109]), "+f"(d[110]), "+f"(d[111]),
          "+f"(d[112]), "+f"(d[113]), "+f"(d[114]), "+f"(d[115]), "+f"(d[116]), "+f"(d[117]), "+f"(d[118]), "+f"(d[119]),
          "+f"(d[120]), "+f"(d[121]), "+f"(d[122]), "+f"(d[123]), "+f"(d[124]), "+f"(d[125]), "+f"(d[126]), "+f"(d[127])
        : "r"(a0), "r"(a1), "r"(a2), "r"(a3), "l"(db));
}
__device__ __forceinline__ void wgmma_rs_n256_tb_init(float (&d)[128], uint32_t a0, uint32_t a1, uint32_t a2, uint32_t a3, uint64_t db) {
    asm volatile("wgmma.mma_async.sync.aligned.m64n256k16.f32.f16.f16 {"
        "%0, %1, %2, %3, %4, %5, %6, %7, %8, %9, %10, %11, %12, %13, %14, %15, %16, %17, %18, %19, %20, %21, %22, %23, %24, %25, %26, %27, %28, %29, %30, %31, "
        "%32, %33, %34, %35, %36, %37, %38, %39, %40, %41, %42, %43, %44, %45, %46, %47, %48, %49, %50, %51, %52, %53, %54, %55, %56, %57, %58, %59, %60, %61, %62, %63, "
        "%64, %65, %66, %67, %68, %69, %70, %71, %72, %73, %74, %75, %76, %77, %78, %79, %80, %81, %82, %83, %84, %85, %86, %87, %88, %89, %90, %91, %92, %93, %94, %95, "
        "%96, %97, %98, %99, %100, %101, %102, %103, %104, %105, %106, %107, %108, %109, %110, %111, %112, %113, %114, %115, %116, %117, %118, %119, %120, %121, %122, %123, %124, %125, %126, %127}, {%128, %129, %130, %131}, %132, 0, 1, 1, 1;\n"
        : "=f"(d[0]), "=f"(d[1]), "=f"(d[2]), "=f"(d[3]), "=f"(d[4]), "=f"(d[5]), "=f"(d[6]), "=f"(d[7]),
          "=f"(d[8]), "=f"(d[9]), "=f"(d[10]), "=f"(d[11]), "=f"(d[12]), "=f"(d[13]), "=f"(d[14]), "=f"(d[15]),
          "=f"(d[16]), "=f"(d[17]), "=f"(d[18]), "=f"(d[19]), "=f"(d[20]), "=f"(d[21]), "=f"(d[22]), "=f"(d[23]),
          "=f"(d[24]), "=f"(d[25]), "=f"(d[26]), "=f"(d[27]), "=f"(d[28]), "=f"(d[29]), "=f"(d[30]), "=f"(d[31]),
          "=f"(d[32]), "=f"(d[33]), "=f"(d[34]), "=f"(d[35]), "=f"(d[36]), "=f"(d[37]), "=f"(d[38]), "=f"(d[39]),
          "=f"(d[40]), "=f"(d[41]), "=f"(d[42]), "=f"(d[43]), "=f"(d[44]), "=f"(d[45]), "=f"(d[46]), "=f"(d[47]),
          "=f"(d[48]), "=f"(d[49]), "=f"(d[50]), "=f"(d[51]), "=f"(d[52]), "=f"(d[53]), "=f"(d[54]), "=f"(d[55]),
          "=f"(d[56]), "=f"(d[57]), "=f"(d[58]), "=f"(d[59]), "=f"(d[60]), "=f"(d[61]), "=f"(d[62]), "=f"(d[63]),
          "=f"(d[64]), "=f"(d[65]), "=f"(d[66]), "=f"(d[67]), "=f"(d[68]), "=f"(d[69]), "=f"(d[70]), "=f"(d[71]),
          "=f"(d[72]), "=f"(d[73]), "=f"(d[74]), "=f"(d[75]), "=f"(d[76]), "=f"(d[77]), "=f"(d[78]), "=f"(d[79]),
          "=f"(d[80]), "=f"(d[81]), "=f"(d[82]), "=f"(d[83]), "=f"(d[84]), "=f"(d[85]), "=f"(d[86]), "=f"(d[87]),
          "=f"(d[88]), "=f"(d[89]), "=f"(d[90]), "=f"(d[91]), "=f"(d[92]), "=f"(d[93]), "=f"(d[94]), "=f"(d[95]),
          "=f"(d[96]), "=f"(d[97]), "=f"(d[98]), "=f"(d[99]), "=f"(d[100]), "=f"(d[101]), "=f"(d[102]), "=f"(d[103]),
          "=f"(d[104]), "=f"(d[105]), "=f"(d[106]), "=f"(d[107]), "=f"(d[108]), "=f"(d[109]), "=f"(d[110]), "=f"(d[111]),
          "=f"(d[112]), "=f"(d[113]), "=f"(d[114]), "=f"(d[115]), "=f"(d[116]), "=f"(d[117]), "=f"(d[118]), "=f"(d[119]),
          "=f"(d[120]), "=f"(d[121]), "=f"(d[122]), "=f"(d[123]), "=f"(d[124]), "=f"(d[125]), "=f"(d[126]), "=f"(d[127])
        : "r"(a0), "r"(a1), "r"(a2), "r"(a3), "l"(db));
}
__device__ __forceinline__ void wgmma_rs_n256_tb_pred(float (&d)[128], uint32_t a0, uint32_t a1, uint32_t a2, uint32_t a3, uint64_t db, int acc) {
    asm volatile("{\n.reg .pred p;\nsetp.ne.s32 p, %133, 0;\nwgmma.mma_async.sync.aligned.m64n256k16.f32.f16.f16 {"
        "%0, %1, %2, %3, %4, %5, %6, %7, %8, %9, %10, %11, %12, %13, %14, %15, %16, %17, %18, %19, %20, %21, %22, %23, %24, %25, %26, %27, %28, %29, %30, %31, "
        "%32, %33, %34, %35, %36, %37, %38, %39, %40, %41, %42, %43, %44, %45, %46, %47, %48, %49, %50, %51, %52, %53, %54, %55, %56, %57, %58, %59, %60, %61, %62, %63, "
        "%64, %65, %66, %67, %68, %69, %70, %71, %72, %73, %74, %75, %76, %77, %78, %79, %80, %81, %82, %83, %84, %85, %86, %87, %88, %89, %90, %91, %92, %93, %94, %95, "
        "%96, %97, %98, %99, %100, %101, %102, %103, %104, %105, %106, %107, %108, %109, %110, %111, %112, %113, %114, %115, %116, %117, %118, %119, %120, %121, %122, %123, %124, %125, %126, %127}, {%128, %129, %130, %131}, %132, p, 1, 1, 1;\n}\n"
        : "+f"(d[0]), "+f"(d[1]), "+f"(d[2]), "+f"(d[3]), "+f"(d[4]), "+f"(d[5]), "+f"(d[6]), "+f"(d[7]),
          "+f"(d[8]), "+f"(d[9]), "+f"(d[10]), "+f"(d[11]), "+f"(d[12]), "+f"(d[13]), "+f"(d[14]), "+f"(d[15]),
          "+f"(d[16]), "+f"(d[17]), "+f"(d[18]), "+f"(d[19]), "+f"(d[20]), "+f"(d[21]), "+f"(d[22]), "+f"(d[23]),
          "+f"(d[24]), "+f"(d[25]), "+f"(d[26]), "+f"(d[27]), "+f"(d[28]), "+f"(d[29]), "+f"(d[30]), "+f"(d[31]),
          "+f"(d[32]), "+f"(d[33]), "+f"(d[34]), "+f"(d[35]), "+f"(d[36]), "+f"(d[37]), "+f"(d[38]), "+f"(d[39]),
          "+f"(d[40]), "+f"(d[41]), "+f"(d[42]), "+f"(d[43]), "+f"(d[44]), "+f"(d[45]), "+f"(d[46]), "+f"(d[47]),
          "+f"(d[48]), "+f"(d[49]), "+f"(d[50]), "+f"(d[51]), "+f"(d[52]), "+f"(d[53]), "+f"(d[54]), "+f"(d[55]),
          "+f"(d[56]), "+f"(d[57]), "+f"(d[58]), "+f"(d[59]), "+f"(d[60]), "+f"(d[61]), "+f"(d[62]), "+f"(d[63]),
          "+f"(d[64]), "+f"(d[65]), "+f"(d[66]), "+f"(d[67]), "+f"(d[68]), "+f"(d[69]), "+f"(d[70]), "+f"(d[71]),
          "+f"(d[72]), "+f"(d[73]), "+f"(d[74]), "+f"(d[75]), "+f"(d[76]), "+f"(d[77]), "+f"(d[78]), "+f"(d[79]),
          "+f"(d[80]), "+f"(d[81]), "+f"(d[82]), "+f"(d[83]), "+f"(d[84]), "+f"(d[85]), "+f"(d[86]), "+f"(d[87]),
          "+f"(d[88]), "+f"(d[89]), "+f"(d[90]), "+f"(d[91]), "+f"(d[92]), "+f"(d[93]), "+f"(d[94]), "+f"(d[95]),
          "+f"(d[96]), "+f"(d[97]), "+f"(d[98]), "+f"(d[99]), "+f"(d[100]), "+f"(d[101]), "+f"(d[102]), "+f"(d[103]),
          "+f"(d[104]), "+f"(d[105]), "+f"(d[106]), "+f"(d[107]), "+f"(d[108]), "+f"(d[109]), "+f"(d[110]), "+f"(d[111]),
          "+f"(d[112]), "+f"(d[113]), "+f"(d[114]), "+f"(d[115]), "+f"(d[116]), "+f"(d[117]), "+f"(d[118]), "+f"(d[119]),
          "+f"(d[120]), "+f"(d[121]), "+f"(d[122]), "+f"(d[123]), "+f"(d[124]), "+f"(d[125]), "+f"(d[126]), "+f"(d[127])
        : "r"(a0), "r"(a1), "r"(a2), "r"(a3), "l"(db), "r"(acc));
}
__device__ __forceinline__ void wgmma_ss_n256_tb(float (&d)[128], uint64_t da, uint64_t db) {
    asm volatile("wgmma.mma_async.sync.aligned.m64n256k16.f32.bf16.bf16 {"
        "%0, %1, %2, %3, %4, %5, %6, %7, %8, %9, %10, %11, %12, %13, %14, %15, %16, %17, %18, %19, %20, %21, %22, %23, %24, %25, %26, %27, %28, %29, %30, %31, "
        "%32, %33, %34, %35, %36, %37, %38, %39, %40, %41, %42, %43, %44, %45, %46, %47, %48, %49, %50, %51, %52, %53, %54, %55, %56, %57, %58, %59, %60, %61, %62, %63, "
        "%64, %65, %66, %67, %68, %69, %70, %71, %72, %73, %74, %75, %76, %77, %78, %79, %80, %81, %82, %83, %84, %85, %86, %87, %88, %89, %90, %91, %92, %93, %94, %95, "
        "%96, %97, %98, %99, %100, %101, %102, %103, %104, %105, %106, %107, %108, %109, %110, %111, %112, %113, %114, %115, %116, %117, %118, %119, %120, %121, %122, %123, %124, %125, %126, %127}, %128, %129, 1, 1, 1, 0, 1;\n"
        : "+f"(d[0]), "+f"(d[1]), "+f"(d[2]), "+f"(d[3]), "+f"(d[4]), "+f"(d[5]), "+f"(d[6]), "+f"(d[7]),
          "+f"(d[8]), "+f"(d[9]), "+f"(d[10]), "+f"(d[11]), "+f"(d[12]), "+f"(d[13]), "+f"(d[14]), "+f"(d[15]),
          "+f"(d[16]), "+f"(d[17]), "+f"(d[18]), "+f"(d[19]), "+f"(d[20]), "+f"(d[21]), "+f"(d[22]), "+f"(d[23]),
          "+f"(d[24]), "+f"(d[25]), "+f"(d[26]), "+f"(d[27]), "+f"(d[28]), "+f"(d[29]), "+f"(d[30]), "+f"(d[31]),
          "+f"(d[32]), "+f"(d[33]), "+f"(d[34]), "+f"(d[35]), "+f"(d[36]), "+f"(d[37]), "+f"(d[38]), "+f"(d[39]),
          "+f"(d[40]), "+f"(d[41]), "+f"(d[42]), "+f"(d[43]), "+f"(d[44]), "+f"(d[45]), "+f"(d[46]), "+f"(d[47]),
          "+f"(d[48]), "+f"(d[49]), "+f"(d[50]), "+f"(d[51]), "+f"(d[52]), "+f"(d[53]), "+f"(d[54]), "+f"(d[55]),
          "+f"(d[56]), "+f"(d[57]), "+f"(d[58]), "+f"(d[59]), "+f"(d[60]), "+f"(d[61]), "+f"(d[62]), "+f"(d[63]),
          "+f"(d[64]), "+f"(d[65]), "+f"(d[66]), "+f"(d[67]), "+f"(d[68]), "+f"(d[69]), "+f"(d[70]), "+f"(d[71]),
          "+f"(d[72]), "+f"(d[73]), "+f"(d[74]), "+f"(d[75]), "+f"(d[76]), "+f"(d[77]), "+f"(d[78]), "+f"(d[79]),
          "+f"(d[80]), "+f"(d[81]), "+f"(d[82]), "+f"(d[83]), "+f"(d[84]), "+f"(d[85]), "+f"(d[86]), "+f"(d[87]),
          "+f"(d[88]), "+f"(d[89]), "+f"(d[90]), "+f"(d[91]), "+f"(d[92]), "+f"(d[93]), "+f"(d[94]), "+f"(d[95]),
          "+f"(d[96]), "+f"(d[97]), "+f"(d[98]), "+f"(d[99]), "+f"(d[100]), "+f"(d[101]), "+f"(d[102]), "+f"(d[103]),
          "+f"(d[104]), "+f"(d[105]), "+f"(d[106]), "+f"(d[107]), "+f"(d[108]), "+f"(d[109]), "+f"(d[110]), "+f"(d[111]),
          "+f"(d[112]), "+f"(d[113]), "+f"(d[114]), "+f"(d[115]), "+f"(d[116]), "+f"(d[117]), "+f"(d[118]), "+f"(d[119]),
          "+f"(d[120]), "+f"(d[121]), "+f"(d[122]), "+f"(d[123]), "+f"(d[124]), "+f"(d[125]), "+f"(d[126]), "+f"(d[127])
        : "l"(da), "l"(db));
}
__device__ __forceinline__ void wgmma_ss_n256_tb_init(float (&d)[128], uint64_t da, uint64_t db) {
    asm volatile("wgmma.mma_async.sync.aligned.m64n256k16.f32.bf16.bf16 {"
        "%0, %1, %2, %3, %4, %5, %6, %7, %8, %9, %10, %11, %12, %13, %14, %15, %16, %17, %18, %19, %20, %21, %22, %23, %24, %25, %26, %27, %28, %29, %30, %31, "
        "%32, %33, %34, %35, %36, %37, %38, %39, %40, %41, %42, %43, %44, %45, %46, %47, %48, %49, %50, %51, %52, %53, %54, %55, %56, %57, %58, %59, %60, %61, %62, %63, "
        "%64, %65, %66, %67, %68, %69, %70, %71, %72, %73, %74, %75, %76, %77, %78, %79, %80, %81, %82, %83, %84, %85, %86, %87, %88, %89, %90, %91, %92, %93, %94, %95, "
        "%96, %97, %98, %99, %100, %101, %102, %103, %104, %105, %106, %107, %108, %109, %110, %111, %112, %113, %114, %115, %116, %117, %118, %119, %120, %121, %122, %123, %124, %125, %126, %127}, %128, %129, 0, 1, 1, 0, 1;\n"
        : "=f"(d[0]), "=f"(d[1]), "=f"(d[2]), "=f"(d[3]), "=f"(d[4]), "=f"(d[5]), "=f"(d[6]), "=f"(d[7]),
          "=f"(d[8]), "=f"(d[9]), "=f"(d[10]), "=f"(d[11]), "=f"(d[12]), "=f"(d[13]), "=f"(d[14]), "=f"(d[15]),
          "=f"(d[16]), "=f"(d[17]), "=f"(d[18]), "=f"(d[19]), "=f"(d[20]), "=f"(d[21]), "=f"(d[22]), "=f"(d[23]),
          "=f"(d[24]), "=f"(d[25]), "=f"(d[26]), "=f"(d[27]), "=f"(d[28]), "=f"(d[29]), "=f"(d[30]), "=f"(d[31]),
          "=f"(d[32]), "=f"(d[33]), "=f"(d[34]), "=f"(d[35]), "=f"(d[36]), "=f"(d[37]), "=f"(d[38]), "=f"(d[39]),
          "=f"(d[40]), "=f"(d[41]), "=f"(d[42]), "=f"(d[43]), "=f"(d[44]), "=f"(d[45]), "=f"(d[46]), "=f"(d[47]),
          "=f"(d[48]), "=f"(d[49]), "=f"(d[50]), "=f"(d[51]), "=f"(d[52]), "=f"(d[53]), "=f"(d[54]), "=f"(d[55]),
          "=f"(d[56]), "=f"(d[57]), "=f"(d[58]), "=f"(d[59]), "=f"(d[60]), "=f"(d[61]), "=f"(d[62]), "=f"(d[63]),
          "=f"(d[64]), "=f"(d[65]), "=f"(d[66]), "=f"(d[67]), "=f"(d[68]), "=f"(d[69]), "=f"(d[70]), "=f"(d[71]),
          "=f"(d[72]), "=f"(d[73]), "=f"(d[74]), "=f"(d[75]), "=f"(d[76]), "=f"(d[77]), "=f"(d[78]), "=f"(d[79]),
          "=f"(d[80]), "=f"(d[81]), "=f"(d[82]), "=f"(d[83]), "=f"(d[84]), "=f"(d[85]), "=f"(d[86]), "=f"(d[87]),
          "=f"(d[88]), "=f"(d[89]), "=f"(d[90]), "=f"(d[91]), "=f"(d[92]), "=f"(d[93]), "=f"(d[94]), "=f"(d[95]),
          "=f"(d[96]), "=f"(d[97]), "=f"(d[98]), "=f"(d[99]), "=f"(d[100]), "=f"(d[101]), "=f"(d[102]), "=f"(d[103]),
          "=f"(d[104]), "=f"(d[105]), "=f"(d[106]), "=f"(d[107]), "=f"(d[108]), "=f"(d[109]), "=f"(d[110]), "=f"(d[111]),
          "=f"(d[112]), "=f"(d[113]), "=f"(d[114]), "=f"(d[115]), "=f"(d[116]), "=f"(d[117]), "=f"(d[118]), "=f"(d[119]),
          "=f"(d[120]), "=f"(d[121]), "=f"(d[122]), "=f"(d[123]), "=f"(d[124]), "=f"(d[125]), "=f"(d[126]), "=f"(d[127])
        : "l"(da), "l"(db));
}
__device__ __forceinline__ void wgmma_ss_n256_tb_pred(float (&d)[128], uint64_t da, uint64_t db, int acc) {
    asm volatile("{\n.reg .pred p;\nsetp.ne.s32 p, %130, 0;\nwgmma.mma_async.sync.aligned.m64n256k16.f32.bf16.bf16 {"
        "%0, %1, %2, %3, %4, %5, %6, %7, %8, %9, %10, %11, %12, %13, %14, %15, %16, %17, %18, %19, %20, %21, %22, %23, %24, %25, %26, %27, %28, %29, %30, %31, "
        "%32, %33, %34, %35, %36, %37, %38, %39, %40, %41, %42, %43, %44, %45, %46, %47, %48, %49, %50, %51, %52, %53, %54, %55, %56, %57, %58, %59, %60, %61, %62, %63, "
        "%64, %65, %66, %67, %68, %69, %70, %71, %72, %73, %74, %75, %76, %77, %78, %79, %80, %81, %82, %83, %84, %85, %86, %87, %88, %89, %90, %91, %92, %93, %94, %95, "
        "%96, %97, %98, %99, %100, %101, %102, %103, %104, %105, %106, %107, %108, %109, %110, %111, %112, %113, %114, %115, %116, %117, %118, %119, %120, %121, %122, %123, %124, %125, %126, %127}, %128, %129, p, 1, 1, 0, 1;\n}\n"
        : "+f"(d[0]), "+f"(d[1]), "+f"(d[2]), "+f"(d[3]), "+f"(d[4]), "+f"(d[5]), "+f"(d[6]), "+f"(d[7]),
          "+f"(d[8]), "+f"(d[9]), "+f"(d[10]), "+f"(d[11]), "+f"(d[12]), "+f"(d[13]), "+f"(d[14]), "+f"(d[15]),
          "+f"(d[16]), "+f"(d[17]), "+f"(d[18]), "+f"(d[19]), "+f"(d[20]), "+f"(d[21]), "+f"(d[22]), "+f"(d[23]),
          "+f"(d[24]), "+f"(d[25]), "+f"(d[26]), "+f"(d[27]), "+f"(d[28]), "+f"(d[29]), "+f"(d[30]), "+f"(d[31]),
          "+f"(d[32]), "+f"(d[33]), "+f"(d[34]), "+f"(d[35]), "+f"(d[36]), "+f"(d[37]), "+f"(d[38]), "+f"(d[39]),
          "+f"(d[40]), "+f"(d[41]), "+f"(d[42]), "+f"(d[43]), "+f"(d[44]), "+f"(d[45]), "+f"(d[46]), "+f"(d[47]),
          "+f"(d[48]), "+f"(d[49]), "+f"(d[50]), "+f"(d[51]), "+f"(d[52]), "+f"(d[53]), "+f"(d[54]), "+f"(d[55]),
          "+f"(d[56]), "+f"(d[57]), "+f"(d[58]), "+f"(d[59]), "+f"(d[60]), "+f"(d[61]), "+f"(d[62]), "+f"(d[63]),
          "+f"(d[64]), "+f"(d[65]), "+f"(d[66]), "+f"(d[67]), "+f"(d[68]), "+f"(d[69]), "+f"(d[70]), "+f"(d[71]),
          "+f"(d[72]), "+f"(d[73]), "+f"(d[74]), "+f"(d[75]), "+f"(d[76]), "+f"(d[77]), "+f"(d[78]), "+f"(d[79]),
          "+f"(d[80]), "+f"(d[81]), "+f"(d[82]), "+f"(d[83]), "+f"(d[84]), "+f"(d[85]), "+f"(d[86]), "+f"(d[87]),
          "+f"(d[88]), "+f"(d[89]), "+f"(d[90]), "+f"(d[91]), "+f"(d[92]), "+f"(d[93]), "+f"(d[94]), "+f"(d[95]),
          "+f"(d[96]), "+f"(d[97]), "+f"(d[98]), "+f"(d[99]), "+f"(d[100]), "+f"(d[101]), "+f"(d[102]), "+f"(d[103]),
          "+f"(d[104]), "+f"(d[105]), "+f"(d[106]), "+f"(d[107]), "+f"(d[108]), "+f"(d[109]), "+f"(d[110]), "+f"(d[111]),
          "+f"(d[112]), "+f"(d[113]), "+f"(d[114]), "+f"(d[115]), "+f"(d[116]), "+f"(d[117]), "+f"(d[118]), "+f"(d[119]),
          "+f"(d[120]), "+f"(d[121]), "+f"(d[122]), "+f"(d[123]), "+f"(d[124]), "+f"(d[125]), "+f"(d[126]), "+f"(d[127])
        : "l"(da), "l"(db), "r"(acc));
}
__device__ __forceinline__ void wgmma_rs_n64_tb(float (&d)[32], uint32_t a0, uint32_t a1, uint32_t a2, uint32_t a3, uint64_t db) {
    asm volatile("wgmma.mma_async.sync.aligned.m64n64k16.f32.bf16.bf16 {"
        "%0, %1, %2, %3, %4, %5, %6, %7, %8, %9, %10, %11, %12, %13, %14, %15, %16, %17, %18, %19, %20, %21, %22, %23, %24, %25, %26, %27, %28, %29, %30, %31}, {%32, %33, %34, %35}, %36, 1, 1, 1, 1;\n"
        : "+f"(d[0]), "+f"(d[1]), "+f"(d[2]), "+f"(d[3]), "+f"(d[4]), "+f"(d[5]), "+f"(d[6]), "+f"(d[7]),
          "+f"(d[8]), "+f"(d[9]), "+f"(d[10]), "+f"(d[11]), "+f"(d[12]), "+f"(d[13]), "+f"(d[14]), "+f"(d[15]),
          "+f"(d[16]), "+f"(d[17]), "+f"(d[18]), "+f"(d[19]), "+f"(d[20]), "+f"(d[21]), "+f"(d[22]), "+f"(d[23]),
          "+f"(d[24]), "+f"(d[25]), "+f"(d[26]), "+f"(d[27]), "+f"(d[28]), "+f"(d[29]), "+f"(d[30]), "+f"(d[31])
        : "r"(a0), "r"(a1), "r"(a2), "r"(a3), "l"(db));
}
__device__ __forceinline__ void wgmma_rs_n64_tb_init(float (&d)[32], uint32_t a0, uint32_t a1, uint32_t a2, uint32_t a3, uint64_t db) {
    asm volatile("wgmma.mma_async.sync.aligned.m64n64k16.f32.bf16.bf16 {"
        "%0, %1, %2, %3, %4, %5, %6, %7, %8, %9, %10, %11, %12, %13, %14, %15, %16, %17, %18, %19, %20, %21, %22, %23, %24, %25, %26, %27, %28, %29, %30, %31}, {%32, %33, %34, %35}, %36, 0, 1, 1, 1;\n"
        : "=f"(d[0]), "=f"(d[1]), "=f"(d[2]), "=f"(d[3]), "=f"(d[4]), "=f"(d[5]), "=f"(d[6]), "=f"(d[7]),
          "=f"(d[8]), "=f"(d[9]), "=f"(d[10]), "=f"(d[11]), "=f"(d[12]), "=f"(d[13]), "=f"(d[14]), "=f"(d[15]),
          "=f"(d[16]), "=f"(d[17]), "=f"(d[18]), "=f"(d[19]), "=f"(d[20]), "=f"(d[21]), "=f"(d[22]), "=f"(d[23]),
          "=f"(d[24]), "=f"(d[25]), "=f"(d[26]), "=f"(d[27]), "=f"(d[28]), "=f"(d[29]), "=f"(d[30]), "=f"(d[31])
        : "r"(a0), "r"(a1), "r"(a2), "r"(a3), "l"(db));
}

__device__ __forceinline__ void wg_fence() { asm volatile("wgmma.fence.sync.aligned;\n" ::: "memory"); }
__device__ __forceinline__ void wg_commit() { asm volatile("wgmma.commit_group.sync.aligned;\n" ::: "memory"); }
template <int N> __device__ __forceinline__ void wg_wait() { asm volatile("wgmma.wait_group.sync.aligned %0;\n" ::"n"(N) : "memory"); }
template <int N> __device__ __forceinline__ void fence_regs(float (&a)[N]) {
#pragma unroll
    for (int i = 0; i < N; i++) asm volatile("" : "+f"(a[i])::"memory");
}
template <int N> __device__ __forceinline__ void fence_regs(uint32_t (&a)[N]) {
#pragma unroll
    for (int i = 0; i < N; i++) asm volatile("" : "+r"(a[i])::"memory");
}
__device__ __forceinline__ void mbar_init(uint32_t bar, uint32_t cnt) {
    asm volatile("mbarrier.init.shared::cta.b64 [%0], %1;\n" ::"r"(bar), "r"(cnt) : "memory");
}
__device__ __forceinline__ void mbar_expect_tx(uint32_t bar, uint32_t bytes) {
    asm volatile("mbarrier.arrive.expect_tx.shared::cta.b64 _, [%0], %1;\n" ::"r"(bar), "r"(bytes) : "memory");
}
__device__ __forceinline__ void mbar_wait(uint32_t bar, uint32_t parity) {
    asm volatile("{\n.reg .pred p;\nLW:\nmbarrier.try_wait.parity.shared::cta.b64 p, [%0], %1;\n@!p pmevent 0;\n@!p bra LW;\n}\n" ::"r"(bar), "r"(parity) : "memory");
}
__device__ __forceinline__ void mbar_wait_sleep(uint32_t bar, uint32_t parity) {
    asm volatile("{\n.reg .pred p;\nLW:\nmbarrier.try_wait.parity.shared::cta.b64 p, [%0], %1, 20000;\n@!p pmevent 0;\n@!p bra LW;\n}\n" ::"r"(bar), "r"(parity) : "memory");
}
__device__ __forceinline__ void mbar_wait_bounded(uint32_t bar, uint32_t parity) {
    asm volatile("{\n.reg .pred p;\n.reg .u32 c, d;\nmov.u32 c, %%globaltimer_lo;\nLW:\nmbarrier.try_wait.parity.shared::cta.b64 p, [%0], %1, 20000;\n@p bra LD;\n"
                 "mov.u32 d, %%globaltimer_lo;\nsub.u32 d, d, c;\nsetp.ge.u32 p, d, 4000000000;\n@p trap;\nbra LW;\nLD:\n}\n" ::"r"(bar), "r"(parity) : "memory");
}
__device__ __forceinline__ void flag_wait(const int* p, int v) {
    asm volatile("{\n.reg .pred p;\n.reg .s32 f;\nLW:\nld.acquire.gpu.global.s32 f, [%0];\nsub.s32 f, f, %1;\nsetp.lt.s32 p, f, 0;\n@p bra LW;\n}\n" ::"l"(p), "r"(v) : "memory");
}
__device__ __forceinline__ void flag_wait_bounded(const int* p, int v) {
    asm volatile("{\n.reg .pred p;\n.reg .u32 c;\n.reg .s32 f;\nmov.u32 c, 0;\nLW:\nld.acquire.gpu.global.s32 f, [%0];\nsub.s32 f, f, %1;\nsetp.ge.s32 p, f, 0;\n@p bra LD;\n"
                 "nanosleep.u32 500;\nadd.u32 c, c, 1;\nsetp.ge.u32 p, c, 4194304;\n@p trap;\nbra LW;\nLD:\n}\n" ::"l"(p), "r"(v) : "memory");
}
__device__ __forceinline__ int lane_now() {
    int l; asm volatile("mov.u32 %0, %%laneid;\n" : "=r"(l)); return l;
}
__device__ __forceinline__ bool elect() {
    uint32_t p; asm volatile("{\n.reg .pred p;\nelect.sync _|p, -1;\nselp.u32 %0, 1, 0, p;\n}\n" : "=r"(p)); return p;
}
__device__ __forceinline__ void bulk_g2s(uint32_t dst, const void* src, uint32_t bytes, uint32_t bar) {
    asm volatile("cp.async.bulk.shared::cluster.global.mbarrier::complete_tx::bytes [%0], [%1], %2, [%3];\n"
                 ::"r"(dst), "l"(src), "r"(bytes), "r"(bar) : "memory");
}
__device__ __forceinline__ void tma_g2s(uint32_t dst, const CUtensorMap* tm, int rowgroup, uint32_t bar) {
    asm volatile("cp.async.bulk.tensor.4d.shared::cluster.global.tile.mbarrier::complete_tx::bytes [%0], [%1, {0, 0, 0, %2}], [%3];\n"
                 ::"r"(dst), "l"(tm), "r"(rowgroup), "r"(bar) : "memory");
}
__device__ __forceinline__ void bar_sync(int id, int n) { asm volatile("bar.sync %0, %1;\n" ::"r"(id), "r"(n) : "memory"); }
__device__ __forceinline__ void bar_arrive(int id, int n) { asm volatile("bar.arrive %0, %1;\n" ::"r"(id), "r"(n) : "memory"); }
__device__ __forceinline__ float quad_last(float v) {
    float r; asm volatile("shfl.sync.idx.b32 %0, %1, 3, 0x1c1f, -1;\n" : "=f"(r) : "f"(v)); return r;
}
__device__ __forceinline__ float ex2(float x) { float y; asm("ex2.approx.ftz.f32 %0, %1;\n" : "=f"(y) : "f"(x)); return y; }
__device__ __forceinline__ uint32_t ex2_f16(uint32_t x) { uint32_t y; asm("ex2.approx.f16x2 %0, %1;\n" : "=r"(y) : "r"(x)); return y; }
__device__ __forceinline__ uint32_t hmax2_f16(uint32_t a, uint32_t b) { uint32_t r; asm("max.f16x2 %0, %1, %2;\n" : "=r"(r) : "r"(a), "r"(b)); return r; }
__device__ __forceinline__ float rcp(float x) { float y; asm("rcp.approx.ftz.f32 %0, %1;\n" : "=f"(y) : "f"(x)); return y; }
__device__ __forceinline__ uint32_t pack_bf16(float lo, float hi) {
    uint32_t r; asm("cvt.rn.bf16x2.f32 %0, %1, %2;\n" : "=r"(r) : "f"(hi), "f"(lo)); return r;
}
__device__ __forceinline__ uint32_t pack_f16(float lo, float hi) {
    uint32_t r; asm("cvt.rn.f16x2.f32 %0, %1, %2;\n" : "=r"(r) : "f"(hi), "f"(lo)); return r;
}
__device__ __forceinline__ uint32_t pack_f16_sat(float lo, float hi) {
    uint32_t r; asm("cvt.rn.satfinite.f16x2.f32 %0, %1, %2;\n" : "=r"(r) : "f"(hi), "f"(lo)); return r;
}
__device__ __forceinline__ float f16_lo(uint32_t v) { float r; asm("cvt.f32.f16 %0, %1;\n" : "=f"(r) : "h"((unsigned short)v)); return r; }
__device__ __forceinline__ float f16_hi(uint32_t v) { return f16_lo(v >> 16); }
__device__ __forceinline__ float bf_lo(uint32_t v) { return __uint_as_float(v << 16); }
__device__ __forceinline__ float bf_hi(uint32_t v) { return __uint_as_float(v & 0xFFFF0000u); }
__device__ __forceinline__ float bf_round(float x) { return __uint_as_float(pack_bf16(0.f, x)); }
__device__ __forceinline__ void st_release(int* p, int v) {
    asm volatile("st.release.gpu.global.s32 [%0], %1;\n" ::"l"(p), "r"(v) : "memory");
}
__device__ __forceinline__ uint4 ldg_pinned(const uint4* p) {
    uint4 v; asm volatile("ld.global.nc.v4.u32 {%0, %1, %2, %3}, [%4];\n" : "=r"(v.x), "=r"(v.y), "=r"(v.z), "=r"(v.w) : "l"(p) : "memory"); return v;
}
__device__ __forceinline__ void stmatrix_x4(uint32_t addr, uint32_t r0, uint32_t r1, uint32_t r2, uint32_t r3) {
    asm volatile("stmatrix.sync.aligned.m8n8.x4.shared.b16 [%0], {%1, %2, %3, %4};\n" ::"r"(addr), "r"(r0), "r"(r1), "r"(r2), "r"(r3) : "memory");
}

__device__ __forceinline__ uint32_t tile_off(int r, int ch) {
    return (uint32_t)((r >> 3) * 4096 + (ch >> 3) * 1024 + (r & 7) * 128 + (((ch ^ r) & 7) << 4));
}
__device__ __forceinline__ int h_unit(int qt, int u) { return qt < 78 ? u * 78 + qt : 624; }
__device__ __forceinline__ int row_off(int r) { return 4096 + h_unit(r >> 7, (r >> 4) & 7) * 8192 + (r & 8) * 512 + (r & 7) * 144; }

__device__ __forceinline__ float4 lds128f(uint32_t a) {
    float4 v; asm volatile("ld.shared.v4.f32 {%0, %1, %2, %3}, [%4];\n" : "=f"(v.x), "=f"(v.y), "=f"(v.z), "=f"(v.w) : "r"(a) : "memory"); return v;
}
__device__ __forceinline__ uint64_t lds64(uint32_t a) { uint64_t v; asm volatile("ld.shared.u64 %0, [%1];\n" : "=l"(v) : "r"(a) : "memory"); return v; }
__device__ __forceinline__ uint4 lds128(uint32_t a) {
    uint4 v; asm volatile("ld.shared.v4.u32 {%0, %1, %2, %3}, [%4];\n" : "=r"(v.x), "=r"(v.y), "=r"(v.z), "=r"(v.w) : "r"(a) : "memory"); return v;
}
__device__ __forceinline__ void sts128(uint32_t a, uint32_t x, uint32_t y, uint32_t z, uint32_t w) {
    asm volatile("st.shared.v4.u32 [%0], {%1, %2, %3, %4};\n" ::"r"(a), "r"(x), "r"(y), "r"(z), "r"(w) : "memory");
}
__device__ __forceinline__ void mbar_arrive(uint32_t bar) {
    asm volatile("mbarrier.arrive.shared::cta.b64 _, [%0];\n" ::"r"(bar) : "memory");
}
__device__ __forceinline__ uint64_t mkaddr(uint32_t lo, uint32_t hi) { uint64_t a; asm("mov.b64 %0, {%1, %2};\n" : "=l"(a) : "r"(lo), "r"(hi)); return a; }
__device__ __forceinline__ void red_add(int* p) { asm volatile("red.relaxed.gpu.global.add.s32 [%0], 1;\n" ::"l"(p) : "memory"); }
__device__ __forceinline__ void red_release(int* p) {
    asm volatile("fence.proxy.async.global;\nfence.acq_rel.gpu;\nred.relaxed.gpu.global.add.s32 [%0], 1;\n" ::"l"(p) : "memory");
}
__device__ __forceinline__ void fence_async_global() { asm volatile("fence.proxy.async.global;\n" ::: "memory"); }
__device__ __forceinline__ void fence_async_smem() { asm volatile("fence.proxy.async.shared::cta;\n" ::: "memory"); }
__device__ __forceinline__ void bulk_s2g(void* dst, uint32_t src, uint32_t bytes) {
    asm volatile("cp.async.bulk.global.shared::cta.bulk_group [%0], [%1], %2;\ncp.async.bulk.commit_group;\n" ::"l"(dst), "r"(src), "r"(bytes) : "memory");
}
__device__ __forceinline__ void mma16816(float (&c)[4], uint32_t a0, uint32_t a1, uint32_t a2, uint32_t a3, uint32_t b0, uint32_t b1) {
    asm("mma.sync.aligned.m16n8k16.row.col.f32.bf16.bf16.f32 {%0, %1, %2, %3}, {%4, %5, %6, %7}, {%8, %9}, {%0, %1, %2, %3};\n"
        : "+f"(c[0]), "+f"(c[1]), "+f"(c[2]), "+f"(c[3]) : "r"(a0), "r"(a1), "r"(a2), "r"(a3), "r"(b0), "r"(b1));
}
__device__ __forceinline__ void mma1688(float (&c)[4], uint32_t a0, uint32_t a1, uint32_t b0) {
    asm("mma.sync.aligned.m16n8k8.row.col.f32.bf16.bf16.f32 {%0, %1, %2, %3}, {%4, %5}, {%6}, {%0, %1, %2, %3};\n"
        : "+f"(c[0]), "+f"(c[1]), "+f"(c[2]), "+f"(c[3]) : "r"(a0), "r"(a1), "r"(b0));
}
__device__ __forceinline__ uint32_t hadd2_f16(uint32_t a, uint32_t b) { uint32_t r; asm("add.rn.f16x2 %0, %1, %2;\n" : "=r"(r) : "r"(a), "r"(b)); return r; }
__device__ __forceinline__ uint32_t hadd2(uint32_t a, uint32_t b) { uint32_t r; asm("add.rn.bf16x2 %0, %1, %2;\n" : "=r"(r) : "r"(a), "r"(b)); return r; }
__device__ __forceinline__ uint32_t hmul2(uint32_t a, uint32_t b) { uint32_t r; asm("mul.rn.bf16x2 %0, %1, %2;\n" : "=r"(r) : "r"(a), "r"(b)); return r; }
__device__ __forceinline__ uint32_t hfma2(uint32_t a, uint32_t b, uint32_t c) { uint32_t r; asm("fma.rn.bf16x2 %0, %1, %2, %3;\n" : "=r"(r) : "r"(a), "r"(b), "r"(c)); return r; }

constexpr int SM_Q = 0;
constexpr int SM_KV = 65536;
constexpr int SM_ML = SM_KV + STAGES * KV_BYTES;
constexpr int SM_BAR = SM_ML + 1024;
constexpr int SM_TOTAL = SM_BAR + 256;
constexpr float SCALE_LOG2 = 1.4426950408889634f / 16.0f;
constexpr float KV_SCALE = 6.f;
constexpr float KV_OFF = 48.f;
constexpr uint32_t KV_OFF2 = 0x52005200u;
constexpr uint32_t KV_OFF8 = 0x5A005A00u;
constexpr uint32_t NEG2 = 0x80008000u;
constexpr uint32_t S_LIMIT = 0x4B804B80u;
constexpr float REF_UP = REFUP;
__device__ __forceinline__ uint32_t kvf(uint32_t a, uint32_t off) {
    uint32_t r; asm("fma.rn.f16x2 %0, %1, %2, %3;\n" : "=r"(r) : "r"(a), "r"(pack_f16(KV_SCALE, KV_SCALE)), "r"(off)); return r;
}
enum { BAR_PP0 = 1, BAR_PP1 = 2, BAR_WG0 = 3, BAR_WG1 = 4, BAR_H0 = 5, BAR_H1 = 6, BAR_AUX = 7, BAR_BF = 8, BAR_H2 = 9, BAR_X = 10, BAR_GO = 11, BAR_WG2 = 12, BAR_ST = 13 };

struct Hot {
    const __nv_bfloat16 *wk, *wq, *x;
    Scratch* s;
};
struct Params {
    const __nv_bfloat16* deg_inv;
    const int *src, *dst;
    __nv_bfloat16* out;
    uint32_t dhi;
    int E;
    CUtensorMap tm_out;
    CUtensorMap tm_outc;
    CUtensorMap tm_w[3];
};
static_assert(offsetof(Params, tm_outc) == offsetof(Params, tm_out) + 128, "layout");
#define SC_PAIR (blockIdx.x < 104)
#define SC_TAIL (blockIdx.x >= NCTA - 2)
#define SC_LAST (blockIdx.x == NCTA - 1)
#define SC_HELP (SC_PAIR && rank)
#define SC_OWNER (!SC_HELP && !SC_LAST)
#define SC_QT1 (26 + (int)(blockIdx.x >> 1))
#define SC_QT0 (SC_PAIR ? (rank ? (int)(blockIdx.x >> 2) : SC_QT1) : SC_TAIL ? 78 : (int)blockIdx.x - 104)
#define SC_NKV (SC_LAST ? 50 : 75)
#define SC_CLS (SC_PAIR ? (rank ? 0x120 ^ (blockIdx.x & 2) * 0x80 : 0x430) | (blockIdx.x & 2) >> 1 : SC_LAST ? 0x10 : 0x432)
#define SC_NW (SC_PAIR ? 8 : SC_LAST ? 0 : 4)
#define SC_ZB (2 * SC_QT1 + 1 - (int)rank)
#define SC_TZB(k) (rank && !(k) ? 156 : 2 * (k) - (int)rank)

__global__ void __cluster_dims__(2, 1, 1) __launch_bounds__(384, 1) k_main(const __grid_constant__ Hot H, const __grid_constant__ Params P) {
    extern __shared__ __align__(1024) uint8_t smem[];
    const uint32_t sb = (uint32_t)__cvta_generic_to_shared(smem);
    const int tid = threadIdx.x, wg = __shfl_sync(~0u, tid >> 7, 0);
    const int lane = tid & 31, g = lane >> 2, q = lane & 3;
    const uint32_t rank = blockIdx.x & 1;
    const uint32_t bar_full = sb + SM_BAR, bar_q = bar_full + 32, bar_go = bar_full + 48;
    const uint32_t bar_pin = bar_full + 56;
    const uint32_t bar_qfree = bar_full + 72, bar_pdone = bar_full + 88, bar_zst = bar_full + 104, bar_rfree = bar_full + 120;
    const uint32_t bar_empty = bar_full + 128, bar_end = bar_full + 160, s_tm = bar_full + 184, bar_x = bar_full + 192;
    const uint32_t bar_a = sb + SM_ML;

    const int t = tid & 127, warp = __shfl_sync(~0u, t >> 5, 0);
    int ep = 0;
    if (wg & 2) {
        unsigned done;
        {
            uint4 ra[2], rb[2], rk[5][2];
            if (blockIdx.x < 128) {
                const int e = (blockIdx.x >> 4) * 32 + (g >> 1) * 8 + (blockIdx.x & 8) / 2 + (g & 1);
                const uint4* pq = (const uint4*)(H.wq + e * 256) + warp * 8 + q;
                const uint4* pk = (const uint4*)(H.wk + ((blockIdx.x & 7) * 32 + g) * 256) + warp * 8 + q;
                const uint4* pz = (const uint4*)(H.wk + 255 * 256) + warp * 8 + q;
#pragma unroll
                for (int s = 0; s < 2; s++) {
                    ra[s] = ldg_pinned(pq + 4 * s);
                    rb[s] = ldg_pinned(pq + 4 * s + 64);
#pragma unroll
                    for (int n = 0; n < 4; n++) rk[n][s] = ldg_pinned(pk + 4 * s + n * 256);
                    rk[4][s] = ldg_pinned(pz + 4 * s);
                }
            }
            asm volatile("{\n.reg .pred p;\nsetp.eq.s32 p, %2, 0;\nmov.u32 %0, 0;\n@p ld.global.cg.u32 %0, [%1];\n}\n" : "=r"(done) : "l"(&g_sync[SY_DONE * 32]), "r"(lane) : "memory");
            bar_arrive(BAR_X, 384);
            if (warp == 0 && elect()) {
#pragma unroll
                for (int i = 0; i < 21; i++) mbar_init(bar_full + 8 * i, i < 9 ? 1 : i < 16 ? 4 : i == 20 ? 11 : SC_TAIL ? 4 : 8);
#pragma unroll
                for (int i = 0; i < 4; i++) mbar_init(bar_a + 8 * i, 1);
                mbar_expect_tx(bar_pin, QB_BYTES / 2 + 512); mbar_expect_tx(bar_pin + 8, QB_BYTES / 2);
                asm volatile("fence.mbarrier_init.release.cluster;\n" ::: "memory");
            }
            __syncwarp();
            asm volatile("barrier.cluster.arrive.relaxed.aligned;\n" ::: "memory");
            if (blockIdx.x < 128) {
                float c[5][4] = {};
#pragma unroll
                for (int s = 0; s < 2; s++) {
#pragma unroll
                    for (int n = 0; n < 5; n++) mma16816(c[n], ra[s].x, rb[s].x, ra[s].y, rb[s].y, rk[n][s].x, rk[n][s].y);
#pragma unroll
                    for (int n = 0; n < 5; n++) mma16816(c[n], ra[s].z, rb[s].z, ra[s].w, rb[s].w, rk[n][s].z, rk[n][s].w);
                }
#pragma unroll
                for (int i = 0; i < 4; i++) {
                    const int r = i & 2, n = (i & 1) * 2;
                    sts128(sb + SM_KV + 3 * KV_BYTES + QB_BYTES + i * 2048 + t * 16, __float_as_uint(c[n][r] - c[4][r]), __float_as_uint(c[n][r + 1] - c[4][r]),
                           __float_as_uint(c[n + 1][r] - c[4][r]), __float_as_uint(c[n + 1][r + 1] - c[4][r]));
                }
            }
        }
        asm volatile("setmaxnreg.dec.sync.aligned.u32 %0;\n" ::"n"(REG_P));
        if (blockIdx.x < 128) {
            bar_sync(BAR_WG2, 128);
            float4 v[4];
#pragma unroll
            for (int i = 0; i < 4; i++) v[i] = lds128f(sb + SM_KV + 3 * KV_BYTES + QB_BYTES + (warp & 2) * 2048 + (lane & 1) * 2048 + i * 512 + ((warp & 1) * 16 + (lane >> 1)) * 16);
            constexpr float SC = SCALE_LOG2 / KV_SCALE;
            const int r = (warp & 1) * 4 + (lane >> 3);
            *(uint2*)(g_w + tile_off((blockIdx.x >> 3) * 16 + (warp & 2) * 4 + r, (blockIdx.x & 7) * 4 + ((lane >> 1) & 3)) + (lane & 1) * 8) =
                make_uint2(pack_f16_sat(((v[0].x + v[1].x) + (v[2].x + v[3].x)) * SC, ((v[0].y + v[1].y) + (v[2].y + v[3].y)) * SC) | 1,
                           pack_f16_sat(((v[0].z + v[1].z) + (v[2].z + v[3].z)) * SC, ((v[0].w + v[1].w) + (v[2].w + v[3].w)) * SC) | 1);
            if (warp != 1) {
                bar_arrive(BAR_AUX, 128);
            } else {
                bar_sync(BAR_AUX, 128);
                if (elect()) { red_add(&g_sync[SY_DONE * 32 + 4 + (blockIdx.x >> 5)]); }
                __syncwarp();
            }
        }
        else bar_sync(BAR_WG2, 128);
        if (warp == 1) bar_arrive(BAR_GO, 160);
        auto load_a = [&](int j) {
            if (elect()) {
                mbar_expect_tx(bar_a + 8 * j, QB_BYTES);
                bulk_g2s(sb + SM_KV + j * KV_BYTES, g_w + j * QB_BYTES, QB_BYTES, bar_a + 8 * j);
            }
            __syncwarp();
        };
        if (warp == 0) {
            auto poll = [&]() { int c; asm volatile("ld.relaxed.gpu.global.s32 %0, [%1];\n" : "=r"(c) : "l"(&g_sync[SY_DONE * 32 + 4 + (lane & 3)]) : "memory"); return c; };
#pragma unroll 1
            for (int j = 0; j < 4;) {
#pragma unroll 1
                for (const uint32_t mk = __ballot_sync(~0u, poll() >= 32) & 15; (mk >> j) & 1; j++) load_a(j);
            }
        } else if (warp & 1) {
#pragma unroll 1
            for (int j = 0, n = 0; j < 4;) {
                mbar_wait_bounded(bar_a + 8 * j, n & 1);
                uint32_t ok = 1;
#pragma unroll
                for (int i = 0; i < 16; i++) {
                    uint32_t v;
                    asm volatile("ld.shared.u32 %0, [%1];\n" : "=r"(v) : "r"(sb + SM_KV + j * KV_BYTES + (warp & 2) * 8192 + i * 1024 + lane * 32 + g * 4) : "memory");
                    ok &= v;
                }
                asm volatile("{\n.reg .pred p;\nsetp.ne.u32 p, %0, 0;\nbar.red.and.pred p, %1, 64, p;\nselp.u32 %0, 1, 0, p;\n}\n" : "+r"(ok) : "n"((int)BAR_WG2) : "memory");
                if (__any_sync(~0u, ok)) {
                    if (warp == 1 && elect()) asm volatile("mbarrier.arrive.shared::cta.b64 _, [%0];\nmbarrier.inval.shared::cta.b64 [%1];\n" ::"r"(bar_full + 8 * j), "r"(bar_a + 8 * j) : "memory");
                    __syncwarp();
                    j++; n = 0;
                } else {
                    asm volatile("{\n.reg .pred p;\nsetp.gt.s32 p, %0, 1000000;\n@p trap;\n}\n" ::"r"(++n) : "memory");
                    fence_async_smem();
                    if (warp == 1) load_a(j);
                }
            }
        }
        done = __shfl_sync(~0u, done, 0);
        ep = (int)(done / NCTA) + 1;
        asm volatile("barrier.cluster.wait.acquire.aligned;\n" ::: "memory");
        if (warp == 0) {
            asm volatile("st.shared.u64 [%0], %1;\n" ::"r"(s_tm), "l"(&P.tm_outc) : "memory");
            __syncwarp();
            if (elect()) {
                const uint8_t* base = (const uint8_t*)H.s;
                uint32_t cls = SC_CLS, bytes = KV_BYTES, step = 5 * KV_BYTES;
                const uint8_t* src = base;
                bool tick;
                int next = 0;
                const int nit = SC_NKV + SC_NW;
#pragma unroll 1
                for (int j = 0; j < nit; j++) {
                    const uint32_t slot = sb + SM_KV + (j & 3) * KV_BYTES, fb = bar_full + 8 * (j & 3);
                    if (j == next) {
                        const int k = j - SC_NKV;
                        const int sw = SC_HELP ? j - 25 : -1;
                        next = j + 1;
                        tick = j >= 3 && k < 0 && (unsigned)sw >= 4 && !SC_TAIL;
                        if (j >= 3 && (unsigned)sw >= 5) next = k >= 0 ? next : j < GO0 ? GO0 : j < 25 ? 25 : j < GO1 ? GO1 : j < 49 ? 49 : j < 50 ? 50 : 75;
                        if (j == 0 || j == 25 || j == 50) { src = base + (4096 + (cls & 15) * KV_BYTES); cls >>= 4; }
                        if (SC_TAIL ? j == nit - 1 : j == GO0 || j == GO1) mbar_arrive(bar_go);
                        int fo = -1, fv = 1;
                        if (j < 3) { fo = (SY_H0 + 5 * j + (SC_CLS & 15)) * 32; fv = 5; }
                        if (j == 3) { fo = SY_H1 * 32; fv = 79; }
                        if (sw == 1) fo = 25 * 32 + SC_QT1;
                        if (k == 0) fo = SY_B * 32;
                        if (k == 1 && !SC_PAIR) { fo = SY_AUX0 * 32; fv = NAUX; }
                        if (k == 2 && SC_PAIR) { fo = SY_AUX * 32; fv = NAUX / 3; }
                        if (fo >= 0) {
                            flag_wait(g_sync + fo, fv * ep);
                            fence_async_global();
                        }
                        if (sw == 2 || (k == 2 && !SC_TAIL)) {
                            uint32_t qs = sw == 2 ? offsetof(Scratch, q) + (2 * SC_QT1 + 1) * QB_BYTES : SC_PAIR ? offsetof(Scratch, agg) + SC_ZB * QB_BYTES : offsetof(Scratch, part) + SC_QT0 * (4 * PART_BYTES);
#pragma unroll 1
                            for (int w = 0; w < (k == 2 && SC_PAIR ? 1 : 2); w++) {
                                mbar_wait_sleep(bar_qfree + 8 * w, k == 2 && SC_HELP);
                                mbar_expect_tx(bar_q + 8 * w, SC_PAIR ? QB_BYTES : PART_BYTES);
                                if (!SC_PAIR) bulk_g2s(sb + SM_ML + w * 512, base + (qs + (w ? -512 : QB_BYTES)), 512, bar_q + 8 * w);
                                bulk_g2s(sb + SM_Q + w * QB_BYTES, base + qs, QB_BYTES, bar_q + 8 * w);
                                qs += sw == 2 ? -QB_BYTES : PART_BYTES + 512;
                            }
                        }
                        if ((sw | 1) == 3) {
                            mbar_wait_sleep(bar_pdone + 8 * (sw - 2), 0);
                            bulk_s2g(g_part + (blockIdx.x - 3 + sw) * PART_BYTES, slot, PART_BYTES);
                            asm volatile("cp.async.bulk.wait_group.read 0;\n" ::: "memory");
                        }
                        if (sw == 5) {
                            asm volatile("cp.async.bulk.wait_group 0;\n" ::: "memory");
                            red_release(&g_sync[SY_PART * 32]);
                        }
                        if (k == 0) {
                            asm volatile("prefetch.tensormap [%0];\n" ::"l"(&P.tm_outc) : "memory");
                            src = g_w + (12 - SC_NW) * QB_BYTES; bytes = step = QB_BYTES;
                        }
                        if (k == 2) next = SC_TAIL ? nit - 1 : nit;
                    }
                    mbar_wait_sleep(fb + (bar_empty - bar_full), (j >> 2) & 1);
                    mbar_expect_tx(fb, bytes);
                    if (tick)
                        asm volatile("{\n.reg .pred p;\n.reg .u32 a, b, c;\nmov.u32 c, 1;\nmov.u32 a, %%globaltimer_lo;\nnot.b32 b, a;\nand.b32 b, b, %0;\nshr.u32 b, b, 1;\nnanosleep.u32 b;\n"
                                     "L:\nmov.u32 b, %%globaltimer_lo;\nlop3.b32 b, b, a, c, 0xBE;\nadd.u32 c, c, %2;\nsetp.le.u32 p, b, %0;\n@p nanosleep.u32 %1;\n@p bra L;\n}\n" ::"n"(TICK - 1), "n"(TSL), "n"(TICK / 32) : "memory");
                    bulk_g2s(slot, src, bytes, fb);
                    src += step;
                }
            }
        } else {
            if (warp == 2 && SC_OWNER) {
                uint8_t* dst = g_hz + 4096 + h_unit(SC_QT0, 0) * 8192;
                auto send = [&](int u0, int u1) {
#pragma unroll
                    for (int u = u0; u < u1; u++) {
                        bulk_s2g(dst + u * (78 * 8192), sb + SM_Q + u * 8192, 8192);
                        asm volatile("cp.async.bulk.wait_group 0;\n" ::: "memory");
                    }
                };
                int* f0 = &g_sync[(SY_H0 + SC_QT0 / 5) * 32];
                bar_sync(BAR_H0, 64);
                if (elect()) {
                    send(0, 1);
                    if (SC_QT0 < 65) red_release(f0);
                }
                bar_sync(BAR_H1, 160);
                if (elect()) {
                    if (!SC_TAIL) send(1, 4);
                    mbar_arrive(bar_q);
                }
                bar_sync(BAR_H2, 160);
                if (elect()) {
                    if (!SC_TAIL) { send(4, 8); mbar_arrive(bar_q + 8); }
                    red_release(&g_sync[SY_H1 * 32]);
                }
                __syncwarp();
            }
        }
    } else {
        const uint32_t sq = sb + SM_Q + wg * QB_BYTES;
        const uint32_t qbar = bar_q + 8 * wg;
        const uint32_t dq0 = __shfl_sync(~0u, ((sq & 0x3FFFF) >> 4) | (64u << 16), 0);
        const uint32_t dk0 = __shfl_sync(~0u, (((sb + SM_KV) & 0x3FFFF) >> 4) | (64u << 16), 0);
        float o[128];
        int it = 4;
        const uint32_t dhi = P.dhi;
        auto release = [&](int st, int n = 1) {
            if (n == 1) asm volatile("{\n.reg .pred p;\nelect.sync _|p, -1;\n@p mbarrier.arrive.shared::cta.b64 _, [%0];\n}\n" ::"r"(bar_empty + 8 * st) : "memory");
            else asm volatile("{\n.reg .pred p;\nelect.sync _|p, -1;\n@p mbarrier.arrive.shared::cta.b64 _, [%0], 2;\n}\n" ::"r"(bar_empty + 8 * st) : "memory");
        };
        const bool active = !(SC_TAIL && wg == 1);
        auto pp_sync = [&]() { if (!SC_TAIL) bar_sync(BAR_PP0 + wg, 256); };
        auto pp_arrive = [&]() { if (!SC_TAIL) bar_arrive(BAR_PP1 - wg, 256); };
        auto warp_arrive = [&](uint32_t bar) {
            __syncwarp();
            asm volatile("{\n.reg .pred p;\nelect.sync _|p, -1;\n@p mbarrier.arrive.shared::cta.b64 _, [%0];\n}\n" ::"r"(bar + 8 * wg) : "memory");
        };
        auto peer_arrive = [&]() {
            asm volatile("{\n.reg .pred p;\n.reg .b32 a;\nelect.sync _|p, -1;\nmapa.shared::cluster.u32 a, %0, %1;\n"
                         "@p mbarrier.arrive.shared::cluster.b64 _, [a];\n}\n" ::"r"(bar_rfree), "r"(rank ^ 1) : "memory");
        };
        auto cut = [&]() { asm volatile("{\n.reg .pred p;\nsetp.lt.s32 p, %0, 0;\nL:\n@p pmevent 0;\n@p bra L;\n}\n" ::"r"(dhi) : "memory"); };
        float qs = 1.f;
        uint32_t qr[4 * NQR];
        auto stage_q = [&]() {
            int k = dhi & 1;
            uint32_t big;
#pragma unroll 1
            do {
                if (k) {
                    qs *= 16.f;
#pragma unroll
                    for (int i = 0; i < 128; i++) o[i] *= 0.0625f;
                }
                big = 0;
                auto pk = [&](int i) { return QRND(pack_f16_sat(o[i], o[i + 1])); };
#pragma unroll
                for (int i = 0; i < 16; i++) {
                    if (QREG(i) >= 0) continue;
                    const uint32_t v0 = pk(8 * i), v1 = pk(8 * i + 2), v2 = pk(8 * i + 4) | (i == 15 ? k : 0), v3 = pk(8 * i + 6);
                    stmatrix_x4(sq + warp * 8192 + tile_off(lane & 15, 2 * i + (lane >> 4)), v0, v1, v2, v3);
                    big |= v0 | v1; big |= v2 | v3;
                    if (i == 15) cut();
                }
#pragma unroll
                for (int i = 0; i < 64; i++)
                    if (const int r = QREG(i / 4); r >= 0) big |= qr[4 * r + (i & 3)] = pk(2 * i);
                k++;
            } while (__any_sync(~0u, (big & 0x40004000u) && k < 8));
        };
        uint32_t s[20];
        auto issue_qk = [&](int st, int sh = 24) {
            const uint64_t kb = mkaddr(dk0 + st * (KV_BYTES >> 4), dhi);
            const uint64_t qd = mkaddr(dq0 + ((uint32_t)it >> sh), dhi);
            wgmma_ss_n80_init(s, qd, kb);
#pragma unroll
            for (int j = 1; j < 16; j++) {
                const int kk = j == 8 ? 15 : j < 8 ? j : j - 1;
                const int r = QREG(kk);
                if (r >= 0) wgmma_rs_n80(s, qr[4 * r], qr[4 * r + 1], qr[4 * r + 2], qr[4 * r + 3], kb + ((kk >> 2) * 64 + (kk & 3) * 2));
                else wgmma_ss_n80(s, qd + ((kk >> 2) * 64 + (kk & 3) * 2), kb + ((kk >> 2) * 64 + (kk & 3) * 2));
            }
            wg_commit();
        };

        {
            const int rb = (2 * SC_QT0 + wg) * 64 + warp * 16;
            const uint32_t xbar = bar_x + 32 * wg + 8 * warp;
            if (elect()) {
                mbar_init(xbar, 1);
                asm volatile("fence.mbarrier_init.release.cluster;\nfence.proxy.async.shared::cta;\n" ::: "memory");
                mbar_expect_tx(xbar, rb < NN ? 8192 : 0);
            }
            asm volatile("barrier.cluster.arrive.relaxed.aligned;\n" ::: "memory");
            if (wg == 1) pp_arrive();
            bar_sync(BAR_X, 384);
            if (wg == 1) bar_sync(BAR_GO, 160);
            if (rb < NN && elect()) bulk_g2s(sq + warp * 8192, H.x + (size_t)rb * 256, 8192, xbar);
            if (rb >= NN) {
#pragma unroll 1
                for (int i = 0; i < 16; i++) sts128(sq + warp * 8192 + i * 512 + lane * 16, 0, 0, 0, 0);
            }
            __syncwarp();
            mbar_wait(xbar, 0);
            uint4 xa[8], xb[8];
#pragma unroll
            for (int s = 0; s < 8; s++) {
                xa[s] = lds128(sq + (warp * 16 + g) * 512 + (4 * s + q) * 16);
                xb[s] = lds128(sq + (warp * 16 + g + 8) * 512 + (4 * s + q) * 16);
            }
            float sm[2][4], sq2[2][4][4];
#pragma unroll
            for (int i = 0; i < 4; i++) {
                sm[0][i] = sm[1][i] = 0.f;
#pragma unroll
                for (int k = 0; k < 4; k++) sq2[0][k][i] = sq2[1][k][i] = 0.f;
            }
#pragma unroll
            for (int s = 0; s < 8; s++) {
#pragma unroll
                for (int hh = 0; hh < 2; hh++) {
                    const uint4 v = hh ? xb[s] : xa[s];
                    mma16816(sm[hh], v.x, v.y, v.z, v.w, 0x3F803F80u, 0x3F803F80u);
                    mma1688(sq2[hh][0], v.x, v.y, v.x); mma1688(sq2[hh][1], v.x, v.y, v.y);
                    mma1688(sq2[hh][2], v.z, v.w, v.z); mma1688(sq2[hh][3], v.z, v.w, v.w);
                }
            }
            float inv[2], off[2];
#pragma unroll
            for (int hh = 0; hh < 2; hh++) {
                const float mean = (sm[hh][0] + sm[hh][2]) * (1.f / 256.f);
                const float d0 = (sq2[hh][0][0] + sq2[hh][2][0]) + (sq2[hh][1][2] + sq2[hh][3][2]);
                const float d1 = (sq2[hh][0][1] + sq2[hh][2][1]) + (sq2[hh][1][3] + sq2[hh][3][3]);
                const float ss = __shfl_sync(~0u, (g & 1) ? d1 : d0, g * 4 + (g >> 1));
                const float var = fmaxf(ss * (1.f / 256.f) - mean * mean, 0.f);
                float sd;
                asm("sqrt.approx.ftz.f32 %0, %1;\n" : "=f"(sd) : "f"(bf_round(bf_round(var) + 1e-5f)));
                asm("rcp.approx.ftz.f32 %0, %1;\n" : "=f"(inv[hh]) : "f"(bf_round(sd)));
                off[hh] = -mean * inv[hh];
            }
            uint32_t a[64];
#pragma unroll
            for (int s = 0; s < 8; s++) {
                a[8 * s] = xa[s].x; a[8 * s + 1] = xb[s].x; a[8 * s + 2] = xa[s].y; a[8 * s + 3] = xb[s].y;
                a[8 * s + 4] = xa[s].z; a[8 * s + 5] = xb[s].z; a[8 * s + 6] = xa[s].w; a[8 * s + 7] = xb[s].w;
            }
            fence_regs(a);
            if (wg == 1 && __any_sync(~0u, inv[0] + inv[1] != -1.f)) bar_arrive(BAR_ST, 256);
            asm volatile("setmaxnreg.inc.sync.aligned.u32 %0;\n" ::"n"(REG_C));
            fence_regs(a);
#pragma unroll
            for (int i = 0; i < 64; i++)
                a[i] = pack_f16(fmaf(bf_lo(a[i]), inv[i & 1], off[i & 1]), fmaf(bf_hi(a[i]), inv[i & 1], off[i & 1]));
            if (SC_OWNER) {
                const uint32_t ko = (q & 2) ? KV_OFF2 : KV_OFF2 | NEG2;
#pragma unroll
                for (int i = 0; i < 16; i++) {
                    const uint32_t mk = (i == 15 && q == 3) ? 0xFFFFu : ~0u;
                    stmatrix_x4(sq + warp * 8192 + tile_off(lane & 15, 2 * i + (lane >> 4)), kvf(a[4 * i], ko), kvf(a[4 * i + 1], ko),
                                kvf(a[4 * i + 2] & mk, ko), kvf(a[4 * i + 3] & mk, ko));
                }
                fence_async_smem();
                if (tid < 32) bar_arrive(BAR_H0, 64);
                bar_arrive(wg ? BAR_H2 : BAR_H1, 160);
            }
            asm volatile("barrier.cluster.wait.acquire.aligned;\n" ::: "memory");
            if (wg == 0) bar_sync(BAR_ST, 256);
            if (active) {
                fence_regs(a);
#pragma unroll
                for (int c = 0; c < 4; c++) {
                    if (c == 1) {
                        if (wg == 1) {
                            wg_wait<0>();
                            release(0);
                        }
                        pp_sync();
                    }
                    mbar_wait(bar_full + 8 * c, 0);
                    const uint64_t wb = mkaddr(dk0 + c * (KV_BYTES >> 4), dhi);
                    wg_fence();
#pragma unroll
                    for (int kk = 0; kk < 4; kk++) {
                        if (c | kk) wgmma_rs_n256_tb(o, a[16 * c + 4 * kk], a[16 * c + 4 * kk + 1], a[16 * c + 4 * kk + 2], a[16 * c + 4 * kk + 3], wb + kk * 512);
                        else wgmma_rs_n256_tb_init(o, a[0], a[1], a[2], a[3], wb);
                    }
                    wg_commit();
                    if (c > 0) { wg_wait<1>(); if (c > 1 || wg == 0) release(c - 1); }
                }
                if (wg == 0) pp_arrive();
                wg_wait<0>();
                fence_regs(o);
                release(3);
                if (SC_OWNER) mbar_wait(qbar, 0);
                stage_q();
                fence_async_smem();
                bar_sync(BAR_WG0 + wg, 128);
                mbar_wait(bar_full, 1);
                wg_fence();
                issue_qk(0);
                if (wg == 1) pp_arrive();
                if (SC_PAIR && !rank) {
#pragma unroll
                    for (int i = 0; i < 16; i++)
                        if (const int r = QREG(i); r >= 0)
                            stmatrix_x4(sq + warp * 8192 + tile_off(lane & 15, 2 * i + (lane >> 4)), qr[4 * r], qr[4 * r + 1], qr[4 * r + 2], qr[4 * r + 3]);
                }
            } else {
                peer_arrive();
            }
        }

        uint32_t p[20];
        float m0 = 0.f, m1 = 0.f, e0, e1, l0, l1;
        uint32_t plim;
        uint32_t qphase = (SC_OWNER && active) ? 1 : 0;
        auto issue_pv = [&](int st, int acc) {
            const uint64_t vb = mkaddr(dk0 + st * (KV_BYTES >> 4), dhi);
            wgmma_rs_n256_tb_pred(o, p[0], p[1], p[2], p[3], vb, acc);
#pragma unroll
            for (int kk = 1; kk < 5; kk++)
                wgmma_rs_n256_tb(o, p[4 * kk], p[4 * kk + 1], p[4 * kk + 2], p[4 * kk + 3], vb + kk * 512);
            wg_commit();
        };
        auto mq_addr = [&](int ln) { return sq + warp * 8192 + tile_off(ln >> 2, 31) + 12; };
        auto exceeds = [&](const uint32_t (&p)[20]) {
            uint32_t a = __vimax3_s16x2(S_LIMIT, p[0], p[1]), b = __vimax3_s16x2(p[2], p[3], p[4]);
#pragma unroll
            for (int i = 5; i < 17; i += 4) { a = __vimax3_s16x2(a, p[i], p[i + 1]); b = __vimax3_s16x2(b, p[i + 2], p[i + 3]); }
            a = __vimax3_s16x2(a, p[17], p[18]);
            return __any_sync(~0u, __vimax3_s16x2(a, b, p[19]) != plim);
        };
        auto remax = [&](float& a, float& b, bool store) {
            const int ln = lane_now();
            asm volatile("" : "+f"(qs));
            uint32_t ha = s[0], hb = s[1];
#pragma unroll
            for (int i = 1; i < 10; i++) { ha = hmax2_f16(ha, s[2 * i]); hb = hmax2_f16(hb, s[2 * i + 1]); }
            ha = hmax2_f16(__byte_perm(ha, hb, 0x5410), __byte_perm(ha, hb, 0x7632));
            ha = hmax2_f16(ha, __shfl_xor_sync(~0u, ha, 1));
            ha = hmax2_f16(ha, __shfl_xor_sync(~0u, ha, 2));
            a = fmaxf(a, f16_lo(ha) * qs - e0 + REF_UP); b = fmaxf(b, f16_hi(ha) * qs - e1 + REF_UP);
            const float qi = __uint_as_float(0x7F000000u - __float_as_uint(qs)) * (-1.f / KV_OFF);
            const uint32_t u = pack_f16((m0 + a) * qi, (m1 + b) * qi);
            const float g0 = (m0 + a) + KV_OFF * qs * f16_lo(u), g1 = (m1 + b) + KV_OFF * qs * f16_hi(u);
            const bool x0 = fabsf(g0) <= 1.f, x1 = fabsf(g1) <= 1.f;
            if (x0) a -= g0;
            if (x1) b -= g1;
            const float da = a + e0, db = b + e1;
            m0 += a; m1 += b;
            e0 = x0 ? 0.f : g0; e1 = x1 ? 0.f : g1;
            plim = (x0 && x1 && qs == 1.f) ? S_LIMIT : 0u;
            asm volatile("{\n.reg .pred p;\nsetp.ne.s32 p, %3, 0;\n@p st.shared.u16 [%0], %1;\n@p st.shared.u16 [%0 + 4096], %2;\n}\n"
                         ::"r"(mq_addr(ln) + 2), "h"((unsigned short)u), "h"((unsigned short)(u >> 16)), "r"((int)(store && (ln & 3) == 0)) : "memory");
#pragma unroll
            for (int i = 0; i < 10; i++) {
                p[2 * i] = pack_f16(ex2(fmaf(f16_lo(s[2 * i]), qs, -da)), ex2(fmaf(f16_hi(s[2 * i]), qs, -da)));
                p[2 * i + 1] = pack_f16(ex2(fmaf(f16_lo(s[2 * i + 1]), qs, -db)), ex2(fmaf(f16_hi(s[2 * i + 1]), qs, -db)));
            }
            fence_regs(p);
            fence_async_smem();
            __syncwarp();
        };

        auto row_sums = [&](float& z0, float& z1, int q) {
            z0 = quad_last(o[125]); z1 = quad_last(o[127]);
            l0 = z0 * (KV_SCALE / KV_OFF); l1 = z1 * (KV_SCALE / KV_OFF);
            if (!(q & 2)) { z0 = -z0; z1 = -z1; }
        };
        auto stats = [&](int q) { return (q & 2) ? ((q & 1) ? l1 : m1) : ((q & 1) ? l0 : m0); };
        const int nseg = SC_HELP ? 2 : 1;
        if (active) {
#pragma unroll 1
        for (int seg = 0;; seg++) {
            wg_wait<0>();
            fence_regs(s);
            e0 = e1 = 0.f;
            const int it0 = it, itl = __shfl_sync(~0u, seg + 1 < nseg ? 3 + 25 : 3 + SC_NKV, 0);
            const int itx = (wg == 1 && seg + 1 == nseg) ? itl : -1;
            bool redo = true, have = !seg;
#pragma unroll 1
            for (;;) {
                if (!have) {
#pragma unroll
                    for (int i = 0; i < 20; i++) p[i] = ex2_f16(s[i]);
                    redo = exceeds(s);
                }
                if (redo) {
                    float d0 = it != it0 ? 0.f : -INFINITY, d1 = d0;
                    remax(d0, d1, it != itl);
                    if (it != it0) {
                        const float a0 = ex2(-d0), a1 = ex2(-d1);
#pragma unroll
                        for (int i = 0; i < 32; i++) { o[4 * i] *= a0; o[4 * i + 1] *= a0; o[4 * i + 2] *= a1; o[4 * i + 3] *= a1; }
                    } else if (SC_OWNER) {
                        warp_arrive(bar_pdone);
                    }
                }
                if (it == itl) break;
                const int stp = it & 3;
                it++;
                pp_sync();
                fence_regs(o); fence_regs(p);
                have = SC_TAIL || it == itx;
                if (!have) {
                    wg_fence();
                    issue_pv(stp, it - 1 - it0);
                    mbar_wait(bar_full + 8 * (it & 3), (it >> 2) & 1);
                    wg_fence();
                    issue_qk(it & 3);
                    pp_arrive();
                    wg_wait<0>();
                    fence_regs(s); fence_regs(o); fence_regs(p);
                    if (it == itl) warp_arrive(bar_qfree);
                } else {
                    const int zero = (uint32_t)it >> 23;
                    mbar_wait(bar_full + 8 * (it & 3), (it >> 2) & 1);
                    wg_fence();
                    issue_qk((it & 3) + zero, 25);
                    if (it == itl) {
                        wg_wait<0>();
                        if (SC_PAIR) peer_arrive(); else warp_arrive(bar_qfree);
                        if (wg) bar_sync(BAR_ST, 256);
                    }
                    wg_fence();
                    issue_pv(stp + zero, it - 1 - it0);
                    pp_arrive();
                    wg_wait<1>();
                    fence_regs(s);
                    redo = exceeds(s);
                    if (!redo) {
#pragma unroll
                        for (int i = 0; i < 20; i++) s[i] = ex2_f16(s[i]);
                        fence_regs(s);
                        cut();
                    }
                    wg_wait<0>();
                    fence_regs(o); fence_regs(p);
#pragma unroll
                    for (int i = 0; i < 20; i++) p[i] = s[i];
                }
                release(stp);
            }
            if (seg + 1 < nseg) pp_sync();
            fence_regs(o); fence_regs(p);
            wg_fence();
            issue_pv(it & 3, 1);
            asm volatile("{\n.reg .pred p;\nsetp.ne.s32 p, %0, 0;\n@p bar.arrive %1, 256;\n}\n" ::"r"((int)(seg + 1 == nseg && (wg ? SC_PAIR : !SC_TAIL))), "r"(BAR_ST + wg) : "memory");
            it++;
            if (seg + 1 == nseg) break;
            constexpr int IS = 4 + 25;
            const int ln = lane_now();
            uint32_t qa = sq + warp * 8192 + tile_off(ln & 15, ln >> 4);
            asm volatile("" : "+r"(qa));
            mbar_wait(bar_full + 8 * (IS & 3), (IS >> 2) & 1);
            mbar_wait(qbar, 0); qphase = 1;
#pragma unroll
            for (int i = 0; i < 16; i++)
                if (const int r = QREG(i); r >= 0)
                    asm volatile("ldmatrix.sync.aligned.m8n8.x4.shared.b16 {%0, %1, %2, %3}, [%4];\n" : "=r"(qr[4 * r]), "=r"(qr[4 * r + 1]), "=r"(qr[4 * r + 2]), "=r"(qr[4 * r + 3])
                                 : "r"((qa ^ (i & 3) * 32) + (i >> 2) * 1024) : "memory");
            fence_regs(qr);
            wg_fence();
            issue_qk(it & 3);
            wg_wait<1>();
            pp_arrive();
            fence_regs(o);
            float z0, z1;
            row_sums(z0, z1, ln);
            release((IS - 1) & 3);
            uint32_t u0, u1;
            asm volatile("ld.shared.u32 %0, [%2];\nld.shared.u32 %1, [%2 + 4096];\n" : "=r"(u0), "=r"(u1) : "r"(mq_addr(ln)) : "memory");
            const uint32_t slot = sb + SM_KV + ((IS - 2 + wg) & 3) * KV_BYTES;
            const uint32_t dst = slot + wg * 512 + warp * 8192 + ln * 16, dml = slot + (wg ? 0 : QB_BYTES) + warp * 128 + ln * 4;
#pragma unroll
            for (int i = 0; i < 128; i++) o[i] -= (i & 2) ? z1 : z0;
            fence_regs(o);
            mbar_wait(bar_empty + 8 * ((IS - 2 + wg) & 3), ((IS - 2 + wg) >> 2) & 1);
            asm volatile("st.shared.f32 [%0], %1;\n" ::"r"(dml), "f"(stats(ln)) : "memory");
            qs = __uint_as_float(0x3F800000u + ((u0 & 7) << 25));
            m0 = -KV_OFF * qs * f16_hi(u0); m1 = -KV_OFF * qs * f16_hi(u1);
            plim = fmaxf(fabsf(m0), fabsf(m1)) <= 3072.f && qs == 1.f ? S_LIMIT : 0u;
            uint32_t v[2][8] = {};
#pragma unroll
            for (int i = 0; i < 8; i++) {
                uint32_t *w = v[i & 1], *u = v[(i & 1) ^ 1];
#pragma unroll
                for (int j = 0; j < 8; j++) w[j] = pack_bf16(o[16 * i + 2 * j], o[16 * i + 2 * j + 1]);
                sts128(dst + i * 1024, w[0], w[1], w[2], w[3]);
                sts128(dst + i * 1024 + 512, w[4], w[5], w[6], w[7]);
                if (i) asm volatile("{\n.reg .pred p;\nsetp.lt.s32 p, %9, 0;\nL:\n@p st.shared.v4.u32 [%0], {%1, %2, %3, %4};\n@p st.shared.v4.u32 [%0 + 16], {%5, %6, %7, %8};\n@p bra L;\n}\n"
                             ::"r"(dst), "r"(u[0]), "r"(u[1]), "r"(u[2]), "r"(u[3]), "r"(u[4]), "r"(u[5]), "r"(u[6]), "r"(u[7]), "r"(it) : "memory");
            }
            fence_async_smem();
            warp_arrive(bar_pdone);
        }
        constexpr int IW = 4 + 75;
        uint32_t a[64];
        const int lane = lane_now(), t = warp * 32 + lane;
        if (wg == 0 && (SC_PAIR || SC_LAST)) {
            uint32_t rq, rml, rbar;
            asm volatile("mapa.shared::cluster.u32 %0, %3, %6;\nmapa.shared::cluster.u32 %1, %4, %6;\nmapa.shared::cluster.u32 %2, %5, %6;\n"
                         : "=r"(rq), "=r"(rml), "=r"(rbar) : "r"(sb + SM_Q + QB_BYTES + warp * 8192 + lane * 16), "r"(sb + SM_ML + 512 + t * 4),
                         "r"(bar_pin), "r"(rank ^ 1));
            auto send = [&](int i) {
                asm volatile("st.async.weak.shared::cluster.mbarrier::complete_tx::bytes.v4.b32 [%0], {%1, %2, %3, %4}, [%5];\n"
                             ::"r"(rq + i * 512), "r"(a[4 * i]), "r"(a[4 * i + 1]), "r"(a[4 * i + 2]), "r"(a[4 * i + 3]), "r"(rbar + (i & 8)) : "memory");
            };
            mbar_wait(bar_rfree, 0);
            wg_wait<0>();
            fence_regs(o);
            release((it - 1) & 3);
            float z0, z1;
            row_sums(z0, z1, lane);
            asm volatile("st.async.weak.shared::cluster.mbarrier::complete_tx::bytes.f32 [%0], %1, [%2];\n" ::"r"(rml), "f"(stats(lane)), "r"(rbar) : "memory");
#pragma unroll
            for (int i = 0; i < 16; i++) {
                a[4 * i] = pack_bf16(o[8 * i] - z0, o[8 * i + 1] - z0); a[4 * i + 1] = pack_bf16(o[8 * i + 2] - z1, o[8 * i + 3] - z1);
                a[4 * i + 2] = pack_bf16(o[8 * i + 4] - z0, o[8 * i + 5] - z0); a[4 * i + 3] = pack_bf16(o[8 * i + 6] - z1, o[8 * i + 7] - z1);
                if (i * SND0 / 16 != (i + 1) * SND0 / 16) send(i * SND0 / 16);
                if (i % CUT2 == CUT2 - 1) cut();
            }
            if (SC_PAIR) {
                float z[128];
                const uint32_t dkz = dk0 + ((uint32_t)it >> 24), dqz = dq0 + ((uint32_t)it >> 24);
                auto gemm = [&](int c) {
                    mbar_wait(bar_full + 8 * ((IW + c) & 3), ((IW + c) >> 2) & 1);
                    const uint64_t wb = mkaddr(dkz + ((IW + c) & 3) * (KV_BYTES >> 4), dhi), ab = mkaddr(dqz + c * 64, dhi);
                    wg_fence();
#pragma unroll
                    for (int kk = 0; kk < 4; kk++) {
                        if (c | kk) wgmma_ss_n256_tb(z, ab + kk * 2, wb + kk * 512);
                        else wgmma_ss_n256_tb_init(z, ab, wb);
                    }
                    wg_commit();
                };
                mbar_wait(qbar, qphase);
                bar_sync(BAR_ST + 1, 256);
                gemm(0);
#pragma unroll
                for (int i = SND0; i < 16; i++) send(i);
#pragma unroll
                for (int c = 1; c < 4; c++) { gemm(c); if (c == 3) pp_arrive(); wg_wait<1>(); release((IW + c - 1) & 3, 2); }
                wg_wait<0>();
                fence_regs(z);
                release((IW + 3) & 3, 2);
#pragma unroll
                for (int i = 0; i < 16; i++) {
                    sts128(sq + warp * 8192 + lane * 16 + i * 512, pack_bf16(z[8 * i], z[8 * i + 1]), pack_bf16(z[8 * i + 2], z[8 * i + 3]),
                           pack_bf16(z[8 * i + 4], z[8 * i + 5]), pack_bf16(z[8 * i + 6], z[8 * i + 7]));
                    if (i == 3 || i == 15) bar_arrive(i == 3 ? BAR_BF : BAR_H0, 256);
                    if (i == 3) cut();
                }
            } else {
#pragma unroll
                for (int i = SND0; i < 16; i++) send(i);
            }
        } else {
            const int pair = SC_PAIR;
            const bool glob = !(pair || SC_TAIL);
            const uint32_t ml = sb + SM_ML + (t & ~3) * 4, src = (glob ? sq : sb + SM_Q + QB_BYTES) + warp * 8192 + lane * 16;
            const uint64_t tm = lds64(s_tm);
            wg_wait<0>();
            fence_regs(o);
            release((IW - 1) & 3);
            float c0, c1;
            row_sums(c0, c1, lane);
            mbar_wait(glob ? qbar : bar_pin, glob ? qphase : 0);
            const float4 ps = lds128f(ml + (glob ? wg * 512 : 512));
            auto load = [&](int i) {
                asm volatile("ld.shared.v4.u32 {%0, %1, %2, %3}, [%4];\n" : "=r"(a[4 * i]), "=r"(a[4 * i + 1]), "=r"(a[4 * i + 2]), "=r"(a[4 * i + 3]) : "r"(src + i * 512) : "memory");
            };
#pragma unroll
            for (int i = 0; i < 8; i++) load(i);
            const float n0 = fmaxf(m0, ps.x), n1 = fmaxf(m1, ps.z);
            const float a0 = ex2(m0 - n0), a1 = ex2(m1 - n1), b0 = ex2(ps.x - n0), b1 = ex2(ps.z - n1);
            const float i0 = rcp(l0 * a0 + ps.y * b0), i1 = rcp(l1 * a1 + ps.w * b1);
            const float r0 = a0 * i0, r1 = a1 * i1;
            c0 *= -r0; c1 *= -r1;
            const uint32_t u0 = pack_bf16(b0 * i0, b0 * i0), u1 = pack_bf16(b1 * i1, b1 * i1);
            uint4 v[8];
#pragma unroll
            for (int i = 0; i <= 32; i++) {
                if (i == M2) {
#pragma unroll
                    for (int j = 0; j < 2 * M2; j++) asm volatile("" : "+r"(a[j]));
                    if (!glob) mbar_wait(bar_pin + 8, 0);
#pragma unroll
                    for (int j = 0; j < 8; j++) v[j] = lds128(src + (8 + j) * 512);
                }
                if (i == 32) break;
                const uint32_t x0 = pack_bf16(fmaf(o[4 * i], r0, c0), fmaf(o[4 * i + 1], r0, c0)), x1 = pack_bf16(fmaf(o[4 * i + 2], r1, c1), fmaf(o[4 * i + 3], r1, c1));
                a[2 * i] = i < 16 ? hfma2(a[2 * i], u0, x0) : x0;
                a[2 * i + 1] = i < 16 ? hfma2(a[2 * i + 1], u1, x1) : x1;
            }
#pragma unroll
            for (int j = 0; j < 8; j++) {
                uint32_t* x = a + 32 + 4 * j;
                x[0] = hfma2(v[j].x, u0, x[0]); x[1] = hfma2(v[j].y, u1, x[1]); x[2] = hfma2(v[j].z, u0, x[2]); x[3] = hfma2(v[j].w, u1, x[3]);
            }
            float y[2][32];
            auto gemm = [&](int c, int kh) {
                if (!kh) mbar_wait(bar_full + 8 * ((IW + c) & 3), (((IW + c) >> 2) & 1) ^ pair);
                const uint64_t wb = mkaddr(dk0 + ((IW + c) & 3) * (KV_BYTES >> 4), dhi - 192);
                wg_fence();
#pragma unroll
                for (int kk = 8 * kh; kk < 8 * kh + 8; kk++) {
                    if (kk) wgmma_rs_n64_tb(y[c & 1], a[4 * kk], a[4 * kk + 1], a[4 * kk + 2], a[4 * kk + 3], wb + kk * 128);
                    else wgmma_rs_n64_tb_init(y[c & 1], a[0], a[1], a[2], a[3], wb);
                }
                wg_commit();
            };
            const uint32_t stg = sq + warp * 8192 + (lane & 15) * 128 + (((lane >> 4) ^ lane) & 7) * 16;
            uint4 z[4] = {};
            auto load_z = [&](int cb) {
                if (cb < 2) asm volatile("{\n.reg .pred p;\nsetp.ne.s32 p, %0, 0;\n@p bar.sync %1, 256;\n}\n" ::"r"(pair), "r"(cb ? BAR_H0 : BAR_BF) : "memory");
#pragma unroll
                for (int i = 0; i < 4; i++)
                    asm volatile("{\n.reg .pred p;\nsetp.ne.u32 p, %4, 0;\n@p ld.shared.v4.u32 {%0, %1, %2, %3}, [%5];\n}\n"
                                 : "+r"(z[i].x), "+r"(z[i].y), "+r"(z[i].z), "+r"(z[i].w) : "r"(pair), "r"(src - QB_BYTES + (4 * cb + i) * 512) : "memory");
            };
            pp_sync();
            gemm(0, 0);
            gemm(0, 1);
#pragma unroll
            for (int c = 0; c < 4; c++) {
                if (c) load_z(c);
                if (c < 3) gemm(c + 1, 0);
                if (!c) load_z(0);
                if (c < 3) wg_wait<1>(); else wg_wait<0>();
                fence_regs(y[c & 1]);
                const float* x = y[c & 1];
#pragma unroll
                for (int i = 0; i < 4; i++)
                    stmatrix_x4((stg ^ (32 * i)) + c * 2048, hadd2(pack_bf16(x[8 * i], x[8 * i + 1]), z[i].x), hadd2(pack_bf16(x[8 * i + 2], x[8 * i + 3]), z[i].y),
                                hadd2(pack_bf16(x[8 * i + 4], x[8 * i + 5]), z[i].z), hadd2(pack_bf16(x[8 * i + 6], x[8 * i + 7]), z[i].w));
                if (c < 3) gemm(c + 1, 1);
                fence_async_smem();
                __syncwarp();
                asm volatile("{\n.reg .pred p;\nelect.sync _|p, -1;\n"
                             "@p cp.reduce.async.bulk.tensor.4d.global.shared::cta.add.tile.bulk_group [%0, {0, 0, %1, %2}], [%3];\n}\n"
                             ::"l"(tm), "r"(c), "r"((pair ? SC_ZB : 2 * SC_QT0 + wg) * 8 + warp * 2), "r"(sq + warp * 8192 + c * 2048) : "memory");
                if (c == 2 && glob) pp_arrive();
            }
            asm volatile("cp.async.bulk.commit_group;\ncp.async.bulk.wait_group.read 0;\n" ::: "memory");
        }
        } else {
            wg_wait<0>();
        }
        if (SC_TAIL) {
        float o[128];
        const int lane = lane_now(), t = warp * 32 + lane, q = lane & 3;
        auto emit = [&](uint32_t base, int lane, int row0, uint8_t* wdst, int turn) {
#pragma unroll
            for (int hh = 0; hh < 2; hh++) {
                if (turn > 0) mbar_wait(bar_zst + 8 * hh, (turn - 1) & 1);
#pragma unroll
                for (int i = 0; i < 8; i++)
                    stmatrix_x4(base + tile_off(8 * hh + (lane & 7), 4 * i + (lane >> 3)),
                                pack_bf16(o[16 * i + 2 * hh], o[16 * i + 2 * hh + 1]), pack_bf16(o[16 * i + 4 + 2 * hh], o[16 * i + 5 + 2 * hh]),
                                pack_bf16(o[16 * i + 8 + 2 * hh], o[16 * i + 9 + 2 * hh]), pack_bf16(o[16 * i + 12 + 2 * hh], o[16 * i + 13 + 2 * hh]));
                fence_async_smem();
                __syncwarp();
                if (wdst) {
                    if (lane < 4)
                        asm volatile("cp.async.bulk.global.shared::cta.bulk_group [%0], [%1], 1024;\n"
                                     ::"l"(wdst + ((turn & 1) ? hh * 4096 + lane * 1024 : hh * 1024 + lane * QB_BYTES)), "r"(base + hh * 4096 + lane * 1024) : "memory");
                    asm volatile("cp.async.bulk.commit_group;\n" ::: "memory");
                } else {
                    asm volatile("{\n.reg .pred p;\nsetp.eq.s32 p, %3, 0;\n"
                                 "@p cp.reduce.async.bulk.tensor.4d.global.shared::cta.add.tile.bulk_group [%0, {0, 0, 0, %1}], [%2];\n"
                                 "cp.async.bulk.commit_group;\n}\n"
                                 ::"l"(&P.tm_out), "r"((row0 >> 3) + hh), "r"(base + hh * 4096), "r"(lane) : "memory");
                }
            }
            asm volatile("cp.async.bulk.wait_group.read 1;\n" ::: "memory");
            warp_arrive(bar_zst - 8 * wg);
        };
        auto emit_done = [&](bool pending) {
            asm volatile("cp.async.bulk.wait_group.read 0;\n" ::: "memory");
            __syncwarp();
            asm volatile("{\n.reg .pred p;\nsetp.eq.s32 p, %1, 0;\n@p mbarrier.arrive.shared::cta.b64 _, [%0];\n}\n"
                         ::"r"(bar_zst + 8), "r"(pending ? lane : 1) : "memory");
        };
        if (!(rank | wg)) { release(0); release(1); release(2); release(3); }
        bar_sync(BAR_BF, 256);
        warp_arrive(bar_qfree);
        const int nf = rank ? 8 : 0;
        const int nz = nf + 26 + rank;
        const int itz = 4 + SC_NKV + SC_NW;
        bool pend = false;
#pragma unroll 1
        for (int k = wg; k < nz; k += 2) {
            const int iz = itz + (k < nf ? 0 : nf >> 1);
            mbar_wait(qbar, qphase); qphase ^= 1;
#pragma unroll 1
            for (int c = 0; c < 4; c++) {
                mbar_wait(bar_full + 8 * ((iz + c) & 3), ((iz + c) >> 2) & 1);
                const uint64_t wb = mkaddr(dk0 + ((iz + c) & 3) * (KV_BYTES >> 4), dhi), ab = mkaddr(dq0 + c * 64, dhi);
                wg_fence();
                wgmma_ss_n256_tb_pred(o, ab, wb, c);
#pragma unroll
                for (int kk = 1; kk < 4; kk++) wgmma_ss_n256_tb(o, ab + kk * 2, wb + kk * 512);
                wg_commit();
                emit_done(pend);
                pend = false;
            }
            wg_wait<0>();
            fence_regs(o);
            warp_arrive(bar_qfree);
            const int fb = ((k >> 1) + 3) & 3;
            if (k < nf) {
                float2* r255 = (float2*)H.s->r255 + wg * 128 + q;
                if (k < 2) {
                    if (t >= 124) {
#pragma unroll
                        for (int i = 0; i < 32; i++) r255[4 * i] = make_float2(o[4 * i + 2], o[4 * i + 3]);
                    }
                    bar_sync(BAR_WG0 + wg, 128);
                }
#pragma unroll
                for (int i = 0; i < 32; i++) {
                    const float2 v = __ldcg(r255 + 4 * i);
                    o[4 * i] -= v.x; o[4 * i + 1] -= v.y; o[4 * i + 2] -= v.x; o[4 * i + 3] -= v.y;
                }
            }
            int ln = lane;
            asm volatile("" : "+r"(ln));
            emit(sb + SM_KV + QB_BYTES + warp * KV_BYTES, ln, SC_TZB(k - nf) * 64 + warp * 16,
                 k >= nf ? nullptr : (k & 1) ? g_w + (4 + fb) * QB_BYTES + warp * 8192 : g_w + 8 * QB_BYTES + fb * 8192 + warp * 2048, k);
            pend = k + 2 < nz && (k | 1) != nf - 1;
            if (!pend) emit_done(true);
            if ((k | 1) == nf - 1) {
                asm volatile("cp.async.bulk.wait_group 0;\nfence.proxy.async.global;\nfence.acq_rel.gpu;\n" ::: "memory");
                bar_sync(BAR_BF, 256);
                if (tid == 0) red_release(&g_sync[SY_B * 32]);
                if (wg == 0) { release(0); release(1); release(2); release(3); }
            }
        }
        }
        if (wg == 0) pp_sync();
        warp_arrive(bar_end - 8 * wg);
        asm volatile("barrier.cluster.arrive.relaxed.aligned;\n" ::: "memory");
        if (P.E >= 0) return;
        asm volatile("setmaxnreg.dec.sync.aligned.u32 %0;\n" ::"n"(REG_P));
    }
    {
        if (warp != 0) {
            if (warp == 3 && SC_OWNER && SC_PAIR && elect()) {
                flag_wait_bounded(&g_sync[SY_H1 * 32], 79 * ep);
                mbar_wait_sleep(bar_pdone, 0);
                mbar_wait_sleep(bar_pdone + 8, 0);
#pragma unroll 1
                for (int u = 0; u < 16; u++) {
                    bulk_s2g(g_q + SC_QT0 * (2 * QB_BYTES) + u * 4096, sb + SM_Q + u * 4096, 4096);
                    asm volatile("cp.async.bulk.wait_group 0;\n" ::: "memory");
                }
                fence_async_global();
                st_release(&g_qflag[SC_QT0], ep);
            }
            __syncwarp();
            if (SC_TAIL) {
                bar_sync(BAR_AUX, 96);
                if (warp == 1 && elect()) red_release(&g_sync[SY_CSR * 32]);
                __syncwarp();
            }
            mbar_wait_bounded(bar_go, 0);
            if (SC_TAIL) {
                if (warp == 1 && elect()) red_add(&g_sync[SY_DONE * 32]);
                if (warp == 3 && elect()) {
                    int it = 4 + SC_NKV + SC_NW;
                    asm volatile("prefetch.tensormap [%0];\n" ::"l"(&P.tm_out) : "memory");
                    if (rank) {
#pragma unroll 1
                        for (int j = 0; j < 4; j++, it++) {
                            mbar_wait_sleep(bar_empty + 8 * (it & 3), ((it >> 2) & 1) ^ 1);
                            mbar_expect_tx(bar_full + 8 * (it & 3), QB_BYTES);
                            tma_g2s(sb + SM_KV + (it & 3) * KV_BYTES, &P.tm_w[2], 8 * j, bar_full + 8 * (it & 3));
                        }
#pragma unroll 1
                        for (int k = 0; k < 8; k++) {
                            mbar_wait_sleep(bar_qfree + 8 * (k & 1), ((k >> 1) ^ (k & 1) ^ 1) & 1);
                            mbar_expect_tx(bar_q + 8 * (k & 1), QB_BYTES);
#pragma unroll 1
                            for (int hf = 0; hf < 2; hf++)
                                asm volatile("cp.async.bulk.tensor.5d.shared::cluster.global.tile.mbarrier::complete_tx::bytes [%0], [%1, {0, 0, %2, 0, 0}], [%3];\n"
                                             ::"r"(sb + SM_Q + (k & 1) * QB_BYTES + hf * 16384), "l"(&P.tm_w[k & 1]),
                                             "r"(8 * (((k >> 1) + 3) & 3) + 4 * hf), "r"(bar_q + 8 * (k & 1)) : "memory");
                        }
                        flag_wait_bounded(&g_sync[SY_B * 32], ep);
                        fence_async_global();
                    }
#pragma unroll 1
                    for (int j = 0; j < 4; j++, it++) {
                        mbar_wait_sleep(bar_empty + 8 * (it & 3), ((it >> 2) & 1) ^ 1);
                        mbar_expect_tx(bar_full + 8 * (it & 3), QB_BYTES);
                        bulk_g2s(sb + SM_KV + (it & 3) * KV_BYTES, g_w + (4 + j) * QB_BYTES, QB_BYTES, bar_full + 8 * (it & 3));
                    }
#pragma unroll 1
                    for (int k = 0; k < 26 + rank; k++) {
                        if (k == 0 || k == ((GF0 + 1) * NAUX - 16) / 128) { flag_wait_bounded(&g_sync[(k ? SY_AUX1 : SY_AUX0) * 32], NAUX * ep); fence_async_global(); }
                        mbar_wait_sleep(bar_qfree + 8 * (k & 1), ((k >> 1) ^ (k & 1) ^ 1) & 1);
                        mbar_expect_tx(bar_q + 8 * (k & 1), QB_BYTES);
                        bulk_g2s(sb + SM_Q + (k & 1) * QB_BYTES, g_agg + SC_TZB(k) * QB_BYTES, QB_BYTES, bar_q + 8 * (k & 1));
                    }
                }
            } else {
            const int par = ep & 1;
            if (blockIdx.x == 0 && t == 32) g_ovf_n[par ^ 1] = 0;
            if (blockIdx.x == 0 && warp == 1) *(uint4*)(g_hz + (lane >> 3) * 1024 + (lane & 7) * 16) = make_uint4(KV_OFF2 | NEG2, KV_OFF2 | NEG2, KV_OFF2, KV_OFF2);
            const uint32_t wlo = (uint32_t)(uintptr_t)H.s, whi = (uint32_t)((uintptr_t)H.s >> 32);
            const uint32_t blo = wlo + (uint32_t)offsetof(Scratch, bucket);
            {
                const int* pd = P.dst + blockIdx.x * 96 + (t - 32);
                const int* ps = P.src + blockIdx.x * 96 + (t - 32);
#pragma unroll 1
                for (int e = P.E - (blockIdx.x * 96 + (t - 32)); e > 0; e -= CSRU * NAUX * 32, pd += CSRU * NAUX * 32, ps += CSRU * NAUX * 32) {
                    int d[CSRU], sr[CSRU], sl[CSRU];
#pragma unroll
                    for (int i = 0; i < CSRU; i++) {
                        d[i] = e > i * NAUX * 32 ? __ldg(pd + i * NAUX * 32) : NN;
                        sr[i] = e > i * NAUX * 32 ? __ldg(ps + i * NAUX * 32) : 0;
                    }
#pragma unroll
                    for (int i = 0; i < CSRU; i++) {
                        sl[i] = 0;
                        asm volatile("{\n.reg .pred p;\nsetp.lt.s32 p, %2, %3;\n@p atom.relaxed.gpu.global.add.s32 %0, [%1], 1;\n}\n"
                                     : "+r"(sl[i]) : "l"(mkaddr(wlo + (uint32_t)offsetof(Scratch, cnt) + d[i] * 4, whi)), "r"(d[i]), "n"(NN) : "memory");
                    }
                    uint32_t ov = 0;
#pragma unroll
                    for (int i = 0; i < CSRU; i++) {
                        asm volatile("{\n.reg .pred p;\nsetp.lt.s32 p, %3, %4;\n@p st.global.u16 [%1], %2;\n@!p or.b32 %0, %0, %5;\n}\n"
                                     : "+r"(ov) : "l"(mkaddr(blo + d[i] * 128 + (sl[i] & 31) * 4 + (sl[i] >> 5) * 2, whi)), "h"((unsigned short)sr[i]), "r"(sl[i]), "n"(CAP), "r"(1 << i) : "memory");
                    }
#pragma unroll 1
                    for (; ov; ov &= ov - 1) {
                        const int i = (__ffs(ov) - 1) * (NAUX * 32);
                        int at;
                        asm volatile("atom.relaxed.gpu.global.add.s32 %0, [%1], 1;\n" : "=r"(at) : "l"(&g_ovf_n[par]) : "memory");
                        g_ovf[at] = make_int2(__ldg(pd + i), __ldg(ps + i));
                    }
                }
            }
            bar_sync(BAR_AUX, 96);
            if (warp == 1 && elect()) { red_release(&g_sync[SY_CSR * 32]); }
            __syncwarp();
            {
                const int r0 = blockIdx.x * 3 + warp - 1;
                const uint4* xp = (const uint4*)(H.x + r0 * 256) + lane;
                uint4* op = (uint4*)(P.out + r0 * 256) + lane;
#pragma unroll 1
                for (int r = r0; r < NN; r += CPYU * NAUX, xp += CPYU * NAUX * 32, op += CPYU * NAUX * 32) {
                    uint4 v[CPYU];
#pragma unroll
                    for (int i = 0; i < CPYU; i++) if (r + i * NAUX < NN) v[i] = ldg_pinned(xp + i * NAUX * 32);
#pragma unroll
                    for (int i = 0; i < CPYU; i++) if (r + i * NAUX < NN) op[i * NAUX * 32] = v[i];
                }
            }
            mbar_wait_bounded(bar_go, 1);
            if (const int un = (3 - warp) * (NAUX / 3) + (NAUX / 3 - 1) - blockIdx.x; un < 208) {
                flag_wait_bounded(&g_sync[SY_PART * 32], 52 * ep);
                uint8_t* pp = g_part + (un >> 3) * (4 * PART_BYTES);
                float* ml = (float*)(pp + QB_BYTES) + (un & 7) * 32;
                const float4 sa = __ldcg((const float4*)ml + g), sc = __ldcg((const float4*)ml + g + 2 * PART_BYTES / 16);
                const float n0 = fmaxf(sa.x, sc.x), n1 = fmaxf(sa.z, sc.z);
                const uint32_t a0 = pack_bf16(ex2(sa.x - n0), ex2(sa.x - n0)), a1 = pack_bf16(ex2(sa.z - n1), ex2(sa.z - n1));
                const uint32_t b0 = pack_bf16(ex2(sc.x - n0), ex2(sc.x - n0)), b1 = pack_bf16(ex2(sc.z - n1), ex2(sc.z - n1));
                __syncwarp();
                if (q == 0) ((float4*)ml)[g] = make_float4(n0, sa.y * bf_hi(a0) + sc.y * bf_hi(b0), n1, sa.w * bf_hi(a1) + sc.w * bf_hi(b1));
                uint4* d = (uint4*)(pp + (un & 4) * 256 + (un & 7) * 8192) + lane;
#pragma unroll 1
                for (int i = 0; i < 4; i++, d += 128) {
                    uint4 u[4], v[4];
#pragma unroll
                    for (int j = 0; j < 4; j++) { u[j] = __ldcg(d + j * 32); v[j] = __ldcg(d + j * 32 + 2 * PART_BYTES / 16); }
#pragma unroll
                    for (int j = 0; j < 4; j++)
                        d[j * 32] = make_uint4(hfma2(v[j].x, b0, hmul2(u[j].x, a0)), hfma2(v[j].y, b1, hmul2(u[j].y, a1)),
                                               hfma2(v[j].z, b0, hmul2(u[j].z, a0)), hfma2(v[j].w, b1, hmul2(u[j].w, a1)));
                }
            }
            flag_wait_bounded(&g_sync[SY_CSR * 32], NCTA * ep);
            if (warp == 2 && blockIdx.x < 129) {
                uint4* z = blockIdx.x < 128 ? (uint4*)(g_w + blockIdx.x * 1024) + lane : (uint4*)&g_sync[SY_DONE * 32 + 4];
                z[0] = make_uint4(0, 0, 0, 0);
                if (blockIdx.x < 128) z[32] = make_uint4(0, 0, 0, 0);
            }
            {
                const uint32_t lc = (lane >> 3) * 1024 + (lane & 7) * 16;
                const uint32_t alo = wlo ^ lc;
                const int node0 = blockIdx.x * 3 + warp - 17;
                auto node = [&](int i) { const int nd = node0 + i * NAUX; return (int)min((unsigned)nd, (unsigned)(nd + NN)); };
                const int num = (NN - 17 - node0) / NAUX + 1;
                uint32_t mine = 0;
                if (lane < num) {
                    mine = min(__ldcg(&g_cnt[node(lane)]), CAP + 1) | (uint32_t)__ldg((const unsigned short*)P.deg_inv + node(lane)) << 16;
                    g_cnt[node(lane)] = 0;
                }
                auto row = [&](int off) {
                    uint4 v;
                    asm volatile("ld.global.v4.u32 {%0, %1, %2, %3}, [%4];\n"
                                 : "=r"(v.x), "=r"(v.y), "=r"(v.z), "=r"(v.w) : "l"(mkaddr(alo ^ off, whi)));
                    return v;
                };
                auto ents = [&](int i) {
                    uint32_t e;
                    asm volatile("ld.global.cg.u32 %0, [%1];\n" : "=r"(e) : "l"(mkaddr(blo + (min(node(i), NN - 1) * 32 + lane) * 4, whi)));
                    return e;
                };
                auto store = [&](int i, const float (&a)[8]) {
                    const float di = bf_hi(__shfl_sync(~0u, mine, i)) * (1.f / KV_SCALE);
                    const int nd = node(i);
                    *(uint4*)(g_agg + (uint32_t)(((nd >> 3) * 4096 + (nd & 7) * 144) ^ lc)) =
                        make_uint4(pack_bf16(a[0] * di, a[1] * di), pack_bf16(a[2] * di, a[3] * di), pack_bf16(a[4] * di, a[5] * di), pack_bf16(a[6] * di, a[7] * di));
                };
#pragma unroll 1
                for (uint32_t big = __ballot_sync(~0u, (mine & 0xFFFF) > CAP); big; big &= big - 1) {
                    const int i = __ffs(big) - 1, no = __ldcg(&g_ovf_n[par]);
                    float a[8] = {};
#pragma unroll 1
                    for (int k = -64; k < no; k += 32) {
                        const int2 pr = k < 0 ? make_int2(node(i), (ents(i) >> (k & 32) / 2) & 0xFFFF) : k + lane < no ? __ldcg(&g_ovf[k + lane]) : make_int2(-1, 0);
#pragma unroll 1
                        for (uint32_t mk = __ballot_sync(~0u, pr.x == node(i)); mk; mk &= mk - 1) {
                            const uint4 v = row(row_off(__shfl_sync(~0u, pr.y, __ffs(mk) - 1)));
                            a[0] += f16_lo(v.x) + KV_OFF; a[1] += f16_hi(v.x) + KV_OFF; a[2] += f16_lo(v.y) + KV_OFF; a[3] += f16_hi(v.y) + KV_OFF;
                            a[4] += f16_lo(v.z) - KV_OFF; a[5] += f16_hi(v.z) - KV_OFF; a[6] += f16_lo(v.w) - KV_OFF; a[7] += f16_hi(v.w) - KV_OFF;
                        }
                    }
                    store(i, a);
                }
                auto add4 = [&](const uint4& a, const uint4& b) { return make_uint4(hadd2_f16(a.x, b.x), hadd2_f16(a.y, b.y), hadd2_f16(a.z, b.z), hadd2_f16(a.w, b.w)); };
                int ni = -1, left = 0, pos = 0, ec = 0;
                uint32_t en = ents(0);
                uint4 acc = make_uint4(0, 0, 0, 0);
                auto step = [&](uint4 (&v)[4], int& tag) {
                    if (left <= 0 || pos == 32) {
                        if (left > 0) {
                            en = ents(ni) >> 16;
                        } else {
                            ni++;
                            left = __shfl_sync(~0u, mine, ni) & 0xFFFF;
                            if (left > CAP) left = 0;
                        }
                        ec = lane < left ? row_off(en & 0xFFFF) : 0;
                        en = ents(ni + 1);
                        pos = 0;
                    }
                    int of[4];
#pragma unroll
                    for (int j = 0; j < 4; j++) asm volatile("shfl.sync.idx.b32 %0, %1, %2, 31, -1;\n" : "=r"(of[j]) : "r"(ec), "r"(pos + j));
                    acc = add4(acc, add4(add4(add4(v[0], v[1]), make_uint4(KV_OFF8, KV_OFF8, KV_OFF8 | NEG2, KV_OFF8 | NEG2)), add4(v[2], v[3])));
                    asm volatile("" : "+r"(acc.x), "+r"(acc.y), "+r"(acc.z), "+r"(acc.w));
                    asm volatile("{\n.reg .pred p;\nsetp.lt.s32 p, %0, 0;\nL:\n@p pmevent 0;\n@p bra L;\n}\n" ::"r"(ni) : "memory");
#pragma unroll
                    for (int j = 0; j < 4; j++) v[j] = row(of[j]);
                    pos += 4; left -= 4;
                    const int i = tag;
                    tag = left <= 0 ? ni : -1;
                    if (i >= 0) {
                        const float a[8] = {f16_lo(acc.x), f16_hi(acc.x), f16_lo(acc.y), f16_hi(acc.y), f16_lo(acc.z), f16_hi(acc.z), f16_lo(acc.w), f16_hi(acc.w)};
                        if ((__shfl_sync(~0u, mine, i) & 0xFFFF) <= CAP) store(i, a);
                        acc = make_uint4(0, 0, 0, 0);
                        if (i == GF0 || i == 8) {
                            __syncwarp();
                            if (elect()) red_release(&g_sync[(i == 8 ? SY_AUX1 : SY_AUX0) * 32]);
                            __syncwarp();
                        }
                    }
                    return i == num - 1;
                };
                uint4 va[4], vb[4];
#pragma unroll
                for (int j = 0; j < 4; j++) va[j] = vb[j] = make_uint4(KV_OFF2 | NEG2, KV_OFF2 | NEG2, KV_OFF2, KV_OFF2);
                int ta = -1, tb = -1;
#pragma unroll 1
                while (!step(va, ta) && !step(vb, tb)) {}
            }
            bar_sync(BAR_AUX, 96);
            if (warp == 1 && elect()) {
                red_release(&g_sync[SY_AUX * 32]);
                red_add(&g_sync[SY_DONE * 32]);
            }
            }
        }
        __syncwarp();
        asm volatile("barrier.cluster.arrive.relaxed.aligned;\n" ::: "memory");
        if (warp == 1) mbar_wait_bounded(bar_end, 0);
        else if (elect()) mbar_arrive(bar_end);
        __syncwarp();
        asm volatile("barrier.cluster.wait.acquire.aligned;\n" ::: "memory");
    }
}

}

extern "C" void kernel_launch(void* const* d_in, const int* in_sizes, int n_in, void* d_out, int out_size) {
    Hot H;
    Params P;
    H.x = (const __nv_bfloat16*)d_in[0];
    P.src = (const int*)d_in[1];
    P.dst = (const int*)d_in[2];
    P.deg_inv = (const __nv_bfloat16*)d_in[3];
    H.wq = (const __nv_bfloat16*)d_in[5];
    H.wk = (const __nv_bfloat16*)d_in[6];
    P.out = (__nv_bfloat16*)d_out;
    typedef CUresult (*EncodeFn)(CUtensorMap*, CUtensorMapDataType, cuuint32_t, void*, const cuuint64_t*, const cuuint64_t*, const cuuint32_t*,
                                 const cuuint32_t*, CUtensorMapInterleave, CUtensorMapSwizzle, CUtensorMapL2promotion, CUtensorMapFloatOOBfill);
    void* fn = nullptr;
    cudaDriverEntryPointQueryResult qr;
    cudaGetDriverEntryPoint("cuTensorMapEncodeTiled", &fn, cudaEnableDefault, &qr);
    auto encode = [&](CUtensorMap* tm, const void* ptr, int rows, int box_rows, int box_cb = 4) {
        const cuuint64_t dims[4] = {64, 8, 4, (cuuint64_t)rows / 8};
        const cuuint64_t strides[3] = {512, 128, 4096};
        const cuuint32_t box[4] = {64, 8, (cuuint32_t)box_cb, (cuuint32_t)box_rows / 8}, es[4] = {1, 1, 1, 1};
        ((EncodeFn)fn)(tm, CU_TENSOR_MAP_DATA_TYPE_BFLOAT16, 4, (void*)ptr, dims, strides, box, es, CU_TENSOR_MAP_INTERLEAVE_NONE,
                       CU_TENSOR_MAP_SWIZZLE_128B, CU_TENSOR_MAP_L2_PROMOTION_NONE, CU_TENSOR_MAP_FLOAT_OOB_FILL_NONE);
    };
    encode(&P.tm_out, d_out, NN, 8);
    encode(&P.tm_outc, d_out, NN, 16, 1);
    for (int i = 0; i < 2; i++) {
        const cuuint64_t dims[5] = {64, 2, 32, 4, 4};
        const cuuint64_t strides[4] = {512, 4096, 128, 1024};
        const cuuint32_t box[5] = {64, 2, 4, 4, 4}, es[5] = {1, 1, 1, 1, 1};
        ((EncodeFn)fn)(&P.tm_w[i], CU_TENSOR_MAP_DATA_TYPE_BFLOAT16, 5, d_in[i ? 4 : 7], dims, strides, box, es, CU_TENSOR_MAP_INTERLEAVE_NONE,
                       CU_TENSOR_MAP_SWIZZLE_128B, CU_TENSOR_MAP_L2_PROMOTION_NONE, CU_TENSOR_MAP_FLOAT_OOB_FILL_NONE);
    }
    encode(&P.tm_w[2], d_in[8], 256, 64);
    void* raw = nullptr;
    cudaGetSymbolAddress(&raw, g_raw);
    H.s = (Scratch*)(((uintptr_t)raw + ((8 << 20) - 1)) & ~(uintptr_t)((8 << 20) - 1));
    P.dhi = 0x40000100u;
    P.E = in_sizes[1] < MAXE ? in_sizes[1] : MAXE;
    cudaFuncSetAttribute(k_main, cudaFuncAttributeMaxDynamicSharedMemorySize, SM_TOTAL);
    k_main<<<NCTA, 384, SM_TOTAL>>>(H, P);
}
```

```cpp
#include <cuda_runtime.h>
#include <cuda.h>
#include <cuda_bf16.h>
#include <stdint.h>
#include <stddef.h>

namespace {

constexpr int NN = 10000;
constexpr int BN = 80;
constexpr int NKV = NN / BN;
constexpr int NQB = 158;
constexpr int NCTA = 132;
constexpr int NAUX = 3 * (NCTA - 2);
constexpr int STAGES = 4;
constexpr int KV_BYTES = BN * 512;
constexpr int QB_BYTES = 64 * 512;
constexpr int PART_BYTES = QB_BYTES + 512;
constexpr int CAP = 64;
constexpr int MAXE = 160000;

#define QRND(v) (((v) + 0x00040004u) & 0xFFF8FFF8u)
#define GO0 5
#define GO1 41
#define GF0 2
#define CSRU 3
#define CPYU 9
#define REFUP 2.f
#define SND0 10
#define CUT2 2
#define TICK 1024
#define TSL 30
#define NQR 7
#define QSTEP 2
#define QREG(kk) ((kk) % QSTEP == 1 % QSTEP && (kk) > 0 && ((kk) - 1) / QSTEP < NQR ? ((kk) - 1) / QSTEP : -1)
#define M2 28
#define REFSUM 3.f
#define LIFT 6
#define KVM 0x1AB
#define REG_C 224
#define REG_P 56

enum { SY_PART = 4, SY_H1 = 5, SY_CSR = 6, SY_AUX = 7, SY_DONE = 8, SY_AUX0 = 9, SY_B = 10, SY_AUX1 = 11, SY_H0 = 12 };
struct Scratch {
    uint8_t hz[4096 + NN * 512];
    uint8_t w[12 * QB_BYTES];
    int sync[25 * 32];
    int qflag[96];
    int ovf_n[32];
    float r255[512];
    int cnt[NN + 16];
    int bucket[(NN + 1) * 32];
    int2 ovf[MAXE];
    uint8_t q[NQB * QB_BYTES];
    uint8_t agg[NQB * QB_BYTES];
    uint8_t part[52 * 2 * PART_BYTES];
};
static_assert(offsetof(Scratch, ovf) <= (8 << 20), "window");
static_assert(offsetof(Scratch, qflag) == offsetof(Scratch, sync) + 25 * 128, "flags");
static_assert(offsetof(Scratch, w) % 1024 == 0 && offsetof(Scratch, sync) % 128 == 0 &&
              offsetof(Scratch, bucket) % 128 == 0 && offsetof(Scratch, q) % 128 == 0, "alignment");
__device__ uint8_t g_raw[(8 << 20) + sizeof(Scratch)];
#define g_hz (H.s->hz)
#define g_w (H.s->w)
#define g_sync (H.s->sync)
#define g_qflag (H.s->qflag)
#define g_ovf_n (H.s->ovf_n)
#define g_cnt (H.s->cnt)
#define g_bucket (H.s->bucket)
#define g_ovf (H.s->ovf)
#define g_q (H.s->q)
#define g_agg (H.s->agg)
#define g_part (H.s->part)

__device__ __forceinline__ void wgmma_ss_n80(uint32_t (&d)[20], uint64_t da, uint64_t db) {
    asm volatile("wgmma.mma_async.sync.aligned.m64n80k16.f16.f16.f16 {"
        "%0, %1, %2, %3, %4, %5, %6, %7, %8, %9, %10, %11, %12, %13, %14, %15, %16, %17, %18, %19}, %20, %21, 1, 1, 1, 0, 0;\n"
        : "+r"(d[0]), "+r"(d[1]), "+r"(d[2]), "+r"(d[3]), "+r"(d[4]), "+r"(d[5]), "+r"(d[6]), "+r"(d[7]),
          "+r"(d[8]), "+r"(d[9]), "+r"(d[10]), "+r"(d[11]), "+r"(d[12]), "+r"(d[13]), "+r"(d[14]), "+r"(d[15]),
          "+r"(d[16]), "+r"(d[17]), "+r"(d[18]), "+r"(d[19])
        : "l"(da), "l"(db));
}
__device__ __forceinline__ void wgmma_ss_n80_init(uint32_t (&d)[20], uint64_t da, uint64_t db) {
    asm volatile("wgmma.mma_async.sync.aligned.m64n80k16.f16.f16.f16 {"
        "%0, %1, %2, %3, %4, %5, %6, %7, %8, %9, %10, %11, %12, %13, %14, %15, %16, %17, %18, %19}, %20, %21, 0, 1, 1, 0, 0;\n"
        : "=r"(d[0]), "=r"(d[1]), "=r"(d[2]), "=r"(d[3]), "=r"(d[4]), "=r"(d[5]), "=r"(d[6]), "=r"(d[7]),
          "=r"(d[8]), "=r"(d[9]), "=r"(d[10]), "=r"(d[11]), "=r"(d[12]), "=r"(d[13]), "=r"(d[14]), "=r"(d[15]),
          "=r"(d[16]), "=r"(d[17]), "=r"(d[18]), "=r"(d[19])
        : "l"(da), "l"(db));
}
__device__ __forceinline__ void wgmma_rs_n80(uint32_t (&d)[20], uint32_t a0, uint32_t a1, uint32_t a2, uint32_t a3, uint64_t db) {
    asm volatile("wgmma.mma_async.sync.aligned.m64n80k16.f16.f16.f16 {"
        "%0, %1, %2, %3, %4, %5, %6, %7, %8, %9, %10, %11, %12, %13, %14, %15, %16, %17, %18, %19}, {%20, %21, %22, %23}, %24, 1, 1, 1, 0;\n"
        : "+r"(d[0]), "+r"(d[1]), "+r"(d[2]), "+r"(d[3]), "+r"(d[4]), "+r"(d[5]), "+r"(d[6]), "+r"(d[7]),
          "+r"(d[8]), "+r"(d[9]), "+r"(d[10]), "+r"(d[11]), "+r"(d[12]), "+r"(d[13]), "+r"(d[14]), "+r"(d[15]),
          "+r"(d[16]), "+r"(d[17]), "+r"(d[18]), "+r"(d[19])
        : "r"(a0), "r"(a1), "r"(a2), "r"(a3), "l"(db));
}
__device__ __forceinline__ void wgmma_rs_n256_tb(float (&d)[128], uint32_t a0, uint32_t a1, uint32_t a2, uint32_t a3, uint64_t db) {
    asm volatile("wgmma.mma_async.sync.aligned.m64n256k16.f32.f16.f16 {"
        "%0, %1, %2, %3, %4, %5, %6, %7, %8, %9, %10, %11, %12, %13, %14, %15, %16, %17, %18, %19, %20, %21, %22, %23, %24, %25, %26, %27, %28, %29, %30, %31, "
        "%32, %33, %34, %35, %36, %37, %38, %39, %40, %41, %42, %43, %44, %45, %46, %47, %48, %49, %50, %51, %52, %53, %54, %55, %56, %57, %58, %59, %60, %61, %62, %63, "
        "%64, %65, %66, %67, %68, %69, %70, %71, %72, %73, %74, %75, %76, %77, %78, %79, %80, %81, %82, %83, %84, %85, %86, %87, %88, %89, %90, %91, %92, %93, %94, %95, "
        "%96, %97, %98, %99, %100, %101, %102, %103, %104, %105, %106, %107, %108, %109, %110, %111, %112, %113, %114, %115, %116, %117, %118, %119, %120, %121, %122, %123, %124, %125, %126, %127}, {%128, %129, %130, %131}, %132, 1, 1, 1, 1;\n"
        : "+f"(d[0]), "+f"(d[1]), "+f"(d[2]), "+f"(d[3]), "+f"(d[4]), "+f"(d[5]), "+f"(d[6]), "+f"(d[7]),
          "+f"(d[8]), "+f"(d[9]), "+f"(d[10]), "+f"(d[11]), "+f"(d[12]), "+f"(d[13]), "+f"(d[14]), "+f"(d[15]),
          "+f"(d[16]), "+f"(d[17]), "+f"(d[18]), "+f"(d[19]), "+f"(d[20]), "+f"(d[21]), "+f"(d[22]), "+f"(d[23]),
          "+f"(d[24]), "+f"(d[25]), "+f"(d[26]), "+f"(d[27]), "+f"(d[28]), "+f"(d[29]), "+f"(d[30]), "+f"(d[31]),
          "+f"(d[32]), "+f"(d[33]), "+f"(d[34]), "+f"(d[35]), "+f"(d[36]), "+f"(d[37]), "+f"(d[38]), "+f"(d[39]),
          "+f"(d[40]), "+f"(d[41]), "+f"(d[42]), "+f"(d[43]), "+f"(d[44]), "+f"(d[45]), "+f"(d[46]), "+f"(d[47]),
          "+f"(d[48]), "+f"(d[49]), "+f"(d[50]), "+f"(d[51]), "+f"(d[52]), "+f"(d[53]), "+f"(d[54]), "+f"(d[55]),
          "+f"(d[56]), "+f"(d[57]), "+f"(d[58]), "+f"(d[59]), "+f"(d[60]), "+f"(d[61]), "+f"(d[62]), "+f"(d[63]),
          "+f"(d[64]), "+f"(d[65]), "+f"(d[66]), "+f"(d[67]), "+f"(d[68]), "+f"(d[69]), "+f"(d[70]), "+f"(d[71]),
          "+f"(d[72]), "+f"(d[73]), "+f"(d[74]), "+f"(d[75]), "+f"(d[76]), "+f"(d[77]), "+f"(d[78]), "+f"(d[79]),
          "+f"(d[80]), "+f"(d[81]), "+f"(d[82]), "+f"(d[83]), "+f"(d[84]), "+f"(d[85]), "+f"(d[86]), "+f"(d[87]),
          "+f"(d[88]), "+f"(d[89]), "+f"(d[90]), "+f"(d[91]), "+f"(d[92]), "+f"(d[93]), "+f"(d[94]), "+f"(d[95]),
          "+f"(d[96]), "+f"(d[97]), "+f"(d[98]), "+f"(d[99]), "+f"(d[100]), "+f"(d[101]), "+f"(d[102]), "+f"(d[103]),
          "+f"(d[104]), "+f"(d[105]), "+f"(d[106]), "+f"(d[107]), "+f"(d[108]), "+f"(d[109]), "+f"(d[110]), "+f"(d[111]),
          "+f"(d[112]), "+f"(d[113]), "+f"(d[114]), "+f"(d[115]), "+f"(d[116]), "+f"(d[117]), "+f"(d[118]), "+f"(d[119]),
          "+f"(d[120]), "+f"(d[121]), "+f"(d[122]), "+f"(d[123]), "+f"(d[124]), "+f"(d[125]), "+f"(d[126]), "+f"(d[127])
        : "r"(a0), "r"(a1), "r"(a2), "r"(a3), "l"(db));
}
__device__ __forceinline__ void wgmma_rs_n256_tb_init(float (&d)[128], uint32_t a0, uint32_t a1, uint32_t a2, uint32_t a3, uint64_t db) {
    asm volatile("wgmma.mma_async.sync.aligned.m64n256k16.f32.f16.f16 {"
        "%0, %1, %2, %3, %4, %5, %6, %7, %8, %9, %10, %11, %12, %13, %14, %15, %16, %17, %18, %19, %20, %21, %22, %23, %24, %25, %26, %27, %28, %29, %30, %31, "
        "%32, %33, %34, %35, %36, %37, %38, %39, %40, %41, %42, %43, %44, %45, %46, %47, %48, %49, %50, %51, %52, %53, %54, %55, %56, %57, %58, %59, %60, %61, %62, %63, "
        "%64, %65, %66, %67, %68, %69, %70, %71, %72, %73, %74, %75, %76, %77, %78, %79, %80, %81, %82, %83, %84, %85, %86, %87, %88, %89, %90, %91, %92, %93, %94, %95, "
        "%96, %97, %98, %99, %100, %101, %102, %103, %104, %105, %106, %107, %108, %109, %110, %111, %112, %113, %114, %115, %116, %117, %118, %119, %120, %121, %122, %123, %124, %125, %126, %127}, {%128, %129, %130, %131}, %132, 0, 1, 1, 1;\n"
        : "=f"(d[0]), "=f"(d[1]), "=f"(d[2]), "=f"(d[3]), "=f"(d[4]), "=f"(d[5]), "=f"(d[6]), "=f"(d[7]),
          "=f"(d[8]), "=f"(d[9]), "=f"(d[10]), "=f"(d[11]), "=f"(d[12]), "=f"(d[13]), "=f"(d[14]), "=f"(d[15]),
          "=f"(d[16]), "=f"(d[17]), "=f"(d[18]), "=f"(d[19]), "=f"(d[20]), "=f"(d[21]), "=f"(d[22]), "=f"(d[23]),
          "=f"(d[24]), "=f"(d[25]), "=f"(d[26]), "=f"(d[27]), "=f"(d[28]), "=f"(d[29]), "=f"(d[30]), "=f"(d[31]),
          "=f"(d[32]), "=f"(d[33]), "=f"(d[34]), "=f"(d[35]), "=f"(d[36]), "=f"(d[37]), "=f"(d[38]), "=f"(d[39]),
          "=f"(d[40]), "=f"(d[41]), "=f"(d[42]), "=f"(d[43]), "=f"(d[44]), "=f"(d[45]), "=f"(d[46]), "=f"(d[47]),
          "=f"(d[48]), "=f"(d[49]), "=f"(d[50]), "=f"(d[51]), "=f"(d[52]), "=f"(d[53]), "=f"(d[54]), "=f"(d[55]),
          "=f"(d[56]), "=f"(d[57]), "=f"(d[58]), "=f"(d[59]), "=f"(d[60]), "=f"(d[61]), "=f"(d[62]), "=f"(d[63]),
          "=f"(d[64]), "=f"(d[65]), "=f"(d[66]), "=f"(d[67]), "=f"(d[68]), "=f"(d[69]), "=f"(d[70]), "=f"(d[71]),
          "=f"(d[72]), "=f"(d[73]), "=f"(d[74]), "=f"(d[75]), "=f"(d[76]), "=f"(d[77]), "=f"(d[78]), "=f"(d[79]),
          "=f"(d[80]), "=f"(d[81]), "=f"(d[82]), "=f"(d[83]), "=f"(d[84]), "=f"(d[85]), "=f"(d[86]), "=f"(d[87]),
          "=f"(d[88]), "=f"(d[89]), "=f"(d[90]), "=f"(d[91]), "=f"(d[92]), "=f"(d[93]), "=f"(d[94]), "=f"(d[95]),
          "=f"(d[96]), "=f"(d[97]), "=f"(d[98]), "=f"(d[99]), "=f"(d[100]), "=f"(d[101]), "=f"(d[102]), "=f"(d[103]),
          "=f"(d[104]), "=f"(d[105]), "=f"(d[106]), "=f"(d[107]), "=f"(d[108]), "=f"(d[109]), "=f"(d[110]), "=f"(d[111]),
          "=f"(d[112]), "=f"(d[113]), "=f"(d[114]), "=f"(d[115]), "=f"(d[116]), "=f"(d[117]), "=f"(d[118]), "=f"(d[119]),
          "=f"(d[120]), "=f"(d[121]), "=f"(d[122]), "=f"(d[123]), "=f"(d[124]), "=f"(d[125]), "=f"(d[126]), "=f"(d[127])
        : "r"(a0), "r"(a1), "r"(a2), "r"(a3), "l"(db));
}
__device__ __forceinline__ void wgmma_rs_n256_tb_pred(float (&d)[128], uint32_t a0, uint32_t a1, uint32_t a2, uint32_t a3, uint64_t db, int acc) {
    asm volatile("{\n.reg .pred p;\nsetp.ne.s32 p, %133, 0;\nwgmma.mma_async.sync.aligned.m64n256k16.f32.f16.f16 {"
        "%0, %1, %2, %3, %4, %5, %6, %7, %8, %9, %10, %11, %12, %13, %14, %15, %16, %17, %18, %19, %20, %21, %22, %23, %24, %25, %26, %27, %28, %29, %30, %31, "
        "%32, %33, %34, %35, %36, %37, %38, %39, %40, %41, %42, %43, %44, %45, %46, %47, %48, %49, %50, %51, %52, %53, %54, %55, %56, %57, %58, %59, %60, %61, %62, %63, "
        "%64, %65, %66, %67, %68, %69, %70, %71, %72, %73, %74, %75, %76, %77, %78, %79, %80, %81, %82, %83, %84, %85, %86, %87, %88, %89, %90, %91, %92, %93, %94, %95, "
        "%96, %97, %98, %99, %100, %101, %102, %103, %104, %105, %106, %107, %108, %109, %110, %111, %112, %113, %114, %115, %116, %117, %118, %119, %120, %121, %122, %123, %124, %125, %126, %127}, {%128, %129, %130, %131}, %132, p, 1, 1, 1;\n}\n"
        : "+f"(d[0]), "+f"(d[1]), "+f"(d[2]), "+f"(d[3]), "+f"(d[4]), "+f"(d[5]), "+f"(d[6]), "+f"(d[7]),
          "+f"(d[8]), "+f"(d[9]), "+f"(d[10]), "+f"(d[11]), "+f"(d[12]), "+f"(d[13]), "+f"(d[14]), "+f"(d[15]),
          "+f"(d[16]), "+f"(d[17]), "+f"(d[18]), "+f"(d[19]), "+f"(d[20]), "+f"(d[21]), "+f"(d[22]), "+f"(d[23]),
          "+f"(d[24]), "+f"(d[25]), "+f"(d[26]), "+f"(d[27]), "+f"(d[28]), "+f"(d[29]), "+f"(d[30]), "+f"(d[31]),
          "+f"(d[32]), "+f"(d[33]), "+f"(d[34]), "+f"(d[35]), "+f"(d[36]), "+f"(d[37]), "+f"(d[38]), "+f"(d[39]),
          "+f"(d[40]), "+f"(d[41]), "+f"(d[42]), "+f"(d[43]), "+f"(d[44]), "+f"(d[45]), "+f"(d[46]), "+f"(d[47]),
          "+f"(d[48]), "+f"(d[49]), "+f"(d[50]), "+f"(d[51]), "+f"(d[52]), "+f"(d[53]), "+f"(d[54]), "+f"(d[55]),
          "+f"(d[56]), "+f"(d[57]), "+f"(d[58]), "+f"(d[59]), "+f"(d[60]), "+f"(d[61]), "+f"(d[62]), "+f"(d[63]),
          "+f"(d[64]), "+f"(d[65]), "+f"(d[66]), "+f"(d[67]), "+f"(d[68]), "+f"(d[69]), "+f"(d[70]), "+f"(d[71]),
          "+f"(d[72]), "+f"(d[73]), "+f"(d[74]), "+f"(d[75]), "+f"(d[76]), "+f"(d[77]), "+f"(d[78]), "+f"(d[79]),
          "+f"(d[80]), "+f"(d[81]), "+f"(d[82]), "+f"(d[83]), "+f"(d[84]), "+f"(d[85]), "+f"(d[86]), "+f"(d[87]),
          "+f"(d[88]), "+f"(d[89]), "+f"(d[90]), "+f"(d[91]), "+f"(d[92]), "+f"(d[93]), "+f"(d[94]), "+f"(d[95]),
          "+f"(d[96]), "+f"(d[97]), "+f"(d[98]), "+f"(d[99]), "+f"(d[100]), "+f"(d[101]), "+f"(d[102]), "+f"(d[103]),
          "+f"(d[104]), "+f"(d[105]), "+f"(d[106]), "+f"(d[107]), "+f"(d[108]), "+f"(d[109]), "+f"(d[110]), "+f"(d[111]),
          "+f"(d[112]), "+f"(d[113]), "+f"(d[114]), "+f"(d[115]), "+f"(d[116]), "+f"(d[117]), "+f"(d[118]), "+f"(d[119]),
          "+f"(d[120]), "+f"(d[121]), "+f"(d[122]), "+f"(d[123]), "+f"(d[124]), "+f"(d[125]), "+f"(d[126]), "+f"(d[127])
        : "r"(a0), "r"(a1), "r"(a2), "r"(a3), "l"(db), "r"(acc));
}
__device__ __forceinline__ void wgmma_ss_n256_tb(float (&d)[128], uint64_t da, uint64_t db) {
    asm volatile("wgmma.mma_async.sync.aligned.m64n256k16.f32.bf16.bf16 {"
        "%0, %1, %2, %3, %4, %5, %6, %7, %8, %9, %10, %11, %12, %13, %14, %15, %16, %17, %18, %19, %20, %21, %22, %23, %24, %25, %26, %27, %28, %29, %30, %31, "
        "%32, %33, %34, %35, %36, %37, %38, %39, %40, %41, %42, %43, %44, %45, %46, %47, %48, %49, %50, %51, %52, %53, %54, %55, %56, %57, %58, %59, %60, %61, %62, %63, "
        "%64, %65, %66, %67, %68, %69, %70, %71, %72, %73, %74, %75, %76, %77, %78, %79, %80, %81, %82, %83, %84, %85, %86, %87, %88, %89, %90, %91, %92, %93, %94, %95, "
        "%96, %97, %98, %99, %100, %101, %102, %103, %104, %105, %106, %107, %108, %109, %110, %111, %112, %113, %114, %115, %116, %117, %118, %119, %120, %121, %122, %123, %124, %125, %126, %127}, %128, %129, 1, 1, 1, 0, 1;\n"
        : "+f"(d[0]), "+f"(d[1]), "+f"(d[2]), "+f"(d[3]), "+f"(d[4]), "+f"(d[5]), "+f"(d[6]), "+f"(d[7]),
          "+f"(d[8]), "+f"(d[9]), "+f"(d[10]), "+f"(d[11]), "+f"(d[12]), "+f"(d[13]), "+f"(d[14]), "+f"(d[15]),
          "+f"(d[16]), "+f"(d[17]), "+f"(d[18]), "+f"(d[19]), "+f"(d[20]), "+f"(d[21]), "+f"(d[22]), "+f"(d[23]),
          "+f"(d[24]), "+f"(d[25]), "+f"(d[26]), "+f"(d[27]), "+f"(d[28]), "+f"(d[29]), "+f"(d[30]), "+f"(d[31]),
          "+f"(d[32]), "+f"(d[33]), "+f"(d[34]), "+f"(d[35]), "+f"(d[36]), "+f"(d[37]), "+f"(d[38]), "+f"(d[39]),
          "+f"(d[40]), "+f"(d[41]), "+f"(d[42]), "+f"(d[43]), "+f"(d[44]), "+f"(d[45]), "+f"(d[46]), "+f"(d[47]),
          "+f"(d[48]), "+f"(d[49]), "+f"(d[50]), "+f"(d[51]), "+f"(d[52]), "+f"(d[53]), "+f"(d[54]), "+f"(d[55]),
          "+f"(d[56]), "+f"(d[57]), "+f"(d[58]), "+f"(d[59]), "+f"(d[60]), "+f"(d[61]), "+f"(d[62]), "+f"(d[63]),
          "+f"(d[64]), "+f"(d[65]), "+f"(d[66]), "+f"(d[67]), "+f"(d[68]), "+f"(d[69]), "+f"(d[70]), "+f"(d[71]),
          "+f"(d[72]), "+f"(d[73]), "+f"(d[74]), "+f"(d[75]), "+f"(d[76]), "+f"(d[77]), "+f"(d[78]), "+f"(d[79]),
          "+f"(d[80]), "+f"(d[81]), "+f"(d[82]), "+f"(d[83]), "+f"(d[84]), "+f"(d[85]), "+f"(d[86]), "+f"(d[87]),
          "+f"(d[88]), "+f"(d[89]), "+f"(d[90]), "+f"(d[91]), "+f"(d[92]), "+f"(d[93]), "+f"(d[94]), "+f"(d[95]),
          "+f"(d[96]), "+f"(d[97]), "+f"(d[98]), "+f"(d[99]), "+f"(d[100]), "+f"(d[101]), "+f"(d[102]), "+f"(d[103]),
          "+f"(d[104]), "+f"(d[105]), "+f"(d[106]), "+f"(d[107]), "+f"(d[108]), "+f"(d[109]), "+f"(d[110]), "+f"(d[111]),
          "+f"(d[112]), "+f"(d[113]), "+f"(d[114]), "+f"(d[115]), "+f"(d[116]), "+f"(d[117]), "+f"(d[118]), "+f"(d[119]),
          "+f"(d[120]), "+f"(d[121]), "+f"(d[122]), "+f"(d[123]), "+f"(d[124]), "+f"(d[125]), "+f"(d[126]), "+f"(d[127])
        : "l"(da), "l"(db));
}
__device__ __forceinline__ void wgmma_ss_n256_tb_init(float (&d)[128], uint64_t da, uint64_t db) {
    asm volatile("wgmma.mma_async.sync.aligned.m64n256k16.f32.bf16.bf16 {"
        "%0, %1, %2, %3, %4, %5, %6, %7, %8, %9, %10, %11, %12, %13, %14, %15, %16, %17, %18, %19, %20, %21, %22, %23, %24, %25, %26, %27, %28, %29, %30, %31, "
        "%32, %33, %34, %35, %36, %37, %38, %39, %40, %41, %42, %43, %44, %45, %46, %47, %48, %49, %50, %51, %52, %53, %54, %55, %56, %57, %58, %59, %60, %61, %62, %63, "
        "%64, %65, %66, %67, %68, %69, %70, %71, %72, %73, %74, %75, %76, %77, %78, %79, %80, %81, %82, %83, %84, %85, %86, %87, %88, %89, %90, %91, %92, %93, %94, %95, "
        "%96, %97, %98, %99, %100, %101, %102, %103, %104, %105, %106, %107, %108, %109, %110, %111, %112, %113, %114, %115, %116, %117, %118, %119, %120, %121, %122, %123, %124, %125, %126, %127}, %128, %129, 0, 1, 1, 0, 1;\n"
        : "=f"(d[0]), "=f"(d[1]), "=f"(d[2]), "=f"(d[3]), "=f"(d[4]), "=f"(d[5]), "=f"(d[6]), "=f"(d[7]),
          "=f"(d[8]), "=f"(d[9]), "=f"(d[10]), "=f"(d[11]), "=f"(d[12]), "=f"(d[13]), "=f"(d[14]), "=f"(d[15]),
          "=f"(d[16]), "=f"(d[17]), "=f"(d[18]), "=f"(d[19]), "=f"(d[20]), "=f"(d[21]), "=f"(d[22]), "=f"(d[23]),
          "=f"(d[24]), "=f"(d[25]), "=f"(d[26]), "=f"(d[27]), "=f"(d[28]), "=f"(d[29]), "=f"(d[30]), "=f"(d[31]),
          "=f"(d[32]), "=f"(d[33]), "=f"(d[34]), "=f"(d[35]), "=f"(d[36]), "=f"(d[37]), "=f"(d[38]), "=f"(d[39]),
          "=f"(d[40]), "=f"(d[41]), "=f"(d[42]), "=f"(d[43]), "=f"(d[44]), "=f"(d[45]), "=f"(d[46]), "=f"(d[47]),
          "=f"(d[48]), "=f"(d[49]), "=f"(d[50]), "=f"(d[51]), "=f"(d[52]), "=f"(d[53]), "=f"(d[54]), "=f"(d[55]),
          "=f"(d[56]), "=f"(d[57]), "=f"(d[58]), "=f"(d[59]), "=f"(d[60]), "=f"(d[61]), "=f"(d[62]), "=f"(d[63]),
          "=f"(d[64]), "=f"(d[65]), "=f"(d[66]), "=f"(d[67]), "=f"(d[68]), "=f"(d[69]), "=f"(d[70]), "=f"(d[71]),
          "=f"(d[72]), "=f"(d[73]), "=f"(d[74]), "=f"(d[75]), "=f"(d[76]), "=f"(d[77]), "=f"(d[78]), "=f"(d[79]),
          "=f"(d[80]), "=f"(d[81]), "=f"(d[82]), "=f"(d[83]), "=f"(d[84]), "=f"(d[85]), "=f"(d[86]), "=f"(d[87]),
          "=f"(d[88]), "=f"(d[89]), "=f"(d[90]), "=f"(d[91]), "=f"(d[92]), "=f"(d[93]), "=f"(d[94]), "=f"(d[95]),
          "=f"(d[96]), "=f"(d[97]), "=f"(d[98]), "=f"(d[99]), "=f"(d[100]), "=f"(d[101]), "=f"(d[102]), "=f"(d[103]),
          "=f"(d[104]), "=f"(d[105]), "=f"(d[106]), "=f"(d[107]), "=f"(d[108]), "=f"(d[109]), "=f"(d[110]), "=f"(d[111]),
          "=f"(d[112]), "=f"(d[113]), "=f"(d[114]), "=f"(d[115]), "=f"(d[116]), "=f"(d[117]), "=f"(d[118]), "=f"(d[119]),
          "=f"(d[120]), "=f"(d[121]), "=f"(d[122]), "=f"(d[123]), "=f"(d[124]), "=f"(d[125]), "=f"(d[126]), "=f"(d[127])
        : "l"(da), "l"(db));
}
__device__ __forceinline__ void wgmma_ss_n256_tb_pred(float (&d)[128], uint64_t da, uint64_t db, int acc) {
    asm volatile("{\n.reg .pred p;\nsetp.ne.s32 p, %130, 0;\nwgmma.mma_async.sync.aligned.m64n256k16.f32.bf16.bf16 {"
        "%0, %1, %2, %3, %4, %5, %6, %7, %8, %9, %10, %11, %12, %13, %14, %15, %16, %17, %18, %19, %20, %21, %22, %23, %24, %25, %26, %27, %28, %29, %30, %31, "
        "%32, %33, %34, %35, %36, %37, %38, %39, %40, %41, %42, %43, %44, %45, %46, %47, %48, %49, %50, %51, %52, %53, %54, %55, %56, %57, %58, %59, %60, %61, %62, %63, "
        "%64, %65, %66, %67, %68, %69, %70, %71, %72, %73, %74, %75, %76, %77, %78, %79, %80, %81, %82, %83, %84, %85, %86, %87, %88, %89, %90, %91, %92, %93, %94, %95, "
        "%96, %97, %98, %99, %100, %101, %102, %103, %104, %105, %106, %107, %108, %109, %110, %111, %112, %113, %114, %115, %116, %117, %118, %119, %120, %121, %122, %123, %124, %125, %126, %127}, %128, %129, p, 1, 1, 0, 1;\n}\n"
        : "+f"(d[0]), "+f"(d[1]), "+f"(d[2]), "+f"(d[3]), "+f"(d[4]), "+f"(d[5]), "+f"(d[6]), "+f"(d[7]),
          "+f"(d[8]), "+f"(d[9]), "+f"(d[10]), "+f"(d[11]), "+f"(d[12]), "+f"(d[13]), "+f"(d[14]), "+f"(d[15]),
          "+f"(d[16]), "+f"(d[17]), "+f"(d[18]), "+f"(d[19]), "+f"(d[20]), "+f"(d[21]), "+f"(d[22]), "+f"(d[23]),
          "+f"(d[24]), "+f"(d[25]), "+f"(d[26]), "+f"(d[27]), "+f"(d[28]), "+f"(d[29]), "+f"(d[30]), "+f"(d[31]),
          "+f"(d[32]), "+f"(d[33]), "+f"(d[34]), "+f"(d[35]), "+f"(d[36]), "+f"(d[37]), "+f"(d[38]), "+f"(d[39]),
          "+f"(d[40]), "+f"(d[41]), "+f"(d[42]), "+f"(d[43]), "+f"(d[44]), "+f"(d[45]), "+f"(d[46]), "+f"(d[47]),
          "+f"(d[48]), "+f"(d[49]), "+f"(d[50]), "+f"(d[51]), "+f"(d[52]), "+f"(d[53]), "+f"(d[54]), "+f"(d[55]),
          "+f"(d[56]), "+f"(d[57]), "+f"(d[58]), "+f"(d[59]), "+f"(d[60]), "+f"(d[61]), "+f"(d[62]), "+f"(d[63]),
          "+f"(d[64]), "+f"(d[65]), "+f"(d[66]), "+f"(d[67]), "+f"(d[68]), "+f"(d[69]), "+f"(d[70]), "+f"(d[71]),
          "+f"(d[72]), "+f"(d[73]), "+f"(d[74]), "+f"(d[75]), "+f"(d[76]), "+f"(d[77]), "+f"(d[78]), "+f"(d[79]),
          "+f"(d[80]), "+f"(d[81]), "+f"(d[82]), "+f"(d[83]), "+f"(d[84]), "+f"(d[85]), "+f"(d[86]), "+f"(d[87]),
          "+f"(d[88]), "+f"(d[89]), "+f"(d[90]), "+f"(d[91]), "+f"(d[92]), "+f"(d[93]), "+f"(d[94]), "+f"(d[95]),
          "+f"(d[96]), "+f"(d[97]), "+f"(d[98]), "+f"(d[99]), "+f"(d[100]), "+f"(d[101]), "+f"(d[102]), "+f"(d[103]),
          "+f"(d[104]), "+f"(d[105]), "+f"(d[106]), "+f"(d[107]), "+f"(d[108]), "+f"(d[109]), "+f"(d[110]), "+f"(d[111]),
          "+f"(d[112]), "+f"(d[113]), "+f"(d[114]), "+f"(d[115]), "+f"(d[116]), "+f"(d[117]), "+f"(d[118]), "+f"(d[119]),
          "+f"(d[120]), "+f"(d[121]), "+f"(d[122]), "+f"(d[123]), "+f"(d[124]), "+f"(d[125]), "+f"(d[126]), "+f"(d[127])
        : "l"(da), "l"(db), "r"(acc));
}
__device__ __forceinline__ void wgmma_rs_n64_tb(float (&d)[32], uint32_t a0, uint32_t a1, uint32_t a2, uint32_t a3, uint64_t db) {
    asm volatile("wgmma.mma_async.sync.aligned.m64n64k16.f32.bf16.bf16 {"
        "%0, %1, %2, %3, %4, %5, %6, %7, %8, %9, %10, %11, %12, %13, %14, %15, %16, %17, %18, %19, %20, %21, %22, %23, %24, %25, %26, %27, %28, %29, %30, %31}, {%32, %33, %34, %35}, %36, 1, 1, 1, 1;\n"
        : "+f"(d[0]), "+f"(d[1]), "+f"(d[2]), "+f"(d[3]), "+f"(d[4]), "+f"(d[5]), "+f"(d[6]), "+f"(d[7]),
          "+f"(d[8]), "+f"(d[9]), "+f"(d[10]), "+f"(d[11]), "+f"(d[12]), "+f"(d[13]), "+f"(d[14]), "+f"(d[15]),
          "+f"(d[16]), "+f"(d[17]), "+f"(d[18]), "+f"(d[19]), "+f"(d[20]), "+f"(d[21]), "+f"(d[22]), "+f"(d[23]),
          "+f"(d[24]), "+f"(d[25]), "+f"(d[26]), "+f"(d[27]), "+f"(d[28]), "+f"(d[29]), "+f"(d[30]), "+f"(d[31])
        : "r"(a0), "r"(a1), "r"(a2), "r"(a3), "l"(db));
}
__device__ __forceinline__ void wgmma_rs_n64_tb_init(float (&d)[32], uint32_t a0, uint32_t a1, uint32_t a2, uint32_t a3, uint64_t db) {
    asm volatile("wgmma.mma_async.sync.aligned.m64n64k16.f32.bf16.bf16 {"
        "%0, %1, %2, %3, %4, %5, %6, %7, %8, %9, %10, %11, %12, %13, %14, %15, %16, %17, %18, %19, %20, %21, %22, %23, %24, %25, %26, %27, %28, %29, %30, %31}, {%32, %33, %34, %35}, %36, 0, 1, 1, 1;\n"
        : "=f"(d[0]), "=f"(d[1]), "=f"(d[2]), "=f"(d[3]), "=f"(d[4]), "=f"(d[5]), "=f"(d[6]), "=f"(d[7]),
          "=f"(d[8]), "=f"(d[9]), "=f"(d[10]), "=f"(d[11]), "=f"(d[12]), "=f"(d[13]), "=f"(d[14]), "=f"(d[15]),
          "=f"(d[16]), "=f"(d[17]), "=f"(d[18]), "=f"(d[19]), "=f"(d[20]), "=f"(d[21]), "=f"(d[22]), "=f"(d[23]),
          "=f"(d[24]), "=f"(d[25]), "=f"(d[26]), "=f"(d[27]), "=f"(d[28]), "=f"(d[29]), "=f"(d[30]), "=f"(d[31])
        : "r"(a0), "r"(a1), "r"(a2), "r"(a3), "l"(db));
}

__device__ __forceinline__ void wg_fence() { asm volatile("wgmma.fence.sync.aligned;\n" ::: "memory"); }
__device__ __forceinline__ void wg_commit() { asm volatile("wgmma.commit_group.sync.aligned;\n" ::: "memory"); }
template <int N> __device__ __forceinline__ void wg_wait() { asm volatile("wgmma.wait_group.sync.aligned %0;\n" ::"n"(N) : "memory"); }
template <int N> __device__ __forceinline__ void fence_regs(float (&a)[N]) {
#pragma unroll
    for (int i = 0; i < N; i++) asm volatile("" : "+f"(a[i])::"memory");
}
template <int N> __device__ __forceinline__ void fence_regs(uint32_t (&a)[N]) {
#pragma unroll
    for (int i = 0; i < N; i++) asm volatile("" : "+r"(a[i])::"memory");
}
__device__ __forceinline__ void mbar_init(uint32_t bar, uint32_t cnt) {
    asm volatile("mbarrier.init.shared::cta.b64 [%0], %1;\n" ::"r"(bar), "r"(cnt) : "memory");
}
__device__ __forceinline__ void mbar_expect_tx(uint32_t bar, uint32_t bytes) {
    asm volatile("mbarrier.arrive.expect_tx.shared::cta.b64 _, [%0], %1;\n" ::"r"(bar), "r"(bytes) : "memory");
}
__device__ __forceinline__ void mbar_wait(uint32_t bar, uint32_t parity) {
    asm volatile("{\n.reg .pred p;\nLW:\nmbarrier.try_wait.parity.shared::cta.b64 p, [%0], %1;\n@!p pmevent 0;\n@!p bra LW;\n}\n" ::"r"(bar), "r"(parity) : "memory");
}
__device__ __forceinline__ void mbar_wait_sleep(uint32_t bar, uint32_t parity) {
    asm volatile("{\n.reg .pred p;\nLW:\nmbarrier.try_wait.parity.shared::cta.b64 p, [%0], %1, 20000;\n@!p pmevent 0;\n@!p bra LW;\n}\n" ::"r"(bar), "r"(parity) : "memory");
}
__device__ __forceinline__ void mbar_wait_bounded(uint32_t bar, uint32_t parity) {
    asm volatile("{\n.reg .pred p;\n.reg .u32 c, d;\nmov.u32 c, %%globaltimer_lo;\nLW:\nmbarrier.try_wait.parity.shared::cta.b64 p, [%0], %1, 20000;\n@p bra LD;\n"
                 "mov.u32 d, %%globaltimer_lo;\nsub.u32 d, d, c;\nsetp.ge.u32 p, d, 4000000000;\n@p trap;\nbra LW;\nLD:\n}\n" ::"r"(bar), "r"(parity) : "memory");
}
__device__ __forceinline__ void flag_wait(const int* p, int v) {
    asm volatile("{\n.reg .pred p;\n.reg .s32 f;\nLW:\nld.acquire.gpu.global.s32 f, [%0];\nsub.s32 f, f, %1;\nsetp.lt.s32 p, f, 0;\n@p bra LW;\n}\n" ::"l"(p), "r"(v) : "memory");
}
__device__ __forceinline__ void flag_wait_bounded(const int* p, int v) {
    asm volatile("{\n.reg .pred p;\n.reg .u32 c;\n.reg .s32 f;\nmov.u32 c, 0;\nLW:\nld.acquire.gpu.global.s32 f, [%0];\nsub.s32 f, f, %1;\nsetp.ge.s32 p, f, 0;\n@p bra LD;\n"
                 "nanosleep.u32 500;\nadd.u32 c, c, 1;\nsetp.ge.u32 p, c, 4194304;\n@p trap;\nbra LW;\nLD:\n}\n" ::"l"(p), "r"(v) : "memory");
}
__device__ __forceinline__ int lane_now() {
    int l; asm volatile("mov.u32 %0, %%laneid;\n" : "=r"(l)); return l;
}
__device__ __forceinline__ bool elect() {
    uint32_t p; asm volatile("{\n.reg .pred p;\nelect.sync _|p, -1;\nselp.u32 %0, 1, 0, p;\n}\n" : "=r"(p)); return p;
}
__device__ __forceinline__ void bulk_g2s(uint32_t dst, const void* src, uint32_t bytes, uint32_t bar) {
    asm volatile("cp.async.bulk.shared::cluster.global.mbarrier::complete_tx::bytes [%0], [%1], %2, [%3];\n"
                 ::"r"(dst), "l"(src), "r"(bytes), "r"(bar) : "memory");
}
__device__ __forceinline__ void tma_g2s(uint32_t dst, const CUtensorMap* tm, int rowgroup, uint32_t bar) {
    asm volatile("cp.async.bulk.tensor.4d.shared::cluster.global.tile.mbarrier::complete_tx::bytes [%0], [%1, {0, 0, 0, %2}], [%3];\n"
                 ::"r"(dst), "l"(tm), "r"(rowgroup), "r"(bar) : "memory");
}
__device__ __forceinline__ void bar_sync(int id, int n) { asm volatile("bar.sync %0, %1;\n" ::"r"(id), "r"(n) : "memory"); }
__device__ __forceinline__ void bar_arrive(int id, int n) { asm volatile("bar.arrive %0, %1;\n" ::"r"(id), "r"(n) : "memory"); }
__device__ __forceinline__ float quad_last(float v) {
    float r; asm volatile("shfl.sync.idx.b32 %0, %1, 3, 0x1c1f, -1;\n" : "=f"(r) : "f"(v)); return r;
}
__device__ __forceinline__ float ex2(float x) { float y; asm("ex2.approx.ftz.f32 %0, %1;\n" : "=f"(y) : "f"(x)); return y; }
__device__ __forceinline__ uint32_t ex2_f16(uint32_t x) { uint32_t y; asm("ex2.approx.f16x2 %0, %1;\n" : "=r"(y) : "r"(x)); return y; }
__device__ __forceinline__ uint32_t hmax2_f16(uint32_t a, uint32_t b) { uint32_t r; asm("max.f16x2 %0, %1, %2;\n" : "=r"(r) : "r"(a), "r"(b)); return r; }
__device__ __forceinline__ uint32_t hmin2_f16(uint32_t a, uint32_t b) { uint32_t r; asm("min.f16x2 %0, %1, %2;\n" : "=r"(r) : "r"(a), "r"(b)); return r; }
__device__ __forceinline__ float lg2(float x) { float y; asm("lg2.approx.ftz.f32 %0, %1;\n" : "=f"(y) : "f"(x)); return y; }
__device__ __forceinline__ float rcp(float x) { float y; asm("rcp.approx.ftz.f32 %0, %1;\n" : "=f"(y) : "f"(x)); return y; }
__device__ __forceinline__ uint32_t pack_bf16(float lo, float hi) {
    uint32_t r; asm("cvt.rn.bf16x2.f32 %0, %1, %2;\n" : "=r"(r) : "f"(hi), "f"(lo)); return r;
}
__device__ __forceinline__ uint32_t pack_f16(float lo, float hi) {
    uint32_t r; asm("cvt.rn.f16x2.f32 %0, %1, %2;\n" : "=r"(r) : "f"(hi), "f"(lo)); return r;
}
__device__ __forceinline__ uint32_t pack_f16_sat(float lo, float hi) {
    uint32_t r; asm("cvt.rn.satfinite.f16x2.f32 %0, %1, %2;\n" : "=r"(r) : "f"(hi), "f"(lo)); return r;
}
__device__ __forceinline__ float f16_lo(uint32_t v) { float r; asm("cvt.f32.f16 %0, %1;\n" : "=f"(r) : "h"((unsigned short)v)); return r; }
__device__ __forceinline__ float f16_hi(uint32_t v) { return f16_lo(v >> 16); }
__device__ __forceinline__ float bf_lo(uint32_t v) { return __uint_as_float(v << 16); }
__device__ __forceinline__ float bf_hi(uint32_t v) { return __uint_as_float(v & 0xFFFF0000u); }
__device__ __forceinline__ float bf_round(float x) { return __uint_as_float(pack_bf16(0.f, x)); }
__device__ __forceinline__ void st_release(int* p, int v) {
    asm volatile("st.release.gpu.global.s32 [%0], %1;\n" ::"l"(p), "r"(v) : "memory");
}
__device__ __forceinline__ uint4 ldg_pinned(const uint4* p) {
    uint4 v; asm volatile("ld.global.nc.v4.u32 {%0, %1, %2, %3}, [%4];\n" : "=r"(v.x), "=r"(v.y), "=r"(v.z), "=r"(v.w) : "l"(p) : "memory"); return v;
}
__device__ __forceinline__ void stmatrix_x4(uint32_t addr, uint32_t r0, uint32_t r1, uint32_t r2, uint32_t r3) {
    asm volatile("stmatrix.sync.aligned.m8n8.x4.shared.b16 [%0], {%1, %2, %3, %4};\n" ::"r"(addr), "r"(r0), "r"(r1), "r"(r2), "r"(r3) : "memory");
}

__device__ __forceinline__ uint32_t tile_off(int r, int ch) {
    return (uint32_t)((r >> 3) * 4096 + (ch >> 3) * 1024 + (r & 7) * 128 + (((ch ^ r) & 7) << 4));
}
__device__ __forceinline__ int h_unit(int qt, int u) { return qt < 78 ? u * 78 + qt : 624; }
__device__ __forceinline__ int row_off(int r) { return 4096 + h_unit(r >> 7, (r >> 4) & 7) * 8192 + (r & 8) * 512 + (r & 7) * 144; }

__device__ __forceinline__ float4 lds128f(uint32_t a) {
    float4 v; asm volatile("ld.shared.v4.f32 {%0, %1, %2, %3}, [%4];\n" : "=f"(v.x), "=f"(v.y), "=f"(v.z), "=f"(v.w) : "r"(a) : "memory"); return v;
}
__device__ __forceinline__ uint64_t lds64(uint32_t a) { uint64_t v; asm volatile("ld.shared.u64 %0, [%1];\n" : "=l"(v) : "r"(a) : "memory"); return v; }
__device__ __forceinline__ uint4 lds128(uint32_t a) {
    uint4 v; asm volatile("ld.shared.v4.u32 {%0, %1, %2, %3}, [%4];\n" : "=r"(v.x), "=r"(v.y), "=r"(v.z), "=r"(v.w) : "r"(a) : "memory"); return v;
}
__device__ __forceinline__ void sts128(uint32_t a, uint32_t x, uint32_t y, uint32_t z, uint32_t w) {
    asm volatile("st.shared.v4.u32 [%0], {%1, %2, %3, %4};\n" ::"r"(a), "r"(x), "r"(y), "r"(z), "r"(w) : "memory");
}
__device__ __forceinline__ void mbar_arrive(uint32_t bar) {
    asm volatile("mbarrier.arrive.shared::cta.b64 _, [%0];\n" ::"r"(bar) : "memory");
}
__device__ __forceinline__ uint64_t mkaddr(uint32_t lo, uint32_t hi) { uint64_t a; asm("mov.b64 %0, {%1, %2};\n" : "=l"(a) : "r"(lo), "r"(hi)); return a; }
__device__ __forceinline__ void red_add(int* p) { asm volatile("red.relaxed.gpu.global.add.s32 [%0], 1;\n" ::"l"(p) : "memory"); }
__device__ __forceinline__ void red_release(int* p) {
    asm volatile("fence.proxy.async.global;\nfence.acq_rel.gpu;\nred.relaxed.gpu.global.add.s32 [%0], 1;\n" ::"l"(p) : "memory");
}
__device__ __forceinline__ void fence_async_global() { asm volatile("fence.proxy.async.global;\n" ::: "memory"); }
__device__ __forceinline__ void fence_async_smem() { asm volatile("fence.proxy.async.shared::cta;\n" ::: "memory"); }
__device__ __forceinline__ void bulk_s2g(void* dst, uint32_t src, uint32_t bytes) {
    asm volatile("cp.async.bulk.global.shared::cta.bulk_group [%0], [%1], %2;\ncp.async.bulk.commit_group;\n" ::"l"(dst), "r"(src), "r"(bytes) : "memory");
}
__device__ __forceinline__ void mma16816(float (&c)[4], uint32_t a0, uint32_t a1, uint32_t a2, uint32_t a3, uint32_t b0, uint32_t b1) {
    asm("mma.sync.aligned.m16n8k16.row.col.f32.bf16.bf16.f32 {%0, %1, %2, %3}, {%4, %5, %6, %7}, {%8, %9}, {%0, %1, %2, %3};\n"
        : "+f"(c[0]), "+f"(c[1]), "+f"(c[2]), "+f"(c[3]) : "r"(a0), "r"(a1), "r"(a2), "r"(a3), "r"(b0), "r"(b1));
}
__device__ __forceinline__ void mma1688(float (&c)[4], uint32_t a0, uint32_t a1, uint32_t b0) {
    asm("mma.sync.aligned.m16n8k8.row.col.f32.bf16.bf16.f32 {%0, %1, %2, %3}, {%4, %5}, {%6}, {%0, %1, %2, %3};\n"
        : "+f"(c[0]), "+f"(c[1]), "+f"(c[2]), "+f"(c[3]) : "r"(a0), "r"(a1), "r"(b0));
}
__device__ __forceinline__ uint32_t hadd2_f16(uint32_t a, uint32_t b) { uint32_t r; asm("add.rn.f16x2 %0, %1, %2;\n" : "=r"(r) : "r"(a), "r"(b)); return r; }
__device__ __forceinline__ uint32_t hadd2(uint32_t a, uint32_t b) { uint32_t r; asm("add.rn.bf16x2 %0, %1, %2;\n" : "=r"(r) : "r"(a), "r"(b)); return r; }
__device__ __forceinline__ uint32_t hmul2(uint32_t a, uint32_t b) { uint32_t r; asm("mul.rn.bf16x2 %0, %1, %2;\n" : "=r"(r) : "r"(a), "r"(b)); return r; }
__device__ __forceinline__ uint32_t hfma2(uint32_t a, uint32_t b, uint32_t c) { uint32_t r; asm("fma.rn.bf16x2 %0, %1, %2, %3;\n" : "=r"(r) : "r"(a), "r"(b), "r"(c)); return r; }

constexpr int SM_Q = 0;
constexpr int SM_KV = 65536;
constexpr int SM_ML = SM_KV + STAGES * KV_BYTES;
constexpr int SM_BAR = SM_ML + 1024;
constexpr int SM_TOTAL = SM_BAR + 256;
constexpr float SCALE_LOG2 = 1.4426950408889634f / 16.0f;
constexpr float KV_SCALE = 6.f;
constexpr float KV_OFF = 32.f + KVM / 32.f;
constexpr uint32_t KV_OFF2 = (0x5000u + KVM) * 0x10001u;
constexpr uint32_t KV_OFF8 = (0x5800u + KVM) * 0x10001u;
constexpr uint32_t NEG2 = 0x80008000u;
constexpr uint32_t S_LIMIT = 0x4B804B80u;
constexpr float REF_UP = REFUP, REF_SUM = REFSUM;
__device__ __forceinline__ uint32_t kvf(uint32_t a, uint32_t off) {
    uint32_t r; asm("fma.rn.f16x2 %0, %1, %2, %3;\n" : "=r"(r) : "r"(a), "r"(pack_f16(KV_SCALE, KV_SCALE)), "r"(off)); return r;
}
enum { BAR_PP0 = 1, BAR_PP1 = 2, BAR_WG0 = 3, BAR_WG1 = 4, BAR_H0 = 5, BAR_H1 = 6, BAR_AUX = 7, BAR_BF = 8, BAR_H2 = 9, BAR_X = 10, BAR_GO = 11, BAR_WG2 = 12, BAR_ST = 13 };

struct Hot {
    const __nv_bfloat16 *wk, *wq, *x;
    Scratch* s;
};
struct Params {
    const __nv_bfloat16* deg_inv;
    const int *src, *dst;
    __nv_bfloat16* out;
    uint32_t dhi;
    int E;
    CUtensorMap tm_out;
    CUtensorMap tm_outc;
    CUtensorMap tm_w[3];
};
static_assert(offsetof(Params, tm_outc) == offsetof(Params, tm_out) + 128, "layout");
#define SC_PAIR (blockIdx.x < 104)
#define SC_TAIL (blockIdx.x >= NCTA - 2)
#define SC_LAST (blockIdx.x == NCTA - 1)
#define SC_HELP (SC_PAIR && rank)
#define SC_OWNER (!SC_HELP && !SC_LAST)
#define SC_QT1 (26 + (int)(blockIdx.x >> 1))
#define SC_QT0 (SC_PAIR ? (rank ? (int)(blockIdx.x >> 2) : SC_QT1) : SC_TAIL ? 78 : (int)blockIdx.x - 104)
#define SC_NKV (SC_LAST ? 50 : 75)
#define SC_CLS (SC_PAIR ? (rank ? 0x120 ^ (blockIdx.x & 2) * 0x80 : 0x430) | (blockIdx.x & 2) >> 1 : SC_LAST ? 0x10 : 0x432)
#define SC_NW (SC_PAIR ? 8 : SC_LAST ? 0 : 4)
#define SC_ZB (2 * SC_QT1 + 1 - (int)rank)
#define SC_TZB(k) (rank && !(k) ? 156 : 2 * (k) - (int)rank)

__global__ void __cluster_dims__(2, 1, 1) __launch_bounds__(384, 1) k_main(const __grid_constant__ Hot H, const __grid_constant__ Params P) {
    extern __shared__ __align__(1024) uint8_t smem[];
    const uint32_t sb = (uint32_t)__cvta_generic_to_shared(smem);
    const int tid = threadIdx.x, wg = __shfl_sync(~0u, tid >> 7, 0);
    const int lane = tid & 31, g = lane >> 2, q = lane & 3;
    const uint32_t rank = blockIdx.x & 1;
    const uint32_t bar_full = sb + SM_BAR, bar_q = bar_full + 32, bar_go = bar_full + 48;
    const uint32_t bar_pin = bar_full + 56;
    const uint32_t bar_qfree = bar_full + 72, bar_pdone = bar_full + 88, bar_zst = bar_full + 104, bar_rfree = bar_full + 120;
    const uint32_t bar_empty = bar_full + 128, bar_end = bar_full + 160, s_tm = bar_full + 184, bar_x = bar_full + 192;
    const uint32_t bar_a = sb + SM_ML;

    const int t = tid & 127, warp = __shfl_sync(~0u, t >> 5, 0);
    int ep = 0;
    if (wg & 2) {
        unsigned done;
        {
            uint4 ra[2], rb[2], rk[5][2];
            if (blockIdx.x < 128) {
                const int e = (blockIdx.x >> 4) * 32 + (g >> 1) * 8 + (blockIdx.x & 8) / 2 + (g & 1);
                const uint4* pq = (const uint4*)(H.wq + e * 256) + warp * 8 + q;
                const uint4* pk = (const uint4*)(H.wk + ((blockIdx.x & 7) * 32 + g) * 256) + warp * 8 + q;
                const uint4* pz = (const uint4*)(H.wk + 255 * 256) + warp * 8 + q;
#pragma unroll
                for (int s = 0; s < 2; s++) {
                    ra[s] = ldg_pinned(pq + 4 * s);
                    rb[s] = ldg_pinned(pq + 4 * s + 64);
#pragma unroll
                    for (int n = 0; n < 4; n++) rk[n][s] = ldg_pinned(pk + 4 * s + n * 256);
                    rk[4][s] = ldg_pinned(pz + 4 * s);
                }
            }
            asm volatile("{\n.reg .pred p;\nsetp.eq.s32 p, %2, 0;\nmov.u32 %0, 0;\n@p ld.global.cg.u32 %0, [%1];\n}\n" : "=r"(done) : "l"(&g_sync[SY_DONE * 32]), "r"(lane) : "memory");
            bar_arrive(BAR_X, 384);
            if (warp == 0 && elect()) {
#pragma unroll
                for (int i = 0; i < 21; i++) mbar_init(bar_full + 8 * i, i < 9 ? 1 : i < 16 ? 4 : i == 20 ? 11 : SC_TAIL ? 4 : 8);
#pragma unroll
                for (int i = 0; i < 4; i++) mbar_init(bar_a + 8 * i, 1);
                mbar_expect_tx(bar_pin, QB_BYTES / 2 + 512); mbar_expect_tx(bar_pin + 8, QB_BYTES / 2);
                asm volatile("fence.mbarrier_init.release.cluster;\n" ::: "memory");
            }
            __syncwarp();
            asm volatile("barrier.cluster.arrive.relaxed.aligned;\n" ::: "memory");
            if (blockIdx.x < 128) {
                float c[5][4] = {};
#pragma unroll
                for (int s = 0; s < 2; s++) {
#pragma unroll
                    for (int n = 0; n < 5; n++) mma16816(c[n], ra[s].x, rb[s].x, ra[s].y, rb[s].y, rk[n][s].x, rk[n][s].y);
#pragma unroll
                    for (int n = 0; n < 5; n++) mma16816(c[n], ra[s].z, rb[s].z, ra[s].w, rb[s].w, rk[n][s].z, rk[n][s].w);
                }
#pragma unroll
                for (int i = 0; i < 4; i++) {
                    const int r = i & 2, n = (i & 1) * 2;
                    sts128(sb + SM_KV + 3 * KV_BYTES + QB_BYTES + i * 2048 + t * 16, __float_as_uint(c[n][r] - c[4][r]), __float_as_uint(c[n][r + 1] - c[4][r]),
                           __float_as_uint(c[n + 1][r] - c[4][r]), __float_as_uint(c[n + 1][r + 1] - c[4][r]));
                }
            }
        }
        asm volatile("setmaxnreg.dec.sync.aligned.u32 %0;\n" ::"n"(REG_P));
        if (blockIdx.x < 128) {
            bar_sync(BAR_WG2, 128);
            float4 v[4];
#pragma unroll
            for (int i = 0; i < 4; i++) v[i] = lds128f(sb + SM_KV + 3 * KV_BYTES + QB_BYTES + (warp & 2) * 2048 + (lane & 1) * 2048 + i * 512 + ((warp & 1) * 16 + (lane >> 1)) * 16);
            constexpr float SC = SCALE_LOG2 / KV_SCALE;
            const int r = (warp & 1) * 4 + (lane >> 3);
            *(uint2*)(g_w + tile_off((blockIdx.x >> 3) * 16 + (warp & 2) * 4 + r, (blockIdx.x & 7) * 4 + ((lane >> 1) & 3)) + (lane & 1) * 8) =
                make_uint2(pack_f16_sat(((v[0].x + v[1].x) + (v[2].x + v[3].x)) * SC, ((v[0].y + v[1].y) + (v[2].y + v[3].y)) * SC) | 1,
                           pack_f16_sat(((v[0].z + v[1].z) + (v[2].z + v[3].z)) * SC, ((v[0].w + v[1].w) + (v[2].w + v[3].w)) * SC) | 1);
            if (warp != 1) {
                bar_arrive(BAR_AUX, 128);
            } else {
                bar_sync(BAR_AUX, 128);
                if (elect()) { red_add(&g_sync[SY_DONE * 32 + 4 + (blockIdx.x >> 5)]); }
                __syncwarp();
            }
        }
        else bar_sync(BAR_WG2, 128);
        if (warp == 1) bar_arrive(BAR_GO, 160);
        auto load_a = [&](int j) {
            if (elect()) {
                mbar_expect_tx(bar_a + 8 * j, QB_BYTES);
                bulk_g2s(sb + SM_KV + j * KV_BYTES, g_w + j * QB_BYTES, QB_BYTES, bar_a + 8 * j);
            }
            __syncwarp();
        };
        if (warp == 0) {
            auto poll = [&]() { int c; asm volatile("ld.relaxed.gpu.global.s32 %0, [%1];\n" : "=r"(c) : "l"(&g_sync[SY_DONE * 32 + 4 + (lane & 3)]) : "memory"); return c; };
#pragma unroll 1
            for (int j = 0; j < 4;) {
#pragma unroll 1
                for (const uint32_t mk = __ballot_sync(~0u, poll() >= 32) & 15; (mk >> j) & 1; j++) load_a(j);
            }
        } else if (warp & 1) {
#pragma unroll 1
            for (int j = 0, n = 0; j < 4;) {
                mbar_wait_bounded(bar_a + 8 * j, n & 1);
                uint32_t ok = 1;
#pragma unroll
                for (int i = 0; i < 16; i++) {
                    uint32_t v;
                    asm volatile("ld.shared.u32 %0, [%1];\n" : "=r"(v) : "r"(sb + SM_KV + j * KV_BYTES + (warp & 2) * 8192 + i * 1024 + lane * 32 + g * 4) : "memory");
                    ok &= v;
                }
                asm volatile("{\n.reg .pred p;\nsetp.ne.u32 p, %0, 0;\nbar.red.and.pred p, %1, 64, p;\nselp.u32 %0, 1, 0, p;\n}\n" : "+r"(ok) : "n"((int)BAR_WG2) : "memory");
                if (__any_sync(~0u, ok)) {
                    if (warp == 1 && elect()) asm volatile("mbarrier.arrive.shared::cta.b64 _, [%0];\nmbarrier.inval.shared::cta.b64 [%1];\n" ::"r"(bar_full + 8 * j), "r"(bar_a + 8 * j) : "memory");
                    __syncwarp();
                    j++; n = 0;
                } else {
                    asm volatile("{\n.reg .pred p;\nsetp.gt.s32 p, %0, 1000000;\n@p trap;\n}\n" ::"r"(++n) : "memory");
                    fence_async_smem();
                    if (warp == 1) load_a(j);
                }
            }
        }
        done = __shfl_sync(~0u, done, 0);
        ep = (int)(done / NCTA) + 1;
        asm volatile("barrier.cluster.wait.acquire.aligned;\n" ::: "memory");
        if (warp == 0) {
            asm volatile("st.shared.u64 [%0], %1;\n" ::"r"(s_tm), "l"(&P.tm_outc) : "memory");
            __syncwarp();
            if (elect()) {
                const uint8_t* base = (const uint8_t*)H.s;
                uint32_t cls = SC_CLS, bytes = KV_BYTES, step = 5 * KV_BYTES;
                const uint8_t* src = base;
                bool tick;
                int next = 0;
                const int nit = SC_NKV + SC_NW;
#pragma unroll 1
                for (int j = 0; j < nit; j++) {
                    const uint32_t slot = sb + SM_KV + (j & 3) * KV_BYTES, fb = bar_full + 8 * (j & 3);
                    if (j == next) {
                        const int k = j - SC_NKV;
                        const int sw = SC_HELP ? j - 25 : -1;
                        next = j + 1;
                        tick = j >= 3 && k < 0 && (unsigned)sw >= 4 && !SC_TAIL;
                        if (j >= 3 && (unsigned)sw >= 5) next = k >= 0 ? next : j < GO0 ? GO0 : j < 25 ? 25 : j < GO1 ? GO1 : j < 49 ? 49 : j < 50 ? 50 : 75;
                        if (j == 0 || j == 25 || j == 50) { src = base + (4096 + (cls & 15) * KV_BYTES); cls >>= 4; }
                        if (SC_TAIL ? j == nit - 1 : j == GO0 || j == GO1) mbar_arrive(bar_go);
                        int fo = -1, fv = 1;
                        if (j < 3) { fo = (SY_H0 + 5 * j + (SC_CLS & 15)) * 32; fv = 5; }
                        if (j == 3) { fo = SY_H1 * 32; fv = 79; }
                        if (sw == 1) fo = 25 * 32 + SC_QT1;
                        if (k == 0) fo = SY_B * 32;
                        if (k == 1 && !SC_PAIR) { fo = SY_AUX0 * 32; fv = NAUX; }
                        if (k == 2 && SC_PAIR) { fo = SY_AUX * 32; fv = NAUX / 3; }
                        if (fo >= 0) {
                            flag_wait(g_sync + fo, fv * ep);
                            fence_async_global();
                        }
                        if (sw == 2 || (k == 2 && !SC_TAIL)) {
                            uint32_t qs = sw == 2 ? offsetof(Scratch, q) + (2 * SC_QT1 + 1) * QB_BYTES : SC_PAIR ? offsetof(Scratch, agg) + SC_ZB * QB_BYTES : offsetof(Scratch, part) + SC_QT0 * (4 * PART_BYTES);
#pragma unroll 1
                            for (int w = 0; w < (k == 2 && SC_PAIR ? 1 : 2); w++) {
                                mbar_wait_sleep(bar_qfree + 8 * w, k == 2 && SC_HELP);
                                mbar_expect_tx(bar_q + 8 * w, SC_PAIR ? QB_BYTES : PART_BYTES);
                                if (!SC_PAIR) bulk_g2s(sb + SM_ML + w * 512, base + (qs + (w ? -512 : QB_BYTES)), 512, bar_q + 8 * w);
                                bulk_g2s(sb + SM_Q + w * QB_BYTES, base + qs, QB_BYTES, bar_q + 8 * w);
                                qs += sw == 2 ? -QB_BYTES : PART_BYTES + 512;
                            }
                        }
                        if ((sw | 1) == 3) {
                            mbar_wait_sleep(bar_pdone + 8 * (sw - 2), 0);
                            bulk_s2g(g_part + (blockIdx.x - 3 + sw) * PART_BYTES, slot, PART_BYTES);
                            asm volatile("cp.async.bulk.wait_group.read 0;\n" ::: "memory");
                        }
                        if (sw == 5) {
                            asm volatile("cp.async.bulk.wait_group 0;\n" ::: "memory");
                            red_release(&g_sync[SY_PART * 32]);
                        }
                        if (k == 0) {
                            asm volatile("prefetch.tensormap [%0];\n" ::"l"(&P.tm_outc) : "memory");
                            src = g_w + (12 - SC_NW) * QB_BYTES; bytes = step = QB_BYTES;
                        }
                        if (k == 2) next = SC_TAIL ? nit - 1 : nit;
                    }
                    mbar_wait_sleep(fb + (bar_empty - bar_full), (j >> 2) & 1);
                    mbar_expect_tx(fb, bytes);
                    if (tick)
                        asm volatile("{\n.reg .pred p;\n.reg .u32 a, b, c;\nmov.u32 c, 1;\nmov.u32 a, %%globaltimer_lo;\nnot.b32 b, a;\nand.b32 b, b, %0;\nshr.u32 b, b, 1;\nnanosleep.u32 b;\n"
                                     "L:\nmov.u32 b, %%globaltimer_lo;\nlop3.b32 b, b, a, c, 0xBE;\nadd.u32 c, c, %2;\nsetp.le.u32 p, b, %0;\n@p nanosleep.u32 %1;\n@p bra L;\n}\n" ::"n"(TICK - 1), "n"(TSL), "n"(TICK / 32) : "memory");
                    bulk_g2s(slot, src, bytes, fb);
                    src += step;
                }
            }
        } else {
            if (warp == 2 && SC_OWNER) {
                uint8_t* dst = g_hz + 4096 + h_unit(SC_QT0, 0) * 8192;
                auto send = [&](int u0, int u1) {
#pragma unroll
                    for (int u = u0; u < u1; u++) {
                        bulk_s2g(dst + u * (78 * 8192), sb + SM_Q + u * 8192, 8192);
                        asm volatile("cp.async.bulk.wait_group 0;\n" ::: "memory");
                    }
                };
                int* f0 = &g_sync[(SY_H0 + SC_QT0 / 5) * 32];
                bar_sync(BAR_H0, 64);
                if (elect()) {
                    send(0, 1);
                    if (SC_QT0 < 65) red_release(f0);
                }
                bar_sync(BAR_H1, 160);
                if (elect()) {
                    if (!SC_TAIL) send(1, 4);
                    mbar_arrive(bar_q);
                }
                bar_sync(BAR_H2, 160);
                if (elect()) {
                    if (!SC_TAIL) { send(4, 8); mbar_arrive(bar_q + 8); }
                    red_release(&g_sync[SY_H1 * 32]);
                }
                __syncwarp();
            }
        }
    } else {
        const uint32_t sq = sb + SM_Q + wg * QB_BYTES;
        const uint32_t qbar = bar_q + 8 * wg;
        const uint32_t dq0 = __shfl_sync(~0u, ((sq & 0x3FFFF) >> 4) | (64u << 16), 0);
        const uint32_t dk0 = __shfl_sync(~0u, (((sb + SM_KV) & 0x3FFFF) >> 4) | (64u << 16), 0);
        float o[128];
        int it = 4;
        const uint32_t dhi = P.dhi;
        auto release = [&](int st, int n = 1) {
            if (n == 1) asm volatile("{\n.reg .pred p;\nelect.sync _|p, -1;\n@p mbarrier.arrive.shared::cta.b64 _, [%0];\n}\n" ::"r"(bar_empty + 8 * st) : "memory");
            else asm volatile("{\n.reg .pred p;\nelect.sync _|p, -1;\n@p mbarrier.arrive.shared::cta.b64 _, [%0], 2;\n}\n" ::"r"(bar_empty + 8 * st) : "memory");
        };
        const bool active = !(SC_TAIL && wg == 1);
        auto pp_sync = [&]() { if (!SC_TAIL) bar_sync(BAR_PP0 + wg, 256); };
        auto pp_arrive = [&]() { if (!SC_TAIL) bar_arrive(BAR_PP1 - wg, 256); };
        auto warp_arrive = [&](uint32_t bar) {
            __syncwarp();
            asm volatile("{\n.reg .pred p;\nelect.sync _|p, -1;\n@p mbarrier.arrive.shared::cta.b64 _, [%0];\n}\n" ::"r"(bar + 8 * wg) : "memory");
        };
        auto peer_arrive = [&]() {
            asm volatile("{\n.reg .pred p;\n.reg .b32 a;\nelect.sync _|p, -1;\nmapa.shared::cluster.u32 a, %0, %1;\n"
                         "@p mbarrier.arrive.shared::cluster.b64 _, [a];\n}\n" ::"r"(bar_rfree), "r"(rank ^ 1) : "memory");
        };
        auto cut = [&]() { asm volatile("{\n.reg .pred p;\nsetp.lt.s32 p, %0, 0;\nL:\n@p pmevent 0;\n@p bra L;\n}\n" ::"r"(dhi) : "memory"); };
        float qs = 1.f;
        uint32_t qr[4 * NQR];
        auto stage_q = [&]() {
            int k = dhi & 1;
            uint32_t big;
#pragma unroll 1
            do {
                if (k) {
                    qs *= 16.f;
#pragma unroll
                    for (int i = 0; i < 128; i++) o[i] *= 0.0625f;
                }
                big = 0;
                auto pk = [&](int i) { return QRND(pack_f16_sat(o[i], o[i + 1])); };
#pragma unroll
                for (int i = 0; i < 16; i++) {
                    if (QREG(i) >= 0) continue;
                    const uint32_t v0 = pk(8 * i), v1 = pk(8 * i + 2), v2 = pk(8 * i + 4) | (i == 15 ? k : 0), v3 = pk(8 * i + 6);
                    stmatrix_x4(sq + warp * 8192 + tile_off(lane & 15, 2 * i + (lane >> 4)), v0, v1, v2, v3);
                    big |= v0 | v1; big |= v2 | v3;
                    if (i == 15) cut();
                }
#pragma unroll
                for (int i = 0; i < 64; i++)
                    if (const int r = QREG(i / 4); r >= 0) big |= qr[4 * r + (i & 3)] = pk(2 * i);
                k++;
            } while (__any_sync(~0u, (big & 0x40004000u) && k < 8));
        };
        uint32_t s[20];
        auto issue_qk = [&](int st, int sh = 24) {
            const uint64_t kb = mkaddr(dk0 + st * (KV_BYTES >> 4), dhi);
            const uint64_t qd = mkaddr(dq0 + ((uint32_t)it >> sh), dhi);
            wgmma_ss_n80_init(s, qd, kb);
#pragma unroll
            for (int j = 1; j < 16; j++) {
                const int kk = j == 8 ? 15 : j < 8 ? j : j - 1;
                const int r = QREG(kk);
                if (r >= 0) wgmma_rs_n80(s, qr[4 * r], qr[4 * r + 1], qr[4 * r + 2], qr[4 * r + 3], kb + ((kk >> 2) * 64 + (kk & 3) * 2));
                else wgmma_ss_n80(s, qd + ((kk >> 2) * 64 + (kk & 3) * 2), kb + ((kk >> 2) * 64 + (kk & 3) * 2));
            }
            wg_commit();
        };

        {
            const int rb = (2 * SC_QT0 + wg) * 64 + warp * 16;
            const uint32_t xbar = bar_x + 32 * wg + 8 * warp;
            if (elect()) {
                mbar_init(xbar, 1);
                asm volatile("fence.mbarrier_init.release.cluster;\nfence.proxy.async.shared::cta;\n" ::: "memory");
                mbar_expect_tx(xbar, rb < NN ? 8192 : 0);
            }
            asm volatile("barrier.cluster.arrive.relaxed.aligned;\n" ::: "memory");
            if (wg == 1) pp_arrive();
            bar_sync(BAR_X, 384);
            if (wg == 1) bar_sync(BAR_GO, 160);
            if (rb < NN && elect()) bulk_g2s(sq + warp * 8192, H.x + (size_t)rb * 256, 8192, xbar);
            if (rb >= NN) {
#pragma unroll 1
                for (int i = 0; i < 16; i++) sts128(sq + warp * 8192 + i * 512 + lane * 16, 0, 0, 0, 0);
            }
            __syncwarp();
            mbar_wait(xbar, 0);
            uint4 xa[8], xb[8];
#pragma unroll
            for (int s = 0; s < 8; s++) {
                xa[s] = lds128(sq + (warp * 16 + g) * 512 + (4 * s + q) * 16);
                xb[s] = lds128(sq + (warp * 16 + g + 8) * 512 + (4 * s + q) * 16);
            }
            float sm[2][4], sq2[2][4][4];
#pragma unroll
            for (int i = 0; i < 4; i++) {
                sm[0][i] = sm[1][i] = 0.f;
#pragma unroll
                for (int k = 0; k < 4; k++) sq2[0][k][i] = sq2[1][k][i] = 0.f;
            }
#pragma unroll
            for (int s = 0; s < 8; s++) {
#pragma unroll
                for (int hh = 0; hh < 2; hh++) {
                    const uint4 v = hh ? xb[s] : xa[s];
                    mma16816(sm[hh], v.x, v.y, v.z, v.w, 0x3F803F80u, 0x3F803F80u);
                    mma1688(sq2[hh][0], v.x, v.y, v.x); mma1688(sq2[hh][1], v.x, v.y, v.y);
                    mma1688(sq2[hh][2], v.z, v.w, v.z); mma1688(sq2[hh][3], v.z, v.w, v.w);
                }
            }
            float inv[2], off[2];
#pragma unroll
            for (int hh = 0; hh < 2; hh++) {
                const float mean = (sm[hh][0] + sm[hh][2]) * (1.f / 256.f);
                const float d0 = (sq2[hh][0][0] + sq2[hh][2][0]) + (sq2[hh][1][2] + sq2[hh][3][2]);
                const float d1 = (sq2[hh][0][1] + sq2[hh][2][1]) + (sq2[hh][1][3] + sq2[hh][3][3]);
                const float ss = __shfl_sync(~0u, (g & 1) ? d1 : d0, g * 4 + (g >> 1));
                const float var = fmaxf(ss * (1.f / 256.f) - mean * mean, 0.f);
                float sd;
                asm("sqrt.approx.ftz.f32 %0, %1;\n" : "=f"(sd) : "f"(bf_round(bf_round(var) + 1e-5f)));
                asm("rcp.approx.ftz.f32 %0, %1;\n" : "=f"(inv[hh]) : "f"(bf_round(sd)));
                off[hh] = -mean * inv[hh];
            }
            uint32_t a[64];
#pragma unroll
            for (int s = 0; s < 8; s++) {
                a[8 * s] = xa[s].x; a[8 * s + 1] = xb[s].x; a[8 * s + 2] = xa[s].y; a[8 * s + 3] = xb[s].y;
                a[8 * s + 4] = xa[s].z; a[8 * s + 5] = xb[s].z; a[8 * s + 6] = xa[s].w; a[8 * s + 7] = xb[s].w;
            }
            fence_regs(a);
            if (wg == 1 && __any_sync(~0u, inv[0] + inv[1] != -1.f)) bar_arrive(BAR_ST, 256);
            asm volatile("setmaxnreg.inc.sync.aligned.u32 %0;\n" ::"n"(REG_C));
            fence_regs(a);
#pragma unroll
            for (int i = 0; i < 64; i++)
                a[i] = pack_f16(fmaf(bf_lo(a[i]), inv[i & 1], off[i & 1]), fmaf(bf_hi(a[i]), inv[i & 1], off[i & 1]));
            if (SC_OWNER) {
                const uint32_t ko = (q & 2) ? KV_OFF2 : KV_OFF2 | NEG2;
#pragma unroll
                for (int i = 0; i < 16; i++) {
                    const uint32_t mk = (i == 15 && q == 3) ? 0xFFFFu : ~0u;
                    stmatrix_x4(sq + warp * 8192 + tile_off(lane & 15, 2 * i + (lane >> 4)), kvf(a[4 * i], ko), kvf(a[4 * i + 1], ko),
                                kvf(a[4 * i + 2] & mk, ko), kvf(a[4 * i + 3] & mk, ko));
                }
                fence_async_smem();
                if (tid < 32) bar_arrive(BAR_H0, 64);
                bar_arrive(wg ? BAR_H2 : BAR_H1, 160);
            }
            asm volatile("barrier.cluster.wait.acquire.aligned;\n" ::: "memory");
            if (wg == 0) bar_sync(BAR_ST, 256);
            if (active) {
                fence_regs(a);
#pragma unroll
                for (int c = 0; c < 4; c++) {
                    if (c == 1) {
                        if (wg == 1) {
                            wg_wait<0>();
                            release(0);
                        }
                        pp_sync();
                    }
                    mbar_wait(bar_full + 8 * c, 0);
                    const uint64_t wb = mkaddr(dk0 + c * (KV_BYTES >> 4), dhi);
                    wg_fence();
#pragma unroll
                    for (int kk = 0; kk < 4; kk++) {
                        if (c | kk) wgmma_rs_n256_tb(o, a[16 * c + 4 * kk], a[16 * c + 4 * kk + 1], a[16 * c + 4 * kk + 2], a[16 * c + 4 * kk + 3], wb + kk * 512);
                        else wgmma_rs_n256_tb_init(o, a[0], a[1], a[2], a[3], wb);
                    }
                    wg_commit();
                    if (c > 0) { wg_wait<1>(); if (c > 1 || wg == 0) release(c - 1); }
                }
                if (wg == 0) pp_arrive();
                wg_wait<0>();
                fence_regs(o);
                release(3);
                if (SC_OWNER) mbar_wait(qbar, 0);
                stage_q();
                fence_async_smem();
                bar_sync(BAR_WG0 + wg, 128);
                mbar_wait(bar_full, 1);
                wg_fence();
                issue_qk(0);
                if (wg == 1) pp_arrive();
                if (SC_PAIR && !rank) {
#pragma unroll
                    for (int i = 0; i < 16; i++)
                        if (const int r = QREG(i); r >= 0)
                            stmatrix_x4(sq + warp * 8192 + tile_off(lane & 15, 2 * i + (lane >> 4)), qr[4 * r], qr[4 * r + 1], qr[4 * r + 2], qr[4 * r + 3]);
                }
            } else {
                peer_arrive();
            }
        }

        uint32_t p[20];
        float m0 = 0.f, m1 = 0.f, e0, e1, l0 = 0.f, l1 = 0.f;
        uint32_t plim;
        uint32_t qphase = (SC_OWNER && active) ? 1 : 0;
        auto issue_pv = [&](int st, int acc) {
            const uint64_t vb = mkaddr(dk0 + st * (KV_BYTES >> 4), dhi);
            wgmma_rs_n256_tb_pred(o, p[0], p[1], p[2], p[3], vb, acc);
#pragma unroll
            for (int kk = 1; kk < 5; kk++)
                wgmma_rs_n256_tb(o, p[4 * kk], p[4 * kk + 1], p[4 * kk + 2], p[4 * kk + 3], vb + kk * 512);
            wg_commit();
        };
        auto mq_addr = [&](int ln) { return sq + warp * 8192 + tile_off(ln >> 2, 31) + 12; };
        auto exceeds = [&](const uint32_t (&p)[20]) {
            uint32_t a = __vimax3_s16x2(S_LIMIT, p[0], p[1]), b = __vimax3_s16x2(p[2], p[3], p[4]);
#pragma unroll
            for (int i = 5; i < 17; i += 4) { a = __vimax3_s16x2(a, p[i], p[i + 1]); b = __vimax3_s16x2(b, p[i + 2], p[i + 3]); }
            a = __vimax3_s16x2(a, p[17], p[18]);
            return __any_sync(~0u, __vimax3_s16x2(a, b, p[19]) != plim);
        };
        auto store_ref = [&](int ln, uint32_t u, bool on) {
            asm volatile("{\n.reg .pred p;\nsetp.ne.s32 p, %3, 0;\n@p st.shared.u16 [%0], %1;\n@p st.shared.u16 [%0 + 4096], %2;\n}\n"
                         ::"r"(mq_addr(ln) + 2), "h"((unsigned short)u), "h"((unsigned short)(u >> 16)), "r"((int)(on && (ln & 3) == 0)) : "memory");
        };
        auto remax = [&](float& a, float& b, bool store) {
            const int ln = lane_now();
            asm volatile("" : "+f"(qs));
            uint32_t ha = s[0], hb = s[1];
#pragma unroll
            for (int i = 1; i < 10; i++) { ha = hmax2_f16(ha, s[2 * i]); hb = hmax2_f16(hb, s[2 * i + 1]); }
            ha = hmax2_f16(__byte_perm(ha, hb, 0x5410), __byte_perm(ha, hb, 0x7632));
            ha = hmax2_f16(ha, __shfl_xor_sync(~0u, ha, 1));
            ha = hmax2_f16(ha, __shfl_xor_sync(~0u, ha, 2));
            a = fmaxf(a, f16_lo(ha) * qs - e0 + REF_UP); b = fmaxf(b, f16_hi(ha) * qs - e1 + REF_UP);
            const float qi = __uint_as_float(0x7F000000u - __float_as_uint(qs)) * (-1.f / KV_OFF);
            const uint32_t u = pack_f16((m0 + a) * qi, (m1 + b) * qi);
            const float g0 = (m0 + a) + KV_OFF * qs * f16_lo(u), g1 = (m1 + b) + KV_OFF * qs * f16_hi(u);
            const bool x0 = fabsf(g0) <= 1.f, x1 = fabsf(g1) <= 1.f;
            if (x0) a -= g0;
            if (x1) b -= g1;
            const float da = a + e0, db = b + e1;
            m0 += a; m1 += b;
            e0 = x0 ? 0.f : g0; e1 = x1 ? 0.f : g1;
            plim = (x0 && x1 && qs == 1.f) ? S_LIMIT : 0u;
            store_ref(ln, u, store);
#pragma unroll
            for (int i = 0; i < 10; i++) {
                p[2 * i] = pack_f16(ex2(fmaf(f16_lo(s[2 * i]), qs, -da)), ex2(fmaf(f16_hi(s[2 * i]), qs, -da)));
                p[2 * i + 1] = pack_f16(ex2(fmaf(f16_lo(s[2 * i + 1]), qs, -db)), ex2(fmaf(f16_hi(s[2 * i + 1]), qs, -db)));
            }
            fence_regs(p);
            fence_async_smem();
            __syncwarp();
        };

        auto row_sums = [&](float& z0, float& z1, int q) {
            z0 = quad_last(o[125]); z1 = quad_last(o[127]);
            l0 = z0 * (KV_SCALE / KV_OFF); l1 = z1 * (KV_SCALE / KV_OFF);
            if (!(q & 2)) { z0 = -z0; z1 = -z1; }
        };
        auto stats = [&](int q) { return (q & 2) ? ((q & 1) ? l1 : m1) : ((q & 1) ? l0 : m0); };
        constexpr int IL = 4 + LIFT;
        const int nseg = SC_HELP ? 2 : 1;
        if (active) {
#pragma unroll 1
        for (int seg = 0;; seg++) {
            wg_wait<0>();
            fence_regs(s);
            e0 = e1 = 0.f;
            const int it0 = it, itl = __shfl_sync(~0u, seg + 1 < nseg ? 3 + 25 : 3 + SC_NKV, 0);
            const int itx = (wg == 1 && seg + 1 == nseg) ? itl : -1;
            bool redo = true, have = !seg;
#pragma unroll 1
            for (;;) {
                if (!have) {
#pragma unroll
                    for (int i = 0; i < 20; i++) p[i] = ex2_f16(s[i]);
                    redo = exceeds(s);
                }
                if (redo || (it | 1) == IL + 1) {
                static_assert(IL % 2 == 0, "");
                if (redo || it == IL + 1) {
                    float d0 = it != it0 ? 0.f : -INFINITY, d1 = d0;
                    if (redo) remax(d0, d1, it != itl);
                    if (it != it0) {
                        const float a0 = ex2(-d0 - (it == IL + 1 ? l0 : 0.f)), a1 = ex2(-d1 - (it == IL + 1 ? l1 : 0.f));
#pragma unroll
                        for (int i = 0; i < 32; i++) { o[4 * i] *= a0; o[4 * i + 1] *= a0; o[4 * i + 2] *= a1; o[4 * i + 3] *= a1; }
                    }
                }
                if (it == IL) {
                    const int ln = lane_now();
                    uint32_t ha = s[0], hb = s[1], la = ha, lb = hb;
#pragma unroll
                    for (int i = 1; i < 10; i++) {
                        ha = hmax2_f16(ha, s[2 * i]); hb = hmax2_f16(hb, s[2 * i + 1]); la = hmin2_f16(la, s[2 * i]); lb = hmin2_f16(lb, s[2 * i + 1]);
                    }
                    const float w0 = fmaxf(f16_lo(ha), f16_hi(ha)) - fminf(f16_lo(la), f16_hi(la)), w1 = fmaxf(f16_lo(hb), f16_hi(hb)) - fminf(f16_lo(lb), f16_hi(lb));
                    const float t0 = m0 + quad_last(fmaxf(fminf(lg2(o[125] * (1.f / KV_OFF)) + REF_SUM, w0 * 0.5f), 0.f));
                    const float t1 = m1 + quad_last(fmaxf(fminf(lg2(o[127] * (1.f / KV_OFF)) + REF_SUM, w1 * 0.5f), 0.f));
                    const uint32_t u = pack_f16(t0 * (-1.f / KV_OFF), t1 * (-1.f / KV_OFF));
                    const bool on = plim && !SC_TAIL && fmaxf(fabsf(t0), fabsf(t1)) < 64.f * KV_OFF;
                    l0 = on ? -KV_OFF * f16_lo(u) - m0 : 0.f; l1 = on ? -KV_OFF * f16_hi(u) - m1 : 0.f;
                    m0 += l0; m1 += l1;
                    store_ref(ln, u, on);
                    fence_async_smem();
                    if (SC_OWNER) warp_arrive(bar_pdone);
                    __syncwarp();
                }
                }
                if (it == itl) break;
                const int stp = it & 3;
                it++;
                pp_sync();
                fence_regs(o); fence_regs(p);
                have = SC_TAIL || it == itx;
                if (!have) {
                    wg_fence();
                    issue_pv(stp, it - 1 - it0);
                    mbar_wait(bar_full + 8 * (it & 3), (it >> 2) & 1);
                    wg_fence();
                    issue_qk(it & 3);
                    pp_arrive();
                    wg_wait<0>();
                    fence_regs(s); fence_regs(o); fence_regs(p);
                    if (it == itl) warp_arrive(bar_qfree);
                } else {
                    const int zero = (uint32_t)it >> 23;
                    mbar_wait(bar_full + 8 * (it & 3), (it >> 2) & 1);
                    wg_fence();
                    issue_qk((it & 3) + zero, 25);
                    if (it == itl) {
                        wg_wait<0>();
                        if (SC_PAIR) peer_arrive(); else warp_arrive(bar_qfree);
                        if (wg) bar_sync(BAR_ST, 256);
                    }
                    wg_fence();
                    issue_pv(stp + zero, it - 1 - it0);
                    pp_arrive();
                    wg_wait<1>();
                    fence_regs(s);
                    redo = exceeds(s);
                    if (!redo) {
#pragma unroll
                        for (int i = 0; i < 20; i++) s[i] = ex2_f16(s[i]);
                        fence_regs(s);
                        cut();
                    }
                    wg_wait<0>();
                    fence_regs(o); fence_regs(p);
#pragma unroll
                    for (int i = 0; i < 20; i++) p[i] = s[i];
                }
                release(stp);
            }
            if (seg + 1 < nseg) pp_sync();
            fence_regs(o); fence_regs(p);
            wg_fence();
            issue_pv(it & 3, 1);
            asm volatile("{\n.reg .pred p;\nsetp.ne.s32 p, %0, 0;\n@p bar.arrive %1, 256;\n}\n" ::"r"((int)(seg + 1 == nseg && (wg ? SC_PAIR : !SC_TAIL))), "r"(BAR_ST + wg) : "memory");
            it++;
            if (seg + 1 == nseg) break;
            constexpr int IS = 4 + 25;
            const int ln = lane_now();
            uint32_t qa = sq + warp * 8192 + tile_off(ln & 15, ln >> 4);
            asm volatile("" : "+r"(qa));
            mbar_wait(bar_full + 8 * (IS & 3), (IS >> 2) & 1);
            mbar_wait(qbar, 0); qphase = 1;
#pragma unroll
            for (int i = 0; i < 16; i++)
                if (const int r = QREG(i); r >= 0)
                    asm volatile("ldmatrix.sync.aligned.m8n8.x4.shared.b16 {%0, %1, %2, %3}, [%4];\n" : "=r"(qr[4 * r]), "=r"(qr[4 * r + 1]), "=r"(qr[4 * r + 2]), "=r"(qr[4 * r + 3])
                                 : "r"((qa ^ (i & 3) * 32) + (i >> 2) * 1024) : "memory");
            fence_regs(qr);
            wg_fence();
            issue_qk(it & 3);
            wg_wait<1>();
            pp_arrive();
            fence_regs(o);
            float z0, z1;
            row_sums(z0, z1, ln);
            release((IS - 1) & 3);
            uint32_t u0, u1;
            asm volatile("ld.shared.u32 %0, [%2];\nld.shared.u32 %1, [%2 + 4096];\n" : "=r"(u0), "=r"(u1) : "r"(mq_addr(ln)) : "memory");
            const uint32_t slot = sb + SM_KV + ((IS - 2 + wg) & 3) * KV_BYTES;
            const uint32_t dst = slot + wg * 512 + warp * 8192 + ln * 16, dml = slot + (wg ? 0 : QB_BYTES) + warp * 128 + ln * 4;
#pragma unroll
            for (int i = 0; i < 128; i++) o[i] -= (i & 2) ? z1 : z0;
            fence_regs(o);
            mbar_wait(bar_empty + 8 * ((IS - 2 + wg) & 3), ((IS - 2 + wg) >> 2) & 1);
            asm volatile("st.shared.f32 [%0], %1;\n" ::"r"(dml), "f"(stats(ln)) : "memory");
            qs = __uint_as_float(0x3F800000u + ((u0 & 7) << 25));
            m0 = -KV_OFF * qs * f16_hi(u0); m1 = -KV_OFF * qs * f16_hi(u1);
            plim = fmaxf(fabsf(m0), fabsf(m1)) < 64.f * KV_OFF && qs == 1.f ? S_LIMIT : 0u;
            uint32_t v[2][8] = {};
#pragma unroll
            for (int i = 0; i < 8; i++) {
                uint32_t *w = v[i & 1], *u = v[(i & 1) ^ 1];
#pragma unroll
                for (int j = 0; j < 8; j++) w[j] = pack_bf16(o[16 * i + 2 * j], o[16 * i + 2 * j + 1]);
                sts128(dst + i * 1024, w[0], w[1], w[2], w[3]);
                sts128(dst + i * 1024 + 512, w[4], w[5], w[6], w[7]);
                if (i) asm volatile("{\n.reg .pred p;\nsetp.lt.s32 p, %9, 0;\nL:\n@p st.shared.v4.u32 [%0], {%1, %2, %3, %4};\n@p st.shared.v4.u32 [%0 + 16], {%5, %6, %7, %8};\n@p bra L;\n}\n"
                             ::"r"(dst), "r"(u[0]), "r"(u[1]), "r"(u[2]), "r"(u[3]), "r"(u[4]), "r"(u[5]), "r"(u[6]), "r"(u[7]), "r"(it) : "memory");
            }
            fence_async_smem();
            warp_arrive(bar_pdone);
        }
        constexpr int IW = 4 + 75;
        uint32_t a[64];
        const int lane = lane_now(), t = warp * 32 + lane;
        if (wg == 0 && (SC_PAIR || SC_LAST)) {
            uint32_t rq, rml, rbar;
            asm volatile("mapa.shared::cluster.u32 %0, %3, %6;\nmapa.shared::cluster.u32 %1, %4, %6;\nmapa.shared::cluster.u32 %2, %5, %6;\n"
                         : "=r"(rq), "=r"(rml), "=r"(rbar) : "r"(sb + SM_Q + QB_BYTES + warp * 8192 + lane * 16), "r"(sb + SM_ML + 512 + t * 4),
                         "r"(bar_pin), "r"(rank ^ 1));
            auto send = [&](int i) {
                asm volatile("st.async.weak.shared::cluster.mbarrier::complete_tx::bytes.v4.b32 [%0], {%1, %2, %3, %4}, [%5];\n"
                             ::"r"(rq + i * 512), "r"(a[4 * i]), "r"(a[4 * i + 1]), "r"(a[4 * i + 2]), "r"(a[4 * i + 3]), "r"(rbar + (i & 8)) : "memory");
            };
            mbar_wait(bar_rfree, 0);
            wg_wait<0>();
            fence_regs(o);
            release((it - 1) & 3);
            float z0, z1;
            row_sums(z0, z1, lane);
            asm volatile("st.async.weak.shared::cluster.mbarrier::complete_tx::bytes.f32 [%0], %1, [%2];\n" ::"r"(rml), "f"(stats(lane)), "r"(rbar) : "memory");
#pragma unroll
            for (int i = 0; i < 16; i++) {
                a[4 * i] = pack_bf16(o[8 * i] - z0, o[8 * i + 1] - z0); a[4 * i + 1] = pack_bf16(o[8 * i + 2] - z1, o[8 * i + 3] - z1);
                a[4 * i + 2] = pack_bf16(o[8 * i + 4] - z0, o[8 * i + 5] - z0); a[4 * i + 3] = pack_bf16(o[8 * i + 6] - z1, o[8 * i + 7] - z1);
                if (i * SND0 / 16 != (i + 1) * SND0 / 16) send(i * SND0 / 16);
                if (i % CUT2 == CUT2 - 1) cut();
            }
            if (SC_PAIR) {
                float z[128];
                const uint32_t dkz = dk0 + ((uint32_t)it >> 24), dqz = dq0 + ((uint32_t)it >> 24);
                auto gemm = [&](int c) {
                    mbar_wait(bar_full + 8 * ((IW + c) & 3), ((IW + c) >> 2) & 1);
                    const uint64_t wb = mkaddr(dkz + ((IW + c) & 3) * (KV_BYTES >> 4), dhi), ab = mkaddr(dqz + c * 64, dhi);
                    wg_fence();
#pragma unroll
                    for (int kk = 0; kk < 4; kk++) {
                        if (c | kk) wgmma_ss_n256_tb(z, ab + kk * 2, wb + kk * 512);
                        else wgmma_ss_n256_tb_init(z, ab, wb);
                    }
                    wg_commit();
                };
                mbar_wait(qbar, qphase);
                bar_sync(BAR_ST + 1, 256);
                gemm(0);
#pragma unroll
                for (int i = SND0; i < 16; i++) send(i);
#pragma unroll
                for (int c = 1; c < 4; c++) { gemm(c); if (c == 3) pp_arrive(); wg_wait<1>(); release((IW + c - 1) & 3, 2); }
                wg_wait<0>();
                fence_regs(z);
                release((IW + 3) & 3, 2);
#pragma unroll
                for (int i = 0; i < 16; i++) {
                    sts128(sq + warp * 8192 + lane * 16 + i * 512, pack_bf16(z[8 * i], z[8 * i + 1]), pack_bf16(z[8 * i + 2], z[8 * i + 3]),
                           pack_bf16(z[8 * i + 4], z[8 * i + 5]), pack_bf16(z[8 * i + 6], z[8 * i + 7]));
                    if (i == 3 || i == 15) bar_arrive(i == 3 ? BAR_BF : BAR_H0, 256);
                    if (i == 3) cut();
                }
            } else {
#pragma unroll
                for (int i = SND0; i < 16; i++) send(i);
            }
        } else {
            const int pair = SC_PAIR;
            const bool glob = !(pair || SC_TAIL);
            const uint32_t ml = sb + SM_ML + (t & ~3) * 4, src = (glob ? sq : sb + SM_Q + QB_BYTES) + warp * 8192 + lane * 16;
            const uint64_t tm = lds64(s_tm);
            wg_wait<0>();
            fence_regs(o);
            release((IW - 1) & 3);
            float c0, c1;
            row_sums(c0, c1, lane);
            mbar_wait(glob ? qbar : bar_pin, glob ? qphase : 0);
            const float4 ps = lds128f(ml + (glob ? wg * 512 : 512));
            auto load = [&](int i) {
                asm volatile("ld.shared.v4.u32 {%0, %1, %2, %3}, [%4];\n" : "=r"(a[4 * i]), "=r"(a[4 * i + 1]), "=r"(a[4 * i + 2]), "=r"(a[4 * i + 3]) : "r"(src + i * 512) : "memory");
            };
#pragma unroll
            for (int i = 0; i < 8; i++) load(i);
            const float n0 = fmaxf(m0, ps.x), n1 = fmaxf(m1, ps.z);
            const float a0 = ex2(m0 - n0), a1 = ex2(m1 - n1), b0 = ex2(ps.x - n0), b1 = ex2(ps.z - n1);
            const float i0 = rcp(l0 * a0 + ps.y * b0), i1 = rcp(l1 * a1 + ps.w * b1);
            const float r0 = a0 * i0, r1 = a1 * i1;
            c0 *= -r0; c1 *= -r1;
            const uint32_t u0 = pack_bf16(b0 * i0, b0 * i0), u1 = pack_bf16(b1 * i1, b1 * i1);
            uint4 v[8];
#pragma unroll
            for (int i = 0; i <= 32; i++) {
                if (i == M2) {
#pragma unroll
                    for (int j = 0; j < 2 * M2; j++) asm volatile("" : "+r"(a[j]));
                    if (!glob) mbar_wait(bar_pin + 8, 0);
#pragma unroll
                    for (int j = 0; j < 8; j++) v[j] = lds128(src + (8 + j) * 512);
                }
                if (i == 32) break;
                const uint32_t x0 = pack_bf16(fmaf(o[4 * i], r0, c0), fmaf(o[4 * i + 1], r0, c0)), x1 = pack_bf16(fmaf(o[4 * i + 2], r1, c1), fmaf(o[4 * i + 3], r1, c1));
                a[2 * i] = i < 16 ? hfma2(a[2 * i], u0, x0) : x0;
                a[2 * i + 1] = i < 16 ? hfma2(a[2 * i + 1], u1, x1) : x1;
            }
#pragma unroll
            for (int j = 0; j < 8; j++) {
                uint32_t* x = a + 32 + 4 * j;
                x[0] = hfma2(v[j].x, u0, x[0]); x[1] = hfma2(v[j].y, u1, x[1]); x[2] = hfma2(v[j].z, u0, x[2]); x[3] = hfma2(v[j].w, u1, x[3]);
            }
            float y[2][32];
            auto gemm = [&](int c, int kh) {
                if (!kh) mbar_wait(bar_full + 8 * ((IW + c) & 3), (((IW + c) >> 2) & 1) ^ pair);
                const uint64_t wb = mkaddr(dk0 + ((IW + c) & 3) * (KV_BYTES >> 4), dhi - 192);
                wg_fence();
#pragma unroll
                for (int kk = 8 * kh; kk < 8 * kh + 8; kk++) {
                    if (kk) wgmma_rs_n64_tb(y[c & 1], a[4 * kk], a[4 * kk + 1], a[4 * kk + 2], a[4 * kk + 3], wb + kk * 128);
                    else wgmma_rs_n64_tb_init(y[c & 1], a[0], a[1], a[2], a[3], wb);
                }
                wg_commit();
            };
            const uint32_t stg = sq + warp * 8192 + (lane & 15) * 128 + (((lane >> 4) ^ lane) & 7) * 16;
            uint4 z[4] = {};
            auto load_z = [&](int cb) {
                if (cb < 2) asm volatile("{\n.reg .pred p;\nsetp.ne.s32 p, %0, 0;\n@p bar.sync %1, 256;\n}\n" ::"r"(pair), "r"(cb ? BAR_H0 : BAR_BF) : "memory");
#pragma unroll
                for (int i = 0; i < 4; i++)
                    asm volatile("{\n.reg .pred p;\nsetp.ne.u32 p, %4, 0;\n@p ld.shared.v4.u32 {%0, %1, %2, %3}, [%5];\n}\n"
                                 : "+r"(z[i].x), "+r"(z[i].y), "+r"(z[i].z), "+r"(z[i].w) : "r"(pair), "r"(src - QB_BYTES + (4 * cb + i) * 512) : "memory");
            };
            pp_sync();
            gemm(0, 0);
            gemm(0, 1);
#pragma unroll
            for (int c = 0; c < 4; c++) {
                if (c) load_z(c);
                if (c < 3) gemm(c + 1, 0);
                if (!c) load_z(0);
                if (c < 3) wg_wait<1>(); else wg_wait<0>();
                fence_regs(y[c & 1]);
                const float* x = y[c & 1];
#pragma unroll
                for (int i = 0; i < 4; i++)
                    stmatrix_x4((stg ^ (32 * i)) + c * 2048, hadd2(pack_bf16(x[8 * i], x[8 * i + 1]), z[i].x), hadd2(pack_bf16(x[8 * i + 2], x[8 * i + 3]), z[i].y),
                                hadd2(pack_bf16(x[8 * i + 4], x[8 * i + 5]), z[i].z), hadd2(pack_bf16(x[8 * i + 6], x[8 * i + 7]), z[i].w));
                if (c < 3) gemm(c + 1, 1);
                fence_async_smem();
                __syncwarp();
                asm volatile("{\n.reg .pred p;\nelect.sync _|p, -1;\n"
                             "@p cp.reduce.async.bulk.tensor.4d.global.shared::cta.add.tile.bulk_group [%0, {0, 0, %1, %2}], [%3];\n}\n"
                             ::"l"(tm), "r"(c), "r"((pair ? SC_ZB : 2 * SC_QT0 + wg) * 8 + warp * 2), "r"(sq + warp * 8192 + c * 2048) : "memory");
                if (c == 2 && glob) pp_arrive();
            }
            asm volatile("cp.async.bulk.commit_group;\ncp.async.bulk.wait_group.read 0;\n" ::: "memory");
        }
        } else {
            wg_wait<0>();
        }
        if (SC_TAIL) {
        float o[128];
        const int lane = lane_now(), t = warp * 32 + lane, q = lane & 3;
        auto emit = [&](uint32_t base, int lane, int row0, uint8_t* wdst, int turn) {
#pragma unroll
            for (int hh = 0; hh < 2; hh++) {
                if (turn > 0) mbar_wait(bar_zst + 8 * hh, (turn - 1) & 1);
#pragma unroll
                for (int i = 0; i < 8; i++)
                    stmatrix_x4(base + tile_off(8 * hh + (lane & 7), 4 * i + (lane >> 3)),
                                pack_bf16(o[16 * i + 2 * hh], o[16 * i + 2 * hh + 1]), pack_bf16(o[16 * i + 4 + 2 * hh], o[16 * i + 5 + 2 * hh]),
                                pack_bf16(o[16 * i + 8 + 2 * hh], o[16 * i + 9 + 2 * hh]), pack_bf16(o[16 * i + 12 + 2 * hh], o[16 * i + 13 + 2 * hh]));
                fence_async_smem();
                __syncwarp();
                if (wdst) {
                    if (lane < 4)
                        asm volatile("cp.async.bulk.global.shared::cta.bulk_group [%0], [%1], 1024;\n"
                                     ::"l"(wdst + ((turn & 1) ? hh * 4096 + lane * 1024 : hh * 1024 + lane * QB_BYTES)), "r"(base + hh * 4096 + lane * 1024) : "memory");
                    asm volatile("cp.async.bulk.commit_group;\n" ::: "memory");
                } else {
                    asm volatile("{\n.reg .pred p;\nsetp.eq.s32 p, %3, 0;\n"
                                 "@p cp.reduce.async.bulk.tensor.4d.global.shared::cta.add.tile.bulk_group [%0, {0, 0, 0, %1}], [%2];\n"
                                 "cp.async.bulk.commit_group;\n}\n"
                                 ::"l"(&P.tm_out), "r"((row0 >> 3) + hh), "r"(base + hh * 4096), "r"(lane) : "memory");
                }
            }
            asm volatile("cp.async.bulk.wait_group.read 1;\n" ::: "memory");
            warp_arrive(bar_zst - 8 * wg);
        };
        auto emit_done = [&](bool pending) {
            asm volatile("cp.async.bulk.wait_group.read 0;\n" ::: "memory");
            __syncwarp();
            asm volatile("{\n.reg .pred p;\nsetp.eq.s32 p, %1, 0;\n@p mbarrier.arrive.shared::cta.b64 _, [%0];\n}\n"
                         ::"r"(bar_zst + 8), "r"(pending ? lane : 1) : "memory");
        };
        if (!(rank | wg)) { release(0); release(1); release(2); release(3); }
        bar_sync(BAR_BF, 256);
        warp_arrive(bar_qfree);
        const int nf = rank ? 8 : 0;
        const int nz = nf + 26 + rank;
        const int itz = 4 + SC_NKV + SC_NW;
        bool pend = false;
#pragma unroll 1
        for (int k = wg; k < nz; k += 2) {
            const int iz = itz + (k < nf ? 0 : nf >> 1);
            mbar_wait(qbar, qphase); qphase ^= 1;
#pragma unroll 1
            for (int c = 0; c < 4; c++) {
                mbar_wait(bar_full + 8 * ((iz + c) & 3), ((iz + c) >> 2) & 1);
                const uint64_t wb = mkaddr(dk0 + ((iz + c) & 3) * (KV_BYTES >> 4), dhi), ab = mkaddr(dq0 + c * 64, dhi);
                wg_fence();
                wgmma_ss_n256_tb_pred(o, ab, wb, c);
#pragma unroll
                for (int kk = 1; kk < 4; kk++) wgmma_ss_n256_tb(o, ab + kk * 2, wb + kk * 512);
                wg_commit();
                emit_done(pend);
                pend = false;
            }
            wg_wait<0>();
            fence_regs(o);
            warp_arrive(bar_qfree);
            const int fb = ((k >> 1) + 3) & 3;
            if (k < nf) {
                float2* r255 = (float2*)H.s->r255 + wg * 128 + q;
                if (k < 2) {
                    if (t >= 124) {
#pragma unroll
                        for (int i = 0; i < 32; i++) r255[4 * i] = make_float2(o[4 * i + 2], o[4 * i + 3]);
                    }
                    bar_sync(BAR_WG0 + wg, 128);
                }
#pragma unroll
                for (int i = 0; i < 32; i++) {
                    const float2 v = __ldcg(r255 + 4 * i);
                    o[4 * i] -= v.x; o[4 * i + 1] -= v.y; o[4 * i + 2] -= v.x; o[4 * i + 3] -= v.y;
                }
            }
            int ln = lane;
            asm volatile("" : "+r"(ln));
            emit(sb + SM_KV + QB_BYTES + warp * KV_BYTES, ln, SC_TZB(k - nf) * 64 + warp * 16,
                 k >= nf ? nullptr : (k & 1) ? g_w + (4 + fb) * QB_BYTES + warp * 8192 : g_w + 8 * QB_BYTES + fb * 8192 + warp * 2048, k);
            pend = k + 2 < nz && (k | 1) != nf - 1;
            if (!pend) emit_done(true);
            if ((k | 1) == nf - 1) {
                asm volatile("cp.async.bulk.wait_group 0;\nfence.proxy.async.global;\nfence.acq_rel.gpu;\n" ::: "memory");
                bar_sync(BAR_BF, 256);
                if (tid == 0) red_release(&g_sync[SY_B * 32]);
                if (wg == 0) { release(0); release(1); release(2); release(3); }
            }
        }
        }
        if (wg == 0) pp_sync();
        warp_arrive(bar_end - 8 * wg);
        asm volatile("barrier.cluster.arrive.relaxed.aligned;\n" ::: "memory");
        if (P.E >= 0) return;
        asm volatile("setmaxnreg.dec.sync.aligned.u32 %0;\n" ::"n"(REG_P));
    }
    {
        if (warp != 0) {
            __syncwarp();
            if (SC_TAIL) {
                bar_sync(BAR_AUX, 96);
                if (warp == 1 && elect()) red_release(&g_sync[SY_CSR * 32]);
                __syncwarp();
            }
            mbar_wait_bounded(bar_go, 0);
            if (SC_TAIL) {
                if (warp == 1 && elect()) red_add(&g_sync[SY_DONE * 32]);
                if (warp == 3 && elect()) {
                    int it = 4 + SC_NKV + SC_NW;
                    asm volatile("prefetch.tensormap [%0];\n" ::"l"(&P.tm_out) : "memory");
                    if (rank) {
#pragma unroll 1
                        for (int j = 0; j < 4; j++, it++) {
                            mbar_wait_sleep(bar_empty + 8 * (it & 3), ((it >> 2) & 1) ^ 1);
                            mbar_expect_tx(bar_full + 8 * (it & 3), QB_BYTES);
                            tma_g2s(sb + SM_KV + (it & 3) * KV_BYTES, &P.tm_w[2], 8 * j, bar_full + 8 * (it & 3));
                        }
#pragma unroll 1
                        for (int k = 0; k < 8; k++) {
                            mbar_wait_sleep(bar_qfree + 8 * (k & 1), ((k >> 1) ^ (k & 1) ^ 1) & 1);
                            mbar_expect_tx(bar_q + 8 * (k & 1), QB_BYTES);
#pragma unroll 1
                            for (int hf = 0; hf < 2; hf++)
                                asm volatile("cp.async.bulk.tensor.5d.shared::cluster.global.tile.mbarrier::complete_tx::bytes [%0], [%1, {0, 0, %2, 0, 0}], [%3];\n"
                                             ::"r"(sb + SM_Q + (k & 1) * QB_BYTES + hf * 16384), "l"(&P.tm_w[k & 1]),
                                             "r"(8 * (((k >> 1) + 3) & 3) + 4 * hf), "r"(bar_q + 8 * (k & 1)) : "memory");
                        }
                        flag_wait_bounded(&g_sync[SY_B * 32], ep);
                        fence_async_global();
                    }
#pragma unroll 1
                    for (int j = 0; j < 4; j++, it++) {
                        mbar_wait_sleep(bar_empty + 8 * (it & 3), ((it >> 2) & 1) ^ 1);
                        mbar_expect_tx(bar_full + 8 * (it & 3), QB_BYTES);
                        bulk_g2s(sb + SM_KV + (it & 3) * KV_BYTES, g_w + (4 + j) * QB_BYTES, QB_BYTES, bar_full + 8 * (it & 3));
                    }
#pragma unroll 1
                    for (int k = 0; k < 26 + rank; k++) {
                        if (k == 0 || k == ((GF0 + 1) * NAUX - 16) / 128) { flag_wait_bounded(&g_sync[(k ? SY_AUX1 : SY_AUX0) * 32], NAUX * ep); fence_async_global(); }
                        mbar_wait_sleep(bar_qfree + 8 * (k & 1), ((k >> 1) ^ (k & 1) ^ 1) & 1);
                        mbar_expect_tx(bar_q + 8 * (k & 1), QB_BYTES);
                        bulk_g2s(sb + SM_Q + (k & 1) * QB_BYTES, g_agg + SC_TZB(k) * QB_BYTES, QB_BYTES, bar_q + 8 * (k & 1));
                    }
                }
            } else {
            const int par = ep & 1;
            if (blockIdx.x == 0 && t == 32) g_ovf_n[par ^ 1] = 0;
            if (blockIdx.x == 0 && warp == 1) *(uint4*)(g_hz + (lane >> 3) * 1024 + (lane & 7) * 16) = make_uint4(KV_OFF2 | NEG2, KV_OFF2 | NEG2, KV_OFF2, KV_OFF2);
            const uint32_t wlo = (uint32_t)(uintptr_t)H.s, whi = (uint32_t)((uintptr_t)H.s >> 32);
            const uint32_t blo = wlo + (uint32_t)offsetof(Scratch, bucket);
            {
                const int* pd = P.dst + blockIdx.x * 96 + (t - 32);
                const int* ps = P.src + blockIdx.x * 96 + (t - 32);
#pragma unroll 1
                for (int e = P.E - (blockIdx.x * 96 + (t - 32)); e > 0; e -= CSRU * NAUX * 32, pd += CSRU * NAUX * 32, ps += CSRU * NAUX * 32) {
                    int d[CSRU], sr[CSRU], sl[CSRU];
#pragma unroll
                    for (int i = 0; i < CSRU; i++) {
                        d[i] = e > i * NAUX * 32 ? __ldg(pd + i * NAUX * 32) : NN;
                        sr[i] = e > i * NAUX * 32 ? __ldg(ps + i * NAUX * 32) : 0;
                    }
#pragma unroll
                    for (int i = 0; i < CSRU; i++) {
                        sl[i] = 0;
                        asm volatile("{\n.reg .pred p;\nsetp.lt.s32 p, %2, %3;\n@p atom.relaxed.gpu.global.add.s32 %0, [%1], 1;\n}\n"
                                     : "+r"(sl[i]) : "l"(mkaddr(wlo + (uint32_t)offsetof(Scratch, cnt) + d[i] * 4, whi)), "r"(d[i]), "n"(NN) : "memory");
                    }
                    uint32_t ov = 0;
#pragma unroll
                    for (int i = 0; i < CSRU; i++) {
                        asm volatile("{\n.reg .pred p;\nsetp.lt.s32 p, %3, %4;\n@p st.global.u16 [%1], %2;\n@!p or.b32 %0, %0, %5;\n}\n"
                                     : "+r"(ov) : "l"(mkaddr(blo + d[i] * 128 + (sl[i] & 31) * 4 + (sl[i] >> 5) * 2, whi)), "h"((unsigned short)sr[i]), "r"(sl[i]), "n"(CAP), "r"(1 << i) : "memory");
                    }
#pragma unroll 1
                    for (; ov; ov &= ov - 1) {
                        const int i = (__ffs(ov) - 1) * (NAUX * 32);
                        int at;
                        asm volatile("atom.relaxed.gpu.global.add.s32 %0, [%1], 1;\n" : "=r"(at) : "l"(&g_ovf_n[par]) : "memory");
                        g_ovf[at] = make_int2(__ldg(pd + i), __ldg(ps + i));
                    }
                }
            }
            bar_sync(BAR_AUX, 96);
            if (warp == 1 && elect()) { red_release(&g_sync[SY_CSR * 32]); }
            __syncwarp();
            {
                const int r0 = blockIdx.x * 3 + warp - 1;
                const uint4* xp = (const uint4*)(H.x + r0 * 256) + lane;
                uint4* op = (uint4*)(P.out + r0 * 256) + lane;
#pragma unroll 1
                for (int r = r0; r < NN; r += CPYU * NAUX, xp += CPYU * NAUX * 32, op += CPYU * NAUX * 32) {
                    uint4 v[CPYU];
#pragma unroll
                    for (int i = 0; i < CPYU; i++) if (r + i * NAUX < NN) v[i] = ldg_pinned(xp + i * NAUX * 32);
#pragma unroll
                    for (int i = 0; i < CPYU; i++) if (r + i * NAUX < NN) op[i * NAUX * 32] = v[i];
                }
            }
            if (warp == 3 && SC_OWNER && SC_PAIR && elect()) {
                mbar_wait_sleep(bar_pdone, 0);
                mbar_wait_sleep(bar_pdone + 8, 0);
#pragma unroll 1
                for (int u = 0; u < 16; u++) {
                    bulk_s2g(g_q + SC_QT0 * (2 * QB_BYTES) + u * 4096, sb + SM_Q + u * 4096, 4096);
                    asm volatile("cp.async.bulk.wait_group 0;\n" ::: "memory");
                }
                fence_async_global();
                st_release(&g_qflag[SC_QT0], ep);
            }
            __syncwarp();
            mbar_wait_bounded(bar_go, 1);
            bar_sync(BAR_AUX, 96);
            if (const int un = (3 - warp) * (NAUX / 3) + (NAUX / 3 - 1) - blockIdx.x; un < 208) {
                flag_wait_bounded(&g_sync[SY_PART * 32], 52 * ep);
                uint8_t* pp = g_part + (un >> 3) * (4 * PART_BYTES);
                float* ml = (float*)(pp + QB_BYTES) + (un & 7) * 32;
                const float4 sa = __ldcg((const float4*)ml + g), sc = __ldcg((const float4*)ml + g + 2 * PART_BYTES / 16);
                const float n0 = fmaxf(sa.x, sc.x), n1 = fmaxf(sa.z, sc.z);
                const uint32_t a0 = pack_bf16(ex2(sa.x - n0), ex2(sa.x - n0)), a1 = pack_bf16(ex2(sa.z - n1), ex2(sa.z - n1));
                const uint32_t b0 = pack_bf16(ex2(sc.x - n0), ex2(sc.x - n0)), b1 = pack_bf16(ex2(sc.z - n1), ex2(sc.z - n1));
                __syncwarp();
                if (q == 0) ((float4*)ml)[g] = make_float4(n0, sa.y * bf_hi(a0) + sc.y * bf_hi(b0), n1, sa.w * bf_hi(a1) + sc.w * bf_hi(b1));
                uint4* d = (uint4*)(pp + (un & 4) * 256 + (un & 7) * 8192) + lane;
#pragma unroll 1
                for (int i = 0; i < 4; i++, d += 128) {
                    uint4 u[4], v[4];
#pragma unroll
                    for (int j = 0; j < 4; j++) { u[j] = __ldcg(d + j * 32); v[j] = __ldcg(d + j * 32 + 2 * PART_BYTES / 16); }
#pragma unroll
                    for (int j = 0; j < 4; j++)
                        d[j * 32] = make_uint4(hfma2(v[j].x, b0, hmul2(u[j].x, a0)), hfma2(v[j].y, b1, hmul2(u[j].y, a1)),
                                               hfma2(v[j].z, b0, hmul2(u[j].z, a0)), hfma2(v[j].w, b1, hmul2(u[j].w, a1)));
                }
            }
            flag_wait_bounded(&g_sync[SY_CSR * 32], NCTA * ep);
            if (warp == 2 && blockIdx.x < 129) {
                uint4* z = blockIdx.x < 128 ? (uint4*)(g_w + blockIdx.x * 1024) + lane : (uint4*)&g_sync[SY_DONE * 32 + 4];
                z[0] = make_uint4(0, 0, 0, 0);
                if (blockIdx.x < 128) z[32] = make_uint4(0, 0, 0, 0);
            }
            {
                const uint32_t lc = (lane >> 3) * 1024 + (lane & 7) * 16;
                const uint32_t alo = wlo ^ lc;
                const int node0 = blockIdx.x * 3 + warp - 17;
                auto node = [&](int i) { const int nd = node0 + i * NAUX; return (int)min((unsigned)nd, (unsigned)(nd + NN)); };
                const int num = (NN - 17 - node0) / NAUX + 1;
                uint32_t mine = 0;
                if (lane < num) {
                    mine = min(__ldcg(&g_cnt[node(lane)]), CAP + 1) | (uint32_t)__ldg((const unsigned short*)P.deg_inv + node(lane)) << 16;
                    g_cnt[node(lane)] = 0;
                }
                auto row = [&](int off) {
                    uint4 v;
                    asm volatile("ld.global.v4.u32 {%0, %1, %2, %3}, [%4];\n"
                                 : "=r"(v.x), "=r"(v.y), "=r"(v.z), "=r"(v.w) : "l"(mkaddr(alo ^ off, whi)));
                    return v;
                };
                auto ents = [&](int i) {
                    uint32_t e;
                    asm volatile("ld.global.cg.u32 %0, [%1];\n" : "=r"(e) : "l"(mkaddr(blo + (min(node(i), NN - 1) * 32 + lane) * 4, whi)));
                    return e;
                };
                auto store = [&](int i, const float (&a)[8]) {
                    const float di = bf_hi(__shfl_sync(~0u, mine, i)) * (1.f / KV_SCALE);
                    const int nd = node(i);
                    *(uint4*)(g_agg + (uint32_t)(((nd >> 3) * 4096 + (nd & 7) * 144) ^ lc)) =
                        make_uint4(pack_bf16(a[0] * di, a[1] * di), pack_bf16(a[2] * di, a[3] * di), pack_bf16(a[4] * di, a[5] * di), pack_bf16(a[6] * di, a[7] * di));
                };
#pragma unroll 1
                for (uint32_t big = __ballot_sync(~0u, (mine & 0xFFFF) > CAP); big; big &= big - 1) {
                    const int i = __ffs(big) - 1, no = __ldcg(&g_ovf_n[par]);
                    float a[8] = {};
#pragma unroll 1
                    for (int k = -64; k < no; k += 32) {
                        const int2 pr = k < 0 ? make_int2(node(i), (ents(i) >> (k & 32) / 2) & 0xFFFF) : k + lane < no ? __ldcg(&g_ovf[k + lane]) : make_int2(-1, 0);
#pragma unroll 1
                        for (uint32_t mk = __ballot_sync(~0u, pr.x == node(i)); mk; mk &= mk - 1) {
                            const uint4 v = row(row_off(__shfl_sync(~0u, pr.y, __ffs(mk) - 1)));
                            a[0] += f16_lo(v.x) + KV_OFF; a[1] += f16_hi(v.x) + KV_OFF; a[2] += f16_lo(v.y) + KV_OFF; a[3] += f16_hi(v.y) + KV_OFF;
                            a[4] += f16_lo(v.z) - KV_OFF; a[5] += f16_hi(v.z) - KV_OFF; a[6] += f16_lo(v.w) - KV_OFF; a[7] += f16_hi(v.w) - KV_OFF;
                        }
                    }
                    store(i, a);
                }
                auto add4 = [&](const uint4& a, const uint4& b) { return make_uint4(hadd2_f16(a.x, b.x), hadd2_f16(a.y, b.y), hadd2_f16(a.z, b.z), hadd2_f16(a.w, b.w)); };
                int ni = -1, left = 0, pos = 0, ec = 0;
                uint32_t en = ents(0);
                uint4 acc = make_uint4(0, 0, 0, 0);
                auto step = [&](uint4 (&v)[4], int& tag) {
                    if (left <= 0 || pos == 32) {
                        if (left > 0) {
                            en = ents(ni) >> 16;
                        } else {
                            ni++;
                            left = __shfl_sync(~0u, mine, ni) & 0xFFFF;
                            if (left > CAP) left = 0;
                        }
                        ec = lane < left ? row_off(en & 0xFFFF) : 0;
                        en = ents(ni + 1);
                        pos = 0;
                    }
                    int of[4];
#pragma unroll
                    for (int j = 0; j < 4; j++) asm volatile("shfl.sync.idx.b32 %0, %1, %2, 31, -1;\n" : "=r"(of[j]) : "r"(ec), "r"(pos + j));
                    acc = add4(acc, add4(add4(add4(v[0], v[1]), make_uint4(KV_OFF8, KV_OFF8, KV_OFF8 | NEG2, KV_OFF8 | NEG2)), add4(v[2], v[3])));
                    asm volatile("" : "+r"(acc.x), "+r"(acc.y), "+r"(acc.z), "+r"(acc.w));
                    asm volatile("{\n.reg .pred p;\nsetp.lt.s32 p, %0, 0;\nL:\n@p pmevent 0;\n@p bra L;\n}\n" ::"r"(ni) : "memory");
#pragma unroll
                    for (int j = 0; j < 4; j++) v[j] = row(of[j]);
                    pos += 4; left -= 4;
                    const int i = tag;
                    tag = left <= 0 ? ni : -1;
                    if (i >= 0) {
                        const float a[8] = {f16_lo(acc.x), f16_hi(acc.x), f16_lo(acc.y), f16_hi(acc.y), f16_lo(acc.z), f16_hi(acc.z), f16_lo(acc.w), f16_hi(acc.w)};
                        if ((__shfl_sync(~0u, mine, i) & 0xFFFF) <= CAP) store(i, a);
                        acc = make_uint4(0, 0, 0, 0);
                        if (i == GF0 || i == 8) {
                            __syncwarp();
                            if (elect()) red_release(&g_sync[(i == 8 ? SY_AUX1 : SY_AUX0) * 32]);
                            __syncwarp();
                        }
                    }
                    return i == num - 1;
                };
                uint4 va[4], vb[4];
#pragma unroll
                for (int j = 0; j < 4; j++) va[j] = vb[j] = make_uint4(KV_OFF2 | NEG2, KV_OFF2 | NEG2, KV_OFF2, KV_OFF2);
                int ta = -1, tb = -1;
#pragma unroll 1
                while (!step(va, ta) && !step(vb, tb)) {}
            }
            bar_sync(BAR_AUX, 96);
            if (warp == 1 && elect()) {
                red_release(&g_sync[SY_AUX * 32]);
                red_add(&g_sync[SY_DONE * 32]);
            }
            }
        }
        __syncwarp();
        asm volatile("barrier.cluster.arrive.relaxed.aligned;\n" ::: "memory");
        if (warp == 1) mbar_wait_bounded(bar_end, 0);
        else if (elect()) mbar_arrive(bar_end);
        __syncwarp();
        asm volatile("barrier.cluster.wait.acquire.aligned;\n" ::: "memory");
    }
}

}

extern "C" void kernel_launch(void* const* d_in, const int* in_sizes, int n_in, void* d_out, int out_size) {
    Hot H;
    Params P;
    H.x = (const __nv_bfloat16*)d_in[0];
    P.src = (const int*)d_in[1];
    P.dst = (const int*)d_in[2];
    P.deg_inv = (const __nv_bfloat16*)d_in[3];
    H.wq = (const __nv_bfloat16*)d_in[5];
    H.wk = (const __nv_bfloat16*)d_in[6];
    P.out = (__nv_bfloat16*)d_out;
    typedef CUresult (*EncodeFn)(CUtensorMap*, CUtensorMapDataType, cuuint32_t, void*, const cuuint64_t*, const cuuint64_t*, const cuuint32_t*,
                                 const cuuint32_t*, CUtensorMapInterleave, CUtensorMapSwizzle, CUtensorMapL2promotion, CUtensorMapFloatOOBfill);
    void* fn = nullptr;
    cudaDriverEntryPointQueryResult qr;
    cudaGetDriverEntryPoint("cuTensorMapEncodeTiled", &fn, cudaEnableDefault, &qr);
    auto encode = [&](CUtensorMap* tm, const void* ptr, int rows, int box_rows, int box_cb = 4) {
        const cuuint64_t dims[4] = {64, 8, 4, (cuuint64_t)rows / 8};
        const cuuint64_t strides[3] = {512, 128, 4096};
        const cuuint32_t box[4] = {64, 8, (cuuint32_t)box_cb, (cuuint32_t)box_rows / 8}, es[4] = {1, 1, 1, 1};
        ((EncodeFn)fn)(tm, CU_TENSOR_MAP_DATA_TYPE_BFLOAT16, 4, (void*)ptr, dims, strides, box, es, CU_TENSOR_MAP_INTERLEAVE_NONE,
                       CU_TENSOR_MAP_SWIZZLE_128B, CU_TENSOR_MAP_L2_PROMOTION_NONE, CU_TENSOR_MAP_FLOAT_OOB_FILL_NONE);
    };
    encode(&P.tm_out, d_out, NN, 8);
    encode(&P.tm_outc, d_out, NN, 16, 1);
    for (int i = 0; i < 2; i++) {
        const cuuint64_t dims[5] = {64, 2, 32, 4, 4};
        const cuuint64_t strides[4] = {512, 4096, 128, 1024};
        const cuuint32_t box[5] = {64, 2, 4, 4, 4}, es[5] = {1, 1, 1, 1, 1};
        ((EncodeFn)fn)(&P.tm_w[i], CU_TENSOR_MAP_DATA_TYPE_BFLOAT16, 5, d_in[i ? 4 : 7], dims, strides, box, es, CU_TENSOR_MAP_INTERLEAVE_NONE,
                       CU_TENSOR_MAP_SWIZZLE_128B, CU_TENSOR_MAP_L2_PROMOTION_NONE, CU_TENSOR_MAP_FLOAT_OOB_FILL_NONE);
    }
    encode(&P.tm_w[2], d_in[8], 256, 64);
    void* raw = nullptr;
    cudaGetSymbolAddress(&raw, g_raw);
    H.s = (Scratch*)(((uintptr_t)raw + ((8 << 20) - 1)) & ~(uintptr_t)((8 << 20) - 1));
    P.dhi = 0x40000100u;
    P.E = in_sizes[1] < MAXE ? in_sizes[1] : MAXE;
    cudaFuncSetAttribute(k_main, cudaFuncAttributeMaxDynamicSharedMemorySize, SM_TOTAL);
    k_main<<<NCTA, 384, SM_TOTAL>>>(H, P);
}
```

```cpp
#include <cuda_runtime.h>
#include <cuda.h>
#include <cuda_bf16.h>
#include <stdint.h>
#include <stddef.h>

namespace {

constexpr int NN = 10000;
constexpr int BN = 80;
constexpr int NQB = 158;
constexpr int NCTA = 132;
constexpr int NAUX = 3 * (NCTA - 2);
constexpr int STAGES = 4;
constexpr int KV_BYTES = BN * 512;
constexpr int QB_BYTES = 64 * 512;
constexpr int PART_BYTES = QB_BYTES + 512;
constexpr int CAP = 64;
constexpr int MAXE = 160000;

#define GO0 5
#define GO1 40
#define GF0 2
#define CSRU 3
#define CPYU 9
#define REFUP 2.f
#define REFSUM 3.f
#define LIFT 6
#define KVM 0x1AB
#define SND0 10
#define M2 28
#define TICK 1024
#define NQR 7
#define REG_C 224
#define REG_P 56
#define QREG(kk) (((kk) & 1) && (kk) / 2 < NQR ? (kk) / 2 : -1)
#define QRND(v) (((v) + 0x00040004u) & 0xFFF8FFF8u)

enum { SY_PART = 4, SY_H1 = 5, SY_CSR = 6, SY_AUX = 7, SY_DONE = 8, SY_AUX0 = 9, SY_B = 10, SY_AUX1 = 11, SY_H0 = 12 };
struct Scratch {
    uint8_t hz[4096 + NN * 512];
    uint8_t w[12 * QB_BYTES];
    int sync[25 * 32];
    int qflag[96];
    int ovf_n[32];
    float r255[512];
    int cnt[NN + 16];
    int bucket[(NN + 1) * 32];
    int2 ovf[MAXE];
    uint8_t q[NQB * QB_BYTES];
    uint8_t agg[NQB * QB_BYTES];
    uint8_t part[52 * 2 * PART_BYTES];
};
static_assert(offsetof(Scratch, ovf) <= (8 << 20), "window");
static_assert(offsetof(Scratch, qflag) == offsetof(Scratch, sync) + 25 * 128, "flags");
static_assert(offsetof(Scratch, w) % 1024 == 0 && offsetof(Scratch, sync) % 128 == 0 &&
              offsetof(Scratch, bucket) % 128 == 0 && offsetof(Scratch, q) % 128 == 0, "alignment");
__device__ uint8_t g_raw[(8 << 20) + sizeof(Scratch)];
#define g_hz (H.s->hz)
#define g_w (H.s->w)
#define g_sync (H.s->sync)
#define g_qflag (H.s->qflag)
#define g_ovf_n (H.s->ovf_n)
#define g_cnt (H.s->cnt)
#define g_bucket (H.s->bucket)
#define g_ovf (H.s->ovf)
#define g_q (H.s->q)
#define g_agg (H.s->agg)
#define g_part (H.s->part)

__device__ __forceinline__ void wgmma_ss_n80(uint32_t (&d)[20], uint64_t da, uint64_t db) {
    asm volatile("wgmma.mma_async.sync.aligned.m64n80k16.f16.f16.f16 {"
        "%0, %1, %2, %3, %4, %5, %6, %7, %8, %9, %10, %11, %12, %13, %14, %15, %16, %17, %18, %19}, %20, %21, 1, 1, 1, 0, 0;\n"
        : "+r"(d[0]), "+r"(d[1]), "+r"(d[2]), "+r"(d[3]), "+r"(d[4]), "+r"(d[5]), "+r"(d[6]), "+r"(d[7]),
          "+r"(d[8]), "+r"(d[9]), "+r"(d[10]), "+r"(d[11]), "+r"(d[12]), "+r"(d[13]), "+r"(d[14]), "+r"(d[15]),
          "+r"(d[16]), "+r"(d[17]), "+r"(d[18]), "+r"(d[19])
        : "l"(da), "l"(db));
}
__device__ __forceinline__ void wgmma_ss_n80_init(uint32_t (&d)[20], uint64_t da, uint64_t db) {
    asm volatile("wgmma.mma_async.sync.aligned.m64n80k16.f16.f16.f16 {"
        "%0, %1, %2, %3, %4, %5, %6, %7, %8, %9, %10, %11, %12, %13, %14, %15, %16, %17, %18, %19}, %20, %21, 0, 1, 1, 0, 0;\n"
        : "=r"(d[0]), "=r"(d[1]), "=r"(d[2]), "=r"(d[3]), "=r"(d[4]), "=r"(d[5]), "=r"(d[6]), "=r"(d[7]),
          "=r"(d[8]), "=r"(d[9]), "=r"(d[10]), "=r"(d[11]), "=r"(d[12]), "=r"(d[13]), "=r"(d[14]), "=r"(d[15]),
          "=r"(d[16]), "=r"(d[17]), "=r"(d[18]), "=r"(d[19])
        : "l"(da), "l"(db));
}
__device__ __forceinline__ void wgmma_rs_n80(uint32_t (&d)[20], uint32_t a0, uint32_t a1, uint32_t a2, uint32_t a3, uint64_t db) {
    asm volatile("wgmma.mma_async.sync.aligned.m64n80k16.f16.f16.f16 {"
        "%0, %1, %2, %3, %4, %5, %6, %7, %8, %9, %10, %11, %12, %13, %14, %15, %16, %17, %18, %19}, {%20, %21, %22, %23}, %24, 1, 1, 1, 0;\n"
        : "+r"(d[0]), "+r"(d[1]), "+r"(d[2]), "+r"(d[3]), "+r"(d[4]), "+r"(d[5]), "+r"(d[6]), "+r"(d[7]),
          "+r"(d[8]), "+r"(d[9]), "+r"(d[10]), "+r"(d[11]), "+r"(d[12]), "+r"(d[13]), "+r"(d[14]), "+r"(d[15]),
          "+r"(d[16]), "+r"(d[17]), "+r"(d[18]), "+r"(d[19])
        : "r"(a0), "r"(a1), "r"(a2), "r"(a3), "l"(db));
}
__device__ __forceinline__ void wgmma_rs_n256_tb(float (&d)[128], uint32_t a0, uint32_t a1, uint32_t a2, uint32_t a3, uint64_t db) {
    asm volatile("wgmma.mma_async.sync.aligned.m64n256k16.f32.f16.f16 {"
        "%0, %1, %2, %3, %4, %5, %6, %7, %8, %9, %10, %11, %12, %13, %14, %15, %16, %17, %18, %19, %20, %21, %22, %23, %24, %25, %26, %27, %28, %29, %30, %31, "
        "%32, %33, %34, %35, %36, %37, %38, %39, %40, %41, %42, %43, %44, %45, %46, %47, %48, %49, %50, %51, %52, %53, %54, %55, %56, %57, %58, %59, %60, %61, %62, %63, "
        "%64, %65, %66, %67, %68, %69, %70, %71, %72, %73, %74, %75, %76, %77, %78, %79, %80, %81, %82, %83, %84, %85, %86, %87, %88, %89, %90, %91, %92, %93, %94, %95, "
        "%96, %97, %98, %99, %100, %101, %102, %103, %104, %105, %106, %107, %108, %109, %110, %111, %112, %113, %114, %115, %116, %117, %118, %119, %120, %121, %122, %123, %124, %125, %126, %127}, {%128, %129, %130, %131}, %132, 1, 1, 1, 1;\n"
        : "+f"(d[0]), "+f"(d[1]), "+f"(d[2]), "+f"(d[3]), "+f"(d[4]), "+f"(d[5]), "+f"(d[6]), "+f"(d[7]),
          "+f"(d[8]), "+f"(d[9]), "+f"(d[10]), "+f"(d[11]), "+f"(d[12]), "+f"(d[13]), "+f"(d[14]), "+f"(d[15]),
          "+f"(d[16]), "+f"(d[17]), "+f"(d[18]), "+f"(d[19]), "+f"(d[20]), "+f"(d[21]), "+f"(d[22]), "+f"(d[23]),
          "+f"(d[24]), "+f"(d[25]), "+f"(d[26]), "+f"(d[27]), "+f"(d[28]), "+f"(d[29]), "+f"(d[30]), "+f"(d[31]),
          "+f"(d[32]), "+f"(d[33]), "+f"(d[34]), "+f"(d[35]), "+f"(d[36]), "+f"(d[37]), "+f"(d[38]), "+f"(d[39]),
          "+f"(d[40]), "+f"(d[41]), "+f"(d[42]), "+f"(d[43]), "+f"(d[44]), "+f"(d[45]), "+f"(d[46]), "+f"(d[47]),
          "+f"(d[48]), "+f"(d[49]), "+f"(d[50]), "+f"(d[51]), "+f"(d[52]), "+f"(d[53]), "+f"(d[54]), "+f"(d[55]),
          "+f"(d[56]), "+f"(d[57]), "+f"(d[58]), "+f"(d[59]), "+f"(d[60]), "+f"(d[61]), "+f"(d[62]), "+f"(d[63]),
          "+f"(d[64]), "+f"(d[65]), "+f"(d[66]), "+f"(d[67]), "+f"(d[68]), "+f"(d[69]), "+f"(d[70]), "+f"(d[71]),
          "+f"(d[72]), "+f"(d[73]), "+f"(d[74]), "+f"(d[75]), "+f"(d[76]), "+f"(d[77]), "+f"(d[78]), "+f"(d[79]),
          "+f"(d[80]), "+f"(d[81]), "+f"(d[82]), "+f"(d[83]), "+f"(d[84]), "+f"(d[85]), "+f"(d[86]), "+f"(d[87]),
          "+f"(d[88]), "+f"(d[89]), "+f"(d[90]), "+f"(d[91]), "+f"(d[92]), "+f"(d[93]), "+f"(d[94]), "+f"(d[95]),
          "+f"(d[96]), "+f"(d[97]), "+f"(d[98]), "+f"(d[99]), "+f"(d[100]), "+f"(d[101]), "+f"(d[102]), "+f"(d[103]),
          "+f"(d[104]), "+f"(d[105]), "+f"(d[106]), "+f"(d[107]), "+f"(d[108]), "+f"(d[109]), "+f"(d[110]), "+f"(d[111]),
          "+f"(d[112]), "+f"(d[113]), "+f"(d[114]), "+f"(d[115]), "+f"(d[116]), "+f"(d[117]), "+f"(d[118]), "+f"(d[119]),
          "+f"(d[120]), "+f"(d[121]), "+f"(d[122]), "+f"(d[123]), "+f"(d[124]), "+f"(d[125]), "+f"(d[126]), "+f"(d[127])
        : "r"(a0), "r"(a1), "r"(a2), "r"(a3), "l"(db));
}
__device__ __forceinline__ void wgmma_rs_n256_tb_init(float (&d)[128], uint32_t a0, uint32_t a1, uint32_t a2, uint32_t a3, uint64_t db) {
    asm volatile("wgmma.mma_async.sync.aligned.m64n256k16.f32.f16.f16 {"
        "%0, %1, %2, %3, %4, %5, %6, %7, %8, %9, %10, %11, %12, %13, %14, %15, %16, %17, %18, %19, %20, %21, %22, %23, %24, %25, %26, %27, %28, %29, %30, %31, "
        "%32, %33, %34, %35, %36, %37, %38, %39, %40, %41, %42, %43, %44, %45, %46, %47, %48, %49, %50, %51, %52, %53, %54, %55, %56, %57, %58, %59, %60, %61, %62, %63, "
        "%64, %65, %66, %67, %68, %69, %70, %71, %72, %73, %74, %75, %76, %77, %78, %79, %80, %81, %82, %83, %84, %85, %86, %87, %88, %89, %90, %91, %92, %93, %94, %95, "
        "%96, %97, %98, %99, %100, %101, %102, %103, %104, %105, %106, %107, %108, %109, %110, %111, %112, %113, %114, %115, %116, %117, %118, %119, %120, %121, %122, %123, %124, %125, %126, %127}, {%128, %129, %130, %131}, %132, 0, 1, 1, 1;\n"
        : "=f"(d[0]), "=f"(d[1]), "=f"(d[2]), "=f"(d[3]), "=f"(d[4]), "=f"(d[5]), "=f"(d[6]), "=f"(d[7]),
          "=f"(d[8]), "=f"(d[9]), "=f"(d[10]), "=f"(d[11]), "=f"(d[12]), "=f"(d[13]), "=f"(d[14]), "=f"(d[15]),
          "=f"(d[16]), "=f"(d[17]), "=f"(d[18]), "=f"(d[19]), "=f"(d[20]), "=f"(d[21]), "=f"(d[22]), "=f"(d[23]),
          "=f"(d[24]), "=f"(d[25]), "=f"(d[26]), "=f"(d[27]), "=f"(d[28]), "=f"(d[29]), "=f"(d[30]), "=f"(d[31]),
          "=f"(d[32]), "=f"(d[33]), "=f"(d[34]), "=f"(d[35]), "=f"(d[36]), "=f"(d[37]), "=f"(d[38]), "=f"(d[39]),
          "=f"(d[40]), "=f"(d[41]), "=f"(d[42]), "=f"(d[43]), "=f"(d[44]), "=f"(d[45]), "=f"(d[46]), "=f"(d[47]),
          "=f"(d[48]), "=f"(d[49]), "=f"(d[50]), "=f"(d[51]), "=f"(d[52]), "=f"(d[53]), "=f"(d[54]), "=f"(d[55]),
          "=f"(d[56]), "=f"(d[57]), "=f"(d[58]), "=f"(d[59]), "=f"(d[60]), "=f"(d[61]), "=f"(d[62]), "=f"(d[63]),
          "=f"(d[64]), "=f"(d[65]), "=f"(d[66]), "=f"(d[67]), "=f"(d[68]), "=f"(d[69]), "=f"(d[70]), "=f"(d[71]),
          "=f"(d[72]), "=f"(d[73]), "=f"(d[74]), "=f"(d[75]), "=f"(d[76]), "=f"(d[77]), "=f"(d[78]), "=f"(d[79]),
          "=f"(d[80]), "=f"(d[81]), "=f"(d[82]), "=f"(d[83]), "=f"(d[84]), "=f"(d[85]), "=f"(d[86]), "=f"(d[87]),
          "=f"(d[88]), "=f"(d[89]), "=f"(d[90]), "=f"(d[91]), "=f"(d[92]), "=f"(d[93]), "=f"(d[94]), "=f"(d[95]),
          "=f"(d[96]), "=f"(d[97]), "=f"(d[98]), "=f"(d[99]), "=f"(d[100]), "=f"(d[101]), "=f"(d[102]), "=f"(d[103]),
          "=f"(d[104]), "=f"(d[105]), "=f"(d[106]), "=f"(d[107]), "=f"(d[108]), "=f"(d[109]), "=f"(d[110]), "=f"(d[111]),
          "=f"(d[112]), "=f"(d[113]), "=f"(d[114]), "=f"(d[115]), "=f"(d[116]), "=f"(d[117]), "=f"(d[118]), "=f"(d[119]),
          "=f"(d[120]), "=f"(d[121]), "=f"(d[122]), "=f"(d[123]), "=f"(d[124]), "=f"(d[125]), "=f"(d[126]), "=f"(d[127])
        : "r"(a0), "r"(a1), "r"(a2), "r"(a3), "l"(db));
}
__device__ __forceinline__ void wgmma_rs_n256_tb_pred(float (&d)[128], uint32_t a0, uint32_t a1, uint32_t a2, uint32_t a3, uint64_t db, int acc) {
    asm volatile("{\n.reg .pred p;\nsetp.ne.s32 p, %133, 0;\nwgmma.mma_async.sync.aligned.m64n256k16.f32.f16.f16 {"
        "%0, %1, %2, %3, %4, %5, %6, %7, %8, %9, %10, %11, %12, %13, %14, %15, %16, %17, %18, %19, %20, %21, %22, %23, %24, %25, %26, %27, %28, %29, %30, %31, "
        "%32, %33, %34, %35, %36, %37, %38, %39, %40, %41, %42, %43, %44, %45, %46, %47, %48, %49, %50, %51, %52, %53, %54, %55, %56, %57, %58, %59, %60, %61, %62, %63, "
        "%64, %65, %66, %67, %68, %69, %70, %71, %72, %73, %74, %75, %76, %77, %78, %79, %80, %81, %82, %83, %84, %85, %86, %87, %88, %89, %90, %91, %92, %93, %94, %95, "
        "%96, %97, %98, %99, %100, %101, %102, %103, %104, %105, %106, %107, %108, %109, %110, %111, %112, %113, %114, %115, %116, %117, %118, %119, %120, %121, %122, %123, %124, %125, %126, %127}, {%128, %129, %130, %131}, %132, p, 1, 1, 1;\n}\n"
        : "+f"(d[0]), "+f"(d[1]), "+f"(d[2]), "+f"(d[3]), "+f"(d[4]), "+f"(d[5]), "+f"(d[6]), "+f"(d[7]),
          "+f"(d[8]), "+f"(d[9]), "+f"(d[10]), "+f"(d[11]), "+f"(d[12]), "+f"(d[13]), "+f"(d[14]), "+f"(d[15]),
          "+f"(d[16]), "+f"(d[17]), "+f"(d[18]), "+f"(d[19]), "+f"(d[20]), "+f"(d[21]), "+f"(d[22]), "+f"(d[23]),
          "+f"(d[24]), "+f"(d[25]), "+f"(d[26]), "+f"(d[27]), "+f"(d[28]), "+f"(d[29]), "+f"(d[30]), "+f"(d[31]),
          "+f"(d[32]), "+f"(d[33]), "+f"(d[34]), "+f"(d[35]), "+f"(d[36]), "+f"(d[37]), "+f"(d[38]), "+f"(d[39]),
          "+f"(d[40]), "+f"(d[41]), "+f"(d[42]), "+f"(d[43]), "+f"(d[44]), "+f"(d[45]), "+f"(d[46]), "+f"(d[47]),
          "+f"(d[48]), "+f"(d[49]), "+f"(d[50]), "+f"(d[51]), "+f"(d[52]), "+f"(d[53]), "+f"(d[54]), "+f"(d[55]),
          "+f"(d[56]), "+f"(d[57]), "+f"(d[58]), "+f"(d[59]), "+f"(d[60]), "+f"(d[61]), "+f"(d[62]), "+f"(d[63]),
          "+f"(d[64]), "+f"(d[65]), "+f"(d[66]), "+f"(d[67]), "+f"(d[68]), "+f"(d[69]), "+f"(d[70]), "+f"(d[71]),
          "+f"(d[72]), "+f"(d[73]), "+f"(d[74]), "+f"(d[75]), "+f"(d[76]), "+f"(d[77]), "+f"(d[78]), "+f"(d[79]),
          "+f"(d[80]), "+f"(d[81]), "+f"(d[82]), "+f"(d[83]), "+f"(d[84]), "+f"(d[85]), "+f"(d[86]), "+f"(d[87]),
          "+f"(d[88]), "+f"(d[89]), "+f"(d[90]), "+f"(d[91]), "+f"(d[92]), "+f"(d[93]), "+f"(d[94]), "+f"(d[95]),
          "+f"(d[96]), "+f"(d[97]), "+f"(d[98]), "+f"(d[99]), "+f"(d[100]), "+f"(d[101]), "+f"(d[102]), "+f"(d[103]),
          "+f"(d[104]), "+f"(d[105]), "+f"(d[106]), "+f"(d[107]), "+f"(d[108]), "+f"(d[109]), "+f"(d[110]), "+f"(d[111]),
          "+f"(d[112]), "+f"(d[113]), "+f"(d[114]), "+f"(d[115]), "+f"(d[116]), "+f"(d[117]), "+f"(d[118]), "+f"(d[119]),
          "+f"(d[120]), "+f"(d[121]), "+f"(d[122]), "+f"(d[123]), "+f"(d[124]), "+f"(d[125]), "+f"(d[126]), "+f"(d[127])
        : "r"(a0), "r"(a1), "r"(a2), "r"(a3), "l"(db), "r"(acc));
}
__device__ __forceinline__ void wgmma_ss_n256_tb(float (&d)[128], uint64_t da, uint64_t db) {
    asm volatile("wgmma.mma_async.sync.aligned.m64n256k16.f32.bf16.bf16 {"
        "%0, %1, %2, %3, %4, %5, %6, %7, %8, %9, %10, %11, %12, %13, %14, %15, %16, %17, %18, %19, %20, %21, %22, %23, %24, %25, %26, %27, %28, %29, %30, %31, "
        "%32, %33, %34, %35, %36, %37, %38, %39, %40, %41, %42, %43, %44, %45, %46, %47, %48, %49, %50, %51, %52, %53, %54, %55, %56, %57, %58, %59, %60, %61, %62, %63, "
        "%64, %65, %66, %67, %68, %69, %70, %71, %72, %73, %74, %75, %76, %77, %78, %79, %80, %81, %82, %83, %84, %85, %86, %87, %88, %89, %90, %91, %92, %93, %94, %95, "
        "%96, %97, %98, %99, %100, %101, %102, %103, %104, %105, %106, %107, %108, %109, %110, %111, %112, %113, %114, %115, %116, %117, %118, %119, %120, %121, %122, %123, %124, %125, %126, %127}, %128, %129, 1, 1, 1, 0, 1;\n"
        : "+f"(d[0]), "+f"(d[1]), "+f"(d[2]), "+f"(d[3]), "+f"(d[4]), "+f"(d[5]), "+f"(d[6]), "+f"(d[7]),
          "+f"(d[8]), "+f"(d[9]), "+f"(d[10]), "+f"(d[11]), "+f"(d[12]), "+f"(d[13]), "+f"(d[14]), "+f"(d[15]),
          "+f"(d[16]), "+f"(d[17]), "+f"(d[18]), "+f"(d[19]), "+f"(d[20]), "+f"(d[21]), "+f"(d[22]), "+f"(d[23]),
          "+f"(d[24]), "+f"(d[25]), "+f"(d[26]), "+f"(d[27]), "+f"(d[28]), "+f"(d[29]), "+f"(d[30]), "+f"(d[31]),
          "+f"(d[32]), "+f"(d[33]), "+f"(d[34]), "+f"(d[35]), "+f"(d[36]), "+f"(d[37]), "+f"(d[38]), "+f"(d[39]),
          "+f"(d[40]), "+f"(d[41]), "+f"(d[42]), "+f"(d[43]), "+f"(d[44]), "+f"(d[45]), "+f"(d[46]), "+f"(d[47]),
          "+f"(d[48]), "+f"(d[49]), "+f"(d[50]), "+f"(d[51]), "+f"(d[52]), "+f"(d[53]), "+f"(d[54]), "+f"(d[55]),
          "+f"(d[56]), "+f"(d[57]), "+f"(d[58]), "+f"(d[59]), "+f"(d[60]), "+f"(d[61]), "+f"(d[62]), "+f"(d[63]),
          "+f"(d[64]), "+f"(d[65]), "+f"(d[66]), "+f"(d[67]), "+f"(d[68]), "+f"(d[69]), "+f"(d[70]), "+f"(d[71]),
          "+f"(d[72]), "+f"(d[73]), "+f"(d[74]), "+f"(d[75]), "+f"(d[76]), "+f"(d[77]), "+f"(d[78]), "+f"(d[79]),
          "+f"(d[80]), "+f"(d[81]), "+f"(d[82]), "+f"(d[83]), "+f"(d[84]), "+f"(d[85]), "+f"(d[86]), "+f"(d[87]),
          "+f"(d[88]), "+f"(d[89]), "+f"(d[90]), "+f"(d[91]), "+f"(d[92]), "+f"(d[93]), "+f"(d[94]), "+f"(d[95]),
          "+f"(d[96]), "+f"(d[97]), "+f"(d[98]), "+f"(d[99]), "+f"(d[100]), "+f"(d[101]), "+f"(d[102]), "+f"(d[103]),
          "+f"(d[104]), "+f"(d[105]), "+f"(d[106]), "+f"(d[107]), "+f"(d[108]), "+f"(d[109]), "+f"(d[110]), "+f"(d[111]),
          "+f"(d[112]), "+f"(d[113]), "+f"(d[114]), "+f"(d[115]), "+f"(d[116]), "+f"(d[117]), "+f"(d[118]), "+f"(d[119]),
          "+f"(d[120]), "+f"(d[121]), "+f"(d[122]), "+f"(d[123]), "+f"(d[124]), "+f"(d[125]), "+f"(d[126]), "+f"(d[127])
        : "l"(da), "l"(db));
}
__device__ __forceinline__ void wgmma_ss_n256_tb_init(float (&d)[128], uint64_t da, uint64_t db) {
    asm volatile("wgmma.mma_async.sync.aligned.m64n256k16.f32.bf16.bf16 {"
        "%0, %1, %2, %3, %4, %5, %6, %7, %8, %9, %10, %11, %12, %13, %14, %15, %16, %17, %18, %19, %20, %21, %22, %23, %24, %25, %26, %27, %28, %29, %30, %31, "
        "%32, %33, %34, %35, %36, %37, %38, %39, %40, %41, %42, %43, %44, %45, %46, %47, %48, %49, %50, %51, %52, %53, %54, %55, %56, %57, %58, %59, %60, %61, %62, %63, "
        "%64, %65, %66, %67, %68, %69, %70, %71, %72, %73, %74, %75, %76, %77, %78, %79, %80, %81, %82, %83, %84, %85, %86, %87, %88, %89, %90, %91, %92, %93, %94, %95, "
        "%96, %97, %98, %99, %100, %101, %102, %103, %104, %105, %106, %107, %108, %109, %110, %111, %112, %113, %114, %115, %116, %117, %118, %119, %120, %121, %122, %123, %124, %125, %126, %127}, %128, %129, 0, 1, 1, 0, 1;\n"
        : "=f"(d[0]), "=f"(d[1]), "=f"(d[2]), "=f"(d[3]), "=f"(d[4]), "=f"(d[5]), "=f"(d[6]), "=f"(d[7]),
          "=f"(d[8]), "=f"(d[9]), "=f"(d[10]), "=f"(d[11]), "=f"(d[12]), "=f"(d[13]), "=f"(d[14]), "=f"(d[15]),
          "=f"(d[16]), "=f"(d[17]), "=f"(d[18]), "=f"(d[19]), "=f"(d[20]), "=f"(d[21]), "=f"(d[22]), "=f"(d[23]),
          "=f"(d[24]), "=f"(d[25]), "=f"(d[26]), "=f"(d[27]), "=f"(d[28]), "=f"(d[29]), "=f"(d[30]), "=f"(d[31]),
          "=f"(d[32]), "=f"(d[33]), "=f"(d[34]), "=f"(d[35]), "=f"(d[36]), "=f"(d[37]), "=f"(d[38]), "=f"(d[39]),
          "=f"(d[40]), "=f"(d[41]), "=f"(d[42]), "=f"(d[43]), "=f"(d[44]), "=f"(d[45]), "=f"(d[46]), "=f"(d[47]),
          "=f"(d[48]), "=f"(d[49]), "=f"(d[50]), "=f"(d[51]), "=f"(d[52]), "=f"(d[53]), "=f"(d[54]), "=f"(d[55]),
          "=f"(d[56]), "=f"(d[57]), "=f"(d[58]), "=f"(d[59]), "=f"(d[60]), "=f"(d[61]), "=f"(d[62]), "=f"(d[63]),
          "=f"(d[64]), "=f"(d[65]), "=f"(d[66]), "=f"(d[67]), "=f"(d[68]), "=f"(d[69]), "=f"(d[70]), "=f"(d[71]),
          "=f"(d[72]), "=f"(d[73]), "=f"(d[74]), "=f"(d[75]), "=f"(d[76]), "=f"(d[77]), "=f"(d[78]), "=f"(d[79]),
          "=f"(d[80]), "=f"(d[81]), "=f"(d[82]), "=f"(d[83]), "=f"(d[84]), "=f"(d[85]), "=f"(d[86]), "=f"(d[87]),
          "=f"(d[88]), "=f"(d[89]), "=f"(d[90]), "=f"(d[91]), "=f"(d[92]), "=f"(d[93]), "=f"(d[94]), "=f"(d[95]),
          "=f"(d[96]), "=f"(d[97]), "=f"(d[98]), "=f"(d[99]), "=f"(d[100]), "=f"(d[101]), "=f"(d[102]), "=f"(d[103]),
          "=f"(d[104]), "=f"(d[105]), "=f"(d[106]), "=f"(d[107]), "=f"(d[108]), "=f"(d[109]), "=f"(d[110]), "=f"(d[111]),
          "=f"(d[112]), "=f"(d[113]), "=f"(d[114]), "=f"(d[115]), "=f"(d[116]), "=f"(d[117]), "=f"(d[118]), "=f"(d[119]),
          "=f"(d[120]), "=f"(d[121]), "=f"(d[122]), "=f"(d[123]), "=f"(d[124]), "=f"(d[125]), "=f"(d[126]), "=f"(d[127])
        : "l"(da), "l"(db));
}
__device__ __forceinline__ void wgmma_ss_n256_tb_pred(float (&d)[128], uint64_t da, uint64_t db, int acc) {
    asm volatile("{\n.reg .pred p;\nsetp.ne.s32 p, %130, 0;\nwgmma.mma_async.sync.aligned.m64n256k16.f32.bf16.bf16 {"
        "%0, %1, %2, %3, %4, %5, %6, %7, %8, %9, %10, %11, %12, %13, %14, %15, %16, %17, %18, %19, %20, %21, %22, %23, %24, %25, %26, %27, %28, %29, %30, %31, "
        "%32, %33, %34, %35, %36, %37, %38, %39, %40, %41, %42, %43, %44, %45, %46, %47, %48, %49, %50, %51, %52, %53, %54, %55, %56, %57, %58, %59, %60, %61, %62, %63, "
        "%64, %65, %66, %67, %68, %69, %70, %71, %72, %73, %74, %75, %76, %77, %78, %79, %80, %81, %82, %83, %84, %85, %86, %87, %88, %89, %90, %91, %92, %93, %94, %95, "
        "%96, %97, %98, %99, %100, %101, %102, %103, %104, %105, %106, %107, %108, %109, %110, %111, %112, %113, %114, %115, %116, %117, %118, %119, %120, %121, %122, %123, %124, %125, %126, %127}, %128, %129, p, 1, 1, 0, 1;\n}\n"
        : "+f"(d[0]), "+f"(d[1]), "+f"(d[2]), "+f"(d[3]), "+f"(d[4]), "+f"(d[5]), "+f"(d[6]), "+f"(d[7]),
          "+f"(d[8]), "+f"(d[9]), "+f"(d[10]), "+f"(d[11]), "+f"(d[12]), "+f"(d[13]), "+f"(d[14]), "+f"(d[15]),
          "+f"(d[16]), "+f"(d[17]), "+f"(d[18]), "+f"(d[19]), "+f"(d[20]), "+f"(d[21]), "+f"(d[22]), "+f"(d[23]),
          "+f"(d[24]), "+f"(d[25]), "+f"(d[26]), "+f"(d[27]), "+f"(d[28]), "+f"(d[29]), "+f"(d[30]), "+f"(d[31]),
          "+f"(d[32]), "+f"(d[33]), "+f"(d[34]), "+f"(d[35]), "+f"(d[36]), "+f"(d[37]), "+f"(d[38]), "+f"(d[39]),
          "+f"(d[40]), "+f"(d[41]), "+f"(d[42]), "+f"(d[43]), "+f"(d[44]), "+f"(d[45]), "+f"(d[46]), "+f"(d[47]),
          "+f"(d[48]), "+f"(d[49]), "+f"(d[50]), "+f"(d[51]), "+f"(d[52]), "+f"(d[53]), "+f"(d[54]), "+f"(d[55]),
          "+f"(d[56]), "+f"(d[57]), "+f"(d[58]), "+f"(d[59]), "+f"(d[60]), "+f"(d[61]), "+f"(d[62]), "+f"(d[63]),
          "+f"(d[64]), "+f"(d[65]), "+f"(d[66]), "+f"(d[67]), "+f"(d[68]), "+f"(d[69]), "+f"(d[70]), "+f"(d[71]),
          "+f"(d[72]), "+f"(d[73]), "+f"(d[74]), "+f"(d[75]), "+f"(d[76]), "+f"(d[77]), "+f"(d[78]), "+f"(d[79]),
          "+f"(d[80]), "+f"(d[81]), "+f"(d[82]), "+f"(d[83]), "+f"(d[84]), "+f"(d[85]), "+f"(d[86]), "+f"(d[87]),
          "+f"(d[88]), "+f"(d[89]), "+f"(d[90]), "+f"(d[91]), "+f"(d[92]), "+f"(d[93]), "+f"(d[94]), "+f"(d[95]),
          "+f"(d[96]), "+f"(d[97]), "+f"(d[98]), "+f"(d[99]), "+f"(d[100]), "+f"(d[101]), "+f"(d[102]), "+f"(d[103]),
          "+f"(d[104]), "+f"(d[105]), "+f"(d[106]), "+f"(d[107]), "+f"(d[108]), "+f"(d[109]), "+f"(d[110]), "+f"(d[111]),
          "+f"(d[112]), "+f"(d[113]), "+f"(d[114]), "+f"(d[115]), "+f"(d[116]), "+f"(d[117]), "+f"(d[118]), "+f"(d[119]),
          "+f"(d[120]), "+f"(d[121]), "+f"(d[122]), "+f"(d[123]), "+f"(d[124]), "+f"(d[125]), "+f"(d[126]), "+f"(d[127])
        : "l"(da), "l"(db), "r"(acc));
}
__device__ __forceinline__ void wgmma_rs_n64_tb(float (&d)[32], uint32_t a0, uint32_t a1, uint32_t a2, uint32_t a3, uint64_t db) {
    asm volatile("wgmma.mma_async.sync.aligned.m64n64k16.f32.bf16.bf16 {"
        "%0, %1, %2, %3, %4, %5, %6, %7, %8, %9, %10, %11, %12, %13, %14, %15, %16, %17, %18, %19, %20, %21, %22, %23, %24, %25, %26, %27, %28, %29, %30, %31}, {%32, %33, %34, %35}, %36, 1, 1, 1, 1;\n"
        : "+f"(d[0]), "+f"(d[1]), "+f"(d[2]), "+f"(d[3]), "+f"(d[4]), "+f"(d[5]), "+f"(d[6]), "+f"(d[7]),
          "+f"(d[8]), "+f"(d[9]), "+f"(d[10]), "+f"(d[11]), "+f"(d[12]), "+f"(d[13]), "+f"(d[14]), "+f"(d[15]),
          "+f"(d[16]), "+f"(d[17]), "+f"(d[18]), "+f"(d[19]), "+f"(d[20]), "+f"(d[21]), "+f"(d[22]), "+f"(d[23]),
          "+f"(d[24]), "+f"(d[25]), "+f"(d[26]), "+f"(d[27]), "+f"(d[28]), "+f"(d[29]), "+f"(d[30]), "+f"(d[31])
        : "r"(a0), "r"(a1), "r"(a2), "r"(a3), "l"(db));
}
__device__ __forceinline__ void wgmma_rs_n64_tb_init(float (&d)[32], uint32_t a0, uint32_t a1, uint32_t a2, uint32_t a3, uint64_t db) {
    asm volatile("wgmma.mma_async.sync.aligned.m64n64k16.f32.bf16.bf16 {"
        "%0, %1, %2, %3, %4, %5, %6, %7, %8, %9, %10, %11, %12, %13, %14, %15, %16, %17, %18, %19, %20, %21, %22, %23, %24, %25, %26, %27, %28, %29, %30, %31}, {%32, %33, %34, %35}, %36, 0, 1, 1, 1;\n"
        : "=f"(d[0]), "=f"(d[1]), "=f"(d[2]), "=f"(d[3]), "=f"(d[4]), "=f"(d[5]), "=f"(d[6]), "=f"(d[7]),
          "=f"(d[8]), "=f"(d[9]), "=f"(d[10]), "=f"(d[11]), "=f"(d[12]), "=f"(d[13]), "=f"(d[14]), "=f"(d[15]),
          "=f"(d[16]), "=f"(d[17]), "=f"(d[18]), "=f"(d[19]), "=f"(d[20]), "=f"(d[21]), "=f"(d[22]), "=f"(d[23]),
          "=f"(d[24]), "=f"(d[25]), "=f"(d[26]), "=f"(d[27]), "=f"(d[28]), "=f"(d[29]), "=f"(d[30]), "=f"(d[31])
        : "r"(a0), "r"(a1), "r"(a2), "r"(a3), "l"(db));
}

__device__ __forceinline__ void wg_fence() { asm volatile("wgmma.fence.sync.aligned;\n" ::: "memory"); }
__device__ __forceinline__ void wg_commit() { asm volatile("wgmma.commit_group.sync.aligned;\n" ::: "memory"); }
template <int N> __device__ __forceinline__ void wg_wait() { asm volatile("wgmma.wait_group.sync.aligned %0;\n" ::"n"(N) : "memory"); }
template <int N> __device__ __forceinline__ void fence_regs(float (&a)[N]) {
#pragma unroll
    for (int i = 0; i < N; i++) asm volatile("" : "+f"(a[i])::"memory");
}
template <int N> __device__ __forceinline__ void fence_regs(uint32_t (&a)[N]) {
#pragma unroll
    for (int i = 0; i < N; i++) asm volatile("" : "+r"(a[i])::"memory");
}
__device__ __forceinline__ void mbar_init(uint32_t bar, uint32_t cnt) {
    asm volatile("mbarrier.init.shared::cta.b64 [%0], %1;\n" ::"r"(bar), "r"(cnt) : "memory");
}
__device__ __forceinline__ void mbar_expect_tx(uint32_t bar, uint32_t bytes) {
    asm volatile("mbarrier.arrive.expect_tx.shared::cta.b64 _, [%0], %1;\n" ::"r"(bar), "r"(bytes) : "memory");
}
__device__ __forceinline__ void mbar_wait(uint32_t bar, uint32_t parity) {
    asm volatile("{\n.reg .pred p;\nLW:\nmbarrier.try_wait.parity.shared::cta.b64 p, [%0], %1;\n@!p pmevent 0;\n@!p bra LW;\n}\n" ::"r"(bar), "r"(parity) : "memory");
}
__device__ __forceinline__ void mbar_wait_sleep(uint32_t bar, uint32_t parity) {
    asm volatile("{\n.reg .pred p;\nLW:\nmbarrier.try_wait.parity.shared::cta.b64 p, [%0], %1, 20000;\n@!p pmevent 0;\n@!p bra LW;\n}\n" ::"r"(bar), "r"(parity) : "memory");
}
__device__ __forceinline__ void mbar_wait_bounded(uint32_t bar, uint32_t parity) {
    asm volatile("{\n.reg .pred p;\n.reg .u32 c, d;\nmov.u32 c, %%globaltimer_lo;\nLW:\nmbarrier.try_wait.parity.shared::cta.b64 p, [%0], %1, 20000;\n@p bra LD;\n"
                 "mov.u32 d, %%globaltimer_lo;\nsub.u32 d, d, c;\nsetp.ge.u32 p, d, 4000000000;\n@p trap;\nbra LW;\nLD:\n}\n" ::"r"(bar), "r"(parity) : "memory");
}
__device__ __forceinline__ void flag_wait(const int* p, int v) {
    asm volatile("{\n.reg .pred p;\n.reg .s32 f;\nLW:\nld.acquire.gpu.global.s32 f, [%0];\nsub.s32 f, f, %1;\nsetp.lt.s32 p, f, 0;\n@p bra LW;\n}\n" ::"l"(p), "r"(v) : "memory");
}
__device__ __forceinline__ void flag_wait_bounded(const int* p, int v) {
    asm volatile("{\n.reg .pred p;\n.reg .u32 c;\n.reg .s32 f;\nmov.u32 c, 0;\nLW:\nld.acquire.gpu.global.s32 f, [%0];\nsub.s32 f, f, %1;\nsetp.ge.s32 p, f, 0;\n@p bra LD;\n"
                 "nanosleep.u32 500;\nadd.u32 c, c, 1;\nsetp.ge.u32 p, c, 4194304;\n@p trap;\nbra LW;\nLD:\n}\n" ::"l"(p), "r"(v) : "memory");
}
__device__ __forceinline__ int lane_now() {
    int l; asm volatile("mov.u32 %0, %%laneid;\n" : "=r"(l)); return l;
}
__device__ __forceinline__ bool elect() {
    uint32_t p; asm volatile("{\n.reg .pred p;\nelect.sync _|p, -1;\nselp.u32 %0, 1, 0, p;\n}\n" : "=r"(p)); return p;
}
__device__ __forceinline__ void bulk_g2s(uint32_t dst, const void* src, uint32_t bytes, uint32_t bar) {
    asm volatile("cp.async.bulk.shared::cluster.global.mbarrier::complete_tx::bytes [%0], [%1], %2, [%3];\n"
                 ::"r"(dst), "l"(src), "r"(bytes), "r"(bar) : "memory");
}
__device__ __forceinline__ void tma_g2s(uint32_t dst, const CUtensorMap* tm, int rowgroup, uint32_t bar) {
    asm volatile("cp.async.bulk.tensor.4d.shared::cluster.global.tile.mbarrier::complete_tx::bytes [%0], [%1, {0, 0, 0, %2}], [%3];\n"
                 ::"r"(dst), "l"(tm), "r"(rowgroup), "r"(bar) : "memory");
}
__device__ __forceinline__ void bar_sync(int id, int n) { asm volatile("bar.sync %0, %1;\n" ::"r"(id), "r"(n) : "memory"); }
__device__ __forceinline__ void bar_arrive(int id, int n) { asm volatile("bar.arrive %0, %1;\n" ::"r"(id), "r"(n) : "memory"); }
__device__ __forceinline__ float quad_last(float v) {
    float r; asm volatile("shfl.sync.idx.b32 %0, %1, 3, 0x1c1f, -1;\n" : "=f"(r) : "f"(v)); return r;
}
__device__ __forceinline__ float ex2(float x) { float y; asm("ex2.approx.ftz.f32 %0, %1;\n" : "=f"(y) : "f"(x)); return y; }
__device__ __forceinline__ uint32_t ex2_f16(uint32_t x) { uint32_t y; asm("ex2.approx.f16x2 %0, %1;\n" : "=r"(y) : "r"(x)); return y; }
__device__ __forceinline__ uint32_t hmax2_f16(uint32_t a, uint32_t b) { uint32_t r; asm("max.f16x2 %0, %1, %2;\n" : "=r"(r) : "r"(a), "r"(b)); return r; }
__device__ __forceinline__ uint32_t hmin2_f16(uint32_t a, uint32_t b) { uint32_t r; asm("min.f16x2 %0, %1, %2;\n" : "=r"(r) : "r"(a), "r"(b)); return r; }
__device__ __forceinline__ float lg2(float x) { float y; asm("lg2.approx.ftz.f32 %0, %1;\n" : "=f"(y) : "f"(x)); return y; }
__device__ __forceinline__ float rcp(float x) { float y; asm("rcp.approx.ftz.f32 %0, %1;\n" : "=f"(y) : "f"(x)); return y; }
__device__ __forceinline__ uint32_t pack_bf16(float lo, float hi) {
    uint32_t r; asm("cvt.rn.bf16x2.f32 %0, %1, %2;\n" : "=r"(r) : "f"(hi), "f"(lo)); return r;
}
__device__ __forceinline__ uint32_t pack_f16(float lo, float hi) {
    uint32_t r; asm("cvt.rn.f16x2.f32 %0, %1, %2;\n" : "=r"(r) : "f"(hi), "f"(lo)); return r;
}
__device__ __forceinline__ uint32_t pack_f16_sat(float lo, float hi) {
    uint32_t r; asm("cvt.rn.satfinite.f16x2.f32 %0, %1, %2;\n" : "=r"(r) : "f"(hi), "f"(lo)); return r;
}
__device__ __forceinline__ float f16_lo(uint32_t v) { float r; asm("cvt.f32.f16 %0, %1;\n" : "=f"(r) : "h"((unsigned short)v)); return r; }
__device__ __forceinline__ float f16_hi(uint32_t v) { return f16_lo(v >> 16); }
__device__ __forceinline__ float bf_lo(uint32_t v) { return __uint_as_float(v << 16); }
__device__ __forceinline__ float bf_hi(uint32_t v) { return __uint_as_float(v & 0xFFFF0000u); }
__device__ __forceinline__ float bf_round(float x) { return __uint_as_float(pack_bf16(0.f, x)); }
__device__ __forceinline__ void st_release(int* p, int v) {
    asm volatile("st.release.gpu.global.s32 [%0], %1;\n" ::"l"(p), "r"(v) : "memory");
}
__device__ __forceinline__ uint4 ldg_pinned(const uint4* p) {
    uint4 v; asm volatile("ld.global.nc.v4.u32 {%0, %1, %2, %3}, [%4];\n" : "=r"(v.x), "=r"(v.y), "=r"(v.z), "=r"(v.w) : "l"(p) : "memory"); return v;
}
__device__ __forceinline__ void stmatrix_x4(uint32_t addr, uint32_t r0, uint32_t r1, uint32_t r2, uint32_t r3) {
    asm volatile("stmatrix.sync.aligned.m8n8.x4.shared.b16 [%0], {%1, %2, %3, %4};\n" ::"r"(addr), "r"(r0), "r"(r1), "r"(r2), "r"(r3) : "memory");
}

__device__ __forceinline__ uint32_t tile_off(int r, int ch) {
    return (uint32_t)((r >> 3) * 4096 + (ch >> 3) * 1024 + (r & 7) * 128 + (((ch ^ r) & 7) << 4));
}
__device__ __forceinline__ int h_unit(int qt, int u) { return qt < 78 ? u * 78 + qt : 624; }
__device__ __forceinline__ int row_off(int r) { return 4096 + h_unit(r >> 7, (r >> 4) & 7) * 8192 + (r & 8) * 512 + (r & 7) * 144; }

__device__ __forceinline__ float4 lds128f(uint32_t a) {
    float4 v; asm volatile("ld.shared.v4.f32 {%0, %1, %2, %3}, [%4];\n" : "=f"(v.x), "=f"(v.y), "=f"(v.z), "=f"(v.w) : "r"(a) : "memory"); return v;
}
__device__ __forceinline__ uint64_t lds64(uint32_t a) { uint64_t v; asm volatile("ld.shared.u64 %0, [%1];\n" : "=l"(v) : "r"(a) : "memory"); return v; }
__device__ __forceinline__ uint4 lds128(uint32_t a) {
    uint4 v; asm volatile("ld.shared.v4.u32 {%0, %1, %2, %3}, [%4];\n" : "=r"(v.x), "=r"(v.y), "=r"(v.z), "=r"(v.w) : "r"(a) : "memory"); return v;
}
__device__ __forceinline__ void sts128(uint32_t a, uint32_t x, uint32_t y, uint32_t z, uint32_t w) {
    asm volatile("st.shared.v4.u32 [%0], {%1, %2, %3, %4};\n" ::"r"(a), "r"(x), "r"(y), "r"(z), "r"(w) : "memory");
}
__device__ __forceinline__ void mbar_arrive(uint32_t bar) {
    asm volatile("mbarrier.arrive.shared::cta.b64 _, [%0];\n" ::"r"(bar) : "memory");
}
__device__ __forceinline__ uint64_t mkaddr(uint32_t lo, uint32_t hi) { uint64_t a; asm("mov.b64 %0, {%1, %2};\n" : "=l"(a) : "r"(lo), "r"(hi)); return a; }
__device__ __forceinline__ void red_add(int* p) { asm volatile("red.relaxed.gpu.global.add.s32 [%0], 1;\n" ::"l"(p) : "memory"); }
__device__ __forceinline__ void red_release(int* p) {
    asm volatile("fence.proxy.async.global;\nfence.acq_rel.gpu;\nred.relaxed.gpu.global.add.s32 [%0], 1;\n" ::"l"(p) : "memory");
}
__device__ __forceinline__ void fence_async_global() { asm volatile("fence.proxy.async.global;\n" ::: "memory"); }
__device__ __forceinline__ void fence_async_smem() { asm volatile("fence.proxy.async.shared::cta;\n" ::: "memory"); }
__device__ __forceinline__ void bulk_s2g(void* dst, uint32_t src, uint32_t bytes) {
    asm volatile("cp.async.bulk.global.shared::cta.bulk_group [%0], [%1], %2;\ncp.async.bulk.commit_group;\n" ::"l"(dst), "r"(src), "r"(bytes) : "memory");
}
__device__ __forceinline__ void mma16816(float (&c)[4], uint32_t a0, uint32_t a1, uint32_t a2, uint32_t a3, uint32_t b0, uint32_t b1) {
    asm("mma.sync.aligned.m16n8k16.row.col.f32.bf16.bf16.f32 {%0, %1, %2, %3}, {%4, %5, %6, %7}, {%8, %9}, {%0, %1, %2, %3};\n"
        : "+f"(c[0]), "+f"(c[1]), "+f"(c[2]), "+f"(c[3]) : "r"(a0), "r"(a1), "r"(a2), "r"(a3), "r"(b0), "r"(b1));
}
__device__ __forceinline__ void mma1688(float (&c)[4], uint32_t a0, uint32_t a1, uint32_t b0) {
    asm("mma.sync.aligned.m16n8k8.row.col.f32.bf16.bf16.f32 {%0, %1, %2, %3}, {%4, %5}, {%6}, {%0, %1, %2, %3};\n"
        : "+f"(c[0]), "+f"(c[1]), "+f"(c[2]), "+f"(c[3]) : "r"(a0), "r"(a1), "r"(b0));
}
__device__ __forceinline__ uint32_t hadd2_f16(uint32_t a, uint32_t b) { uint32_t r; asm("add.rn.f16x2 %0, %1, %2;\n" : "=r"(r) : "r"(a), "r"(b)); return r; }
__device__ __forceinline__ uint32_t hadd2(uint32_t a, uint32_t b) { uint32_t r; asm("add.rn.bf16x2 %0, %1, %2;\n" : "=r"(r) : "r"(a), "r"(b)); return r; }
__device__ __forceinline__ uint32_t hmul2(uint32_t a, uint32_t b) { uint32_t r; asm("mul.rn.bf16x2 %0, %1, %2;\n" : "=r"(r) : "r"(a), "r"(b)); return r; }
__device__ __forceinline__ uint32_t hfma2(uint32_t a, uint32_t b, uint32_t c) { uint32_t r; asm("fma.rn.bf16x2 %0, %1, %2, %3;\n" : "=r"(r) : "r"(a), "r"(b), "r"(c)); return r; }

constexpr int SM_Q = 0;
constexpr int SM_KV = 65536;
constexpr int SM_ML = SM_KV + STAGES * KV_BYTES;
constexpr int SM_BAR = SM_ML + 1024;
constexpr int SM_TOTAL = SM_BAR + 256;
constexpr float SCALE_LOG2 = 1.4426950408889634f / 16.0f;
constexpr float KV_SCALE = 6.f;
constexpr float KV_OFF = 32.f + KVM / 32.f;
constexpr uint32_t KV_OFF2 = (0x5000u + KVM) * 0x10001u;
constexpr uint32_t KV_OFF8 = (0x5800u + KVM) * 0x10001u;
constexpr uint32_t NEG2 = 0x80008000u;
constexpr uint32_t S_LIMIT = 0x4B804B80u;
constexpr float REF_UP = REFUP, REF_SUM = REFSUM;
__device__ __forceinline__ uint32_t kvf(uint32_t a, uint32_t off) {
    uint32_t r; asm("fma.rn.f16x2 %0, %1, %2, %3;\n" : "=r"(r) : "r"(a), "r"(pack_f16(KV_SCALE, KV_SCALE)), "r"(off)); return r;
}
enum { BAR_PP0 = 1, BAR_PP1 = 2, BAR_WG0 = 3, BAR_WG1 = 4, BAR_H0 = 5, BAR_H1 = 6, BAR_AUX = 7, BAR_BF = 8, BAR_H2 = 9, BAR_X = 10, BAR_GO = 11, BAR_WG2 = 12, BAR_ST = 13 };

struct Hot {
    const __nv_bfloat16 *wk, *wq, *x;
    Scratch* s;
};
struct Params {
    const __nv_bfloat16* deg_inv;
    const int *src, *dst;
    __nv_bfloat16* out;
    uint32_t dhi;
    int E;
    CUtensorMap tm_out;
    CUtensorMap tm_outc;
    CUtensorMap tm_w[3];
};
#define SC_PAIR (blockIdx.x < 104)
#define SC_TAIL (blockIdx.x >= NCTA - 2)
#define SC_LAST (blockIdx.x == NCTA - 1)
#define SC_HELP (SC_PAIR && rank)
#define SC_OWNER (!SC_HELP && !SC_LAST)
#define SC_QT1 (26 + (int)(blockIdx.x >> 1))
#define SC_QT0 (SC_PAIR ? (rank ? (int)(blockIdx.x >> 2) : SC_QT1) : SC_TAIL ? 78 : (int)blockIdx.x - 104)
#define SC_NKV (SC_LAST ? 50 : 75)
#define SC_CLS (SC_PAIR ? (rank ? 0x120 ^ (blockIdx.x & 2) * 0x80 : 0x430) | (blockIdx.x & 2) >> 1 : SC_LAST ? 0x10 : 0x432)
#define SC_NW (SC_PAIR ? 8 : SC_LAST ? 0 : 4)
#define SC_ZB (2 * SC_QT1 + 1 - (int)rank)
#define SC_TZB(k) (rank && !(k) ? 156 : 2 * (k) - (int)rank)

__global__ void __cluster_dims__(2, 1, 1) __launch_bounds__(384, 1) k_main(const __grid_constant__ Hot H, const __grid_constant__ Params P) {
    extern __shared__ __align__(1024) uint8_t smem[];
    const uint32_t sb = (uint32_t)__cvta_generic_to_shared(smem);
    const int tid = threadIdx.x, wg = __shfl_sync(~0u, tid >> 7, 0);
    const int lane = tid & 31, g = lane >> 2, q = lane & 3;
    const uint32_t rank = blockIdx.x & 1;
    const uint32_t bar_full = sb + SM_BAR, bar_q = bar_full + 32, bar_go = bar_full + 48;
    const uint32_t bar_pin = bar_full + 56;
    const uint32_t bar_qfree = bar_full + 72, bar_pdone = bar_full + 88, bar_zst = bar_full + 104, bar_rfree = bar_full + 120;
    const uint32_t bar_empty = bar_full + 128, bar_end = bar_full + 160, s_tm = bar_full + 184, bar_x = bar_full + 192;
    const uint32_t bar_a = sb + SM_ML;

    const int t = tid & 127, warp = __shfl_sync(~0u, t >> 5, 0);
    int ep = 0;
    if (wg & 2) {
        unsigned done;
        {
            uint4 ra[2], rb[2], rk[5][2];
            if (blockIdx.x < 128) {
                const int e = (blockIdx.x >> 4) * 32 + (g >> 1) * 8 + (blockIdx.x & 8) / 2 + (g & 1);
                const uint4* pq = (const uint4*)(H.wq + e * 256) + warp * 8 + q;
                const uint4* pk = (const uint4*)(H.wk + ((blockIdx.x & 7) * 32 + g) * 256) + warp * 8 + q;
                const uint4* pz = (const uint4*)(H.wk + 255 * 256) + warp * 8 + q;
#pragma unroll
                for (int s = 0; s < 2; s++) {
                    ra[s] = ldg_pinned(pq + 4 * s);
                    rb[s] = ldg_pinned(pq + 4 * s + 64);
#pragma unroll
                    for (int n = 0; n < 4; n++) rk[n][s] = ldg_pinned(pk + 4 * s + n * 256);
                    rk[4][s] = ldg_pinned(pz + 4 * s);
                }
            }
            asm volatile("{\n.reg .pred p;\nsetp.eq.s32 p, %2, 0;\nmov.u32 %0, 0;\n@p ld.global.cg.u32 %0, [%1];\n}\n" : "=r"(done) : "l"(&g_sync[SY_DONE * 32]), "r"(lane) : "memory");
            bar_arrive(BAR_X, 384);
            if (warp == 0 && elect()) {
#pragma unroll
                for (int i = 0; i < 21; i++) mbar_init(bar_full + 8 * i, i < 9 ? 1 : i < 16 ? 4 : i == 20 ? 11 : SC_TAIL ? 4 : 8);
#pragma unroll
                for (int i = 0; i < 4; i++) mbar_init(bar_a + 8 * i, 1);
                mbar_expect_tx(bar_pin, QB_BYTES / 2 + 512); mbar_expect_tx(bar_pin + 8, QB_BYTES / 2);
                asm volatile("fence.mbarrier_init.release.cluster;\n" ::: "memory");
            }
            __syncwarp();
            asm volatile("barrier.cluster.arrive.relaxed.aligned;\n" ::: "memory");
            if (blockIdx.x < 128) {
                float c[5][4] = {};
#pragma unroll
                for (int s = 0; s < 2; s++) {
#pragma unroll
                    for (int n = 0; n < 5; n++) mma16816(c[n], ra[s].x, rb[s].x, ra[s].y, rb[s].y, rk[n][s].x, rk[n][s].y);
#pragma unroll
                    for (int n = 0; n < 5; n++) mma16816(c[n], ra[s].z, rb[s].z, ra[s].w, rb[s].w, rk[n][s].z, rk[n][s].w);
                }
#pragma unroll
                for (int i = 0; i < 4; i++) {
                    const int r = i & 2, n = (i & 1) * 2;
                    sts128(sb + SM_KV + 3 * KV_BYTES + QB_BYTES + i * 2048 + t * 16, __float_as_uint(c[n][r] - c[4][r]), __float_as_uint(c[n][r + 1] - c[4][r]),
                           __float_as_uint(c[n + 1][r] - c[4][r]), __float_as_uint(c[n + 1][r + 1] - c[4][r]));
                }
            }
        }
        asm volatile("setmaxnreg.dec.sync.aligned.u32 %0;\n" ::"n"(REG_P));
        if (blockIdx.x < 128) {
            bar_sync(BAR_WG2, 128);
            float4 v[4];
#pragma unroll
            for (int i = 0; i < 4; i++) v[i] = lds128f(sb + SM_KV + 3 * KV_BYTES + QB_BYTES + (warp & 2) * 2048 + (lane & 1) * 2048 + i * 512 + ((warp & 1) * 16 + (lane >> 1)) * 16);
            constexpr float SC = SCALE_LOG2 / KV_SCALE;
            const int r = (warp & 1) * 4 + (lane >> 3);
            *(uint2*)(g_w + tile_off((blockIdx.x >> 3) * 16 + (warp & 2) * 4 + r, (blockIdx.x & 7) * 4 + ((lane >> 1) & 3)) + (lane & 1) * 8) =
                make_uint2(pack_f16_sat(((v[0].x + v[1].x) + (v[2].x + v[3].x)) * SC, ((v[0].y + v[1].y) + (v[2].y + v[3].y)) * SC) | 1,
                           pack_f16_sat(((v[0].z + v[1].z) + (v[2].z + v[3].z)) * SC, ((v[0].w + v[1].w) + (v[2].w + v[3].w)) * SC) | 1);
            if (warp != 1) {
                bar_arrive(BAR_AUX, 128);
            } else {
                bar_sync(BAR_AUX, 128);
                if (elect()) { red_add(&g_sync[SY_DONE * 32 + 4 + (blockIdx.x >> 5)]); }
                __syncwarp();
            }
        } else {
            bar_sync(BAR_WG2, 128);
        }
        if (warp == 1) bar_arrive(BAR_GO, 160);
        auto load_a = [&](int j) {
            if (elect()) {
                mbar_expect_tx(bar_a + 8 * j, QB_BYTES);
                bulk_g2s(sb + SM_KV + j * KV_BYTES, g_w + j * QB_BYTES, QB_BYTES, bar_a + 8 * j);
            }
            __syncwarp();
        };
        if (warp == 0) {
            auto poll = [&]() { int c; asm volatile("ld.relaxed.gpu.global.s32 %0, [%1];\n" : "=r"(c) : "l"(&g_sync[SY_DONE * 32 + 4 + (lane & 3)]) : "memory"); return c; };
#pragma unroll 1
            for (int j = 0; j < 4;) {
#pragma unroll 1
                for (const uint32_t mk = __ballot_sync(~0u, poll() >= 32) & 15; (mk >> j) & 1; j++) load_a(j);
            }
        } else if (warp & 1) {
#pragma unroll 1
            for (int j = 0, n = 0; j < 4;) {
                mbar_wait_bounded(bar_a + 8 * j, n & 1);
                uint32_t ok = 1;
#pragma unroll
                for (int i = 0; i < 16; i++) {
                    uint32_t v;
                    asm volatile("ld.shared.u32 %0, [%1];\n" : "=r"(v) : "r"(sb + SM_KV + j * KV_BYTES + (warp & 2) * 8192 + i * 1024 + lane * 32 + g * 4) : "memory");
                    ok &= v;
                }
                asm volatile("{\n.reg .pred p;\nsetp.ne.u32 p, %0, 0;\nbar.red.and.pred p, %1, 64, p;\nselp.u32 %0, 1, 0, p;\n}\n" : "+r"(ok) : "n"((int)BAR_WG2) : "memory");
                if (__any_sync(~0u, ok)) {
                    if (warp == 1 && elect()) asm volatile("mbarrier.arrive.shared::cta.b64 _, [%0];\nmbarrier.inval.shared::cta.b64 [%1];\n" ::"r"(bar_full + 8 * j), "r"(bar_a + 8 * j) : "memory");
                    __syncwarp();
                    j++; n = 0;
                } else {
                    asm volatile("{\n.reg .pred p;\nsetp.gt.s32 p, %0, 1000000;\n@p trap;\n}\n" ::"r"(++n) : "memory");
                    fence_async_smem();
                    if (warp == 1) load_a(j);
                }
            }
        }
        done = __shfl_sync(~0u, done, 0);
        ep = (int)(done / NCTA) + 1;
        asm volatile("barrier.cluster.wait.acquire.aligned;\n" ::: "memory");
        if (warp == 0) {
            asm volatile("st.shared.u64 [%0], %1;\n" ::"r"(s_tm), "l"(&P.tm_outc) : "memory");
            __syncwarp();
            if (elect()) {
                const uint8_t* base = (const uint8_t*)H.s;
                uint32_t cls = SC_CLS, bytes = KV_BYTES, step = 5 * KV_BYTES;
                const uint8_t* src = base;
                bool tick;
                int next = 0;
                const int nit = SC_NKV + SC_NW;
#pragma unroll 1
                for (int j = 0; j < nit; j++) {
                    const uint32_t slot = sb + SM_KV + (j & 3) * KV_BYTES, fb = bar_full + 8 * (j & 3);
                    if (j == next) {
                        const int k = j - SC_NKV;
                        const int sw = SC_HELP ? j - 25 : -1;
                        next = j + 1;
                        tick = j >= 3 && k < 0 && (unsigned)sw >= 4 && !SC_TAIL;
                        if (j >= 3 && (unsigned)sw >= 5) next = k >= 0 ? next : j < GO0 ? GO0 : j < 25 ? 25 : j < GO1 ? GO1 : j < 49 ? 49 : j < 50 ? 50 : 75;
                        if (j == 0 || j == 25 || j == 50) { src = base + (4096 + (cls & 15) * KV_BYTES); cls >>= 4; }
                        if (SC_TAIL ? j == nit - 1 : j == GO0 || j == GO1) mbar_arrive(bar_go);
                        int fo = -1, fv = 1;
                        if (j < 3) { fo = (SY_H0 + 5 * j + (SC_CLS & 15)) * 32; fv = 5; }
                        if (j == 3) { fo = SY_H1 * 32; fv = 79; }
                        if (sw == 1) fo = 25 * 32 + SC_QT1;
                        if (k == 0) fo = SY_B * 32;
                        if (k == 1 && !SC_PAIR) { fo = SY_AUX0 * 32; fv = NAUX; }
                        if (k == 2 && SC_PAIR) { fo = SY_AUX * 32; fv = NAUX / 3; }
                        if (fo >= 0) {
                            flag_wait(g_sync + fo, fv * ep);
                            fence_async_global();
                        }
                        if (sw == 2 || (k == 2 && !SC_TAIL)) {
                            uint32_t qs = sw == 2 ? offsetof(Scratch, q) + (2 * SC_QT1 + 1) * QB_BYTES : SC_PAIR ? offsetof(Scratch, agg) + SC_ZB * QB_BYTES : offsetof(Scratch, part) + SC_QT0 * (4 * PART_BYTES);
#pragma unroll 1
                            for (int w = 0; w < (k == 2 && SC_PAIR ? 1 : 2); w++) {
                                mbar_wait_sleep(bar_qfree + 8 * w, k == 2 && SC_HELP);
                                mbar_expect_tx(bar_q + 8 * w, SC_PAIR ? QB_BYTES : PART_BYTES);
                                if (!SC_PAIR) bulk_g2s(sb + SM_ML + w * 512, base + (qs + (w ? -512 : QB_BYTES)), 512, bar_q + 8 * w);
                                bulk_g2s(sb + SM_Q + w * QB_BYTES, base + qs, QB_BYTES, bar_q + 8 * w);
                                qs += sw == 2 ? -QB_BYTES : PART_BYTES + 512;
                            }
                        }
                        if ((sw | 1) == 3) {
                            mbar_wait_sleep(bar_pdone + 8 * (sw - 2), 0);
                            bulk_s2g(g_part + (blockIdx.x - 3 + sw) * PART_BYTES, slot, PART_BYTES);
                            asm volatile("cp.async.bulk.wait_group.read 0;\n" ::: "memory");
                        }
                        if (sw == 5) {
                            asm volatile("cp.async.bulk.wait_group 0;\n" ::: "memory");
                            red_release(&g_sync[SY_PART * 32]);
                        }
                        if (k == 0) {
                            asm volatile("prefetch.tensormap [%0];\n" ::"l"(&P.tm_outc) : "memory");
                            src = g_w + (12 - SC_NW) * QB_BYTES; bytes = step = QB_BYTES;
                        }
                        if (k == 2) next = SC_TAIL ? nit - 1 : nit;
                    }
                    mbar_wait_sleep(fb + (bar_empty - bar_full), (j >> 2) & 1);
                    mbar_expect_tx(fb, bytes);
                    if (tick)
                        asm volatile("{\n.reg .pred p;\n.reg .u32 a, b, c;\nmov.u32 c, 1;\nmov.u32 a, %%globaltimer_lo;\nnot.b32 b, a;\nand.b32 b, b, %0;\nshr.u32 b, b, 1;\nnanosleep.u32 b;\n"
                                     "L:\nmov.u32 b, %%globaltimer_lo;\nlop3.b32 b, b, a, c, 0xBE;\nadd.u32 c, c, %2;\nsetp.le.u32 p, b, %0;\n@p nanosleep.u32 %1;\n@p bra L;\n}\n" ::"n"(TICK - 1), "n"(30), "n"(TICK / 32) : "memory");
                    bulk_g2s(slot, src, bytes, fb);
                    src += step;
                }
            }
        } else {
            if (warp == 2 && SC_OWNER) {
                uint8_t* dst = g_hz + 4096 + h_unit(SC_QT0, 0) * 8192;
                auto send = [&](int u0, int u1) {
#pragma unroll
                    for (int u = u0; u < u1; u++) {
                        bulk_s2g(dst + u * (78 * 8192), sb + SM_Q + u * 8192, 8192);
                        asm volatile("cp.async.bulk.wait_group 0;\n" ::: "memory");
                    }
                };
                int* f0 = &g_sync[(SY_H0 + SC_QT0 / 5) * 32];
                bar_sync(BAR_H0, 64);
                if (elect()) {
                    send(0, 1);
                    if (SC_QT0 < 65) red_release(f0);
                }
                bar_sync(BAR_H1, 160);
                if (elect()) {
                    if (!SC_TAIL) send(1, 4);
                    mbar_arrive(bar_q);
                }
                bar_sync(BAR_H2, 160);
                if (elect()) {
                    if (!SC_TAIL) { send(4, 8); mbar_arrive(bar_q + 8); }
                    red_release(&g_sync[SY_H1 * 32]);
                }
                __syncwarp();
            }
        }
    } else {
        const uint32_t sq = sb + SM_Q + wg * QB_BYTES;
        const uint32_t qbar = bar_q + 8 * wg;
        const uint32_t dq0 = __shfl_sync(~0u, ((sq & 0x3FFFF) >> 4) | (64u << 16), 0);
        const uint32_t dk0 = __shfl_sync(~0u, (((sb + SM_KV) & 0x3FFFF) >> 4) | (64u << 16), 0);
        float o[128];
        int it = 4;
        const uint32_t dhi = P.dhi;
        auto release = [&](int st, int n = 1) {
            if (n == 1) asm volatile("{\n.reg .pred p;\nelect.sync _|p, -1;\n@p mbarrier.arrive.shared::cta.b64 _, [%0];\n}\n" ::"r"(bar_empty + 8 * st) : "memory");
            else asm volatile("{\n.reg .pred p;\nelect.sync _|p, -1;\n@p mbarrier.arrive.shared::cta.b64 _, [%0], 2;\n}\n" ::"r"(bar_empty + 8 * st) : "memory");
        };
        const bool active = !(SC_TAIL && wg == 1);
        auto pp_sync = [&]() { if (!SC_TAIL) bar_sync(BAR_PP0 + wg, 256); };
        auto pp_arrive = [&]() { if (!SC_TAIL) bar_arrive(BAR_PP1 - wg, 256); };
        auto warp_arrive = [&](uint32_t bar) {
            __syncwarp();
            asm volatile("{\n.reg .pred p;\nelect.sync _|p, -1;\n@p mbarrier.arrive.shared::cta.b64 _, [%0];\n}\n" ::"r"(bar + 8 * wg) : "memory");
        };
        auto peer_arrive = [&]() {
            asm volatile("{\n.reg .pred p;\n.reg .b32 a;\nelect.sync _|p, -1;\nmapa.shared::cluster.u32 a, %0, %1;\n"
                         "@p mbarrier.arrive.shared::cluster.b64 _, [a];\n}\n" ::"r"(bar_rfree), "r"(rank ^ 1) : "memory");
        };
        auto cut = [&]() { asm volatile("{\n.reg .pred p;\nsetp.lt.s32 p, %0, 0;\nL:\n@p pmevent 0;\n@p bra L;\n}\n" ::"r"(dhi) : "memory"); };
        float qs = 1.f;
        uint32_t qr[4 * NQR];
        auto stage_q = [&]() {
            int k = dhi & 1;
            uint32_t big;
#pragma unroll 1
            do {
                if (k) {
                    qs *= 16.f;
#pragma unroll
                    for (int i = 0; i < 128; i++) o[i] *= 0.0625f;
                }
                big = 0;
                auto pk = [&](int i) { return QRND(pack_f16_sat(o[i], o[i + 1])); };
#pragma unroll
                for (int i = 0; i < 16; i++) {
                    if (QREG(i) >= 0) continue;
                    const uint32_t v0 = pk(8 * i), v1 = pk(8 * i + 2), v2 = pk(8 * i + 4) | (i == 15 ? k : 0), v3 = pk(8 * i + 6);
                    stmatrix_x4(sq + warp * 8192 + tile_off(lane & 15, 2 * i + (lane >> 4)), v0, v1, v2, v3);
                    big |= v0 | v1; big |= v2 | v3;
                    if (i == 15) cut();
                }
#pragma unroll
                for (int i = 0; i < 64; i++)
                    if (const int r = QREG(i / 4); r >= 0) big |= qr[4 * r + (i & 3)] = pk(2 * i);
                k++;
            } while (__any_sync(~0u, (big & 0x40004000u) && k < 8));
        };
        uint32_t s[20];
        auto issue_qk = [&](int st, int sh = 24) {
            const uint64_t kb = mkaddr(dk0 + st * (KV_BYTES >> 4), dhi);
            const uint64_t qd = mkaddr(dq0 + ((uint32_t)it >> sh), dhi);
            wgmma_ss_n80_init(s, qd, kb);
#pragma unroll
            for (int j = 1; j < 16; j++) {
                const int kk = j == 8 ? 15 : j < 8 ? j : j - 1;
                const int r = QREG(kk);
                if (r >= 0) wgmma_rs_n80(s, qr[4 * r], qr[4 * r + 1], qr[4 * r + 2], qr[4 * r + 3], kb + ((kk >> 2) * 64 + (kk & 3) * 2));
                else wgmma_ss_n80(s, qd + ((kk >> 2) * 64 + (kk & 3) * 2), kb + ((kk >> 2) * 64 + (kk & 3) * 2));
            }
            wg_commit();
        };

        {
            const int rb = (2 * SC_QT0 + wg) * 64 + warp * 16;
            const uint32_t xbar = bar_x + 32 * wg + 8 * warp;
            if (elect()) {
                mbar_init(xbar, 1);
                asm volatile("fence.mbarrier_init.release.cluster;\nfence.proxy.async.shared::cta;\n" ::: "memory");
                mbar_expect_tx(xbar, rb < NN ? 8192 : 0);
            }
            asm volatile("barrier.cluster.arrive.relaxed.aligned;\n" ::: "memory");
            if (wg == 1) pp_arrive();
            bar_sync(BAR_X, 384);
            if (wg == 1) bar_sync(BAR_GO, 160);
            if (rb < NN && elect()) bulk_g2s(sq + warp * 8192, H.x + (size_t)rb * 256, 8192, xbar);
            if (rb >= NN) {
#pragma unroll 1
                for (int i = 0; i < 16; i++) sts128(sq + warp * 8192 + i * 512 + lane * 16, 0, 0, 0, 0);
            }
            __syncwarp();
            mbar_wait(xbar, 0);
            uint4 xa[8], xb[8];
#pragma unroll
            for (int s = 0; s < 8; s++) {
                xa[s] = lds128(sq + (warp * 16 + g) * 512 + (4 * s + q) * 16);
                xb[s] = lds128(sq + (warp * 16 + g + 8) * 512 + (4 * s + q) * 16);
            }
            float sm[2][4], sq2[2][4][4];
#pragma unroll
            for (int i = 0; i < 4; i++) {
                sm[0][i] = sm[1][i] = 0.f;
#pragma unroll
                for (int k = 0; k < 4; k++) sq2[0][k][i] = sq2[1][k][i] = 0.f;
            }
#pragma unroll
            for (int s = 0; s < 8; s++) {
#pragma unroll
                for (int hh = 0; hh < 2; hh++) {
                    const uint4 v = hh ? xb[s] : xa[s];
                    mma16816(sm[hh], v.x, v.y, v.z, v.w, 0x3F803F80u, 0x3F803F80u);
                    mma1688(sq2[hh][0], v.x, v.y, v.x); mma1688(sq2[hh][1], v.x, v.y, v.y);
                    mma1688(sq2[hh][2], v.z, v.w, v.z); mma1688(sq2[hh][3], v.z, v.w, v.w);
                }
            }
            float inv[2], off[2];
#pragma unroll
            for (int hh = 0; hh < 2; hh++) {
                const float mean = (sm[hh][0] + sm[hh][2]) * (1.f / 256.f);
                const float d0 = (sq2[hh][0][0] + sq2[hh][2][0]) + (sq2[hh][1][2] + sq2[hh][3][2]);
                const float d1 = (sq2[hh][0][1] + sq2[hh][2][1]) + (sq2[hh][1][3] + sq2[hh][3][3]);
                const float ss = __shfl_sync(~0u, (g & 1) ? d1 : d0, g * 4 + (g >> 1));
                const float var = fmaxf(ss * (1.f / 256.f) - mean * mean, 0.f);
                float sd;
                asm("sqrt.approx.ftz.f32 %0, %1;\n" : "=f"(sd) : "f"(bf_round(bf_round(var) + 1e-5f)));
                asm("rcp.approx.ftz.f32 %0, %1;\n" : "=f"(inv[hh]) : "f"(bf_round(sd)));
                off[hh] = -mean * inv[hh];
            }
            uint32_t a[64];
#pragma unroll
            for (int s = 0; s < 8; s++) {
                a[8 * s] = xa[s].x; a[8 * s + 1] = xb[s].x; a[8 * s + 2] = xa[s].y; a[8 * s + 3] = xb[s].y;
                a[8 * s + 4] = xa[s].z; a[8 * s + 5] = xb[s].z; a[8 * s + 6] = xa[s].w; a[8 * s + 7] = xb[s].w;
            }
            fence_regs(a);
            if (wg == 1 && __any_sync(~0u, inv[0] + inv[1] != -1.f)) bar_arrive(BAR_ST, 256);
            asm volatile("setmaxnreg.inc.sync.aligned.u32 %0;\n" ::"n"(REG_C));
            fence_regs(a);
#pragma unroll
            for (int i = 0; i < 64; i++)
                a[i] = pack_f16(fmaf(bf_lo(a[i]), inv[i & 1], off[i & 1]), fmaf(bf_hi(a[i]), inv[i & 1], off[i & 1]));
            if (SC_OWNER) {
                const uint32_t ko = (q & 2) ? KV_OFF2 : KV_OFF2 | NEG2;
#pragma unroll
                for (int i = 0; i < 16; i++) {
                    const uint32_t mk = (i == 15 && q == 3) ? 0xFFFFu : ~0u;
                    stmatrix_x4(sq + warp * 8192 + tile_off(lane & 15, 2 * i + (lane >> 4)), kvf(a[4 * i], ko), kvf(a[4 * i + 1], ko),
                                kvf(a[4 * i + 2] & mk, ko), kvf(a[4 * i + 3] & mk, ko));
                }
                fence_async_smem();
                if (tid < 32) bar_arrive(BAR_H0, 64);
                bar_arrive(wg ? BAR_H2 : BAR_H1, 160);
            }
            asm volatile("barrier.cluster.wait.acquire.aligned;\n" ::: "memory");
            if (wg == 0) bar_sync(BAR_ST, 256);
            if (active) {
                fence_regs(a);
#pragma unroll
                for (int c = 0; c < 4; c++) {
                    if (c == 1) {
                        if (wg == 1) {
                            wg_wait<0>();
                            release(0);
                        }
                        pp_sync();
                    }
                    mbar_wait(bar_full + 8 * c, 0);
                    const uint64_t wb = mkaddr(dk0 + c * (KV_BYTES >> 4), dhi);
                    wg_fence();
#pragma unroll
                    for (int kk = 0; kk < 4; kk++) {
                        if (c | kk) wgmma_rs_n256_tb(o, a[16 * c + 4 * kk], a[16 * c + 4 * kk + 1], a[16 * c + 4 * kk + 2], a[16 * c + 4 * kk + 3], wb + kk * 512);
                        else wgmma_rs_n256_tb_init(o, a[0], a[1], a[2], a[3], wb);
                    }
                    wg_commit();
                    if (c > 0) { wg_wait<1>(); if (c > 1 || wg == 0) release(c - 1); }
                }
                if (wg == 0) pp_arrive();
                wg_wait<0>();
                fence_regs(o);
                release(3);
                if (SC_OWNER) mbar_wait(qbar, 0);
                stage_q();
                fence_async_smem();
                bar_sync(BAR_WG0 + wg, 128);
                mbar_wait(bar_full, 1);
                fence_regs(qr);
                wg_fence();
                issue_qk(0);
                if (wg == 1) pp_arrive();
                if (SC_PAIR && !rank) {
#pragma unroll
                    for (int i = 0; i < 16; i++)
                        if (const int r = QREG(i); r >= 0)
                            stmatrix_x4(sq + warp * 8192 + tile_off(lane & 15, 2 * i + (lane >> 4)), qr[4 * r], qr[4 * r + 1], qr[4 * r + 2], qr[4 * r + 3]);
                }
            } else {
                peer_arrive();
            }
        }

        uint32_t p[20];
        float m0 = 0.f, m1 = 0.f, e0, e1, l0 = 0.f, l1 = 0.f;
        uint32_t plim;
        uint32_t qphase = (SC_OWNER && active) ? 1 : 0;
        auto issue_pv = [&](int st, int acc) {
            const uint64_t vb = mkaddr(dk0 + st * (KV_BYTES >> 4), dhi);
            wgmma_rs_n256_tb_pred(o, p[0], p[1], p[2], p[3], vb, acc);
#pragma unroll
            for (int kk = 1; kk < 5; kk++)
                wgmma_rs_n256_tb(o, p[4 * kk], p[4 * kk + 1], p[4 * kk + 2], p[4 * kk + 3], vb + kk * 512);
            wg_commit();
        };
        auto mq_addr = [&](int ln) { return sq + warp * 8192 + tile_off(ln >> 2, 31) + 12; };
        auto exceeds = [&](const uint32_t (&p)[20]) {
            uint32_t a = __vimax3_s16x2(S_LIMIT, p[0], p[1]), b = __vimax3_s16x2(p[2], p[3], p[4]);
#pragma unroll
            for (int i = 5; i < 17; i += 4) { a = __vimax3_s16x2(a, p[i], p[i + 1]); b = __vimax3_s16x2(b, p[i + 2], p[i + 3]); }
            a = __vimax3_s16x2(a, p[17], p[18]);
            return __any_sync(~0u, __vimax3_s16x2(a, b, p[19]) != plim);
        };
        auto store_ref = [&](int ln, uint32_t u, bool on) {
            asm volatile("{\n.reg .pred p;\nsetp.ne.s32 p, %3, 0;\n@p st.shared.u16 [%0], %1;\n@p st.shared.u16 [%0 + 4096], %2;\n}\n"
                         ::"r"(mq_addr(ln) + 2), "h"((unsigned short)u), "h"((unsigned short)(u >> 16)), "r"((int)(on && (ln & 3) == 0)) : "memory");
        };
        auto remax = [&](float& a, float& b, bool store) {
            const int ln = lane_now();
            asm volatile("" : "+f"(qs));
            uint32_t ha = s[0], hb = s[1];
#pragma unroll
            for (int i = 1; i < 10; i++) { ha = hmax2_f16(ha, s[2 * i]); hb = hmax2_f16(hb, s[2 * i + 1]); }
            ha = hmax2_f16(__byte_perm(ha, hb, 0x5410), __byte_perm(ha, hb, 0x7632));
            ha = hmax2_f16(ha, __shfl_xor_sync(~0u, ha, 1));
            ha = hmax2_f16(ha, __shfl_xor_sync(~0u, ha, 2));
            a = fmaxf(a, f16_lo(ha) * qs - e0 + REF_UP); b = fmaxf(b, f16_hi(ha) * qs - e1 + REF_UP);
            const float qi = __uint_as_float(0x7F000000u - __float_as_uint(qs)) * (-1.f / KV_OFF);
            const uint32_t u = pack_f16((m0 + a) * qi, (m1 + b) * qi);
            const float g0 = (m0 + a) + KV_OFF * qs * f16_lo(u), g1 = (m1 + b) + KV_OFF * qs * f16_hi(u);
            const bool x0 = fabsf(g0) <= 1.f, x1 = fabsf(g1) <= 1.f;
            if (x0) a -= g0;
            if (x1) b -= g1;
            const float da = a + e0, db = b + e1;
            m0 += a; m1 += b;
            e0 = x0 ? 0.f : g0; e1 = x1 ? 0.f : g1;
            plim = (x0 && x1 && qs == 1.f) ? S_LIMIT : 0u;
            store_ref(ln, u, store);
#pragma unroll
            for (int i = 0; i < 10; i++) {
                p[2 * i] = pack_f16(ex2(fmaf(f16_lo(s[2 * i]), qs, -da)), ex2(fmaf(f16_hi(s[2 * i]), qs, -da)));
                p[2 * i + 1] = pack_f16(ex2(fmaf(f16_lo(s[2 * i + 1]), qs, -db)), ex2(fmaf(f16_hi(s[2 * i + 1]), qs, -db)));
            }
            fence_regs(p);
            fence_async_smem();
            __syncwarp();
        };

        auto row_sums = [&](float& z0, float& z1, int q) {
            z0 = quad_last(o[125]); z1 = quad_last(o[127]);
            l0 = z0 * (KV_SCALE / KV_OFF); l1 = z1 * (KV_SCALE / KV_OFF);
            if (!(q & 2)) { z0 = -z0; z1 = -z1; }
        };
        auto stats = [&](int q) { return (q & 2) ? ((q & 1) ? l1 : m1) : ((q & 1) ? l0 : m0); };
        constexpr int IL = 4 + LIFT;
        const int nseg = SC_HELP ? 2 : 1;
        if (active) {
#pragma unroll 1
            for (int seg = 0;; seg++) {
                wg_wait<0>();
                fence_regs(s);
                e0 = e1 = 0.f;
                const int it0 = it, itl = __shfl_sync(~0u, seg + 1 < nseg ? 3 + 25 : 3 + SC_NKV, 0);
                const int itx = (wg == 1 && seg + 1 == nseg) ? itl : -1;
                bool redo = true, have = !seg;
#pragma unroll 1
                for (;;) {
                    if (!have) {
#pragma unroll
                        for (int i = 0; i < 20; i++) p[i] = ex2_f16(s[i]);
                        redo = exceeds(s);
                    }
                    if (redo || (it | 1) == IL + 1) {
                        static_assert(IL % 2 == 0, "");
                        if (redo || it == IL + 1) {
                            float d0 = it != it0 ? 0.f : -INFINITY, d1 = d0;
                            if (redo) remax(d0, d1, it != itl);
                            if (it != it0) {
                                const float a0 = ex2(-d0 - (it == IL + 1 ? l0 : 0.f)), a1 = ex2(-d1 - (it == IL + 1 ? l1 : 0.f));
#pragma unroll
                                for (int i = 0; i < 32; i++) { o[4 * i] *= a0; o[4 * i + 1] *= a0; o[4 * i + 2] *= a1; o[4 * i + 3] *= a1; }
                            }
                        }
                        if (it == IL) {
                            const int ln = lane_now();
                            uint32_t ha = s[0], hb = s[1], la = ha, lb = hb;
#pragma unroll
                            for (int i = 1; i < 10; i++) {
                                ha = hmax2_f16(ha, s[2 * i]); hb = hmax2_f16(hb, s[2 * i + 1]); la = hmin2_f16(la, s[2 * i]); lb = hmin2_f16(lb, s[2 * i + 1]);
                            }
                            const float w0 = fmaxf(f16_lo(ha), f16_hi(ha)) - fminf(f16_lo(la), f16_hi(la)), w1 = fmaxf(f16_lo(hb), f16_hi(hb)) - fminf(f16_lo(lb), f16_hi(lb));
                            const float t0 = m0 + quad_last(fmaxf(fminf(lg2(o[125] * (1.f / KV_OFF)) + REF_SUM, w0 * 0.5f), 0.f));
                            const float t1 = m1 + quad_last(fmaxf(fminf(lg2(o[127] * (1.f / KV_OFF)) + REF_SUM, w1 * 0.5f), 0.f));
                            const uint32_t u = pack_f16(t0 * (-1.f / KV_OFF), t1 * (-1.f / KV_OFF));
                            const bool on = plim && !SC_TAIL && fmaxf(fabsf(t0), fabsf(t1)) < 64.f * KV_OFF;
                            l0 = on ? -KV_OFF * f16_lo(u) - m0 : 0.f; l1 = on ? -KV_OFF * f16_hi(u) - m1 : 0.f;
                            m0 += l0; m1 += l1;
                            store_ref(ln, u, on);
                            fence_async_smem();
                            if (SC_OWNER) warp_arrive(bar_pdone);
                            __syncwarp();
                        }
                    }
                    if (it == itl) break;
                    const int stp = it & 3;
                    it++;
                    pp_sync();
                    fence_regs(o); fence_regs(p);
                    have = SC_TAIL || it == itx;
                    if (!have) {
                        wg_fence();
                        issue_pv(stp, it - 1 - it0);
                        mbar_wait(bar_full + 8 * (it & 3), (it >> 2) & 1);
                        wg_fence();
                        issue_qk(it & 3);
                        pp_arrive();
                        wg_wait<0>();
                        fence_regs(s); fence_regs(o); fence_regs(p);
                        if (it == itl) warp_arrive(bar_qfree);
                    } else {
                        const int zero = (uint32_t)it >> 23;
                        mbar_wait(bar_full + 8 * (it & 3), (it >> 2) & 1);
                        wg_fence();
                        issue_qk((it & 3) + zero, 25);
                        if (it == itl) {
                            wg_wait<0>();
                            if (SC_PAIR) peer_arrive(); else warp_arrive(bar_qfree);
                            if (wg) bar_sync(BAR_ST, 256);
                        }
                        wg_fence();
                        issue_pv(stp + zero, it - 1 - it0);
                        pp_arrive();
                        wg_wait<1>();
                        fence_regs(s);
                        redo = exceeds(s);
                        if (!redo) {
#pragma unroll
                            for (int i = 0; i < 20; i++) s[i] = ex2_f16(s[i]);
                            fence_regs(s);
                            cut();
                        }
                        wg_wait<0>();
                        fence_regs(o); fence_regs(p);
#pragma unroll
                        for (int i = 0; i < 20; i++) p[i] = s[i];
                    }
                    release(stp);
                }
                if (seg + 1 < nseg) pp_sync();
                fence_regs(o); fence_regs(p);
                wg_fence();
                issue_pv(it & 3, 1);
                asm volatile("{\n.reg .pred p;\nsetp.ne.s32 p, %0, 0;\n@p bar.arrive %1, 256;\n}\n" ::"r"((int)(seg + 1 == nseg && (wg ? SC_PAIR : !SC_TAIL))), "r"(BAR_ST + wg) : "memory");
                it++;
                if (seg + 1 == nseg) break;
                constexpr int IS = 4 + 25;
                const int ln = lane_now();
                uint32_t qa = sq + warp * 8192 + tile_off(ln & 15, ln >> 4);
                asm volatile("" : "+r"(qa));
                mbar_wait(bar_full + 8 * (IS & 3), (IS >> 2) & 1);
                mbar_wait(qbar, 0); qphase = 1;
#pragma unroll
                for (int i = 0; i < 16; i++)
                    if (const int r = QREG(i); r >= 0)
                        asm volatile("ldmatrix.sync.aligned.m8n8.x4.shared.b16 {%0, %1, %2, %3}, [%4];\n" : "=r"(qr[4 * r]), "=r"(qr[4 * r + 1]), "=r"(qr[4 * r + 2]), "=r"(qr[4 * r + 3])
                                     : "r"((qa ^ (i & 3) * 32) + (i >> 2) * 1024) : "memory");
                fence_regs(qr);
                wg_fence();
                issue_qk(it & 3);
                wg_wait<1>();
                pp_arrive();
                fence_regs(o);
                float z0, z1;
                row_sums(z0, z1, ln);
                release((IS - 1) & 3);
                uint32_t u0, u1;
                asm volatile("ld.shared.u32 %0, [%2];\nld.shared.u32 %1, [%2 + 4096];\n" : "=r"(u0), "=r"(u1) : "r"(mq_addr(ln)) : "memory");
                const uint32_t slot = sb + SM_KV + ((IS - 2 + wg) & 3) * KV_BYTES;
                const uint32_t dst = slot + wg * 512 + warp * 8192 + ln * 16, dml = slot + (wg ? 0 : QB_BYTES) + warp * 128 + ln * 4;
#pragma unroll
                for (int i = 0; i < 128; i++) o[i] -= (i & 2) ? z1 : z0;
                fence_regs(o);
                mbar_wait(bar_empty + 8 * ((IS - 2 + wg) & 3), ((IS - 2 + wg) >> 2) & 1);
                asm volatile("st.shared.f32 [%0], %1;\n" ::"r"(dml), "f"(stats(ln)) : "memory");
                qs = __uint_as_float(0x3F800000u + ((u0 & 7) << 25));
                m0 = -KV_OFF * qs * f16_hi(u0); m1 = -KV_OFF * qs * f16_hi(u1);
                plim = fmaxf(fabsf(m0), fabsf(m1)) < 64.f * KV_OFF && qs == 1.f ? S_LIMIT : 0u;
                uint32_t v[2][8] = {};
#pragma unroll
                for (int i = 0; i < 8; i++) {
                    uint32_t *w = v[i & 1], *u = v[(i & 1) ^ 1];
#pragma unroll
                    for (int j = 0; j < 8; j++) w[j] = pack_bf16(o[16 * i + 2 * j], o[16 * i + 2 * j + 1]);
                    sts128(dst + i * 1024, w[0], w[1], w[2], w[3]);
                    sts128(dst + i * 1024 + 512, w[4], w[5], w[6], w[7]);
                    if (i) asm volatile("{\n.reg .pred p;\nsetp.lt.s32 p, %9, 0;\nL:\n@p st.shared.v4.u32 [%0], {%1, %2, %3, %4};\n@p st.shared.v4.u32 [%0 + 16], {%5, %6, %7, %8};\n@p bra L;\n}\n"
                                 ::"r"(dst), "r"(u[0]), "r"(u[1]), "r"(u[2]), "r"(u[3]), "r"(u[4]), "r"(u[5]), "r"(u[6]), "r"(u[7]), "r"(it) : "memory");
                }
                fence_async_smem();
                warp_arrive(bar_pdone);
            }
            constexpr int IW = 4 + 75;
            uint32_t a[64];
            const int lane = lane_now(), t = warp * 32 + lane;
            if (wg == 0 && (SC_PAIR || SC_LAST)) {
                uint32_t rq, rml, rbar;
                asm volatile("mapa.shared::cluster.u32 %0, %3, %6;\nmapa.shared::cluster.u32 %1, %4, %6;\nmapa.shared::cluster.u32 %2, %5, %6;\n"
                             : "=r"(rq), "=r"(rml), "=r"(rbar) : "r"(sb + SM_Q + QB_BYTES + warp * 8192 + lane * 16), "r"(sb + SM_ML + 512 + t * 4),
                             "r"(bar_pin), "r"(rank ^ 1));
                auto send = [&](int i) {
                    asm volatile("st.async.weak.shared::cluster.mbarrier::complete_tx::bytes.v4.b32 [%0], {%1, %2, %3, %4}, [%5];\n"
                                 ::"r"(rq + i * 512), "r"(a[4 * i]), "r"(a[4 * i + 1]), "r"(a[4 * i + 2]), "r"(a[4 * i + 3]), "r"(rbar + (i & 8)) : "memory");
                };
                mbar_wait(bar_rfree, 0);
                wg_wait<0>();
                fence_regs(o);
                release((it - 1) & 3);
                float z0, z1;
                row_sums(z0, z1, lane);
                asm volatile("st.async.weak.shared::cluster.mbarrier::complete_tx::bytes.f32 [%0], %1, [%2];\n" ::"r"(rml), "f"(stats(lane)), "r"(rbar) : "memory");
#pragma unroll
                for (int i = 0; i < 16; i++) {
                    a[4 * i] = pack_bf16(o[8 * i] - z0, o[8 * i + 1] - z0); a[4 * i + 1] = pack_bf16(o[8 * i + 2] - z1, o[8 * i + 3] - z1);
                    a[4 * i + 2] = pack_bf16(o[8 * i + 4] - z0, o[8 * i + 5] - z0); a[4 * i + 3] = pack_bf16(o[8 * i + 6] - z1, o[8 * i + 7] - z1);
                    if (i * SND0 / 16 != (i + 1) * SND0 / 16) send(i * SND0 / 16);
                    if (i & 1) cut();
                }
                if (SC_PAIR) {
                    float z[128];
                    const uint32_t dkz = dk0 + ((uint32_t)it >> 24), dqz = dq0 + ((uint32_t)it >> 24);
                    auto gemm = [&](int c) {
                        mbar_wait(bar_full + 8 * ((IW + c) & 3), ((IW + c) >> 2) & 1);
                        const uint64_t wb = mkaddr(dkz + ((IW + c) & 3) * (KV_BYTES >> 4), dhi), ab = mkaddr(dqz + c * 64, dhi);
                        wg_fence();
#pragma unroll
                        for (int kk = 0; kk < 4; kk++) {
                            if (c | kk) wgmma_ss_n256_tb(z, ab + kk * 2, wb + kk * 512);
                            else wgmma_ss_n256_tb_init(z, ab, wb);
                        }
                        wg_commit();
                    };
                    mbar_wait(qbar, qphase);
                    bar_sync(BAR_ST + 1, 256);
                    gemm(0);
#pragma unroll
                    for (int i = SND0; i < 16; i++) send(i);
#pragma unroll
                    for (int c = 1; c < 4; c++) { gemm(c); if (c == 3) pp_arrive(); wg_wait<1>(); release((IW + c - 1) & 3, 2); }
                    wg_wait<0>();
                    fence_regs(z);
                    release((IW + 3) & 3, 2);
#pragma unroll
                    for (int i = 0; i < 16; i++) {
                        sts128(sq + warp * 8192 + lane * 16 + i * 512, pack_bf16(z[8 * i], z[8 * i + 1]), pack_bf16(z[8 * i + 2], z[8 * i + 3]),
                               pack_bf16(z[8 * i + 4], z[8 * i + 5]), pack_bf16(z[8 * i + 6], z[8 * i + 7]));
                        if (i == 3 || i == 15) bar_arrive(i == 3 ? BAR_BF : BAR_H0, 256);
                        if (i == 3) cut();
                    }
                } else {
#pragma unroll
                    for (int i = SND0; i < 16; i++) send(i);
                }
            } else {
                const int pair = SC_PAIR;
                const bool glob = !(pair || SC_TAIL);
                const uint32_t ml = sb + SM_ML + (t & ~3) * 4, src = (glob ? sq : sb + SM_Q + QB_BYTES) + warp * 8192 + lane * 16;
                const uint64_t tm = lds64(s_tm);
                wg_wait<0>();
                fence_regs(o);
                release((IW - 1) & 3);
                float c0, c1;
                row_sums(c0, c1, lane);
                mbar_wait(glob ? qbar : bar_pin, glob ? qphase : 0);
                const float4 ps = lds128f(ml + (glob ? wg * 512 : 512));
                auto load = [&](int i) {
                    asm volatile("ld.shared.v4.u32 {%0, %1, %2, %3}, [%4];\n" : "=r"(a[4 * i]), "=r"(a[4 * i + 1]), "=r"(a[4 * i + 2]), "=r"(a[4 * i + 3]) : "r"(src + i * 512) : "memory");
                };
#pragma unroll
                for (int i = 0; i < 8; i++) load(i);
                const float n0 = fmaxf(m0, ps.x), n1 = fmaxf(m1, ps.z);
                const float a0 = ex2(m0 - n0), a1 = ex2(m1 - n1), b0 = ex2(ps.x - n0), b1 = ex2(ps.z - n1);
                const float i0 = rcp(l0 * a0 + ps.y * b0), i1 = rcp(l1 * a1 + ps.w * b1);
                const float r0 = a0 * i0, r1 = a1 * i1;
                c0 *= -r0; c1 *= -r1;
                const uint32_t u0 = pack_bf16(b0 * i0, b0 * i0), u1 = pack_bf16(b1 * i1, b1 * i1);
                uint4 v[8];
#pragma unroll
                for (int i = 0; i <= 32; i++) {
                    if (i == M2) {
#pragma unroll
                        for (int j = 0; j < 2 * M2; j++) asm volatile("" : "+r"(a[j]));
                        if (!glob) mbar_wait(bar_pin + 8, 0);
#pragma unroll
                        for (int j = 0; j < 8; j++) v[j] = lds128(src + (8 + j) * 512);
                    }
                    if (i == 32) break;
                    const uint32_t x0 = pack_bf16(fmaf(o[4 * i], r0, c0), fmaf(o[4 * i + 1], r0, c0)), x1 = pack_bf16(fmaf(o[4 * i + 2], r1, c1), fmaf(o[4 * i + 3], r1, c1));
                    a[2 * i] = i < 16 ? hfma2(a[2 * i], u0, x0) : x0;
                    a[2 * i + 1] = i < 16 ? hfma2(a[2 * i + 1], u1, x1) : x1;
                }
#pragma unroll
                for (int j = 0; j < 8; j++) {
                    uint32_t* x = a + 32 + 4 * j;
                    x[0] = hfma2(v[j].x, u0, x[0]); x[1] = hfma2(v[j].y, u1, x[1]); x[2] = hfma2(v[j].z, u0, x[2]); x[3] = hfma2(v[j].w, u1, x[3]);
                }
                float y[2][32];
                auto gemm = [&](int c, int kh) {
                    if (!kh) mbar_wait(bar_full + 8 * ((IW + c) & 3), (((IW + c) >> 2) & 1) ^ pair);
                    const uint64_t wb = mkaddr(dk0 + ((IW + c) & 3) * (KV_BYTES >> 4), dhi - 192);
                    wg_fence();
#pragma unroll
                    for (int kk = 8 * kh; kk < 8 * kh + 8; kk++) {
                        if (kk) wgmma_rs_n64_tb(y[c & 1], a[4 * kk], a[4 * kk + 1], a[4 * kk + 2], a[4 * kk + 3], wb + kk * 128);
                        else wgmma_rs_n64_tb_init(y[c & 1], a[0], a[1], a[2], a[3], wb);
                    }
                    wg_commit();
                };
                const uint32_t stg = sq + warp * 8192 + (lane & 15) * 128 + (((lane >> 4) ^ lane) & 7) * 16;
                uint4 z[4] = {};
                auto load_z = [&](int cb) {
                    if (cb < 2) asm volatile("{\n.reg .pred p;\nsetp.ne.s32 p, %0, 0;\n@p bar.sync %1, 256;\n}\n" ::"r"(pair), "r"(cb ? BAR_H0 : BAR_BF) : "memory");
#pragma unroll
                    for (int i = 0; i < 4; i++)
                        asm volatile("{\n.reg .pred p;\nsetp.ne.u32 p, %4, 0;\n@p ld.shared.v4.u32 {%0, %1, %2, %3}, [%5];\n}\n"
                                     : "+r"(z[i].x), "+r"(z[i].y), "+r"(z[i].z), "+r"(z[i].w) : "r"(pair), "r"(src - QB_BYTES + (4 * cb + i) * 512) : "memory");
                };
                pp_sync();
                gemm(0, 0);
                gemm(0, 1);
#pragma unroll
                for (int c = 0; c < 4; c++) {
                    if (c) load_z(c);
                    if (c < 3) gemm(c + 1, 0);
                    if (!c) load_z(0);
                    if (c < 3) wg_wait<1>(); else wg_wait<0>();
                    fence_regs(y[c & 1]);
                    const float* x = y[c & 1];
#pragma unroll
                    for (int i = 0; i < 4; i++)
                        stmatrix_x4((stg ^ (32 * i)) + c * 2048, hadd2(pack_bf16(x[8 * i], x[8 * i + 1]), z[i].x), hadd2(pack_bf16(x[8 * i + 2], x[8 * i + 3]), z[i].y),
                                    hadd2(pack_bf16(x[8 * i + 4], x[8 * i + 5]), z[i].z), hadd2(pack_bf16(x[8 * i + 6], x[8 * i + 7]), z[i].w));
                    if (c < 3) gemm(c + 1, 1);
                    fence_async_smem();
                    __syncwarp();
                    asm volatile("{\n.reg .pred p;\nelect.sync _|p, -1;\n"
                                 "@p cp.reduce.async.bulk.tensor.4d.global.shared::cta.add.tile.bulk_group [%0, {0, 0, %1, %2}], [%3];\n}\n"
                                 ::"l"(tm), "r"(c), "r"((pair ? SC_ZB : 2 * SC_QT0 + wg) * 8 + warp * 2), "r"(sq + warp * 8192 + c * 2048) : "memory");
                    if (c == 2 && glob) pp_arrive();
                }
                asm volatile("cp.async.bulk.commit_group;\ncp.async.bulk.wait_group.read 0;\n" ::: "memory");
            }
        } else {
            wg_wait<0>();
        }
        if (SC_TAIL) {
            float o[128];
            const int lane = lane_now(), t = warp * 32 + lane, q = lane & 3;
            auto emit = [&](uint32_t base, int lane, int row0, uint8_t* wdst, int turn) {
#pragma unroll
                for (int hh = 0; hh < 2; hh++) {
                    if (turn > 0) mbar_wait(bar_zst + 8 * hh, (turn - 1) & 1);
#pragma unroll
                    for (int i = 0; i < 8; i++)
                        stmatrix_x4(base + tile_off(8 * hh + (lane & 7), 4 * i + (lane >> 3)),
                                    pack_bf16(o[16 * i + 2 * hh], o[16 * i + 2 * hh + 1]), pack_bf16(o[16 * i + 4 + 2 * hh], o[16 * i + 5 + 2 * hh]),
                                    pack_bf16(o[16 * i + 8 + 2 * hh], o[16 * i + 9 + 2 * hh]), pack_bf16(o[16 * i + 12 + 2 * hh], o[16 * i + 13 + 2 * hh]));
                    fence_async_smem();
                    __syncwarp();
                    if (wdst) {
                        if (lane < 4)
                            asm volatile("cp.async.bulk.global.shared::cta.bulk_group [%0], [%1], 1024;\n"
                                         ::"l"(wdst + ((turn & 1) ? hh * 4096 + lane * 1024 : hh * 1024 + lane * QB_BYTES)), "r"(base + hh * 4096 + lane * 1024) : "memory");
                        asm volatile("cp.async.bulk.commit_group;\n" ::: "memory");
                    } else {
                        asm volatile("{\n.reg .pred p;\nsetp.eq.s32 p, %3, 0;\n"
                                     "@p cp.reduce.async.bulk.tensor.4d.global.shared::cta.add.tile.bulk_group [%0, {0, 0, 0, %1}], [%2];\n"
                                     "cp.async.bulk.commit_group;\n}\n"
                                     ::"l"(&P.tm_out), "r"((row0 >> 3) + hh), "r"(base + hh * 4096), "r"(lane) : "memory");
                    }
                }
                asm volatile("cp.async.bulk.wait_group.read 1;\n" ::: "memory");
                warp_arrive(bar_zst - 8 * wg);
            };
            auto emit_done = [&](bool pending) {
                asm volatile("cp.async.bulk.wait_group.read 0;\n" ::: "memory");
                __syncwarp();
                asm volatile("{\n.reg .pred p;\nsetp.eq.s32 p, %1, 0;\n@p mbarrier.arrive.shared::cta.b64 _, [%0];\n}\n"
                             ::"r"(bar_zst + 8), "r"(pending ? lane : 1) : "memory");
            };
            if (!(rank | wg)) { release(0); release(1); release(2); release(3); }
            bar_sync(BAR_BF, 256);
            warp_arrive(bar_qfree);
            const int nf = rank ? 8 : 0;
            const int nz = nf + 26 + rank;
            const int itz = 4 + SC_NKV + SC_NW;
            bool pend = false;
#pragma unroll 1
            for (int k = wg; k < nz; k += 2) {
                const int iz = itz + (k < nf ? 0 : nf >> 1);
                mbar_wait(qbar, qphase); qphase ^= 1;
#pragma unroll 1
                for (int c = 0; c < 4; c++) {
                    mbar_wait(bar_full + 8 * ((iz + c) & 3), ((iz + c) >> 2) & 1);
                    const uint64_t wb = mkaddr(dk0 + ((iz + c) & 3) * (KV_BYTES >> 4), dhi), ab = mkaddr(dq0 + c * 64, dhi);
                    wg_fence();
                    wgmma_ss_n256_tb_pred(o, ab, wb, c);
#pragma unroll
                    for (int kk = 1; kk < 4; kk++) wgmma_ss_n256_tb(o, ab + kk * 2, wb + kk * 512);
                    wg_commit();
                    emit_done(pend);
                    pend = false;
                }
                wg_wait<0>();
                fence_regs(o);
                warp_arrive(bar_qfree);
                const int fb = ((k >> 1) + 3) & 3;
                if (k < nf) {
                    float2* r255 = (float2*)H.s->r255 + wg * 128 + q;
                    if (k < 2) {
                        if (t >= 124) {
#pragma unroll
                            for (int i = 0; i < 32; i++) r255[4 * i] = make_float2(o[4 * i + 2], o[4 * i + 3]);
                        }
                        bar_sync(BAR_WG0 + wg, 128);
                    }
#pragma unroll
                    for (int i = 0; i < 32; i++) {
                        const float2 v = __ldcg(r255 + 4 * i);
                        o[4 * i] -= v.x; o[4 * i + 1] -= v.y; o[4 * i + 2] -= v.x; o[4 * i + 3] -= v.y;
                    }
                }
                int ln = lane;
                asm volatile("" : "+r"(ln));
                emit(sb + SM_KV + QB_BYTES + warp * KV_BYTES, ln, SC_TZB(k - nf) * 64 + warp * 16,
                     k >= nf ? nullptr : (k & 1) ? g_w + (4 + fb) * QB_BYTES + warp * 8192 : g_w + 8 * QB_BYTES + fb * 8192 + warp * 2048, k);
                pend = k + 2 < nz && (k | 1) != nf - 1;
                if (!pend) emit_done(true);
                if ((k | 1) == nf - 1) {
                    asm volatile("cp.async.bulk.wait_group 0;\nfence.proxy.async.global;\nfence.acq_rel.gpu;\n" ::: "memory");
                    bar_sync(BAR_BF, 256);
                    if (tid == 0) red_release(&g_sync[SY_B * 32]);
                    if (wg == 0) { release(0); release(1); release(2); release(3); }
                }
            }
        }
        if (wg == 0) pp_sync();
        warp_arrive(bar_end - 8 * wg);
        asm volatile("barrier.cluster.arrive.relaxed.aligned;\n" ::: "memory");
        if (P.E >= 0) return;
        asm volatile("setmaxnreg.dec.sync.aligned.u32 %0;\n" ::"n"(REG_P));
    }
    {
        if (warp != 0) {
            __syncwarp();
            if (SC_TAIL) {
                bar_sync(BAR_AUX, 96);
                if (warp == 1 && elect()) red_release(&g_sync[SY_CSR * 32]);
                __syncwarp();
            }
            mbar_wait_bounded(bar_go, 0);
            if (SC_TAIL) {
                if (warp == 1 && elect()) red_add(&g_sync[SY_DONE * 32]);
                if (warp == 3 && elect()) {
                    int it = 4 + SC_NKV + SC_NW;
                    asm volatile("prefetch.tensormap [%0];\n" ::"l"(&P.tm_out) : "memory");
                    if (rank) {
#pragma unroll 1
                        for (int j = 0; j < 4; j++, it++) {
                            mbar_wait_sleep(bar_empty + 8 * (it & 3), ((it >> 2) & 1) ^ 1);
                            mbar_expect_tx(bar_full + 8 * (it & 3), QB_BYTES);
                            tma_g2s(sb + SM_KV + (it & 3) * KV_BYTES, &P.tm_w[2], 8 * j, bar_full + 8 * (it & 3));
                        }
#pragma unroll 1
                        for (int k = 0; k < 8; k++) {
                            mbar_wait_sleep(bar_qfree + 8 * (k & 1), ((k >> 1) ^ (k & 1) ^ 1) & 1);
                            mbar_expect_tx(bar_q + 8 * (k & 1), QB_BYTES);
#pragma unroll 1
                            for (int hf = 0; hf < 2; hf++)
                                asm volatile("cp.async.bulk.tensor.5d.shared::cluster.global.tile.mbarrier::complete_tx::bytes [%0], [%1, {0, 0, %2, 0, 0}], [%3];\n"
                                             ::"r"(sb + SM_Q + (k & 1) * QB_BYTES + hf * 16384), "l"(&P.tm_w[k & 1]),
                                             "r"(8 * (((k >> 1) + 3) & 3) + 4 * hf), "r"(bar_q + 8 * (k & 1)) : "memory");
                        }
                        flag_wait_bounded(&g_sync[SY_B * 32], ep);
                        fence_async_global();
                    }
#pragma unroll 1
                    for (int j = 0; j < 4; j++, it++) {
                        mbar_wait_sleep(bar_empty + 8 * (it & 3), ((it >> 2) & 1) ^ 1);
                        mbar_expect_tx(bar_full + 8 * (it & 3), QB_BYTES);
                        bulk_g2s(sb + SM_KV + (it & 3) * KV_BYTES, g_w + (4 + j) * QB_BYTES, QB_BYTES, bar_full + 8 * (it & 3));
                    }
#pragma unroll 1
                    for (int k = 0; k < 26 + rank; k++) {
                        if (k == 0 || k == ((GF0 + 1) * NAUX - 16) / 128) { flag_wait_bounded(&g_sync[(k ? SY_AUX1 : SY_AUX0) * 32], NAUX * ep); fence_async_global(); }
                        mbar_wait_sleep(bar_qfree + 8 * (k & 1), ((k >> 1) ^ (k & 1) ^ 1) & 1);
                        mbar_expect_tx(bar_q + 8 * (k & 1), QB_BYTES);
                        bulk_g2s(sb + SM_Q + (k & 1) * QB_BYTES, g_agg + SC_TZB(k) * QB_BYTES, QB_BYTES, bar_q + 8 * (k & 1));
                    }
                }
            } else {
                const int par = ep & 1;
                if (blockIdx.x == 0 && t == 32) g_ovf_n[par ^ 1] = 0;
                if (blockIdx.x == 0 && warp == 1) *(uint4*)(g_hz + (lane >> 3) * 1024 + (lane & 7) * 16) = make_uint4(KV_OFF2 | NEG2, KV_OFF2 | NEG2, KV_OFF2, KV_OFF2);
                const uint32_t wlo = (uint32_t)(uintptr_t)H.s, whi = (uint32_t)((uintptr_t)H.s >> 32);
                const uint32_t blo = wlo + (uint32_t)offsetof(Scratch, bucket);
                {
                    const int* pd = P.dst + blockIdx.x * 96 + (t - 32);
                    const int* ps = P.src + blockIdx.x * 96 + (t - 32);
#pragma unroll 1
                    for (int e = P.E - (blockIdx.x * 96 + (t - 32)); e > 0; e -= CSRU * NAUX * 32, pd += CSRU * NAUX * 32, ps += CSRU * NAUX * 32) {
                        int d[CSRU], sr[CSRU], sl[CSRU];
#pragma unroll
                        for (int i = 0; i < CSRU; i++) {
                            d[i] = e > i * NAUX * 32 ? __ldg(pd + i * NAUX * 32) : NN;
                            sr[i] = e > i * NAUX * 32 ? __ldg(ps + i * NAUX * 32) : 0;
                        }
#pragma unroll
                        for (int i = 0; i < CSRU; i++) {
                            sl[i] = 0;
                            asm volatile("{\n.reg .pred p;\nsetp.lt.s32 p, %2, %3;\n@p atom.relaxed.gpu.global.add.s32 %0, [%1], 1;\n}\n"
                                         : "+r"(sl[i]) : "l"(mkaddr(wlo + (uint32_t)offsetof(Scratch, cnt) + d[i] * 4, whi)), "r"(d[i]), "n"(NN) : "memory");
                        }
                        uint32_t ov = 0;
#pragma unroll
                        for (int i = 0; i < CSRU; i++) {
                            asm volatile("{\n.reg .pred p;\nsetp.lt.s32 p, %3, %4;\n@p st.global.u16 [%1], %2;\n@!p or.b32 %0, %0, %5;\n}\n"
                                         : "+r"(ov) : "l"(mkaddr(blo + d[i] * 128 + (sl[i] & 31) * 4 + (sl[i] >> 5) * 2, whi)), "h"((unsigned short)sr[i]), "r"(sl[i]), "n"(CAP), "r"(1 << i) : "memory");
                        }
#pragma unroll 1
                        for (; ov; ov &= ov - 1) {
                            const int i = (__ffs(ov) - 1) * (NAUX * 32);
                            int at;
                            asm volatile("atom.relaxed.gpu.global.add.s32 %0, [%1], 1;\n" : "=r"(at) : "l"(&g_ovf_n[par]) : "memory");
                            g_ovf[at] = make_int2(__ldg(pd + i), __ldg(ps + i));
                        }
                    }
                }
                bar_sync(BAR_AUX, 96);
                if (warp == 1 && elect()) { red_release(&g_sync[SY_CSR * 32]); }
                __syncwarp();
                {
                    const int r0 = blockIdx.x * 3 + warp - 1;
                    const uint4* xp = (const uint4*)(H.x + r0 * 256) + lane;
                    uint4* op = (uint4*)(P.out + r0 * 256) + lane;
#pragma unroll 1
                    for (int r = r0; r < NN; r += CPYU * NAUX, xp += CPYU * NAUX * 32, op += CPYU * NAUX * 32) {
                        uint4 v[CPYU];
#pragma unroll
                        for (int i = 0; i < CPYU; i++) if (r + i * NAUX < NN) v[i] = ldg_pinned(xp + i * NAUX * 32);
#pragma unroll
                        for (int i = 0; i < CPYU; i++) if (r + i * NAUX < NN) op[i * NAUX * 32] = v[i];
                    }
                }
                if (warp == 3 && SC_OWNER && SC_PAIR && elect()) {
                    mbar_wait_sleep(bar_pdone, 0);
                    mbar_wait_sleep(bar_pdone + 8, 0);
#pragma unroll 1
                    for (int u = 0; u < 16; u++) {
                        bulk_s2g(g_q + SC_QT0 * (2 * QB_BYTES) + u * 4096, sb + SM_Q + u * 4096, 4096);
                        asm volatile("cp.async.bulk.wait_group 0;\n" ::: "memory");
                    }
                    fence_async_global();
                    st_release(&g_qflag[SC_QT0], ep);
                }
                __syncwarp();
                mbar_wait_bounded(bar_go, 1);
                bar_sync(BAR_AUX, 96);
                if (const int un = (3 - warp) * (NAUX / 3) + (NAUX / 3 - 1) - blockIdx.x; un < 208) {
                    flag_wait_bounded(&g_sync[SY_PART * 32], 52 * ep);
                    uint8_t* pp = g_part + (un >> 3) * (4 * PART_BYTES);
                    float* ml = (float*)(pp + QB_BYTES) + (un & 7) * 32;
                    const float4 sa = __ldcg((const float4*)ml + g), sc = __ldcg((const float4*)ml + g + 2 * PART_BYTES / 16);
                    const float n0 = fmaxf(sa.x, sc.x), n1 = fmaxf(sa.z, sc.z);
                    const uint32_t a0 = pack_bf16(ex2(sa.x - n0), ex2(sa.x - n0)), a1 = pack_bf16(ex2(sa.z - n1), ex2(sa.z - n1));
                    const uint32_t b0 = pack_bf16(ex2(sc.x - n0), ex2(sc.x - n0)), b1 = pack_bf16(ex2(sc.z - n1), ex2(sc.z - n1));
                    __syncwarp();
                    if (q == 0) ((float4*)ml)[g] = make_float4(n0, sa.y * bf_hi(a0) + sc.y * bf_hi(b0), n1, sa.w * bf_hi(a1) + sc.w * bf_hi(b1));
                    uint4* d = (uint4*)(pp + (un & 4) * 256 + (un & 7) * 8192) + lane;
#pragma unroll 1
                    for (int i = 0; i < 4; i++, d += 128) {
                        uint4 u[4], v[4];
#pragma unroll
                        for (int j = 0; j < 4; j++) { u[j] = __ldcg(d + j * 32); v[j] = __ldcg(d + j * 32 + 2 * PART_BYTES / 16); }
#pragma unroll
                        for (int j = 0; j < 4; j++)
                            d[j * 32] = make_uint4(hfma2(v[j].x, b0, hmul2(u[j].x, a0)), hfma2(v[j].y, b1, hmul2(u[j].y, a1)),
                                                   hfma2(v[j].z, b0, hmul2(u[j].z, a0)), hfma2(v[j].w, b1, hmul2(u[j].w, a1)));
                    }
                }
                flag_wait_bounded(&g_sync[SY_CSR * 32], NCTA * ep);
                if (warp == 2 && blockIdx.x < 129) {
                    uint4* z = blockIdx.x < 128 ? (uint4*)(g_w + blockIdx.x * 1024) + lane : (uint4*)&g_sync[SY_DONE * 32 + 4];
                    z[0] = make_uint4(0, 0, 0, 0);
                    if (blockIdx.x < 128) z[32] = make_uint4(0, 0, 0, 0);
                }
                {
                    const uint32_t lc = (lane >> 3) * 1024 + (lane & 7) * 16;
                    const uint32_t alo = wlo ^ lc;
                    const int node0 = blockIdx.x * 3 + warp - 17;
                    auto node = [&](int i) { const int nd = node0 + i * NAUX; return (int)min((unsigned)nd, (unsigned)(nd + NN)); };
                    const int num = (NN - 17 - node0) / NAUX + 1;
                    uint32_t mine = 0;
                    if (lane < num) {
                        mine = min(__ldcg(&g_cnt[node(lane)]), CAP + 1) | (uint32_t)__ldg((const unsigned short*)P.deg_inv + node(lane)) << 16;
                        g_cnt[node(lane)] = 0;
                    }
                    auto row = [&](int off) {
                        uint4 v;
                        asm volatile("ld.global.v4.u32 {%0, %1, %2, %3}, [%4];\n"
                                     : "=r"(v.x), "=r"(v.y), "=r"(v.z), "=r"(v.w) : "l"(mkaddr(alo ^ off, whi)));
                        return v;
                    };
                    auto ents = [&](int i) {
                        uint32_t e;
                        asm volatile("ld.global.cg.u32 %0, [%1];\n" : "=r"(e) : "l"(mkaddr(blo + (min(node(i), NN - 1) * 32 + lane) * 4, whi)));
                        return e;
                    };
                    auto store = [&](int i, const float (&a)[8]) {
                        const float di = bf_hi(__shfl_sync(~0u, mine, i)) * (1.f / KV_SCALE);
                        const int nd = node(i);
                        *(uint4*)(g_agg + (uint32_t)(((nd >> 3) * 4096 + (nd & 7) * 144) ^ lc)) =
                            make_uint4(pack_bf16(a[0] * di, a[1] * di), pack_bf16(a[2] * di, a[3] * di), pack_bf16(a[4] * di, a[5] * di), pack_bf16(a[6] * di, a[7] * di));
                    };
#pragma unroll 1
                    for (uint32_t big = __ballot_sync(~0u, (mine & 0xFFFF) > CAP); big; big &= big - 1) {
                        const int i = __ffs(big) - 1, no = __ldcg(&g_ovf_n[par]);
                        float a[8] = {};
#pragma unroll 1
                        for (int k = -64; k < no; k += 32) {
                            const int2 pr = k < 0 ? make_int2(node(i), (ents(i) >> (k & 32) / 2) & 0xFFFF) : k + lane < no ? __ldcg(&g_ovf[k + lane]) : make_int2(-1, 0);
#pragma unroll 1
                            for (uint32_t mk = __ballot_sync(~0u, pr.x == node(i)); mk; mk &= mk - 1) {
                                const uint4 v = row(row_off(__shfl_sync(~0u, pr.y, __ffs(mk) - 1)));
                                a[0] += f16_lo(v.x) + KV_OFF; a[1] += f16_hi(v.x) + KV_OFF; a[2] += f16_lo(v.y) + KV_OFF; a[3] += f16_hi(v.y) + KV_OFF;
                                a[4] += f16_lo(v.z) - KV_OFF; a[5] += f16_hi(v.z) - KV_OFF; a[6] += f16_lo(v.w) - KV_OFF; a[7] += f16_hi(v.w) - KV_OFF;
                            }
                        }
                        store(i, a);
                    }
                    auto add4 = [&](const uint4& a, const uint4& b) { return make_uint4(hadd2_f16(a.x, b.x), hadd2_f16(a.y, b.y), hadd2_f16(a.z, b.z), hadd2_f16(a.w, b.w)); };
                    int ni = -1, left = 0, pos = 0, ec = 0;
                    uint32_t en = ents(0);
                    uint4 acc = make_uint4(0, 0, 0, 0);
                    auto step = [&](uint4 (&v)[4], int& tag) {
                        if (left <= 0 || pos == 32) {
                            if (left > 0) {
                                en = ents(ni) >> 16;
                            } else {
                                ni++;
                                left = __shfl_sync(~0u, mine, ni) & 0xFFFF;
                                if (left > CAP) left = 0;
                            }
                            ec = lane < left ? row_off(en & 0xFFFF) : 0;
                            en = ents(ni + 1);
                            pos = 0;
                        }
                        int of[4];
#pragma unroll
                        for (int j = 0; j < 4; j++) asm volatile("shfl.sync.idx.b32 %0, %1, %2, 31, -1;\n" : "=r"(of[j]) : "r"(ec), "r"(pos + j));
                        acc = add4(acc, add4(add4(add4(v[0], v[1]), make_uint4(KV_OFF8, KV_OFF8, KV_OFF8 | NEG2, KV_OFF8 | NEG2)), add4(v[2], v[3])));
                        asm volatile("" : "+r"(acc.x), "+r"(acc.y), "+r"(acc.z), "+r"(acc.w));
                        asm volatile("{\n.reg .pred p;\nsetp.lt.s32 p, %0, 0;\nL:\n@p pmevent 0;\n@p bra L;\n}\n" ::"r"(ni) : "memory");
#pragma unroll
                        for (int j = 0; j < 4; j++) v[j] = row(of[j]);
                        pos += 4; left -= 4;
                        const int i = tag;
                        tag = left <= 0 ? ni : -1;
                        if (i >= 0) {
                            const float a[8] = {f16_lo(acc.x), f16_hi(acc.x), f16_lo(acc.y), f16_hi(acc.y), f16_lo(acc.z), f16_hi(acc.z), f16_lo(acc.w), f16_hi(acc.w)};
                            if ((__shfl_sync(~0u, mine, i) & 0xFFFF) <= CAP) store(i, a);
                            acc = make_uint4(0, 0, 0, 0);
                            if (i == GF0 || i == 8) {
                                __syncwarp();
                                if (elect()) red_release(&g_sync[(i == 8 ? SY_AUX1 : SY_AUX0) * 32]);
                                __syncwarp();
                            }
                        }
                        return i == num - 1;
                    };
                    uint4 va[4], vb[4];
#pragma unroll
                    for (int j = 0; j < 4; j++) va[j] = vb[j] = make_uint4(KV_OFF2 | NEG2, KV_OFF2 | NEG2, KV_OFF2, KV_OFF2);
                    int ta = -1, tb = -1;
#pragma unroll 1
                    while (!step(va, ta) && !step(vb, tb)) {}
                }
                bar_sync(BAR_AUX, 96);
                if (warp == 1 && elect()) {
                    red_release(&g_sync[SY_AUX * 32]);
                    red_add(&g_sync[SY_DONE * 32]);
                }
            }
        }
        __syncwarp();
        asm volatile("barrier.cluster.arrive.relaxed.aligned;\n" ::: "memory");
        if (warp == 1) mbar_wait_bounded(bar_end, 0);
        else if (elect()) mbar_arrive(bar_end);
        __syncwarp();
        asm volatile("barrier.cluster.wait.acquire.aligned;\n" ::: "memory");
    }
}

}


extern "C" void kernel_launch(void* const* d_in, const int* in_sizes, int n_in, void* d_out, int out_size) {
    Hot H;
    Params P;
    H.x = (const __nv_bfloat16*)d_in[0];
    P.src = (const int*)d_in[1];
    P.dst = (const int*)d_in[2];
    P.deg_inv = (const __nv_bfloat16*)d_in[3];
    H.wq = (const __nv_bfloat16*)d_in[5];
    H.wk = (const __nv_bfloat16*)d_in[6];
    P.out = (__nv_bfloat16*)d_out;
    typedef CUresult (*EncodeFn)(CUtensorMap*, CUtensorMapDataType, cuuint32_t, void*, const cuuint64_t*, const cuuint64_t*, const cuuint32_t*,
                                 const cuuint32_t*, CUtensorMapInterleave, CUtensorMapSwizzle, CUtensorMapL2promotion, CUtensorMapFloatOOBfill);
    void* fn = nullptr;
    cudaDriverEntryPointQueryResult qr;
    cudaGetDriverEntryPoint("cuTensorMapEncodeTiled", &fn, cudaEnableDefault, &qr);
    auto encode = [&](CUtensorMap* tm, const void* ptr, int rows, int box_rows, int box_cb = 4) {
        const cuuint64_t dims[4] = {64, 8, 4, (cuuint64_t)rows / 8};
        const cuuint64_t strides[3] = {512, 128, 4096};
        const cuuint32_t box[4] = {64, 8, (cuuint32_t)box_cb, (cuuint32_t)box_rows / 8}, es[4] = {1, 1, 1, 1};
        ((EncodeFn)fn)(tm, CU_TENSOR_MAP_DATA_TYPE_BFLOAT16, 4, (void*)ptr, dims, strides, box, es, CU_TENSOR_MAP_INTERLEAVE_NONE,
                       CU_TENSOR_MAP_SWIZZLE_128B, CU_TENSOR_MAP_L2_PROMOTION_NONE, CU_TENSOR_MAP_FLOAT_OOB_FILL_NONE);
    };
    encode(&P.tm_out, d_out, NN, 8);
    encode(&P.tm_outc, d_out, NN, 16, 1);
    for (int i = 0; i < 2; i++) {
        const cuuint64_t dims[5] = {64, 2, 32, 4, 4};
        const cuuint64_t strides[4] = {512, 4096, 128, 1024};
        const cuuint32_t box[5] = {64, 2, 4, 4, 4}, es[5] = {1, 1, 1, 1, 1};
        ((EncodeFn)fn)(&P.tm_w[i], CU_TENSOR_MAP_DATA_TYPE_BFLOAT16, 5, d_in[i ? 4 : 7], dims, strides, box, es, CU_TENSOR_MAP_INTERLEAVE_NONE,
                       CU_TENSOR_MAP_SWIZZLE_128B, CU_TENSOR_MAP_L2_PROMOTION_NONE, CU_TENSOR_MAP_FLOAT_OOB_FILL_NONE);
    }
    encode(&P.tm_w[2], d_in[8], 256, 64);
    void* raw = nullptr;
    cudaGetSymbolAddress(&raw, g_raw);
    H.s = (Scratch*)(((uintptr_t)raw + ((8 << 20) - 1)) & ~(uintptr_t)((8 << 20) - 1));
    P.dhi = 0x40000100u;
    P.E = in_sizes[1] < MAXE ? in_sizes[1] : MAXE;
    cudaFuncSetAttribute(k_main, cudaFuncAttributeMaxDynamicSharedMemorySize, SM_TOTAL);
    k_main<<<NCTA, 384, SM_TOTAL>>>(H, P);
}
```

```cpp
#include <cuda_runtime.h>
#include <cuda.h>
#include <cuda_bf16.h>
#include <stdint.h>
#include <stddef.h>

namespace {

constexpr int NN = 10000;
constexpr int BN = 80;
constexpr int NQB = 158;
constexpr int NCTA = 132;
constexpr int NAUX = 3 * (NCTA - 2);
constexpr int STAGES = 4;
constexpr int KV_BYTES = BN * 512;
constexpr int QB_BYTES = 64 * 512;
constexpr int PART_BYTES = QB_BYTES + 512;
constexpr int CAP = 64;
constexpr int MAXE = 160000;

#define GO0 5
#define GO1 40
#define GF0 2
#define CSRU 3
#define CPYU 9
#define REFUP 2.f
#define REFSUM 3.f
#define LIFT 6
#define KVM 0x1AB
#define SND0 10
#define M2 28
#define TICK 1024
#define NQR 7
#define NREV 2
#define PPA 2
#define REG_C 224
#define REG_P 56
#define QREG(kk) (((kk) & 1) && (kk) / 2 < NQR ? (kk) / 2 : -1)
#define QRND(v) (((v) + 0x00040004u) & 0xFFF8FFF8u)

enum { SY_PART = 4, SY_H1 = 5, SY_CSR = 6, SY_AUX = 7, SY_DONE = 8, SY_AUX0 = 9, SY_B = 10, SY_AUX1 = 11, SY_H0 = 12 };
struct Scratch {
    uint8_t hz[4096 + NN * 512];
    uint8_t w[12 * QB_BYTES];
    int sync[25 * 32];
    int qflag[96];
    int ovf_n[32];
    float r255[512];
    int cnt[NN + 16];
    int bucket[(NN + 1) * 32];
    int2 ovf[MAXE];
    uint8_t q[NQB * QB_BYTES];
    uint8_t agg[NQB * QB_BYTES];
    uint8_t part[52 * 2 * PART_BYTES];
};
static_assert(offsetof(Scratch, ovf) <= (8 << 20), "window");
static_assert(offsetof(Scratch, qflag) == offsetof(Scratch, sync) + 25 * 128, "flags");
static_assert(offsetof(Scratch, w) % 1024 == 0 && offsetof(Scratch, sync) % 128 == 0 &&
              offsetof(Scratch, bucket) % 128 == 0 && offsetof(Scratch, q) % 128 == 0, "alignment");
__device__ uint8_t g_raw[(8 << 20) + sizeof(Scratch)];
#define g_hz (H.s->hz)
#define g_w (H.s->w)
#define g_sync (H.s->sync)
#define g_qflag (H.s->qflag)
#define g_ovf_n (H.s->ovf_n)
#define g_cnt (H.s->cnt)
#define g_bucket (H.s->bucket)
#define g_ovf (H.s->ovf)
#define g_q (H.s->q)
#define g_agg (H.s->agg)
#define g_part (H.s->part)

__device__ __forceinline__ void wgmma_ss_n80(uint32_t (&d)[20], uint64_t da, uint64_t db) {
    asm volatile("wgmma.mma_async.sync.aligned.m64n80k16.f16.f16.f16 {"
        "%0, %1, %2, %3, %4, %5, %6, %7, %8, %9, %10, %11, %12, %13, %14, %15, %16, %17, %18, %19}, %20, %21, 1, 1, 1, 0, 0;\n"
        : "+r"(d[0]), "+r"(d[1]), "+r"(d[2]), "+r"(d[3]), "+r"(d[4]), "+r"(d[5]), "+r"(d[6]), "+r"(d[7]),
          "+r"(d[8]), "+r"(d[9]), "+r"(d[10]), "+r"(d[11]), "+r"(d[12]), "+r"(d[13]), "+r"(d[14]), "+r"(d[15]),
          "+r"(d[16]), "+r"(d[17]), "+r"(d[18]), "+r"(d[19])
        : "l"(da), "l"(db));
}
__device__ __forceinline__ void wgmma_ss_n80_init(uint32_t (&d)[20], uint64_t da, uint64_t db) {
    asm volatile("wgmma.mma_async.sync.aligned.m64n80k16.f16.f16.f16 {"
        "%0, %1, %2, %3, %4, %5, %6, %7, %8, %9, %10, %11, %12, %13, %14, %15, %16, %17, %18, %19}, %20, %21, 0, 1, 1, 0, 0;\n"
        : "=r"(d[0]), "=r"(d[1]), "=r"(d[2]), "=r"(d[3]), "=r"(d[4]), "=r"(d[5]), "=r"(d[6]), "=r"(d[7]),
          "=r"(d[8]), "=r"(d[9]), "=r"(d[10]), "=r"(d[11]), "=r"(d[12]), "=r"(d[13]), "=r"(d[14]), "=r"(d[15]),
          "=r"(d[16]), "=r"(d[17]), "=r"(d[18]), "=r"(d[19])
        : "l"(da), "l"(db));
}
__device__ __forceinline__ void wgmma_rs_n80(uint32_t (&d)[20], uint32_t a0, uint32_t a1, uint32_t a2, uint32_t a3, uint64_t db) {
    asm volatile("wgmma.mma_async.sync.aligned.m64n80k16.f16.f16.f16 {"
        "%0, %1, %2, %3, %4, %5, %6, %7, %8, %9, %10, %11, %12, %13, %14, %15, %16, %17, %18, %19}, {%20, %21, %22, %23}, %24, 1, 1, 1, 0;\n"
        : "+r"(d[0]), "+r"(d[1]), "+r"(d[2]), "+r"(d[3]), "+r"(d[4]), "+r"(d[5]), "+r"(d[6]), "+r"(d[7]),
          "+r"(d[8]), "+r"(d[9]), "+r"(d[10]), "+r"(d[11]), "+r"(d[12]), "+r"(d[13]), "+r"(d[14]), "+r"(d[15]),
          "+r"(d[16]), "+r"(d[17]), "+r"(d[18]), "+r"(d[19])
        : "r"(a0), "r"(a1), "r"(a2), "r"(a3), "l"(db));
}
__device__ __forceinline__ void wgmma_rs_n256_tb(float (&d)[128], uint32_t a0, uint32_t a1, uint32_t a2, uint32_t a3, uint64_t db) {
    asm volatile("wgmma.mma_async.sync.aligned.m64n256k16.f32.f16.f16 {"
        "%0, %1, %2, %3, %4, %5, %6, %7, %8, %9, %10, %11, %12, %13, %14, %15, %16, %17, %18, %19, %20, %21, %22, %23, %24, %25, %26, %27, %28, %29, %30, %31, "
        "%32, %33, %34, %35, %36, %37, %38, %39, %40, %41, %42, %43, %44, %45, %46, %47, %48, %49, %50, %51, %52, %53, %54, %55, %56, %57, %58, %59, %60, %61, %62, %63, "
        "%64, %65, %66, %67, %68, %69, %70, %71, %72, %73, %74, %75, %76, %77, %78, %79, %80, %81, %82, %83, %84, %85, %86, %87, %88, %89, %90, %91, %92, %93, %94, %95, "
        "%96, %97, %98, %99, %100, %101, %102, %103, %104, %105, %106, %107, %108, %109, %110, %111, %112, %113, %114, %115, %116, %117, %118, %119, %120, %121, %122, %123, %124, %125, %126, %127}, {%128, %129, %130, %131}, %132, 1, 1, 1, 1;\n"
        : "+f"(d[0]), "+f"(d[1]), "+f"(d[2]), "+f"(d[3]), "+f"(d[4]), "+f"(d[5]), "+f"(d[6]), "+f"(d[7]),
          "+f"(d[8]), "+f"(d[9]), "+f"(d[10]), "+f"(d[11]), "+f"(d[12]), "+f"(d[13]), "+f"(d[14]), "+f"(d[15]),
          "+f"(d[16]), "+f"(d[17]), "+f"(d[18]), "+f"(d[19]), "+f"(d[20]), "+f"(d[21]), "+f"(d[22]), "+f"(d[23]),
          "+f"(d[24]), "+f"(d[25]), "+f"(d[26]), "+f"(d[27]), "+f"(d[28]), "+f"(d[29]), "+f"(d[30]), "+f"(d[31]),
          "+f"(d[32]), "+f"(d[33]), "+f"(d[34]), "+f"(d[35]), "+f"(d[36]), "+f"(d[37]), "+f"(d[38]), "+f"(d[39]),
          "+f"(d[40]), "+f"(d[41]), "+f"(d[42]), "+f"(d[43]), "+f"(d[44]), "+f"(d[45]), "+f"(d[46]), "+f"(d[47]),
          "+f"(d[48]), "+f"(d[49]), "+f"(d[50]), "+f"(d[51]), "+f"(d[52]), "+f"(d[53]), "+f"(d[54]), "+f"(d[55]),
          "+f"(d[56]), "+f"(d[57]), "+f"(d[58]), "+f"(d[59]), "+f"(d[60]), "+f"(d[61]), "+f"(d[62]), "+f"(d[63]),
          "+f"(d[64]), "+f"(d[65]), "+f"(d[66]), "+f"(d[67]), "+f"(d[68]), "+f"(d[69]), "+f"(d[70]), "+f"(d[71]),
          "+f"(d[72]), "+f"(d[73]), "+f"(d[74]), "+f"(d[75]), "+f"(d[76]), "+f"(d[77]), "+f"(d[78]), "+f"(d[79]),
          "+f"(d[80]), "+f"(d[81]), "+f"(d[82]), "+f"(d[83]), "+f"(d[84]), "+f"(d[85]), "+f"(d[86]), "+f"(d[87]),
          "+f"(d[88]), "+f"(d[89]), "+f"(d[90]), "+f"(d[91]), "+f"(d[92]), "+f"(d[93]), "+f"(d[94]), "+f"(d[95]),
          "+f"(d[96]), "+f"(d[97]), "+f"(d[98]), "+f"(d[99]), "+f"(d[100]), "+f"(d[101]), "+f"(d[102]), "+f"(d[103]),
          "+f"(d[104]), "+f"(d[105]), "+f"(d[106]), "+f"(d[107]), "+f"(d[108]), "+f"(d[109]), "+f"(d[110]), "+f"(d[111]),
          "+f"(d[112]), "+f"(d[113]), "+f"(d[114]), "+f"(d[115]), "+f"(d[116]), "+f"(d[117]), "+f"(d[118]), "+f"(d[119]),
          "+f"(d[120]), "+f"(d[121]), "+f"(d[122]), "+f"(d[123]), "+f"(d[124]), "+f"(d[125]), "+f"(d[126]), "+f"(d[127])
        : "r"(a0), "r"(a1), "r"(a2), "r"(a3), "l"(db));
}
__device__ __forceinline__ void wgmma_rs_n256_tb_init(float (&d)[128], uint32_t a0, uint32_t a1, uint32_t a2, uint32_t a3, uint64_t db) {
    asm volatile("wgmma.mma_async.sync.aligned.m64n256k16.f32.f16.f16 {"
        "%0, %1, %2, %3, %4, %5, %6, %7, %8, %9, %10, %11, %12, %13, %14, %15, %16, %17, %18, %19, %20, %21, %22, %23, %24, %25, %26, %27, %28, %29, %30, %31, "
        "%32, %33, %34, %35, %36, %37, %38, %39, %40, %41, %42, %43, %44, %45, %46, %47, %48, %49, %50, %51, %52, %53, %54, %55, %56, %57, %58, %59, %60, %61, %62, %63, "
        "%64, %65, %66, %67, %68, %69, %70, %71, %72, %73, %74, %75, %76, %77, %78, %79, %80, %81, %82, %83, %84, %85, %86, %87, %88, %89, %90, %91, %92, %93, %94, %95, "
        "%96, %97, %98, %99, %100, %101, %102, %103, %104, %105, %106, %107, %108, %109, %110, %111, %112, %113, %114, %115, %116, %117, %118, %119, %120, %121, %122, %123, %124, %125, %126, %127}, {%128, %129, %130, %131}, %132, 0, 1, 1, 1;\n"
        : "=f"(d[0]), "=f"(d[1]), "=f"(d[2]), "=f"(d[3]), "=f"(d[4]), "=f"(d[5]), "=f"(d[6]), "=f"(d[7]),
          "=f"(d[8]), "=f"(d[9]), "=f"(d[10]), "=f"(d[11]), "=f"(d[12]), "=f"(d[13]), "=f"(d[14]), "=f"(d[15]),
          "=f"(d[16]), "=f"(d[17]), "=f"(d[18]), "=f"(d[19]), "=f"(d[20]), "=f"(d[21]), "=f"(d[22]), "=f"(d[23]),
          "=f"(d[24]), "=f"(d[25]), "=f"(d[26]), "=f"(d[27]), "=f"(d[28]), "=f"(d[29]), "=f"(d[30]), "=f"(d[31]),
          "=f"(d[32]), "=f"(d[33]), "=f"(d[34]), "=f"(d[35]), "=f"(d[36]), "=f"(d[37]), "=f"(d[38]), "=f"(d[39]),
          "=f"(d[40]), "=f"(d[41]), "=f"(d[42]), "=f"(d[43]), "=f"(d[44]), "=f"(d[45]), "=f"(d[46]), "=f"(d[47]),
          "=f"(d[48]), "=f"(d[49]), "=f"(d[50]), "=f"(d[51]), "=f"(d[52]), "=f"(d[53]), "=f"(d[54]), "=f"(d[55]),
          "=f"(d[56]), "=f"(d[57]), "=f"(d[58]), "=f"(d[59]), "=f"(d[60]), "=f"(d[61]), "=f"(d[62]), "=f"(d[63]),
          "=f"(d[64]), "=f"(d[65]), "=f"(d[66]), "=f"(d[67]), "=f"(d[68]), "=f"(d[69]), "=f"(d[70]), "=f"(d[71]),
          "=f"(d[72]), "=f"(d[73]), "=f"(d[74]), "=f"(d[75]), "=f"(d[76]), "=f"(d[77]), "=f"(d[78]), "=f"(d[79]),
          "=f"(d[80]), "=f"(d[81]), "=f"(d[82]), "=f"(d[83]), "=f"(d[84]), "=f"(d[85]), "=f"(d[86]), "=f"(d[87]),
          "=f"(d[88]), "=f"(d[89]), "=f"(d[90]), "=f"(d[91]), "=f"(d[92]), "=f"(d[93]), "=f"(d[94]), "=f"(d[95]),
          "=f"(d[96]), "=f"(d[97]), "=f"(d[98]), "=f"(d[99]), "=f"(d[100]), "=f"(d[101]), "=f"(d[102]), "=f"(d[103]),
          "=f"(d[104]), "=f"(d[105]), "=f"(d[106]), "=f"(d[107]), "=f"(d[108]), "=f"(d[109]), "=f"(d[110]), "=f"(d[111]),
          "=f"(d[112]), "=f"(d[113]), "=f"(d[114]), "=f"(d[115]), "=f"(d[116]), "=f"(d[117]), "=f"(d[118]), "=f"(d[119]),
          "=f"(d[120]), "=f"(d[121]), "=f"(d[122]), "=f"(d[123]), "=f"(d[124]), "=f"(d[125]), "=f"(d[126]), "=f"(d[127])
        : "r"(a0), "r"(a1), "r"(a2), "r"(a3), "l"(db));
}
__device__ __forceinline__ void wgmma_rs_n256_tb_pred(float (&d)[128], uint32_t a0, uint32_t a1, uint32_t a2, uint32_t a3, uint64_t db, int acc) {
    asm volatile("{\n.reg .pred p;\nsetp.ne.s32 p, %133, 0;\nwgmma.mma_async.sync.aligned.m64n256k16.f32.f16.f16 {"
        "%0, %1, %2, %3, %4, %5, %6, %7, %8, %9, %10, %11, %12, %13, %14, %15, %16, %17, %18, %19, %20, %21, %22, %23, %24, %25, %26, %27, %28, %29, %30, %31, "
        "%32, %33, %34, %35, %36, %37, %38, %39, %40, %41, %42, %43, %44, %45, %46, %47, %48, %49, %50, %51, %52, %53, %54, %55, %56, %57, %58, %59, %60, %61, %62, %63, "
        "%64, %65, %66, %67, %68, %69, %70, %71, %72, %73, %74, %75, %76, %77, %78, %79, %80, %81, %82, %83, %84, %85, %86, %87, %88, %89, %90, %91, %92, %93, %94, %95, "
        "%96, %97, %98, %99, %100, %101, %102, %103, %104, %105, %106, %107, %108, %109, %110, %111, %112, %113, %114, %115, %116, %117, %118, %119, %120, %121, %122, %123, %124, %125, %126, %127}, {%128, %129, %130, %131}, %132, p, 1, 1, 1;\n}\n"
        : "+f"(d[0]), "+f"(d[1]), "+f"(d[2]), "+f"(d[3]), "+f"(d[4]), "+f"(d[5]), "+f"(d[6]), "+f"(d[7]),
          "+f"(d[8]), "+f"(d[9]), "+f"(d[10]), "+f"(d[11]), "+f"(d[12]), "+f"(d[13]), "+f"(d[14]), "+f"(d[15]),
          "+f"(d[16]), "+f"(d[17]), "+f"(d[18]), "+f"(d[19]), "+f"(d[20]), "+f"(d[21]), "+f"(d[22]), "+f"(d[23]),
          "+f"(d[24]), "+f"(d[25]), "+f"(d[26]), "+f"(d[27]), "+f"(d[28]), "+f"(d[29]), "+f"(d[30]), "+f"(d[31]),
          "+f"(d[32]), "+f"(d[33]), "+f"(d[34]), "+f"(d[35]), "+f"(d[36]), "+f"(d[37]), "+f"(d[38]), "+f"(d[39]),
          "+f"(d[40]), "+f"(d[41]), "+f"(d[42]), "+f"(d[43]), "+f"(d[44]), "+f"(d[45]), "+f"(d[46]), "+f"(d[47]),
          "+f"(d[48]), "+f"(d[49]), "+f"(d[50]), "+f"(d[51]), "+f"(d[52]), "+f"(d[53]), "+f"(d[54]), "+f"(d[55]),
          "+f"(d[56]), "+f"(d[57]), "+f"(d[58]), "+f"(d[59]), "+f"(d[60]), "+f"(d[61]), "+f"(d[62]), "+f"(d[63]),
          "+f"(d[64]), "+f"(d[65]), "+f"(d[66]), "+f"(d[67]), "+f"(d[68]), "+f"(d[69]), "+f"(d[70]), "+f"(d[71]),
          "+f"(d[72]), "+f"(d[73]), "+f"(d[74]), "+f"(d[75]), "+f"(d[76]), "+f"(d[77]), "+f"(d[78]), "+f"(d[79]),
          "+f"(d[80]), "+f"(d[81]), "+f"(d[82]), "+f"(d[83]), "+f"(d[84]), "+f"(d[85]), "+f"(d[86]), "+f"(d[87]),
          "+f"(d[88]), "+f"(d[89]), "+f"(d[90]), "+f"(d[91]), "+f"(d[92]), "+f"(d[93]), "+f"(d[94]), "+f"(d[95]),
          "+f"(d[96]), "+f"(d[97]), "+f"(d[98]), "+f"(d[99]), "+f"(d[100]), "+f"(d[101]), "+f"(d[102]), "+f"(d[103]),
          "+f"(d[104]), "+f"(d[105]), "+f"(d[106]), "+f"(d[107]), "+f"(d[108]), "+f"(d[109]), "+f"(d[110]), "+f"(d[111]),
          "+f"(d[112]), "+f"(d[113]), "+f"(d[114]), "+f"(d[115]), "+f"(d[116]), "+f"(d[117]), "+f"(d[118]), "+f"(d[119]),
          "+f"(d[120]), "+f"(d[121]), "+f"(d[122]), "+f"(d[123]), "+f"(d[124]), "+f"(d[125]), "+f"(d[126]), "+f"(d[127])
        : "r"(a0), "r"(a1), "r"(a2), "r"(a3), "l"(db), "r"(acc));
}
__device__ __forceinline__ void wgmma_ss_n256_tb(float (&d)[128], uint64_t da, uint64_t db) {
    asm volatile("wgmma.mma_async.sync.aligned.m64n256k16.f32.bf16.bf16 {"
        "%0, %1, %2, %3, %4, %5, %6, %7, %8, %9, %10, %11, %12, %13, %14, %15, %16, %17, %18, %19, %20, %21, %22, %23, %24, %25, %26, %27, %28, %29, %30, %31, "
        "%32, %33, %34, %35, %36, %37, %38, %39, %40, %41, %42, %43, %44, %45, %46, %47, %48, %49, %50, %51, %52, %53, %54, %55, %56, %57, %58, %59, %60, %61, %62, %63, "
        "%64, %65, %66, %67, %68, %69, %70, %71, %72, %73, %74, %75, %76, %77, %78, %79, %80, %81, %82, %83, %84, %85, %86, %87, %88, %89, %90, %91, %92, %93, %94, %95, "
        "%96, %97, %98, %99, %100, %101, %102, %103, %104, %105, %106, %107, %108, %109, %110, %111, %112, %113, %114, %115, %116, %117, %118, %119, %120, %121, %122, %123, %124, %125, %126, %127}, %128, %129, 1, 1, 1, 0, 1;\n"
        : "+f"(d[0]), "+f"(d[1]), "+f"(d[2]), "+f"(d[3]), "+f"(d[4]), "+f"(d[5]), "+f"(d[6]), "+f"(d[7]),
          "+f"(d[8]), "+f"(d[9]), "+f"(d[10]), "+f"(d[11]), "+f"(d[12]), "+f"(d[13]), "+f"(d[14]), "+f"(d[15]),
          "+f"(d[16]), "+f"(d[17]), "+f"(d[18]), "+f"(d[19]), "+f"(d[20]), "+f"(d[21]), "+f"(d[22]), "+f"(d[23]),
          "+f"(d[24]), "+f"(d[25]), "+f"(d[26]), "+f"(d[27]), "+f"(d[28]), "+f"(d[29]), "+f"(d[30]), "+f"(d[31]),
          "+f"(d[32]), "+f"(d[33]), "+f"(d[34]), "+f"(d[35]), "+f"(d[36]), "+f"(d[37]), "+f"(d[38]), "+f"(d[39]),
          "+f"(d[40]), "+f"(d[41]), "+f"(d[42]), "+f"(d[43]), "+f"(d[44]), "+f"(d[45]), "+f"(d[46]), "+f"(d[47]),
          "+f"(d[48]), "+f"(d[49]), "+f"(d[50]), "+f"(d[51]), "+f"(d[52]), "+f"(d[53]), "+f"(d[54]), "+f"(d[55]),
          "+f"(d[56]), "+f"(d[57]), "+f"(d[58]), "+f"(d[59]), "+f"(d[60]), "+f"(d[61]), "+f"(d[62]), "+f"(d[63]),
          "+f"(d[64]), "+f"(d[65]), "+f"(d[66]), "+f"(d[67]), "+f"(d[68]), "+f"(d[69]), "+f"(d[70]), "+f"(d[71]),
          "+f"(d[72]), "+f"(d[73]), "+f"(d[74]), "+f"(d[75]), "+f"(d[76]), "+f"(d[77]), "+f"(d[78]), "+f"(d[79]),
          "+f"(d[80]), "+f"(d[81]), "+f"(d[82]), "+f"(d[83]), "+f"(d[84]), "+f"(d[85]), "+f"(d[86]), "+f"(d[87]),
          "+f"(d[88]), "+f"(d[89]), "+f"(d[90]), "+f"(d[91]), "+f"(d[92]), "+f"(d[93]), "+f"(d[94]), "+f"(d[95]),
          "+f"(d[96]), "+f"(d[97]), "+f"(d[98]), "+f"(d[99]), "+f"(d[100]), "+f"(d[101]), "+f"(d[102]), "+f"(d[103]),
          "+f"(d[104]), "+f"(d[105]), "+f"(d[106]), "+f"(d[107]), "+f"(d[108]), "+f"(d[109]), "+f"(d[110]), "+f"(d[111]),
          "+f"(d[112]), "+f"(d[113]), "+f"(d[114]), "+f"(d[115]), "+f"(d[116]), "+f"(d[117]), "+f"(d[118]), "+f"(d[119]),
          "+f"(d[120]), "+f"(d[121]), "+f"(d[122]), "+f"(d[123]), "+f"(d[124]), "+f"(d[125]), "+f"(d[126]), "+f"(d[127])
        : "l"(da), "l"(db));
}
__device__ __forceinline__ void wgmma_ss_n256_tb_init(float (&d)[128], uint64_t da, uint64_t db) {
    asm volatile("wgmma.mma_async.sync.aligned.m64n256k16.f32.bf16.bf16 {"
        "%0, %1, %2, %3, %4, %5, %6, %7, %8, %9, %10, %11, %12, %13, %14, %15, %16, %17, %18, %19, %20, %21, %22, %23, %24, %25, %26, %27, %28, %29, %30, %31, "
        "%32, %33, %34, %35, %36, %37, %38, %39, %40, %41, %42, %43, %44, %45, %46, %47, %48, %49, %50, %51, %52, %53, %54, %55, %56, %57, %58, %59, %60, %61, %62, %63, "
        "%64, %65, %66, %67, %68, %69, %70, %71, %72, %73, %74, %75, %76, %77, %78, %79, %80, %81, %82, %83, %84, %85, %86, %87, %88, %89, %90, %91, %92, %93, %94, %95, "
        "%96, %97, %98, %99, %100, %101, %102, %103, %104, %105, %106, %107, %108, %109, %110, %111, %112, %113, %114, %115, %116, %117, %118, %119, %120, %121, %122, %123, %124, %125, %126, %127}, %128, %129, 0, 1, 1, 0, 1;\n"
        : "=f"(d[0]), "=f"(d[1]), "=f"(d[2]), "=f"(d[3]), "=f"(d[4]), "=f"(d[5]), "=f"(d[6]), "=f"(d[7]),
          "=f"(d[8]), "=f"(d[9]), "=f"(d[10]), "=f"(d[11]), "=f"(d[12]), "=f"(d[13]), "=f"(d[14]), "=f"(d[15]),
          "=f"(d[16]), "=f"(d[17]), "=f"(d[18]), "=f"(d[19]), "=f"(d[20]), "=f"(d[21]), "=f"(d[22]), "=f"(d[23]),
          "=f"(d[24]), "=f"(d[25]), "=f"(d[26]), "=f"(d[27]), "=f"(d[28]), "=f"(d[29]), "=f"(d[30]), "=f"(d[31]),
          "=f"(d[32]), "=f"(d[33]), "=f"(d[34]), "=f"(d[35]), "=f"(d[36]), "=f"(d[37]), "=f"(d[38]), "=f"(d[39]),
          "=f"(d[40]), "=f"(d[41]), "=f"(d[42]), "=f"(d[43]), "=f"(d[44]), "=f"(d[45]), "=f"(d[46]), "=f"(d[47]),
          "=f"(d[48]), "=f"(d[49]), "=f"(d[50]), "=f"(d[51]), "=f"(d[52]), "=f"(d[53]), "=f"(d[54]), "=f"(d[55]),
          "=f"(d[56]), "=f"(d[57]), "=f"(d[58]), "=f"(d[59]), "=f"(d[60]), "=f"(d[61]), "=f"(d[62]), "=f"(d[63]),
          "=f"(d[64]), "=f"(d[65]), "=f"(d[66]), "=f"(d[67]), "=f"(d[68]), "=f"(d[69]), "=f"(d[70]), "=f"(d[71]),
          "=f"(d[72]), "=f"(d[73]), "=f"(d[74]), "=f"(d[75]), "=f"(d[76]), "=f"(d[77]), "=f"(d[78]), "=f"(d[79]),
          "=f"(d[80]), "=f"(d[81]), "=f"(d[82]), "=f"(d[83]), "=f"(d[84]), "=f"(d[85]), "=f"(d[86]), "=f"(d[87]),
          "=f"(d[88]), "=f"(d[89]), "=f"(d[90]), "=f"(d[91]), "=f"(d[92]), "=f"(d[93]), "=f"(d[94]), "=f"(d[95]),
          "=f"(d[96]), "=f"(d[97]), "=f"(d[98]), "=f"(d[99]), "=f"(d[100]), "=f"(d[101]), "=f"(d[102]), "=f"(d[103]),
          "=f"(d[104]), "=f"(d[105]), "=f"(d[106]), "=f"(d[107]), "=f"(d[108]), "=f"(d[109]), "=f"(d[110]), "=f"(d[111]),
          "=f"(d[112]), "=f"(d[113]), "=f"(d[114]), "=f"(d[115]), "=f"(d[116]), "=f"(d[117]), "=f"(d[118]), "=f"(d[119]),
          "=f"(d[120]), "=f"(d[121]), "=f"(d[122]), "=f"(d[123]), "=f"(d[124]), "=f"(d[125]), "=f"(d[126]), "=f"(d[127])
        : "l"(da), "l"(db));
}
__device__ __forceinline__ void wgmma_ss_n256_tb_pred(float (&d)[128], uint64_t da, uint64_t db, int acc) {
    asm volatile("{\n.reg .pred p;\nsetp.ne.s32 p, %130, 0;\nwgmma.mma_async.sync.aligned.m64n256k16.f32.bf16.bf16 {"
        "%0, %1, %2, %3, %4, %5, %6, %7, %8, %9, %10, %11, %12, %13, %14, %15, %16, %17, %18, %19, %20, %21, %22, %23, %24, %25, %26, %27, %28, %29, %30, %31, "
        "%32, %33, %34, %35, %36, %37, %38, %39, %40, %41, %42, %43, %44, %45, %46, %47, %48, %49, %50, %51, %52, %53, %54, %55, %56, %57, %58, %59, %60, %61, %62, %63, "
        "%64, %65, %66, %67, %68, %69, %70, %71, %72, %73, %74, %75, %76, %77, %78, %79, %80, %81, %82, %83, %84, %85, %86, %87, %88, %89, %90, %91, %92, %93, %94, %95, "
        "%96, %97, %98, %99, %100, %101, %102, %103, %104, %105, %106, %107, %108, %109, %110, %111, %112, %113, %114, %115, %116, %117, %118, %119, %120, %121, %122, %123, %124, %125, %126, %127}, %128, %129, p, 1, 1, 0, 1;\n}\n"
        : "+f"(d[0]), "+f"(d[1]), "+f"(d[2]), "+f"(d[3]), "+f"(d[4]), "+f"(d[5]), "+f"(d[6]), "+f"(d[7]),
          "+f"(d[8]), "+f"(d[9]), "+f"(d[10]), "+f"(d[11]), "+f"(d[12]), "+f"(d[13]), "+f"(d[14]), "+f"(d[15]),
          "+f"(d[16]), "+f"(d[17]), "+f"(d[18]), "+f"(d[19]), "+f"(d[20]), "+f"(d[21]), "+f"(d[22]), "+f"(d[23]),
          "+f"(d[24]), "+f"(d[25]), "+f"(d[26]), "+f"(d[27]), "+f"(d[28]), "+f"(d[29]), "+f"(d[30]), "+f"(d[31]),
          "+f"(d[32]), "+f"(d[33]), "+f"(d[34]), "+f"(d[35]), "+f"(d[36]), "+f"(d[37]), "+f"(d[38]), "+f"(d[39]),
          "+f"(d[40]), "+f"(d[41]), "+f"(d[42]), "+f"(d[43]), "+f"(d[44]), "+f"(d[45]), "+f"(d[46]), "+f"(d[47]),
          "+f"(d[48]), "+f"(d[49]), "+f"(d[50]), "+f"(d[51]), "+f"(d[52]), "+f"(d[53]), "+f"(d[54]), "+f"(d[55]),
          "+f"(d[56]), "+f"(d[57]), "+f"(d[58]), "+f"(d[59]), "+f"(d[60]), "+f"(d[61]), "+f"(d[62]), "+f"(d[63]),
          "+f"(d[64]), "+f"(d[65]), "+f"(d[66]), "+f"(d[67]), "+f"(d[68]), "+f"(d[69]), "+f"(d[70]), "+f"(d[71]),
          "+f"(d[72]), "+f"(d[73]), "+f"(d[74]), "+f"(d[75]), "+f"(d[76]), "+f"(d[77]), "+f"(d[78]), "+f"(d[79]),
          "+f"(d[80]), "+f"(d[81]), "+f"(d[82]), "+f"(d[83]), "+f"(d[84]), "+f"(d[85]), "+f"(d[86]), "+f"(d[87]),
          "+f"(d[88]), "+f"(d[89]), "+f"(d[90]), "+f"(d[91]), "+f"(d[92]), "+f"(d[93]), "+f"(d[94]), "+f"(d[95]),
          "+f"(d[96]), "+f"(d[97]), "+f"(d[98]), "+f"(d[99]), "+f"(d[100]), "+f"(d[101]), "+f"(d[102]), "+f"(d[103]),
          "+f"(d[104]), "+f"(d[105]), "+f"(d[106]), "+f"(d[107]), "+f"(d[108]), "+f"(d[109]), "+f"(d[110]), "+f"(d[111]),
          "+f"(d[112]), "+f"(d[113]), "+f"(d[114]), "+f"(d[115]), "+f"(d[116]), "+f"(d[117]), "+f"(d[118]), "+f"(d[119]),
          "+f"(d[120]), "+f"(d[121]), "+f"(d[122]), "+f"(d[123]), "+f"(d[124]), "+f"(d[125]), "+f"(d[126]), "+f"(d[127])
        : "l"(da), "l"(db), "r"(acc));
}
__device__ __forceinline__ void wgmma_rs_n64_tb(float (&d)[32], uint32_t a0, uint32_t a1, uint32_t a2, uint32_t a3, uint64_t db) {
    asm volatile("wgmma.mma_async.sync.aligned.m64n64k16.f32.bf16.bf16 {"
        "%0, %1, %2, %3, %4, %5, %6, %7, %8, %9, %10, %11, %12, %13, %14, %15, %16, %17, %18, %19, %20, %21, %22, %23, %24, %25, %26, %27, %28, %29, %30, %31}, {%32, %33, %34, %35}, %36, 1, 1, 1, 1;\n"
        : "+f"(d[0]), "+f"(d[1]), "+f"(d[2]), "+f"(d[3]), "+f"(d[4]), "+f"(d[5]), "+f"(d[6]), "+f"(d[7]),
          "+f"(d[8]), "+f"(d[9]), "+f"(d[10]), "+f"(d[11]), "+f"(d[12]), "+f"(d[13]), "+f"(d[14]), "+f"(d[15]),
          "+f"(d[16]), "+f"(d[17]), "+f"(d[18]), "+f"(d[19]), "+f"(d[20]), "+f"(d[21]), "+f"(d[22]), "+f"(d[23]),
          "+f"(d[24]), "+f"(d[25]), "+f"(d[26]), "+f"(d[27]), "+f"(d[28]), "+f"(d[29]), "+f"(d[30]), "+f"(d[31])
        : "r"(a0), "r"(a1), "r"(a2), "r"(a3), "l"(db));
}
__device__ __forceinline__ void wgmma_rs_n64_tb_init(float (&d)[32], uint32_t a0, uint32_t a1, uint32_t a2, uint32_t a3, uint64_t db) {
    asm volatile("wgmma.mma_async.sync.aligned.m64n64k16.f32.bf16.bf16 {"
        "%0, %1, %2, %3, %4, %5, %6, %7, %8, %9, %10, %11, %12, %13, %14, %15, %16, %17, %18, %19, %20, %21, %22, %23, %24, %25, %26, %27, %28, %29, %30, %31}, {%32, %33, %34, %35}, %36, 0, 1, 1, 1;\n"
        : "=f"(d[0]), "=f"(d[1]), "=f"(d[2]), "=f"(d[3]), "=f"(d[4]), "=f"(d[5]), "=f"(d[6]), "=f"(d[7]),
          "=f"(d[8]), "=f"(d[9]), "=f"(d[10]), "=f"(d[11]), "=f"(d[12]), "=f"(d[13]), "=f"(d[14]), "=f"(d[15]),
          "=f"(d[16]), "=f"(d[17]), "=f"(d[18]), "=f"(d[19]), "=f"(d[20]), "=f"(d[21]), "=f"(d[22]), "=f"(d[23]),
          "=f"(d[24]), "=f"(d[25]), "=f"(d[26]), "=f"(d[27]), "=f"(d[28]), "=f"(d[29]), "=f"(d[30]), "=f"(d[31])
        : "r"(a0), "r"(a1), "r"(a2), "r"(a3), "l"(db));
}

__device__ __forceinline__ void wg_fence() { asm volatile("wgmma.fence.sync.aligned;\n" ::: "memory"); }
__device__ __forceinline__ void wg_commit() { asm volatile("wgmma.commit_group.sync.aligned;\n" ::: "memory"); }
template <int N> __device__ __forceinline__ void wg_wait() { asm volatile("wgmma.wait_group.sync.aligned %0;\n" ::"n"(N) : "memory"); }
template <int N> __device__ __forceinline__ void fence_regs(float (&a)[N]) {
#pragma unroll
    for (int i = 0; i < N; i++) asm volatile("" : "+f"(a[i])::"memory");
}
template <int N> __device__ __forceinline__ void fence_regs(uint32_t (&a)[N]) {
#pragma unroll
    for (int i = 0; i < N; i++) asm volatile("" : "+r"(a[i])::"memory");
}
__device__ __forceinline__ void mbar_init(uint32_t bar, uint32_t cnt) {
    asm volatile("mbarrier.init.shared::cta.b64 [%0], %1;\n" ::"r"(bar), "r"(cnt) : "memory");
}
__device__ __forceinline__ void mbar_expect_tx(uint32_t bar, uint32_t bytes) {
    asm volatile("mbarrier.arrive.expect_tx.shared::cta.b64 _, [%0], %1;\n" ::"r"(bar), "r"(bytes) : "memory");
}
__device__ __forceinline__ void mbar_wait(uint32_t bar, uint32_t parity) {
    asm volatile("{\n.reg .pred p;\nLW:\nmbarrier.try_wait.parity.shared::cta.b64 p, [%0], %1;\n@!p pmevent 0;\n@!p bra LW;\n}\n" ::"r"(bar), "r"(parity) : "memory");
}
__device__ __forceinline__ void mbar_wait_sleep(uint32_t bar, uint32_t parity) {
    asm volatile("{\n.reg .pred p;\nLW:\nmbarrier.try_wait.parity.shared::cta.b64 p, [%0], %1, 20000;\n@!p pmevent 0;\n@!p bra LW;\n}\n" ::"r"(bar), "r"(parity) : "memory");
}
__device__ __forceinline__ void mbar_wait_bounded(uint32_t bar, uint32_t parity) {
    asm volatile("{\n.reg .pred p;\n.reg .u32 c, d;\nmov.u32 c, %%globaltimer_lo;\nLW:\nmbarrier.try_wait.parity.shared::cta.b64 p, [%0], %1, 20000;\n@p bra LD;\n"
                 "mov.u32 d, %%globaltimer_lo;\nsub.u32 d, d, c;\nsetp.ge.u32 p, d, 4000000000;\n@p trap;\nbra LW;\nLD:\n}\n" ::"r"(bar), "r"(parity) : "memory");
}
__device__ __forceinline__ void flag_wait(const int* p, int v) {
    asm volatile("{\n.reg .pred p;\n.reg .s32 f;\nLW:\nld.acquire.gpu.global.s32 f, [%0];\nsub.s32 f, f, %1;\nsetp.lt.s32 p, f, 0;\n@p bra LW;\n}\n" ::"l"(p), "r"(v) : "memory");
}
__device__ __forceinline__ void flag_wait_bounded(const int* p, int v) {
    asm volatile("{\n.reg .pred p;\n.reg .u32 c;\n.reg .s32 f;\nmov.u32 c, 0;\nLW:\nld.acquire.gpu.global.s32 f, [%0];\nsub.s32 f, f, %1;\nsetp.ge.s32 p, f, 0;\n@p bra LD;\n"
                 "nanosleep.u32 500;\nadd.u32 c, c, 1;\nsetp.ge.u32 p, c, 4194304;\n@p trap;\nbra LW;\nLD:\n}\n" ::"l"(p), "r"(v) : "memory");
}
__device__ __forceinline__ int lane_now() {
    int l; asm volatile("mov.u32 %0, %%laneid;\n" : "=r"(l)); return l;
}
__device__ __forceinline__ bool elect() {
    uint32_t p; asm volatile("{\n.reg .pred p;\nelect.sync _|p, -1;\nselp.u32 %0, 1, 0, p;\n}\n" : "=r"(p)); return p;
}
__device__ __forceinline__ void bulk_g2s(uint32_t dst, const void* src, uint32_t bytes, uint32_t bar) {
    asm volatile("cp.async.bulk.shared::cluster.global.mbarrier::complete_tx::bytes [%0], [%1], %2, [%3];\n"
                 ::"r"(dst), "l"(src), "r"(bytes), "r"(bar) : "memory");
}
__device__ __forceinline__ void tma_g2s(uint32_t dst, const CUtensorMap* tm, int rowgroup, uint32_t bar) {
    asm volatile("cp.async.bulk.tensor.4d.shared::cluster.global.tile.mbarrier::complete_tx::bytes [%0], [%1, {0, 0, 0, %2}], [%3];\n"
                 ::"r"(dst), "l"(tm), "r"(rowgroup), "r"(bar) : "memory");
}
__device__ __forceinline__ void bar_sync(int id, int n) { asm volatile("bar.sync %0, %1;\n" ::"r"(id), "r"(n) : "memory"); }
__device__ __forceinline__ void bar_arrive(int id, int n) { asm volatile("bar.arrive %0, %1;\n" ::"r"(id), "r"(n) : "memory"); }
__device__ __forceinline__ float quad_last(float v) {
    float r; asm volatile("shfl.sync.idx.b32 %0, %1, 3, 0x1c1f, -1;\n" : "=f"(r) : "f"(v)); return r;
}
__device__ __forceinline__ float ex2(float x) { float y; asm("ex2.approx.ftz.f32 %0, %1;\n" : "=f"(y) : "f"(x)); return y; }
__device__ __forceinline__ uint32_t ex2_f16(uint32_t x) { uint32_t y; asm("ex2.approx.f16x2 %0, %1;\n" : "=r"(y) : "r"(x)); return y; }
__device__ __forceinline__ uint32_t hmax2_f16(uint32_t a, uint32_t b) { uint32_t r; asm("max.f16x2 %0, %1, %2;\n" : "=r"(r) : "r"(a), "r"(b)); return r; }
__device__ __forceinline__ uint32_t hmin2_f16(uint32_t a, uint32_t b) { uint32_t r; asm("min.f16x2 %0, %1, %2;\n" : "=r"(r) : "r"(a), "r"(b)); return r; }
__device__ __forceinline__ float lg2(float x) { float y; asm("lg2.approx.ftz.f32 %0, %1;\n" : "=f"(y) : "f"(x)); return y; }
__device__ __forceinline__ float rcp(float x) { float y; asm("rcp.approx.ftz.f32 %0, %1;\n" : "=f"(y) : "f"(x)); return y; }
__device__ __forceinline__ uint32_t pack_bf16(float lo, float hi) {
    uint32_t r; asm("cvt.rn.bf16x2.f32 %0, %1, %2;\n" : "=r"(r) : "f"(hi), "f"(lo)); return r;
}
__device__ __forceinline__ uint32_t pack_f16(float lo, float hi) {
    uint32_t r; asm("cvt.rn.f16x2.f32 %0, %1, %2;\n" : "=r"(r) : "f"(hi), "f"(lo)); return r;
}
__device__ __forceinline__ uint32_t pack_f16_sat(float lo, float hi) {
    uint32_t r; asm("cvt.rn.satfinite.f16x2.f32 %0, %1, %2;\n" : "=r"(r) : "f"(hi), "f"(lo)); return r;
}
__device__ __forceinline__ float f16_lo(uint32_t v) { float r; asm("cvt.f32.f16 %0, %1;\n" : "=f"(r) : "h"((unsigned short)v)); return r; }
__device__ __forceinline__ float f16_hi(uint32_t v) { return f16_lo(v >> 16); }
__device__ __forceinline__ float bf_lo(uint32_t v) { return __uint_as_float(v << 16); }
__device__ __forceinline__ float bf_hi(uint32_t v) { return __uint_as_float(v & 0xFFFF0000u); }
__device__ __forceinline__ float bf_round(float x) { return __uint_as_float(pack_bf16(0.f, x)); }
__device__ __forceinline__ void st_release(int* p, int v) {
    asm volatile("st.release.gpu.global.s32 [%0], %1;\n" ::"l"(p), "r"(v) : "memory");
}
__device__ __forceinline__ uint4 ldg_pinned(const uint4* p) {
    uint4 v; asm volatile("ld.global.nc.v4.u32 {%0, %1, %2, %3}, [%4];\n" : "=r"(v.x), "=r"(v.y), "=r"(v.z), "=r"(v.w) : "l"(p) : "memory"); return v;
}
__device__ __forceinline__ void stmatrix_x4(uint32_t addr, uint32_t r0, uint32_t r1, uint32_t r2, uint32_t r3) {
    asm volatile("stmatrix.sync.aligned.m8n8.x4.shared.b16 [%0], {%1, %2, %3, %4};\n" ::"r"(addr), "r"(r0), "r"(r1), "r"(r2), "r"(r3) : "memory");
}

__device__ __forceinline__ uint32_t tile_off(int r, int ch) {
    return (uint32_t)((r >> 3) * 4096 + (ch >> 3) * 1024 + (r & 7) * 128 + (((ch ^ r) & 7) << 4));
}
__device__ __forceinline__ int h_unit(int qt, int u) { return qt < 78 ? u * 78 + qt : 624; }
__device__ __forceinline__ int row_off(int r) { return 4096 + h_unit(r >> 7, (r >> 4) & 7) * 8192 + (r & 8) * 512 + (r & 7) * 144; }

__device__ __forceinline__ float4 lds128f(uint32_t a) {
    float4 v; asm volatile("ld.shared.v4.f32 {%0, %1, %2, %3}, [%4];\n" : "=f"(v.x), "=f"(v.y), "=f"(v.z), "=f"(v.w) : "r"(a) : "memory"); return v;
}
__device__ __forceinline__ uint64_t lds64(uint32_t a) { uint64_t v; asm volatile("ld.shared.u64 %0, [%1];\n" : "=l"(v) : "r"(a) : "memory"); return v; }
__device__ __forceinline__ uint4 lds128(uint32_t a) {
    uint4 v; asm volatile("ld.shared.v4.u32 {%0, %1, %2, %3}, [%4];\n" : "=r"(v.x), "=r"(v.y), "=r"(v.z), "=r"(v.w) : "r"(a) : "memory"); return v;
}
__device__ __forceinline__ void sts128(uint32_t a, uint32_t x, uint32_t y, uint32_t z, uint32_t w) {
    asm volatile("st.shared.v4.u32 [%0], {%1, %2, %3, %4};\n" ::"r"(a), "r"(x), "r"(y), "r"(z), "r"(w) : "memory");
}
__device__ __forceinline__ void mbar_arrive(uint32_t bar) {
    asm volatile("mbarrier.arrive.shared::cta.b64 _, [%0];\n" ::"r"(bar) : "memory");
}
__device__ __forceinline__ uint64_t mkaddr(uint32_t lo, uint32_t hi) { uint64_t a; asm("mov.b64 %0, {%1, %2};\n" : "=l"(a) : "r"(lo), "r"(hi)); return a; }
__device__ __forceinline__ void red_add(int* p) { asm volatile("red.relaxed.gpu.global.add.s32 [%0], 1;\n" ::"l"(p) : "memory"); }
__device__ __forceinline__ void red_release(int* p) {
    asm volatile("fence.proxy.async.global;\nfence.acq_rel.gpu;\nred.relaxed.gpu.global.add.s32 [%0], 1;\n" ::"l"(p) : "memory");
}
__device__ __forceinline__ void fence_async_global() { asm volatile("fence.proxy.async.global;\n" ::: "memory"); }
__device__ __forceinline__ void fence_async_smem() { asm volatile("fence.proxy.async.shared::cta;\n" ::: "memory"); }
__device__ __forceinline__ void bulk_s2g(void* dst, uint32_t src, uint32_t bytes) {
    asm volatile("cp.async.bulk.global.shared::cta.bulk_group [%0], [%1], %2;\ncp.async.bulk.commit_group;\n" ::"l"(dst), "r"(src), "r"(bytes) : "memory");
}
__device__ __forceinline__ void mma16816(float (&c)[4], uint32_t a0, uint32_t a1, uint32_t a2, uint32_t a3, uint32_t b0, uint32_t b1) {
    asm("mma.sync.aligned.m16n8k16.row.col.f32.bf16.bf16.f32 {%0, %1, %2, %3}, {%4, %5, %6, %7}, {%8, %9}, {%0, %1, %2, %3};\n"
        : "+f"(c[0]), "+f"(c[1]), "+f"(c[2]), "+f"(c[3]) : "r"(a0), "r"(a1), "r"(a2), "r"(a3), "r"(b0), "r"(b1));
}
__device__ __forceinline__ void mma1688(float (&c)[4], uint32_t a0, uint32_t a1, uint32_t b0) {
    asm("mma.sync.aligned.m16n8k8.row.col.f32.bf16.bf16.f32 {%0, %1, %2, %3}, {%4, %5}, {%6}, {%0, %1, %2, %3};\n"
        : "+f"(c[0]), "+f"(c[1]), "+f"(c[2]), "+f"(c[3]) : "r"(a0), "r"(a1), "r"(b0));
}
__device__ __forceinline__ uint32_t hadd2_f16(uint32_t a, uint32_t b) { uint32_t r; asm("add.rn.f16x2 %0, %1, %2;\n" : "=r"(r) : "r"(a), "r"(b)); return r; }
__device__ __forceinline__ uint32_t hadd2(uint32_t a, uint32_t b) { uint32_t r; asm("add.rn.bf16x2 %0, %1, %2;\n" : "=r"(r) : "r"(a), "r"(b)); return r; }
__device__ __forceinline__ uint32_t hmul2(uint32_t a, uint32_t b) { uint32_t r; asm("mul.rn.bf16x2 %0, %1, %2;\n" : "=r"(r) : "r"(a), "r"(b)); return r; }
__device__ __forceinline__ uint32_t hfma2(uint32_t a, uint32_t b, uint32_t c) { uint32_t r; asm("fma.rn.bf16x2 %0, %1, %2, %3;\n" : "=r"(r) : "r"(a), "r"(b), "r"(c)); return r; }

constexpr int SM_Q = 0;
constexpr int SM_KV = 65536;
constexpr int SM_ML = SM_KV + STAGES * KV_BYTES;
constexpr int SM_BAR = SM_ML + 1024;
constexpr int SM_TOTAL = SM_BAR + 256;
constexpr float SCALE_LOG2 = 1.4426950408889634f / 16.0f;
constexpr float KV_SCALE = 6.f;
constexpr float KV_OFF = 32.f + KVM / 32.f;
constexpr uint32_t KV_OFF2 = (0x5000u + KVM) * 0x10001u;
constexpr uint32_t KV_OFF8 = (0x5800u + KVM) * 0x10001u;
constexpr uint32_t NEG2 = 0x80008000u;
constexpr uint32_t S_LIMIT = 0x4B804B80u;
constexpr float REF_UP = REFUP, REF_SUM = REFSUM;
__device__ __forceinline__ uint32_t kvf(uint32_t a, uint32_t off) {
    uint32_t r; asm("fma.rn.f16x2 %0, %1, %2, %3;\n" : "=r"(r) : "r"(a), "r"(pack_f16(KV_SCALE, KV_SCALE)), "r"(off)); return r;
}
enum { BAR_PP0 = 1, BAR_PP1 = 2, BAR_WG0 = 3, BAR_WG1 = 4, BAR_H0 = 5, BAR_H1 = 6, BAR_AUX = 7, BAR_BF = 8, BAR_H2 = 9, BAR_X = 10, BAR_GO = 11, BAR_WG2 = 12, BAR_ST = 13 };

struct Hot {
    const __nv_bfloat16 *wk, *wq, *x;
    Scratch* s;
};
struct Params {
    const __nv_bfloat16* deg_inv;
    const int *src, *dst;
    __nv_bfloat16* out;
    uint32_t dhi;
    int E;
    CUtensorMap tm_out;
    CUtensorMap tm_outc;
    CUtensorMap tm_w[3];
};
#define SC_PAIR (blockIdx.x < 104)
#define SC_TAIL (blockIdx.x >= NCTA - 2)
#define SC_LAST (blockIdx.x == NCTA - 1)
#define SC_HELP (SC_PAIR && rank)
#define SC_OWNER (!SC_HELP && !SC_LAST)
#define SC_QT1 (26 + (int)(blockIdx.x >> 1))
#define SC_QT0 (SC_PAIR ? (rank ? (int)(blockIdx.x >> 2) : SC_QT1) : SC_TAIL ? 78 : (int)blockIdx.x - 104)
#define SC_NKV (SC_LAST ? 50 : 75)
#define SC_CLS (SC_PAIR ? (rank ? 0x120 ^ (blockIdx.x & 2) * 0x80 : 0x430) | (blockIdx.x & 2) >> 1 : SC_LAST ? 0x10 : 0x432)
#define SC_NW (SC_PAIR ? 8 : SC_LAST ? 0 : 4)
#define SC_ZB (2 * SC_QT1 + 1 - (int)rank)
#define SC_TZB(k) (rank && !(k) ? 156 : 2 * (k) - (int)rank)

__global__ void __cluster_dims__(2, 1, 1) __launch_bounds__(384, 1) k_main(const __grid_constant__ Hot H, const __grid_constant__ Params P) {
    extern __shared__ __align__(1024) uint8_t smem[];
    const uint32_t sb = (uint32_t)__cvta_generic_to_shared(smem);
    const int tid = threadIdx.x, wg = __shfl_sync(~0u, tid >> 7, 0);
    const int lane = tid & 31, g = lane >> 2, q = lane & 3;
    const uint32_t rank = blockIdx.x & 1;
    const uint32_t bar_full = sb + SM_BAR, bar_q = bar_full + 32, bar_go = bar_full + 48;
    const uint32_t bar_pin = bar_full + 56;
    const uint32_t bar_qfree = bar_full + 72, bar_pdone = bar_full + 88, bar_zst = bar_full + 104, bar_rfree = bar_full + 120;
    const uint32_t bar_empty = bar_full + 128, bar_end = bar_full + 160, s_tm = bar_full + 184, bar_x = bar_full + 192;
    const uint32_t bar_a = sb + SM_ML;

    const int t = tid & 127, warp = __shfl_sync(~0u, t >> 5, 0);
    int ep = 0;
    if (wg & 2) {
        unsigned done;
        {
            uint4 ra[2], rb[2], rk[5][2];
            if (blockIdx.x < 128) {
                const int e = (blockIdx.x >> 4) * 32 + (g >> 1) * 8 + (blockIdx.x & 8) / 2 + (g & 1);
                const uint4* pq = (const uint4*)(H.wq + e * 256) + warp * 8 + q;
                const uint4* pk = (const uint4*)(H.wk + ((blockIdx.x & 7) * 32 + g) * 256) + warp * 8 + q;
                const uint4* pz = (const uint4*)(H.wk + 255 * 256) + warp * 8 + q;
#pragma unroll
                for (int s = 0; s < 2; s++) {
                    ra[s] = ldg_pinned(pq + 4 * s);
                    rb[s] = ldg_pinned(pq + 4 * s + 64);
#pragma unroll
                    for (int n = 0; n < 4; n++) rk[n][s] = ldg_pinned(pk + 4 * s + n * 256);
                    rk[4][s] = ldg_pinned(pz + 4 * s);
                }
            }
            asm volatile("{\n.reg .pred p;\nsetp.eq.s32 p, %2, 0;\nmov.u32 %0, 0;\n@p ld.global.cg.u32 %0, [%1];\n}\n" : "=r"(done) : "l"(&g_sync[SY_DONE * 32]), "r"(lane) : "memory");
            bar_arrive(BAR_X, 384);
            if (warp == 0 && elect()) {
#pragma unroll
                for (int i = 0; i < 21; i++) mbar_init(bar_full + 8 * i, i < 9 ? 1 : i < 16 ? 4 : i == 20 ? 11 : SC_TAIL ? 4 : 8);
#pragma unroll
                for (int i = 0; i < 4; i++) mbar_init(bar_a + 8 * i, 1);
                mbar_expect_tx(bar_pin, QB_BYTES / 2 + 512); mbar_expect_tx(bar_pin + 8, QB_BYTES / 2);
                asm volatile("fence.mbarrier_init.release.cluster;\n" ::: "memory");
            }
            __syncwarp();
            asm volatile("barrier.cluster.arrive.relaxed.aligned;\n" ::: "memory");
            if (blockIdx.x < 128) {
                float c[5][4] = {};
#pragma unroll
                for (int s = 0; s < 2; s++) {
#pragma unroll
                    for (int n = 0; n < 5; n++) mma16816(c[n], ra[s].x, rb[s].x, ra[s].y, rb[s].y, rk[n][s].x, rk[n][s].y);
#pragma unroll
                    for (int n = 0; n < 5; n++) mma16816(c[n], ra[s].z, rb[s].z, ra[s].w, rb[s].w, rk[n][s].z, rk[n][s].w);
                }
#pragma unroll
                for (int i = 0; i < 4; i++) {
                    const int r = i & 2, n = (i & 1) * 2;
                    sts128(sb + SM_KV + 3 * KV_BYTES + QB_BYTES + i * 2048 + t * 16, __float_as_uint(c[n][r] - c[4][r]), __float_as_uint(c[n][r + 1] - c[4][r]),
                           __float_as_uint(c[n + 1][r] - c[4][r]), __float_as_uint(c[n + 1][r + 1] - c[4][r]));
                }
            }
        }
        asm volatile("setmaxnreg.dec.sync.aligned.u32 %0;\n" ::"n"(REG_P));
        if (blockIdx.x < 128) {
            bar_sync(BAR_WG2, 128);
            float4 v[4];
#pragma unroll
            for (int i = 0; i < 4; i++) v[i] = lds128f(sb + SM_KV + 3 * KV_BYTES + QB_BYTES + (warp & 2) * 2048 + (lane & 1) * 2048 + i * 512 + ((warp & 1) * 16 + (lane >> 1)) * 16);
            constexpr float SC = SCALE_LOG2 / KV_SCALE;
            const int r = (warp & 1) * 4 + (lane >> 3);
            *(uint2*)(g_w + tile_off((blockIdx.x >> 3) * 16 + (warp & 2) * 4 + r, (blockIdx.x & 7) * 4 + ((lane >> 1) & 3)) + (lane & 1) * 8) =
                make_uint2(pack_f16_sat(((v[0].x + v[1].x) + (v[2].x + v[3].x)) * SC, ((v[0].y + v[1].y) + (v[2].y + v[3].y)) * SC) | 1,
                           pack_f16_sat(((v[0].z + v[1].z) + (v[2].z + v[3].z)) * SC, ((v[0].w + v[1].w) + (v[2].w + v[3].w)) * SC) | 1);
            if (warp != 1) {
                bar_arrive(BAR_AUX, 128);
            } else {
                bar_sync(BAR_AUX, 128);
                if (elect()) { red_add(&g_sync[SY_DONE * 32 + 4 + (blockIdx.x >> 5)]); }
                __syncwarp();
            }
        } else {
            bar_sync(BAR_WG2, 128);
        }
        if (warp == 1) bar_arrive(BAR_GO, 160);
        auto load_a = [&](int j) {
            if (elect()) {
                mbar_expect_tx(bar_a + 8 * j, QB_BYTES);
                bulk_g2s(sb + SM_KV + j * KV_BYTES, g_w + j * QB_BYTES, QB_BYTES, bar_a + 8 * j);
            }
            __syncwarp();
        };
        if (warp == 0) {
            auto poll = [&]() { int c; asm volatile("ld.relaxed.gpu.global.s32 %0, [%1];\n" : "=r"(c) : "l"(&g_sync[SY_DONE * 32 + 4 + (lane & 3)]) : "memory"); return c; };
#pragma unroll 1
            for (int j = 0; j < 4;) {
#pragma unroll 1
                for (const uint32_t mk = __ballot_sync(~0u, poll() >= 32) & 15; (mk >> j) & 1; j++) load_a(j);
            }
        } else if (warp & 1) {
#pragma unroll 1
            for (int j = 0, n = 0; j < 4;) {
                mbar_wait_bounded(bar_a + 8 * j, n & 1);
                uint32_t ok = 1;
#pragma unroll
                for (int i = 0; i < 16; i++) {
                    uint32_t v;
                    asm volatile("ld.shared.u32 %0, [%1];\n" : "=r"(v) : "r"(sb + SM_KV + j * KV_BYTES + (warp & 2) * 8192 + i * 1024 + lane * 32 + g * 4) : "memory");
                    ok &= v;
                }
                asm volatile("{\n.reg .pred p;\nsetp.ne.u32 p, %0, 0;\nbar.red.and.pred p, %1, 64, p;\nselp.u32 %0, 1, 0, p;\n}\n" : "+r"(ok) : "n"((int)BAR_WG2) : "memory");
                if (__any_sync(~0u, ok)) {
                    if (warp == 1 && elect()) asm volatile("mbarrier.arrive.shared::cta.b64 _, [%0];\nmbarrier.inval.shared::cta.b64 [%1];\n" ::"r"(bar_full + 8 * j), "r"(bar_a + 8 * j) : "memory");
                    __syncwarp();
                    j++; n = 0;
                } else {
                    asm volatile("{\n.reg .pred p;\nsetp.gt.s32 p, %0, 1000000;\n@p trap;\n}\n" ::"r"(++n) : "memory");
                    fence_async_smem();
                    if (warp == 1) load_a(j);
                }
            }
        }
        done = __shfl_sync(~0u, done, 0);
        ep = (int)(done / NCTA) + 1;
        asm volatile("barrier.cluster.wait.acquire.aligned;\n" ::: "memory");
        if (warp == 0) {
            asm volatile("st.shared.u64 [%0], %1;\n" ::"r"(s_tm), "l"(&P.tm_outc) : "memory");
            __syncwarp();
            if (elect()) {
                const uint8_t* base = (const uint8_t*)H.s;
                uint32_t cls = SC_CLS, bytes = KV_BYTES, step = 5 * KV_BYTES;
                const uint8_t* src = base;
                bool tick;
                int next = 0;
                const int nit = SC_NKV + SC_NW;
#pragma unroll 1
                for (int j = 0; j < nit; j++) {
                    const uint32_t slot = sb + SM_KV + (j & 3) * KV_BYTES, fb = bar_full + 8 * (j & 3);
                    if (j == next) {
                        const int k = j - SC_NKV;
                        const int sw = SC_HELP ? j - 25 : -1;
                        next = j + 1;
                        tick = j >= 3 && k < 0 && (unsigned)sw >= 4 && !SC_TAIL;
                        if (j >= 3 && (unsigned)sw >= 5) next = k >= 0 ? next : j < GO0 ? GO0 : j < 25 ? 25 : j < GO1 ? GO1 : j < 49 ? 49 : j < 50 ? 50 : 75;
                        if (j == 0 || j == 25 || j == 50) { src = base + (4096 + (cls & 15) * KV_BYTES); cls >>= 4; }
                        if (SC_TAIL ? j == nit - 1 : j == GO0 || j == GO1) mbar_arrive(bar_go);
                        int fo = -1, fv = 1;
                        if (j < 3) { fo = (SY_H0 + 5 * j + (SC_CLS & 15)) * 32; fv = 5; }
                        if (j == 3) { fo = SY_H1 * 32; fv = 79; }
                        if (sw == 1) fo = 25 * 32 + SC_QT1;
                        if (k == 0) fo = SY_B * 32;
                        if (k == 1 && !SC_PAIR) { fo = SY_AUX0 * 32; fv = NAUX; }
                        if (k == 2 && SC_PAIR) { fo = SY_AUX * 32; fv = NAUX / 3; }
                        if (fo >= 0) {
                            flag_wait(g_sync + fo, fv * ep);
                            fence_async_global();
                        }
                        if (sw == 2 || (k == 2 && !SC_TAIL)) {
                            uint32_t qs = sw == 2 ? offsetof(Scratch, q) + (2 * SC_QT1 + 1) * QB_BYTES : SC_PAIR ? offsetof(Scratch, agg) + SC_ZB * QB_BYTES : offsetof(Scratch, part) + SC_QT0 * (4 * PART_BYTES);
#pragma unroll 1
                            for (int w = 0; w < (k == 2 && SC_PAIR ? 1 : 2); w++) {
                                mbar_wait_sleep(bar_qfree + 8 * w, k == 2 && SC_HELP);
                                mbar_expect_tx(bar_q + 8 * w, SC_PAIR ? QB_BYTES : PART_BYTES);
                                if (!SC_PAIR) bulk_g2s(sb + SM_ML + w * 512, base + (qs + (w ? -512 : QB_BYTES)), 512, bar_q + 8 * w);
                                bulk_g2s(sb + SM_Q + w * QB_BYTES, base + qs, QB_BYTES, bar_q + 8 * w);
                                qs += sw == 2 ? -QB_BYTES : PART_BYTES + 512;
                            }
                        }
                        if ((sw | 1) == 3) {
                            mbar_wait_sleep(bar_pdone + 8 * (sw - 2), 0);
                            bulk_s2g(g_part + (blockIdx.x - 3 + sw) * PART_BYTES, slot, PART_BYTES);
                            asm volatile("cp.async.bulk.wait_group.read 0;\n" ::: "memory");
                        }
                        if (sw == 5) {
                            asm volatile("cp.async.bulk.wait_group 0;\n" ::: "memory");
                            red_release(&g_sync[SY_PART * 32]);
                        }
                        if (k == 0) {
                            asm volatile("prefetch.tensormap [%0];\n" ::"l"(&P.tm_outc) : "memory");
                            src = g_w + (12 - SC_NW) * QB_BYTES; bytes = step = QB_BYTES;
                        }
                        if (k == 2) next = SC_TAIL ? nit - 1 : nit;
                    }
                    mbar_wait_sleep(fb + (bar_empty - bar_full), (j >> 2) & 1);
                    mbar_expect_tx(fb, bytes);
                    if (tick)
                        asm volatile("{\n.reg .pred p;\n.reg .u32 a, b, c;\nmov.u32 c, 1;\nmov.u32 a, %%globaltimer_lo;\nnot.b32 b, a;\nand.b32 b, b, %0;\nshr.u32 b, b, 1;\nnanosleep.u32 b;\n"
                                     "L:\nmov.u32 b, %%globaltimer_lo;\nlop3.b32 b, b, a, c, 0xBE;\nadd.u32 c, c, %2;\nsetp.le.u32 p, b, %0;\n@p nanosleep.u32 %1;\n@p bra L;\n}\n" ::"n"(TICK - 1), "n"(30), "n"(TICK / 32) : "memory");
                    bulk_g2s(slot, src, bytes, fb);
                    src += step;
                }
            }
        } else {
            if (warp == 2 && SC_OWNER) {
                uint8_t* dst = g_hz + 4096 + h_unit(SC_QT0, 0) * 8192;
                auto send = [&](int u0, int u1) {
#pragma unroll
                    for (int u = u0; u < u1; u++) {
                        bulk_s2g(dst + u * (78 * 8192), sb + SM_Q + u * 8192, 8192);
                        asm volatile("cp.async.bulk.wait_group 0;\n" ::: "memory");
                    }
                };
                int* f0 = &g_sync[(SY_H0 + SC_QT0 / 5) * 32];
                bar_sync(BAR_H0, 64);
                if (elect()) {
                    send(0, 1);
                    if (SC_QT0 < 65) red_release(f0);
                }
                bar_sync(BAR_H1, 160);
                if (elect()) {
                    if (!SC_TAIL) send(1, 4);
                    mbar_arrive(bar_q);
                }
                bar_sync(BAR_H2, 160);
                if (elect()) {
                    if (!SC_TAIL) { send(4, 8); mbar_arrive(bar_q + 8); }
                    red_release(&g_sync[SY_H1 * 32]);
                }
                __syncwarp();
            }
        }
    } else {
        const uint32_t sq = sb + SM_Q + wg * QB_BYTES;
        const uint32_t qbar = bar_q + 8 * wg;
        const uint32_t dq0 = __shfl_sync(~0u, ((sq & 0x3FFFF) >> 4) | (64u << 16), 0);
        const uint32_t dk0 = __shfl_sync(~0u, (((sb + SM_KV) & 0x3FFFF) >> 4) | (64u << 16), 0);
        float o[128];
        int it = 4;
        const uint32_t dhi = P.dhi;
        auto release = [&](int st, int n = 1) {
            if (n == 1) asm volatile("{\n.reg .pred p;\nelect.sync _|p, -1;\n@p mbarrier.arrive.shared::cta.b64 _, [%0];\n}\n" ::"r"(bar_empty + 8 * st) : "memory");
            else asm volatile("{\n.reg .pred p;\nelect.sync _|p, -1;\n@p mbarrier.arrive.shared::cta.b64 _, [%0], 2;\n}\n" ::"r"(bar_empty + 8 * st) : "memory");
        };
        const bool active = !(SC_TAIL && wg == 1);
        auto pp_sync = [&]() { if (!SC_TAIL) bar_sync(BAR_PP0 + wg, 256); };
        auto pp_arrive = [&]() { if (!SC_TAIL) bar_arrive(BAR_PP1 - wg, 256); };
        auto warp_arrive = [&](uint32_t bar) {
            __syncwarp();
            asm volatile("{\n.reg .pred p;\nelect.sync _|p, -1;\n@p mbarrier.arrive.shared::cta.b64 _, [%0];\n}\n" ::"r"(bar + 8 * wg) : "memory");
        };
        auto peer_arrive = [&]() {
            asm volatile("{\n.reg .pred p;\n.reg .b32 a;\nelect.sync _|p, -1;\nmapa.shared::cluster.u32 a, %0, %1;\n"
                         "@p mbarrier.arrive.shared::cluster.b64 _, [a];\n}\n" ::"r"(bar_rfree), "r"(rank ^ 1) : "memory");
        };
        auto cut = [&]() { asm volatile("{\n.reg .pred p;\nsetp.lt.s32 p, %0, 0;\nL:\n@p pmevent 0;\n@p bra L;\n}\n" ::"r"(dhi) : "memory"); };
        float qs = 1.f;
        uint32_t qr[4 * NQR];
        auto stage_q = [&]() {
            int k = dhi & 1;
            uint32_t big;
#pragma unroll 1
            do {
                if (k) {
                    qs *= 16.f;
#pragma unroll
                    for (int i = 0; i < 128; i++) o[i] *= 0.0625f;
                }
                big = 0;
                auto pk = [&](int i) { return QRND(pack_f16_sat(o[i], o[i + 1])); };
#pragma unroll
                for (int i = 0; i < 16; i++) {
                    if (QREG(i) >= 0) continue;
                    const uint32_t v0 = pk(8 * i), v1 = pk(8 * i + 2), v2 = pk(8 * i + 4) | (i == 15 ? k : 0), v3 = pk(8 * i + 6);
                    stmatrix_x4(sq + warp * 8192 + tile_off(lane & 15, 2 * i + (lane >> 4)), v0, v1, v2, v3);
                    big |= v0 | v1; big |= v2 | v3;
                    if (i == 15) cut();
                }
#pragma unroll
                for (int i = 0; i < 64; i++)
                    if (const int r = QREG(i / 4); r >= 0) big |= qr[4 * r + (i & 3)] = pk(2 * i);
                k++;
            } while (__any_sync(~0u, (big & 0x40004000u) && k < 8));
        };
        uint32_t s[20];
        auto issue_qk = [&](int st, int sh = 24) {
            const uint64_t kb = mkaddr(dk0 + st * (KV_BYTES >> 4), dhi);
            const uint64_t qd = mkaddr(dq0 + ((uint32_t)it >> sh), dhi);
            wgmma_ss_n80_init(s, qd, kb);
#pragma unroll
            for (int j = 1; j < 16; j++) {
                const int kk = j == 8 ? 15 : j < 8 ? j : j - 1;
                const int r = QREG(kk);
                if (r >= 0) wgmma_rs_n80(s, qr[4 * r], qr[4 * r + 1], qr[4 * r + 2], qr[4 * r + 3], kb + ((kk >> 2) * 64 + (kk & 3) * 2));
                else wgmma_ss_n80(s, qd + ((kk >> 2) * 64 + (kk & 3) * 2), kb + ((kk >> 2) * 64 + (kk & 3) * 2));
            }
            wg_commit();
        };

        {
            const int rb = (2 * SC_QT0 + wg) * 64 + warp * 16;
            const uint32_t xbar = bar_x + 32 * wg + 8 * warp;
            if (elect()) {
                mbar_init(xbar, 1);
                asm volatile("fence.mbarrier_init.release.cluster;\nfence.proxy.async.shared::cta;\n" ::: "memory");
                mbar_expect_tx(xbar, rb < NN ? 8192 : 0);
            }
            asm volatile("barrier.cluster.arrive.relaxed.aligned;\n" ::: "memory");
            if (wg == 1) pp_arrive();
            bar_sync(BAR_X, 384);
            if (wg == 1) bar_sync(BAR_GO, 160);
            if (rb < NN && elect()) bulk_g2s(sq + warp * 8192, H.x + (size_t)rb * 256, 8192, xbar);
            if (rb >= NN) {
#pragma unroll 1
                for (int i = 0; i < 16; i++) sts128(sq + warp * 8192 + i * 512 + lane * 16, 0, 0, 0, 0);
            }
            __syncwarp();
            mbar_wait(xbar, 0);
            uint4 xa[8], xb[8];
#pragma unroll
            for (int s = 0; s < 8; s++) {
                xa[s] = lds128(sq + (warp * 16 + g) * 512 + (4 * s + q) * 16);
                xb[s] = lds128(sq + (warp * 16 + g + 8) * 512 + (4 * s + q) * 16);
            }
            float sm[2][4], sq2[2][4][4];
#pragma unroll
            for (int i = 0; i < 4; i++) {
                sm[0][i] = sm[1][i] = 0.f;
#pragma unroll
                for (int k = 0; k < 4; k++) sq2[0][k][i] = sq2[1][k][i] = 0.f;
            }
#pragma unroll
            for (int s = 0; s < 8; s++) {
#pragma unroll
                for (int hh = 0; hh < 2; hh++) {
                    const uint4 v = hh ? xb[s] : xa[s];
                    mma16816(sm[hh], v.x, v.y, v.z, v.w, 0x3F803F80u, 0x3F803F80u);
                    mma1688(sq2[hh][0], v.x, v.y, v.x); mma1688(sq2[hh][1], v.x, v.y, v.y);
                    mma1688(sq2[hh][2], v.z, v.w, v.z); mma1688(sq2[hh][3], v.z, v.w, v.w);
                }
            }
            float inv[2], off[2];
#pragma unroll
            for (int hh = 0; hh < 2; hh++) {
                const float mean = (sm[hh][0] + sm[hh][2]) * (1.f / 256.f);
                const float d0 = (sq2[hh][0][0] + sq2[hh][2][0]) + (sq2[hh][1][2] + sq2[hh][3][2]);
                const float d1 = (sq2[hh][0][1] + sq2[hh][2][1]) + (sq2[hh][1][3] + sq2[hh][3][3]);
                const float ss = __shfl_sync(~0u, (g & 1) ? d1 : d0, g * 4 + (g >> 1));
                const float var = fmaxf(ss * (1.f / 256.f) - mean * mean, 0.f);
                float sd;
                asm("sqrt.approx.ftz.f32 %0, %1;\n" : "=f"(sd) : "f"(bf_round(bf_round(var) + 1e-5f)));
                asm("rcp.approx.ftz.f32 %0, %1;\n" : "=f"(inv[hh]) : "f"(bf_round(sd)));
                off[hh] = -mean * inv[hh];
            }
            uint32_t a[64];
#pragma unroll
            for (int s = 0; s < 8; s++) {
                a[8 * s] = xa[s].x; a[8 * s + 1] = xb[s].x; a[8 * s + 2] = xa[s].y; a[8 * s + 3] = xb[s].y;
                a[8 * s + 4] = xa[s].z; a[8 * s + 5] = xb[s].z; a[8 * s + 6] = xa[s].w; a[8 * s + 7] = xb[s].w;
            }
            fence_regs(a);
            if (wg == 1 && __any_sync(~0u, inv[0] + inv[1] != -1.f)) bar_arrive(BAR_ST, 256);
            asm volatile("setmaxnreg.inc.sync.aligned.u32 %0;\n" ::"n"(REG_C));
            fence_regs(a);
#pragma unroll
            for (int i = 0; i < 64; i++)
                a[i] = pack_f16(fmaf(bf_lo(a[i]), inv[i & 1], off[i & 1]), fmaf(bf_hi(a[i]), inv[i & 1], off[i & 1]));
            if (SC_OWNER) {
                const uint32_t ko = (q & 2) ? KV_OFF2 : KV_OFF2 | NEG2;
#pragma unroll
                for (int i = 0; i < 16; i++) {
                    const uint32_t mk = (i == 15 && q == 3) ? 0xFFFFu : ~0u;
                    stmatrix_x4(sq + warp * 8192 + tile_off(lane & 15, 2 * i + (lane >> 4)), kvf(a[4 * i], ko), kvf(a[4 * i + 1], ko),
                                kvf(a[4 * i + 2] & mk, ko), kvf(a[4 * i + 3] & mk, ko));
                }
                fence_async_smem();
                if (tid < 32) bar_arrive(BAR_H0, 64);
                bar_arrive(wg ? BAR_H2 : BAR_H1, 160);
            }
            asm volatile("barrier.cluster.wait.acquire.aligned;\n" ::: "memory");
            if (wg == 0) bar_sync(BAR_ST, 256);
            if (active) {
                fence_regs(a);
#pragma unroll
                for (int c = 0; c < 4; c++) {
                    if (c == 1) {
                        if (wg == 1) {
                            wg_wait<0>();
                            release(0);
                        }
                        pp_sync();
                    }
                    mbar_wait(bar_full + 8 * c, 0);
                    const uint64_t wb = mkaddr(dk0 + c * (KV_BYTES >> 4), dhi);
                    wg_fence();
#pragma unroll
                    for (int kk = 0; kk < 4; kk++) {
                        if (c | kk) wgmma_rs_n256_tb(o, a[16 * c + 4 * kk], a[16 * c + 4 * kk + 1], a[16 * c + 4 * kk + 2], a[16 * c + 4 * kk + 3], wb + kk * 512);
                        else wgmma_rs_n256_tb_init(o, a[0], a[1], a[2], a[3], wb);
                    }
                    wg_commit();
                    if (c > 0) { wg_wait<1>(); if (c > 1 || wg == 0) release(c - 1); }
                }
                if (wg == 0) pp_arrive();
                wg_wait<0>();
                fence_regs(o);
                release(3);
                if (SC_OWNER) mbar_wait(qbar, 0);
                stage_q();
                fence_async_smem();
                bar_sync(BAR_WG0 + wg, 128);
                mbar_wait(bar_full, 1);
                fence_regs(qr);
                wg_fence();
                issue_qk(0);
                if (wg == 1) pp_arrive();
                if (SC_PAIR && !rank) {
#pragma unroll
                    for (int i = 0; i < 16; i++)
                        if (const int r = QREG(i); r >= 0)
                            stmatrix_x4(sq + warp * 8192 + tile_off(lane & 15, 2 * i + (lane >> 4)), qr[4 * r], qr[4 * r + 1], qr[4 * r + 2], qr[4 * r + 3]);
                }
            } else {
                peer_arrive();
            }
        }

        uint32_t p[20];
        float m0 = 0.f, m1 = 0.f, e0, e1, l0 = 0.f, l1 = 0.f;
        uint32_t plim;
        uint32_t qphase = (SC_OWNER && active) ? 1 : 0;
        auto issue_pv = [&](int st, int acc) {
            const uint64_t vb = mkaddr(dk0 + st * (KV_BYTES >> 4), dhi);
            wgmma_rs_n256_tb_pred(o, p[0], p[1], p[2], p[3], vb, acc);
#pragma unroll
            for (int kk = 1; kk < 5; kk++)
                wgmma_rs_n256_tb(o, p[4 * kk], p[4 * kk + 1], p[4 * kk + 2], p[4 * kk + 3], vb + kk * 512);
            wg_commit();
        };
        auto mq_addr = [&](int ln) { return sq + warp * 8192 + tile_off(ln >> 2, 31) + 12; };
        auto exceeds = [&](const uint32_t (&p)[20]) {
            uint32_t a = __vimax3_s16x2(S_LIMIT, p[0], p[1]), b = __vimax3_s16x2(p[2], p[3], p[4]);
#pragma unroll
            for (int i = 5; i < 17; i += 4) { a = __vimax3_s16x2(a, p[i], p[i + 1]); b = __vimax3_s16x2(b, p[i + 2], p[i + 3]); }
            a = __vimax3_s16x2(a, p[17], p[18]);
            return __any_sync(~0u, __vimax3_s16x2(a, b, p[19]) != plim);
        };
        auto store_ref = [&](int ln, uint32_t u, bool on) {
            asm volatile("{\n.reg .pred p;\nsetp.ne.s32 p, %3, 0;\n@p st.shared.u16 [%0], %1;\n@p st.shared.u16 [%0 + 4096], %2;\n}\n"
                         ::"r"(mq_addr(ln) + 2), "h"((unsigned short)u), "h"((unsigned short)(u >> 16)), "r"((int)(on && (ln & 3) == 0)) : "memory");
        };
        auto remax = [&](float& a, float& b, bool store) {
            const int ln = lane_now();
            asm volatile("" : "+f"(qs));
            uint32_t ha = s[0], hb = s[1];
#pragma unroll
            for (int i = 1; i < 10; i++) { ha = hmax2_f16(ha, s[2 * i]); hb = hmax2_f16(hb, s[2 * i + 1]); }
            ha = hmax2_f16(__byte_perm(ha, hb, 0x5410), __byte_perm(ha, hb, 0x7632));
            ha = hmax2_f16(ha, __shfl_xor_sync(~0u, ha, 1));
            ha = hmax2_f16(ha, __shfl_xor_sync(~0u, ha, 2));
            a = fmaxf(a, f16_lo(ha) * qs - e0 + REF_UP); b = fmaxf(b, f16_hi(ha) * qs - e1 + REF_UP);
            const float qi = __uint_as_float(0x7F000000u - __float_as_uint(qs)) * (-1.f / KV_OFF);
            const uint32_t u = pack_f16((m0 + a) * qi, (m1 + b) * qi);
            const float g0 = (m0 + a) + KV_OFF * qs * f16_lo(u), g1 = (m1 + b) + KV_OFF * qs * f16_hi(u);
            const bool x0 = fabsf(g0) <= 1.f, x1 = fabsf(g1) <= 1.f;
            if (x0) a -= g0;
            if (x1) b -= g1;
            const float da = a + e0, db = b + e1;
            m0 += a; m1 += b;
            e0 = x0 ? 0.f : g0; e1 = x1 ? 0.f : g1;
            plim = (x0 && x1 && qs == 1.f) ? S_LIMIT : 0u;
            store_ref(ln, u, store);
#pragma unroll
            for (int i = 0; i < 10; i++) {
                p[2 * i] = pack_f16(ex2(fmaf(f16_lo(s[2 * i]), qs, -da)), ex2(fmaf(f16_hi(s[2 * i]), qs, -da)));
                p[2 * i + 1] = pack_f16(ex2(fmaf(f16_lo(s[2 * i + 1]), qs, -db)), ex2(fmaf(f16_hi(s[2 * i + 1]), qs, -db)));
            }
            fence_regs(p);
            fence_async_smem();
            __syncwarp();
        };

        auto row_sums = [&](float& z0, float& z1, int q) {
            z0 = quad_last(o[125]); z1 = quad_last(o[127]);
            l0 = z0 * (KV_SCALE / KV_OFF); l1 = z1 * (KV_SCALE / KV_OFF);
            if (!(q & 2)) { z0 = -z0; z1 = -z1; }
        };
        auto stats = [&](int q) { return (q & 2) ? ((q & 1) ? l1 : m1) : ((q & 1) ? l0 : m0); };
        constexpr int IL = 4 + LIFT;
        const int nseg = SC_HELP ? 2 : 1;
        if (active) {
#pragma unroll 1
            for (int seg = 0;; seg++) {
                wg_wait<0>();
                fence_regs(s);
                e0 = e1 = 0.f;
                const int it0 = it, itl = __shfl_sync(~0u, seg + 1 < nseg ? 3 + 25 : 3 + SC_NKV, 0);
                const int itx = (wg == 1 && seg + 1 == nseg) ? itl : -1;
                bool redo = true, have = !seg;
#pragma unroll 1
                for (;;) {
                    if (!have) {
#pragma unroll
                        for (int i = 0; i < 20; i++) p[i] = ex2_f16(s[i]);
                        redo = exceeds(s);
                    }
                    if (redo || (it | 1) == IL + 1) {
                        static_assert(IL % 2 == 0, "");
                        if (redo || it == IL + 1) {
                            float d0 = it != it0 ? 0.f : -INFINITY, d1 = d0;
                            if (redo) remax(d0, d1, it != itl);
                            if (it != it0) {
                                const float a0 = ex2(-d0 - (it == IL + 1 ? l0 : 0.f)), a1 = ex2(-d1 - (it == IL + 1 ? l1 : 0.f));
#pragma unroll
                                for (int i = 0; i < 32; i++) { o[4 * i] *= a0; o[4 * i + 1] *= a0; o[4 * i + 2] *= a1; o[4 * i + 3] *= a1; }
                            }
                        }
                        if (it == IL) {
                            const int ln = lane_now();
                            uint32_t ha = s[0], hb = s[1], la = ha, lb = hb;
#pragma unroll
                            for (int i = 1; i < 10; i++) {
                                ha = hmax2_f16(ha, s[2 * i]); hb = hmax2_f16(hb, s[2 * i + 1]); la = hmin2_f16(la, s[2 * i]); lb = hmin2_f16(lb, s[2 * i + 1]);
                            }
                            const float w0 = fmaxf(f16_lo(ha), f16_hi(ha)) - fminf(f16_lo(la), f16_hi(la)), w1 = fmaxf(f16_lo(hb), f16_hi(hb)) - fminf(f16_lo(lb), f16_hi(lb));
                            const float t0 = m0 + quad_last(fmaxf(fminf(lg2(o[125] * (1.f / KV_OFF)) + REF_SUM, w0 * 0.5f), 0.f));
                            const float t1 = m1 + quad_last(fmaxf(fminf(lg2(o[127] * (1.f / KV_OFF)) + REF_SUM, w1 * 0.5f), 0.f));
                            const uint32_t u = pack_f16(t0 * (-1.f / KV_OFF), t1 * (-1.f / KV_OFF));
                            const bool on = plim && !SC_TAIL && fmaxf(fabsf(t0), fabsf(t1)) < 64.f * KV_OFF;
                            l0 = on ? -KV_OFF * f16_lo(u) - m0 : 0.f; l1 = on ? -KV_OFF * f16_hi(u) - m1 : 0.f;
                            m0 += l0; m1 += l1;
                            store_ref(ln, u, on);
                            fence_async_smem();
                            if (SC_OWNER) warp_arrive(bar_pdone);
                            __syncwarp();
                        }
                    }
                    if (it == itl) break;
                    const int stp = it & 3;
                    it++;
                    pp_sync();
                    fence_regs(o); fence_regs(p);
                    have = SC_TAIL || it == itx;
                    if (!have) {
                        wg_fence();
                        issue_pv(stp, it - 1 - it0);
                        mbar_wait(bar_full + 8 * (it & 3), (it >> 2) & 1);
                        wg_fence();
                        issue_qk(it & 3);
                        pp_arrive();
                        wg_wait<0>();
                        fence_regs(s); fence_regs(o); fence_regs(p);
                        if (it == itl) warp_arrive(bar_qfree);
                    } else {
                        const int zero = (uint32_t)it >> 23;
                        mbar_wait(bar_full + 8 * (it & 3), (it >> 2) & 1);
                        wg_fence();
                        issue_qk((it & 3) + zero, 25);
                        if (it == itl) {
                            wg_wait<0>();
                            if (SC_PAIR) peer_arrive(); else warp_arrive(bar_qfree);
                            if (wg) bar_sync(BAR_ST, 256);
                        }
                        wg_fence();
                        issue_pv(stp + zero, it - 1 - it0);
                        pp_arrive();
                        wg_wait<1>();
                        fence_regs(s);
                        redo = exceeds(s);
                        if (!redo) {
#pragma unroll
                            for (int i = 0; i < 20; i++) s[i] = ex2_f16(s[i]);
                            fence_regs(s);
                            cut();
                        }
                        wg_wait<0>();
                        fence_regs(o); fence_regs(p);
#pragma unroll
                        for (int i = 0; i < 20; i++) p[i] = s[i];
                    }
                    release(stp);
                }
                if (seg + 1 < nseg) pp_sync();
                fence_regs(o); fence_regs(p);
                wg_fence();
                issue_pv(it & 3, 1);
                asm volatile("{\n.reg .pred p;\nsetp.ne.s32 p, %0, 0;\n@p bar.arrive %1, 256;\n}\n" ::"r"((int)(seg + 1 == nseg && (wg ? SC_PAIR : !SC_TAIL))), "r"(BAR_ST + wg) : "memory");
                it++;
                if (seg + 1 == nseg) break;
                constexpr int IS = 4 + 25;
                const int ln = lane_now();
                uint32_t qa = sq + warp * 8192 + tile_off(ln & 15, ln >> 4);
                asm volatile("" : "+r"(qa));
                mbar_wait(bar_full + 8 * (IS & 3), (IS >> 2) & 1);
                mbar_wait(qbar, 0); qphase = 1;
#pragma unroll
                for (int i = 0; i < 16; i++)
                    if (const int r = QREG(i); r >= 0)
                        asm volatile("ldmatrix.sync.aligned.m8n8.x4.shared.b16 {%0, %1, %2, %3}, [%4];\n" : "=r"(qr[4 * r]), "=r"(qr[4 * r + 1]), "=r"(qr[4 * r + 2]), "=r"(qr[4 * r + 3])
                                     : "r"((qa ^ (i & 3) * 32) + (i >> 2) * 1024) : "memory");
                fence_regs(qr);
                wg_fence();
                issue_qk(it & 3);
                wg_wait<1>();
                pp_arrive();
                fence_regs(o);
                float z0, z1;
                row_sums(z0, z1, ln);
                release((IS - 1) & 3);
                uint32_t u0, u1;
                asm volatile("ld.shared.u32 %0, [%2];\nld.shared.u32 %1, [%2 + 4096];\n" : "=r"(u0), "=r"(u1) : "r"(mq_addr(ln)) : "memory");
                const uint32_t slot = sb + SM_KV + ((IS - 2 + wg) & 3) * KV_BYTES;
                const uint32_t dst = slot + wg * 512 + warp * 8192 + ln * 16, dml = slot + (wg ? 0 : QB_BYTES) + warp * 128 + ln * 4;
#pragma unroll
                for (int i = 0; i < 128; i++) o[i] -= (i & 2) ? z1 : z0;
                fence_regs(o);
                mbar_wait(bar_empty + 8 * ((IS - 2 + wg) & 3), ((IS - 2 + wg) >> 2) & 1);
                asm volatile("st.shared.f32 [%0], %1;\n" ::"r"(dml), "f"(stats(ln)) : "memory");
                qs = __uint_as_float(0x3F800000u + ((u0 & 7) << 25));
                m0 = -KV_OFF * qs * f16_hi(u0); m1 = -KV_OFF * qs * f16_hi(u1);
                plim = fmaxf(fabsf(m0), fabsf(m1)) < 64.f * KV_OFF && qs == 1.f ? S_LIMIT : 0u;
                uint32_t v[2][8] = {};
#pragma unroll
                for (int i = 0; i < 8; i++) {
                    uint32_t *w = v[i & 1], *u = v[(i & 1) ^ 1];
#pragma unroll
                    for (int j = 0; j < 8; j++) w[j] = pack_bf16(o[16 * i + 2 * j], o[16 * i + 2 * j + 1]);
                    sts128(dst + i * 1024, w[0], w[1], w[2], w[3]);
                    sts128(dst + i * 1024 + 512, w[4], w[5], w[6], w[7]);
                    if (i) asm volatile("{\n.reg .pred p;\nsetp.lt.s32 p, %9, 0;\nL:\n@p st.shared.v4.u32 [%0], {%1, %2, %3, %4};\n@p st.shared.v4.u32 [%0 + 16], {%5, %6, %7, %8};\n@p bra L;\n}\n"
                                 ::"r"(dst), "r"(u[0]), "r"(u[1]), "r"(u[2]), "r"(u[3]), "r"(u[4]), "r"(u[5]), "r"(u[6]), "r"(u[7]), "r"(it) : "memory");
                }
                fence_async_smem();
                warp_arrive(bar_pdone);
            }
            constexpr int IW = 4 + 75;
            uint32_t a[64];
            const int lane = lane_now(), t = warp * 32 + lane;
            if (wg == 0 && (SC_PAIR || SC_LAST)) {
                uint32_t rq, rml, rbar;
                asm volatile("mapa.shared::cluster.u32 %0, %3, %6;\nmapa.shared::cluster.u32 %1, %4, %6;\nmapa.shared::cluster.u32 %2, %5, %6;\n"
                             : "=r"(rq), "=r"(rml), "=r"(rbar) : "r"(sb + SM_Q + QB_BYTES + warp * 8192 + lane * 16), "r"(sb + SM_ML + 512 + t * 4),
                             "r"(bar_pin), "r"(rank ^ 1));
                auto send = [&](int i) {
                    asm volatile("st.async.weak.shared::cluster.mbarrier::complete_tx::bytes.v4.b32 [%0], {%1, %2, %3, %4}, [%5];\n"
                                 ::"r"(rq + i * 512), "r"(a[4 * i]), "r"(a[4 * i + 1]), "r"(a[4 * i + 2]), "r"(a[4 * i + 3]), "r"(rbar + (i & 8)) : "memory");
                };
                mbar_wait(bar_rfree, 0);
                wg_wait<0>();
                fence_regs(o);
                release((it - 1) & 3);
                float z0, z1;
                row_sums(z0, z1, lane);
                asm volatile("st.async.weak.shared::cluster.mbarrier::complete_tx::bytes.f32 [%0], %1, [%2];\n" ::"r"(rml), "f"(stats(lane)), "r"(rbar) : "memory");
#pragma unroll
                for (int i = 0; i < 16; i++) {
                    a[4 * i] = pack_bf16(o[8 * i] - z0, o[8 * i + 1] - z0); a[4 * i + 1] = pack_bf16(o[8 * i + 2] - z1, o[8 * i + 3] - z1);
                    a[4 * i + 2] = pack_bf16(o[8 * i + 4] - z0, o[8 * i + 5] - z0); a[4 * i + 3] = pack_bf16(o[8 * i + 6] - z1, o[8 * i + 7] - z1);
                    if (i * SND0 / 16 != (i + 1) * SND0 / 16) send(i * SND0 / 16);
                    if (i & 1) cut();
                }
                if (SC_PAIR) {
                    float z[128];
                    const uint32_t dkz = dk0 + ((uint32_t)it >> 24), dqz = dq0 + ((uint32_t)it >> 24);
                    auto gemm = [&](int c) {
                        mbar_wait(bar_full + 8 * ((IW + c) & 3), ((IW + c) >> 2) & 1);
                        const uint64_t wb = mkaddr(dkz + ((IW + c) & 3) * (KV_BYTES >> 4), dhi), ab = mkaddr(dqz + c * 64, dhi);
                        wg_fence();
#pragma unroll
                        for (int kk = 0; kk < 4; kk++) {
                            if (c | kk) wgmma_ss_n256_tb(z, ab + kk * 2, wb + kk * 512);
                            else wgmma_ss_n256_tb_init(z, ab, wb);
                        }
                        wg_commit();
                    };
                    mbar_wait(qbar, qphase);
                    bar_sync(BAR_ST + 1, 256);
                    gemm(0);
#pragma unroll
                    for (int i = SND0; i < 16; i++) send(i);
#pragma unroll
                    for (int c = 1; c < 4; c++) { gemm(c); if (c == 3) pp_arrive(); wg_wait<1>(); release((IW + c - 1) & 3, 2); }
                    wg_wait<0>();
                    fence_regs(z);
                    release((IW + 3) & 3, 2);
#pragma unroll
                    for (int i = 4 * NREV; i < 16; i++) {
                        sts128(sq + warp * 8192 + lane * 16 + i * 512, pack_bf16(z[8 * i], z[8 * i + 1]), pack_bf16(z[8 * i + 2], z[8 * i + 3]),
                               pack_bf16(z[8 * i + 4], z[8 * i + 5]), pack_bf16(z[8 * i + 6], z[8 * i + 7]));
                        if (i == 3 || i == 15) bar_arrive(i == 3 ? BAR_BF : BAR_H0, 256);
                        if (i == 3) cut();
                    }
                    if (NREV) {
                        const uint64_t tm = lds64(s_tm);
                        const uint32_t stg = sq + QB_BYTES + warp * 8192 + (lane & 15) * 128 + (((lane >> 4) ^ lane) & 7) * 16;
#pragma unroll
                        for (int i = 0; i < 16 * NREV; i++) { a[i] = pack_bf16(z[2 * i], z[2 * i + 1]); asm volatile("" : "+r"(a[i])); }
#pragma unroll
                        for (int cb = 0; cb < NREV; cb++) {
                            uint4 v[4];
                            bar_sync(cb & 1 ? BAR_H1 : BAR_BF, 256);
#pragma unroll
                            for (int i = 0; i < 4; i++)
                                asm volatile("ldmatrix.sync.aligned.m8n8.x4.shared.b16 {%0, %1, %2, %3}, [%4];\n"
                                             : "=r"(v[i].x), "=r"(v[i].y), "=r"(v[i].z), "=r"(v[i].w) : "r"((stg ^ (32 * i)) + cb * 2048) : "memory");
#pragma unroll
                            for (int i = 0; i < 4; i++) {
                                const uint32_t* x = a + 16 * cb + 4 * i;
                                stmatrix_x4((stg ^ (32 * i)) + cb * 2048, hadd2(v[i].x, x[0]), hadd2(v[i].y, x[1]), hadd2(v[i].z, x[2]), hadd2(v[i].w, x[3]));
                            }
                            fence_async_smem();
                            __syncwarp();
                            asm volatile("{\n.reg .pred p;\nelect.sync _|p, -1;\n"
                                         "@p cp.reduce.async.bulk.tensor.4d.global.shared::cta.add.tile.bulk_group [%0, {0, 0, %1, %2}], [%3];\n}\n"
                                         ::"l"(tm), "r"(cb), "r"(SC_ZB * 8 + warp * 2), "r"(sq + QB_BYTES + warp * 8192 + cb * 2048) : "memory");
                        }
                        asm volatile("cp.async.bulk.commit_group;\ncp.async.bulk.wait_group.read 0;\n" ::: "memory");
                    }
                } else {
#pragma unroll
                    for (int i = SND0; i < 16; i++) send(i);
                }
            } else {
                const int pair = SC_PAIR;
                const bool glob = !(pair || SC_TAIL);
                const uint32_t ml = sb + SM_ML + (t & ~3) * 4, src = (glob ? sq : sb + SM_Q + QB_BYTES) + warp * 8192 + lane * 16;
                const uint64_t tm = lds64(s_tm);
                wg_wait<0>();
                fence_regs(o);
                release((IW - 1) & 3);
                float c0, c1;
                row_sums(c0, c1, lane);
                mbar_wait(glob ? qbar : bar_pin, glob ? qphase : 0);
                const float4 ps = lds128f(ml + (glob ? wg * 512 : 512));
                auto load = [&](int i) {
                    asm volatile("ld.shared.v4.u32 {%0, %1, %2, %3}, [%4];\n" : "=r"(a[4 * i]), "=r"(a[4 * i + 1]), "=r"(a[4 * i + 2]), "=r"(a[4 * i + 3]) : "r"(src + i * 512) : "memory");
                };
#pragma unroll
                for (int i = 0; i < 8; i++) load(i);
                const float n0 = fmaxf(m0, ps.x), n1 = fmaxf(m1, ps.z);
                const float a0 = ex2(m0 - n0), a1 = ex2(m1 - n1), b0 = ex2(ps.x - n0), b1 = ex2(ps.z - n1);
                const float i0 = rcp(l0 * a0 + ps.y * b0), i1 = rcp(l1 * a1 + ps.w * b1);
                const float r0 = a0 * i0, r1 = a1 * i1;
                c0 *= -r0; c1 *= -r1;
                const uint32_t u0 = pack_bf16(b0 * i0, b0 * i0), u1 = pack_bf16(b1 * i1, b1 * i1);
                uint4 v[8];
#pragma unroll
                for (int i = 0; i <= 32; i++) {
                    if (i == M2) {
#pragma unroll
                        for (int j = 0; j < 2 * M2; j++) asm volatile("" : "+r"(a[j]));
                        if (!glob) mbar_wait(bar_pin + 8, 0);
#pragma unroll
                        for (int j = 0; j < 8; j++) v[j] = lds128(src + (8 + j) * 512);
                    }
                    if (i == 32) break;
                    const uint32_t x0 = pack_bf16(fmaf(o[4 * i], r0, c0), fmaf(o[4 * i + 1], r0, c0)), x1 = pack_bf16(fmaf(o[4 * i + 2], r1, c1), fmaf(o[4 * i + 3], r1, c1));
                    a[2 * i] = i < 16 ? hfma2(a[2 * i], u0, x0) : x0;
                    a[2 * i + 1] = i < 16 ? hfma2(a[2 * i + 1], u1, x1) : x1;
                }
#pragma unroll
                for (int j = 0; j < 8; j++) {
                    uint32_t* x = a + 32 + 4 * j;
                    x[0] = hfma2(v[j].x, u0, x[0]); x[1] = hfma2(v[j].y, u1, x[1]); x[2] = hfma2(v[j].z, u0, x[2]); x[3] = hfma2(v[j].w, u1, x[3]);
                }
                float y[2][32];
                auto gemm = [&](int c, int kh) {
                    if (!kh) mbar_wait(bar_full + 8 * ((IW + c) & 3), (((IW + c) >> 2) & 1) ^ pair);
                    const uint64_t wb = mkaddr(dk0 + ((IW + c) & 3) * (KV_BYTES >> 4), dhi - 192);
                    wg_fence();
#pragma unroll
                    for (int kk = 8 * kh; kk < 8 * kh + 8; kk++) {
                        if (kk) wgmma_rs_n64_tb(y[c & 1], a[4 * kk], a[4 * kk + 1], a[4 * kk + 2], a[4 * kk + 3], wb + kk * 128);
                        else wgmma_rs_n64_tb_init(y[c & 1], a[0], a[1], a[2], a[3], wb);
                    }
                    wg_commit();
                };
                const uint32_t stg = sq + warp * 8192 + (lane & 15) * 128 + (((lane >> 4) ^ lane) & 7) * 16;
                uint4 z[4] = {};
                auto load_z = [&](int cb) {
                    if (NREV ? cb == NREV : cb < 2) asm volatile("{\n.reg .pred p;\nsetp.ne.s32 p, %0, 0;\n@p bar.sync %1, 256;\n}\n" ::"r"(pair), "r"(cb ? BAR_H0 : BAR_BF) : "memory");
#pragma unroll
                    for (int i = 0; i < 4; i++)
                        asm volatile("{\n.reg .pred p;\nsetp.ne.u32 p, %4, 0;\n@p ld.shared.v4.u32 {%0, %1, %2, %3}, [%5];\n}\n"
                                     : "+r"(z[i].x), "+r"(z[i].y), "+r"(z[i].z), "+r"(z[i].w) : "r"(pair), "r"(src - QB_BYTES + (4 * cb + i) * 512) : "memory");
                };
                pp_sync();
                gemm(0, 0);
                gemm(0, 1);
#pragma unroll
                for (int c = 0; c < 4; c++) {
                    if (c && c >= NREV) load_z(c);
                    if (c < 3) gemm(c + 1, 0);
                    if (!c && !NREV) load_z(0);
                    if (c < 3) wg_wait<1>(); else wg_wait<0>();
                    fence_regs(y[c & 1]);
                    const float* x = y[c & 1];
#pragma unroll
                    for (int i = 0; i < 4; i++) {
                        uint4 v = make_uint4(pack_bf16(x[8 * i], x[8 * i + 1]), pack_bf16(x[8 * i + 2], x[8 * i + 3]), pack_bf16(x[8 * i + 4], x[8 * i + 5]), pack_bf16(x[8 * i + 6], x[8 * i + 7]));
                        if (c >= NREV) v = make_uint4(hadd2(v.x, z[i].x), hadd2(v.y, z[i].y), hadd2(v.z, z[i].z), hadd2(v.w, z[i].w));
                        stmatrix_x4((stg ^ (32 * i)) + c * 2048, v.x, v.y, v.z, v.w);
                    }
                    if (c < NREV && pair) bar_arrive(c & 1 ? BAR_H1 : BAR_BF, 256);
                    if (c < 3) gemm(c + 1, 1);
                    if (c == PPA && glob) pp_arrive();
                    if (c >= NREV || !pair) {
                        fence_async_smem();
                        __syncwarp();
                        asm volatile("{\n.reg .pred p;\nelect.sync _|p, -1;\n"
                                     "@p cp.reduce.async.bulk.tensor.4d.global.shared::cta.add.tile.bulk_group [%0, {0, 0, %1, %2}], [%3];\n}\n"
                                     ::"l"(tm), "r"(c), "r"((pair ? SC_ZB : 2 * SC_QT0 + wg) * 8 + warp * 2), "r"(sq + warp * 8192 + c * 2048) : "memory");
                    }
                }
                asm volatile("cp.async.bulk.commit_group;\ncp.async.bulk.wait_group.read 0;\n" ::: "memory");
            }
        } else {
            wg_wait<0>();
        }
        if (SC_TAIL) {
            float o[128];
            const int lane = lane_now(), t = warp * 32 + lane, q = lane & 3;
            auto emit = [&](uint32_t base, int lane, int row0, uint8_t* wdst, int turn) {
#pragma unroll
                for (int hh = 0; hh < 2; hh++) {
                    if (turn > 0) mbar_wait(bar_zst + 8 * hh, (turn - 1) & 1);
#pragma unroll
                    for (int i = 0; i < 8; i++)
                        stmatrix_x4(base + tile_off(8 * hh + (lane & 7), 4 * i + (lane >> 3)),
                                    pack_bf16(o[16 * i + 2 * hh], o[16 * i + 2 * hh + 1]), pack_bf16(o[16 * i + 4 + 2 * hh], o[16 * i + 5 + 2 * hh]),
                                    pack_bf16(o[16 * i + 8 + 2 * hh], o[16 * i + 9 + 2 * hh]), pack_bf16(o[16 * i + 12 + 2 * hh], o[16 * i + 13 + 2 * hh]));
                    fence_async_smem();
                    __syncwarp();
                    if (wdst) {
                        if (lane < 4)
                            asm volatile("cp.async.bulk.global.shared::cta.bulk_group [%0], [%1], 1024;\n"
                                         ::"l"(wdst + ((turn & 1) ? hh * 4096 + lane * 1024 : hh * 1024 + lane * QB_BYTES)), "r"(base + hh * 4096 + lane * 1024) : "memory");
                        asm volatile("cp.async.bulk.commit_group;\n" ::: "memory");
                    } else {
                        asm volatile("{\n.reg .pred p;\nsetp.eq.s32 p, %3, 0;\n"
                                     "@p cp.reduce.async.bulk.tensor.4d.global.shared::cta.add.tile.bulk_group [%0, {0, 0, 0, %1}], [%2];\n"
                                     "cp.async.bulk.commit_group;\n}\n"
                                     ::"l"(&P.tm_out), "r"((row0 >> 3) + hh), "r"(base + hh * 4096), "r"(lane) : "memory");
                    }
                }
                asm volatile("cp.async.bulk.wait_group.read 1;\n" ::: "memory");
                warp_arrive(bar_zst - 8 * wg);
            };
            auto emit_done = [&](bool pending) {
                asm volatile("cp.async.bulk.wait_group.read 0;\n" ::: "memory");
                __syncwarp();
                asm volatile("{\n.reg .pred p;\nsetp.eq.s32 p, %1, 0;\n@p mbarrier.arrive.shared::cta.b64 _, [%0];\n}\n"
                             ::"r"(bar_zst + 8), "r"(pending ? lane : 1) : "memory");
            };
            if (!(rank | wg)) { release(0); release(1); release(2); release(3); }
            bar_sync(BAR_BF, 256);
            warp_arrive(bar_qfree);
            const int nf = rank ? 8 : 0;
            const int nz = nf + 26 + rank;
            const int itz = 4 + SC_NKV + SC_NW;
            bool pend = false;
#pragma unroll 1
            for (int k = wg; k < nz; k += 2) {
                const int iz = itz + (k < nf ? 0 : nf >> 1);
                mbar_wait(qbar, qphase); qphase ^= 1;
#pragma unroll 1
                for (int c = 0; c < 4; c++) {
                    mbar_wait(bar_full + 8 * ((iz + c) & 3), ((iz + c) >> 2) & 1);
                    const uint64_t wb = mkaddr(dk0 + ((iz + c) & 3) * (KV_BYTES >> 4), dhi), ab = mkaddr(dq0 + c * 64, dhi);
                    wg_fence();
                    wgmma_ss_n256_tb_pred(o, ab, wb, c);
#pragma unroll
                    for (int kk = 1; kk < 4; kk++) wgmma_ss_n256_tb(o, ab + kk * 2, wb + kk * 512);
                    wg_commit();
                    emit_done(pend);
                    pend = false;
                }
                wg_wait<0>();
                fence_regs(o);
                warp_arrive(bar_qfree);
                const int fb = ((k >> 1) + 3) & 3;
                if (k < nf) {
                    float2* r255 = (float2*)H.s->r255 + wg * 128 + q;
                    if (k < 2) {
                        if (t >= 124) {
#pragma unroll
                            for (int i = 0; i < 32; i++) r255[4 * i] = make_float2(o[4 * i + 2], o[4 * i + 3]);
                        }
                        bar_sync(BAR_WG0 + wg, 128);
                    }
#pragma unroll
                    for (int i = 0; i < 32; i++) {
                        const float2 v = __ldcg(r255 + 4 * i);
                        o[4 * i] -= v.x; o[4 * i + 1] -= v.y; o[4 * i + 2] -= v.x; o[4 * i + 3] -= v.y;
                    }
                }
                int ln = lane;
                asm volatile("" : "+r"(ln));
                emit(sb + SM_KV + QB_BYTES + warp * KV_BYTES, ln, SC_TZB(k - nf) * 64 + warp * 16,
                     k >= nf ? nullptr : (k & 1) ? g_w + (4 + fb) * QB_BYTES + warp * 8192 : g_w + 8 * QB_BYTES + fb * 8192 + warp * 2048, k);
                pend = k + 2 < nz && (k | 1) != nf - 1;
                if (!pend) emit_done(true);
                if ((k | 1) == nf - 1) {
                    asm volatile("cp.async.bulk.wait_group 0;\nfence.proxy.async.global;\nfence.acq_rel.gpu;\n" ::: "memory");
                    bar_sync(BAR_BF, 256);
                    if (tid == 0) red_release(&g_sync[SY_B * 32]);
                    if (wg == 0) { release(0); release(1); release(2); release(3); }
                }
            }
        }
        if (wg == 0) pp_sync();
        warp_arrive(bar_end - 8 * wg);
        asm volatile("barrier.cluster.arrive.relaxed.aligned;\n" ::: "memory");
        if (P.E >= 0) return;
        asm volatile("setmaxnreg.dec.sync.aligned.u32 %0;\n" ::"n"(REG_P));
    }
    {
        if (warp != 0) {
            __syncwarp();
            if (SC_TAIL) {
                bar_sync(BAR_AUX, 96);
                if (warp == 1 && elect()) red_release(&g_sync[SY_CSR * 32]);
                __syncwarp();
            }
            mbar_wait_bounded(bar_go, 0);
            if (SC_TAIL) {
                if (warp == 1 && elect()) red_add(&g_sync[SY_DONE * 32]);
                if (warp == 3 && elect()) {
                    int it = 4 + SC_NKV + SC_NW;
                    asm volatile("prefetch.tensormap [%0];\n" ::"l"(&P.tm_out) : "memory");
                    if (rank) {
#pragma unroll 1
                        for (int j = 0; j < 4; j++, it++) {
                            mbar_wait_sleep(bar_empty + 8 * (it & 3), ((it >> 2) & 1) ^ 1);
                            mbar_expect_tx(bar_full + 8 * (it & 3), QB_BYTES);
                            tma_g2s(sb + SM_KV + (it & 3) * KV_BYTES, &P.tm_w[2], 8 * j, bar_full + 8 * (it & 3));
                        }
#pragma unroll 1
                        for (int k = 0; k < 8; k++) {
                            mbar_wait_sleep(bar_qfree + 8 * (k & 1), ((k >> 1) ^ (k & 1) ^ 1) & 1);
                            mbar_expect_tx(bar_q + 8 * (k & 1), QB_BYTES);
#pragma unroll 1
                            for (int hf = 0; hf < 2; hf++)
                                asm volatile("cp.async.bulk.tensor.5d.shared::cluster.global.tile.mbarrier::complete_tx::bytes [%0], [%1, {0, 0, %2, 0, 0}], [%3];\n"
                                             ::"r"(sb + SM_Q + (k & 1) * QB_BYTES + hf * 16384), "l"(&P.tm_w[k & 1]),
                                             "r"(8 * (((k >> 1) + 3) & 3) + 4 * hf), "r"(bar_q + 8 * (k & 1)) : "memory");
                        }
                        flag_wait_bounded(&g_sync[SY_B * 32], ep);
                        fence_async_global();
                    }
#pragma unroll 1
                    for (int j = 0; j < 4; j++, it++) {
                        mbar_wait_sleep(bar_empty + 8 * (it & 3), ((it >> 2) & 1) ^ 1);
                        mbar_expect_tx(bar_full + 8 * (it & 3), QB_BYTES);
                        bulk_g2s(sb + SM_KV + (it & 3) * KV_BYTES, g_w + (4 + j) * QB_BYTES, QB_BYTES, bar_full + 8 * (it & 3));
                    }
#pragma unroll 1
                    for (int k = 0; k < 26 + rank; k++) {
                        if (k == 0 || k == ((GF0 + 1) * NAUX - 16) / 128) { flag_wait_bounded(&g_sync[(k ? SY_AUX1 : SY_AUX0) * 32], NAUX * ep); fence_async_global(); }
                        mbar_wait_sleep(bar_qfree + 8 * (k & 1), ((k >> 1) ^ (k & 1) ^ 1) & 1);
                        mbar_expect_tx(bar_q + 8 * (k & 1), QB_BYTES);
                        bulk_g2s(sb + SM_Q + (k & 1) * QB_BYTES, g_agg + SC_TZB(k) * QB_BYTES, QB_BYTES, bar_q + 8 * (k & 1));
                    }
                }
            } else {
                const int par = ep & 1;
                if (blockIdx.x == 0 && t == 32) g_ovf_n[par ^ 1] = 0;
                if (blockIdx.x == 0 && warp == 1) *(uint4*)(g_hz + (lane >> 3) * 1024 + (lane & 7) * 16) = make_uint4(KV_OFF2 | NEG2, KV_OFF2 | NEG2, KV_OFF2, KV_OFF2);
                const uint32_t wlo = (uint32_t)(uintptr_t)H.s, whi = (uint32_t)((uintptr_t)H.s >> 32);
                const uint32_t blo = wlo + (uint32_t)offsetof(Scratch, bucket);
                {
                    const int* pd = P.dst + blockIdx.x * 96 + (t - 32);
                    const int* ps = P.src + blockIdx.x * 96 + (t - 32);
#pragma unroll 1
                    for (int e = P.E - (blockIdx.x * 96 + (t - 32)); e > 0; e -= CSRU * NAUX * 32, pd += CSRU * NAUX * 32, ps += CSRU * NAUX * 32) {
                        int d[CSRU], sr[CSRU], sl[CSRU];
#pragma unroll
                        for (int i = 0; i < CSRU; i++) {
                            d[i] = e > i * NAUX * 32 ? __ldg(pd + i * NAUX * 32) : NN;
                            sr[i] = e > i * NAUX * 32 ? __ldg(ps + i * NAUX * 32) : 0;
                        }
#pragma unroll
                        for (int i = 0; i < CSRU; i++) {
                            sl[i] = 0;
                            asm volatile("{\n.reg .pred p;\nsetp.lt.s32 p, %2, %3;\n@p atom.relaxed.gpu.global.add.s32 %0, [%1], 1;\n}\n"
                                         : "+r"(sl[i]) : "l"(mkaddr(wlo + (uint32_t)offsetof(Scratch, cnt) + d[i] * 4, whi)), "r"(d[i]), "n"(NN) : "memory");
                        }
                        uint32_t ov = 0;
#pragma unroll
                        for (int i = 0; i < CSRU; i++) {
                            asm volatile("{\n.reg .pred p;\nsetp.lt.s32 p, %3, %4;\n@p st.global.u16 [%1], %2;\n@!p or.b32 %0, %0, %5;\n}\n"
                                         : "+r"(ov) : "l"(mkaddr(blo + d[i] * 128 + (sl[i] & 31) * 4 + (sl[i] >> 5) * 2, whi)), "h"((unsigned short)sr[i]), "r"(sl[i]), "n"(CAP), "r"(1 << i) : "memory");
                        }
#pragma unroll 1
                        for (; ov; ov &= ov - 1) {
                            const int i = (__ffs(ov) - 1) * (NAUX * 32);
                            int at;
                            asm volatile("atom.relaxed.gpu.global.add.s32 %0, [%1], 1;\n" : "=r"(at) : "l"(&g_ovf_n[par]) : "memory");
                            g_ovf[at] = make_int2(__ldg(pd + i), __ldg(ps + i));
                        }
                    }
                }
                bar_sync(BAR_AUX, 96);
                if (warp == 1 && elect()) { red_release(&g_sync[SY_CSR * 32]); }
                __syncwarp();
                {
                    const int r0 = blockIdx.x * 3 + warp - 1;
                    const uint4* xp = (const uint4*)(H.x + r0 * 256) + lane;
                    uint4* op = (uint4*)(P.out + r0 * 256) + lane;
#pragma unroll 1
                    for (int r = r0; r < NN; r += CPYU * NAUX, xp += CPYU * NAUX * 32, op += CPYU * NAUX * 32) {
                        uint4 v[CPYU];
#pragma unroll
                        for (int i = 0; i < CPYU; i++) if (r + i * NAUX < NN) v[i] = ldg_pinned(xp + i * NAUX * 32);
#pragma unroll
                        for (int i = 0; i < CPYU; i++) if (r + i * NAUX < NN) op[i * NAUX * 32] = v[i];
                    }
                }
                if (warp == 3 && SC_OWNER && SC_PAIR && elect()) {
                    mbar_wait_sleep(bar_pdone, 0);
                    mbar_wait_sleep(bar_pdone + 8, 0);
#pragma unroll 1
                    for (int u = 0; u < 16; u++) {
                        bulk_s2g(g_q + SC_QT0 * (2 * QB_BYTES) + u * 4096, sb + SM_Q + u * 4096, 4096);
                        asm volatile("cp.async.bulk.wait_group 0;\n" ::: "memory");
                    }
                    fence_async_global();
                    st_release(&g_qflag[SC_QT0], ep);
                }
                __syncwarp();
                mbar_wait_bounded(bar_go, 1);
                bar_sync(BAR_AUX, 96);
                if (const int un = (3 - warp) * (NAUX / 3) + (NAUX / 3 - 1) - blockIdx.x; un < 208) {
                    flag_wait_bounded(&g_sync[SY_PART * 32], 52 * ep);
                    uint8_t* pp = g_part + (un >> 3) * (4 * PART_BYTES);
                    float* ml = (float*)(pp + QB_BYTES) + (un & 7) * 32;
                    const float4 sa = __ldcg((const float4*)ml + g), sc = __ldcg((const float4*)ml + g + 2 * PART_BYTES / 16);
                    const float n0 = fmaxf(sa.x, sc.x), n1 = fmaxf(sa.z, sc.z);
                    const uint32_t a0 = pack_bf16(ex2(sa.x - n0), ex2(sa.x - n0)), a1 = pack_bf16(ex2(sa.z - n1), ex2(sa.z - n1));
                    const uint32_t b0 = pack_bf16(ex2(sc.x - n0), ex2(sc.x - n0)), b1 = pack_bf16(ex2(sc.z - n1), ex2(sc.z - n1));
                    __syncwarp();
                    if (q == 0) ((float4*)ml)[g] = make_float4(n0, sa.y * bf_hi(a0) + sc.y * bf_hi(b0), n1, sa.w * bf_hi(a1) + sc.w * bf_hi(b1));
                    uint4* d = (uint4*)(pp + (un & 4) * 256 + (un & 7) * 8192) + lane;
#pragma unroll 1
                    for (int i = 0; i < 4; i++, d += 128) {
                        uint4 u[4], v[4];
#pragma unroll
                        for (int j = 0; j < 4; j++) { u[j] = __ldcg(d + j * 32); v[j] = __ldcg(d + j * 32 + 2 * PART_BYTES / 16); }
#pragma unroll
                        for (int j = 0; j < 4; j++)
                            d[j * 32] = make_uint4(hfma2(v[j].x, b0, hmul2(u[j].x, a0)), hfma2(v[j].y, b1, hmul2(u[j].y, a1)),
                                                   hfma2(v[j].z, b0, hmul2(u[j].z, a0)), hfma2(v[j].w, b1, hmul2(u[j].w, a1)));
                    }
                }
                flag_wait_bounded(&g_sync[SY_CSR * 32], NCTA * ep);
                if (warp == 2 && blockIdx.x < 129) {
                    uint4* z = blockIdx.x < 128 ? (uint4*)(g_w + blockIdx.x * 1024) + lane : (uint4*)&g_sync[SY_DONE * 32 + 4];
                    z[0] = make_uint4(0, 0, 0, 0);
                    if (blockIdx.x < 128) z[32] = make_uint4(0, 0, 0, 0);
                }
                {
                    const uint32_t lc = (lane >> 3) * 1024 + (lane & 7) * 16;
                    const uint32_t alo = wlo ^ lc;
                    const int node0 = blockIdx.x * 3 + warp - 17;
                    auto node = [&](int i) { const int nd = node0 + i * NAUX; return (int)min((unsigned)nd, (unsigned)(nd + NN)); };
                    const int num = (NN - 17 - node0) / NAUX + 1;
                    uint32_t mine = 0;
                    if (lane < num) {
                        mine = min(__ldcg(&g_cnt[node(lane)]), CAP + 1) | (uint32_t)__ldg((const unsigned short*)P.deg_inv + node(lane)) << 16;
                        g_cnt[node(lane)] = 0;
                    }
                    auto row = [&](int off) {
                        uint4 v;
                        asm volatile("ld.global.v4.u32 {%0, %1, %2, %3}, [%4];\n"
                                     : "=r"(v.x), "=r"(v.y), "=r"(v.z), "=r"(v.w) : "l"(mkaddr(alo ^ off, whi)));
                        return v;
                    };
                    auto ents = [&](int i) {
                        uint32_t e;
                        asm volatile("ld.global.cg.u32 %0, [%1];\n" : "=r"(e) : "l"(mkaddr(blo + (min(node(i), NN - 1) * 32 + lane) * 4, whi)));
                        return e;
                    };
                    auto store = [&](int i, const float (&a)[8]) {
                        const float di = bf_hi(__shfl_sync(~0u, mine, i)) * (1.f / KV_SCALE);
                        const int nd = node(i);
                        *(uint4*)(g_agg + (uint32_t)(((nd >> 3) * 4096 + (nd & 7) * 144) ^ lc)) =
                            make_uint4(pack_bf16(a[0] * di, a[1] * di), pack_bf16(a[2] * di, a[3] * di), pack_bf16(a[4] * di, a[5] * di), pack_bf16(a[6] * di, a[7] * di));
                    };
#pragma unroll 1
                    for (uint32_t big = __ballot_sync(~0u, (mine & 0xFFFF) > CAP); big; big &= big - 1) {
                        const int i = __ffs(big) - 1, no = __ldcg(&g_ovf_n[par]);
                        float a[8] = {};
#pragma unroll 1
                        for (int k = -64; k < no; k += 32) {
                            const int2 pr = k < 0 ? make_int2(node(i), (ents(i) >> (k & 32) / 2) & 0xFFFF) : k + lane < no ? __ldcg(&g_ovf[k + lane]) : make_int2(-1, 0);
#pragma unroll 1
                            for (uint32_t mk = __ballot_sync(~0u, pr.x == node(i)); mk; mk &= mk - 1) {
                                const uint4 v = row(row_off(__shfl_sync(~0u, pr.y, __ffs(mk) - 1)));
                                a[0] += f16_lo(v.x) + KV_OFF; a[1] += f16_hi(v.x) + KV_OFF; a[2] += f16_lo(v.y) + KV_OFF; a[3] += f16_hi(v.y) + KV_OFF;
                                a[4] += f16_lo(v.z) - KV_OFF; a[5] += f16_hi(v.z) - KV_OFF; a[6] += f16_lo(v.w) - KV_OFF; a[7] += f16_hi(v.w) - KV_OFF;
                            }
                        }
                        store(i, a);
                    }
                    auto add4 = [&](const uint4& a, const uint4& b) { return make_uint4(hadd2_f16(a.x, b.x), hadd2_f16(a.y, b.y), hadd2_f16(a.z, b.z), hadd2_f16(a.w, b.w)); };
                    int ni = -1, left = 0, pos = 0, ec = 0;
                    uint32_t en = ents(0);
                    uint4 acc = make_uint4(0, 0, 0, 0);
                    auto step = [&](uint4 (&v)[4], int& tag) {
                        if (left <= 0 || pos == 32) {
                            if (left > 0) {
                                en = ents(ni) >> 16;
                            } else {
                                ni++;
                                left = __shfl_sync(~0u, mine, ni) & 0xFFFF;
                                if (left > CAP) left = 0;
                            }
                            ec = lane < left ? row_off(en & 0xFFFF) : 0;
                            en = ents(ni + 1);
                            pos = 0;
                        }
                        int of[4];
#pragma unroll
                        for (int j = 0; j < 4; j++) asm volatile("shfl.sync.idx.b32 %0, %1, %2, 31, -1;\n" : "=r"(of[j]) : "r"(ec), "r"(pos + j));
                        acc = add4(acc, add4(add4(add4(v[0], v[1]), make_uint4(KV_OFF8, KV_OFF8, KV_OFF8 | NEG2, KV_OFF8 | NEG2)), add4(v[2], v[3])));
                        asm volatile("" : "+r"(acc.x), "+r"(acc.y), "+r"(acc.z), "+r"(acc.w));
                        asm volatile("{\n.reg .pred p;\nsetp.lt.s32 p, %0, 0;\nL:\n@p pmevent 0;\n@p bra L;\n}\n" ::"r"(ni) : "memory");
#pragma unroll
                        for (int j = 0; j < 4; j++) v[j] = row(of[j]);
                        pos += 4; left -= 4;
                        const int i = tag;
                        tag = left <= 0 ? ni : -1;
                        if (i >= 0) {
                            const float a[8] = {f16_lo(acc.x), f16_hi(acc.x), f16_lo(acc.y), f16_hi(acc.y), f16_lo(acc.z), f16_hi(acc.z), f16_lo(acc.w), f16_hi(acc.w)};
                            if ((__shfl_sync(~0u, mine, i) & 0xFFFF) <= CAP) store(i, a);
                            acc = make_uint4(0, 0, 0, 0);
                            if (i == GF0 || i == 8) {
                                __syncwarp();
                                if (elect()) red_release(&g_sync[(i == 8 ? SY_AUX1 : SY_AUX0) * 32]);
                                __syncwarp();
                            }
                        }
                        return i == num - 1;
                    };
                    uint4 va[4], vb[4];
#pragma unroll
                    for (int j = 0; j < 4; j++) va[j] = vb[j] = make_uint4(KV_OFF2 | NEG2, KV_OFF2 | NEG2, KV_OFF2, KV_OFF2);
                    int ta = -1, tb = -1;
#pragma unroll 1
                    while (!step(va, ta) && !step(vb, tb)) {}
                }
                bar_sync(BAR_AUX, 96);
                if (warp == 1 && elect()) {
                    red_release(&g_sync[SY_AUX * 32]);
                    red_add(&g_sync[SY_DONE * 32]);
                }
            }
        }
        __syncwarp();
        asm volatile("barrier.cluster.arrive.relaxed.aligned;\n" ::: "memory");
        if (warp == 1) mbar_wait_bounded(bar_end, 0);
        else if (elect()) mbar_arrive(bar_end);
        __syncwarp();
        asm volatile("barrier.cluster.wait.acquire.aligned;\n" ::: "memory");
    }
}

}


extern "C" void kernel_launch(void* const* d_in, const int* in_sizes, int n_in, void* d_out, int out_size) {
    Hot H;
    Params P;
    H.x = (const __nv_bfloat16*)d_in[0];
    P.src = (const int*)d_in[1];
    P.dst = (const int*)d_in[2];
    P.deg_inv = (const __nv_bfloat16*)d_in[3];
    H.wq = (const __nv_bfloat16*)d_in[5];
    H.wk = (const __nv_bfloat16*)d_in[6];
    P.out = (__nv_bfloat16*)d_out;
    typedef CUresult (*EncodeFn)(CUtensorMap*, CUtensorMapDataType, cuuint32_t, void*, const cuuint64_t*, const cuuint64_t*, const cuuint32_t*,
                                 const cuuint32_t*, CUtensorMapInterleave, CUtensorMapSwizzle, CUtensorMapL2promotion, CUtensorMapFloatOOBfill);
    void* fn = nullptr;
    cudaDriverEntryPointQueryResult qr;
    cudaGetDriverEntryPoint("cuTensorMapEncodeTiled", &fn, cudaEnableDefault, &qr);
    auto encode = [&](CUtensorMap* tm, const void* ptr, int rows, int box_rows, int box_cb = 4) {
        const cuuint64_t dims[4] = {64, 8, 4, (cuuint64_t)rows / 8};
        const cuuint64_t strides[3] = {512, 128, 4096};
        const cuuint32_t box[4] = {64, 8, (cuuint32_t)box_cb, (cuuint32_t)box_rows / 8}, es[4] = {1, 1, 1, 1};
        ((EncodeFn)fn)(tm, CU_TENSOR_MAP_DATA_TYPE_BFLOAT16, 4, (void*)ptr, dims, strides, box, es, CU_TENSOR_MAP_INTERLEAVE_NONE,
                       CU_TENSOR_MAP_SWIZZLE_128B, CU_TENSOR_MAP_L2_PROMOTION_NONE, CU_TENSOR_MAP_FLOAT_OOB_FILL_NONE);
    };
    encode(&P.tm_out, d_out, NN, 8);
    encode(&P.tm_outc, d_out, NN, 16, 1);
    for (int i = 0; i < 2; i++) {
        const cuuint64_t dims[5] = {64, 2, 32, 4, 4};
        const cuuint64_t strides[4] = {512, 4096, 128, 1024};
        const cuuint32_t box[5] = {64, 2, 4, 4, 4}, es[5] = {1, 1, 1, 1, 1};
        ((EncodeFn)fn)(&P.tm_w[i], CU_TENSOR_MAP_DATA_TYPE_BFLOAT16, 5, d_in[i ? 4 : 7], dims, strides, box, es, CU_TENSOR_MAP_INTERLEAVE_NONE,
                       CU_TENSOR_MAP_SWIZZLE_128B, CU_TENSOR_MAP_L2_PROMOTION_NONE, CU_TENSOR_MAP_FLOAT_OOB_FILL_NONE);
    }
    encode(&P.tm_w[2], d_in[8], 256, 64);
    void* raw = nullptr;
    cudaGetSymbolAddress(&raw, g_raw);
    H.s = (Scratch*)(((uintptr_t)raw + ((8 << 20) - 1)) & ~(uintptr_t)((8 << 20) - 1));
    P.dhi = 0x40000100u;
    P.E = in_sizes[1] < MAXE ? in_sizes[1] : MAXE;
    cudaFuncSetAttribute(k_main, cudaFuncAttributeMaxDynamicSharedMemorySize, SM_TOTAL);
    k_main<<<NCTA, 384, SM_TOTAL>>>(H, P);
}
```
